```python
import torch

def _softmax(x, axis=-1):
    return torch.softmax(x, dim=axis)
def _gelu(x):
    return torch.nn.functional.gelu(x, approximate="tanh")
def _silu(x):
    return torch.nn.functional.silu(x)
def _sigmoid(x):
    return torch.sigmoid(x)
def _layernorm(x, axis=-1, eps=1e-5):
    m = x.mean(dim=axis, keepdim=True)
    v = x.var(dim=axis, keepdim=True, unbiased=False)
    return (x - m) / torch.sqrt(v + eps)
def _scatter_add(tgt, idx, src, axis=0):
    return tgt.clone().index_add_(axis, idx, src)
def _segment_sum(src, seg, n):
    out = torch.zeros((n,) + src.shape[1:], dtype=src.dtype)
    return out.index_add_(0, seg, src)
def _pad(x, pw):
    flat = tuple(v for pair in reversed(pw) for v in pair)
    return torch.nn.functional.pad(x, flat)

kernel_name = 'sequential_preLN__ssm_conv_s4d__moe_arch_mod__prompt'

def setup_inputs():

    _w = (lambda a: (lambda t: t.to(torch.bfloat16) if t.is_floating_point() else t)(torch.as_tensor(a)))
    def _A_setup():
        Bsz, L, D, N = 1, 2048, 576, 128
        return {
            "u": _w((lambda *s: torch.randn(*s, dtype=torch.bfloat16) * 0.2)(Bsz, L, D)),
            "log_A_real": _w((lambda *s: torch.randn(*s, dtype=torch.bfloat16) * 6.4)(D, N) * 0.5),
            "A_imag": _w((lambda *s: torch.randn(*s, dtype=torch.bfloat16) * 0.2)(D, N) * 3.14),
            "C_real": _w((lambda *s: torch.randn(*s, dtype=torch.bfloat16) * 0.2)(D, N) / N ** 0.5),
            "C_imag": _w((lambda *s: torch.randn(*s, dtype=torch.bfloat16) * 0.2)(D, N) / N ** 0.5),
            "log_dt": _w((lambda *s: torch.randn(*s, dtype=torch.bfloat16) * 0.2)(D) * 0.5 - 4.0),
            "D_skip": _w((lambda *s: torch.randn(*s, dtype=torch.bfloat16) * 0.2)(D)),
        }
    _A_in = _A_setup()

    def _B_setup():
        B, S, D, F, C = 1, 2048, 576, 4608, 8
        return {
            "x": _w((lambda *s: torch.randn(*s, dtype=torch.bfloat16) * 0.2)(B, S, D)),
            "w_r": _w((lambda *s: torch.randn(*s, dtype=torch.bfloat16) * 0.2)(D)),
            "w_gate": _w((lambda *s: torch.randn(*s, dtype=torch.bfloat16) * 0.2)(D, F)),
            "w_up": _w((lambda *s: torch.randn(*s, dtype=torch.bfloat16) * 0.2)(D, F)),
            "w_down": _w((lambda *s: torch.randn(*s, dtype=torch.bfloat16) * 0.2)(F, D)),
        }
    _B_in = _B_setup()

    return {
        "A_u": _A_in["u"],
        "A_log_A_real": _A_in["log_A_real"],
        "A_A_imag": _A_in["A_imag"],
        "A_C_real": _A_in["C_real"],
        "A_C_imag": _A_in["C_imag"],
        "A_log_dt": _A_in["log_dt"],
        "A_D_skip": _A_in["D_skip"],
        "B_x": _B_in["x"],
        "B_w_r": _B_in["w_r"],
        "B_w_gate": _B_in["w_gate"],
        "B_w_up": _B_in["w_up"],
        "B_w_down": _B_in["w_down"],
    }

def reference(A_u, A_log_A_real, A_A_imag, A_C_real, A_C_imag, A_log_dt, A_D_skip, B_x, B_w_r, B_w_gate, B_w_up, B_w_down):
    def _A_ref(u, log_A_real, A_imag, C_real, C_imag, log_dt, D_skip):
        L = u.shape[1]
        dt = torch.exp(log_dt)
        A = -torch.exp(log_A_real) + 1j * A_imag
        C = (C_real + 1j * C_imag) * dt[:, None]
        pos = (lambda x, dt: x.to(dt))(torch.arange(L), log_dt.dtype)
        P = torch.exp((A * dt[:, None])[:, :, None] * pos[None, None, :])
        K = 2.0 * torch.einsum("dn,dnl->dl", C, P).real
        L2 = 2 * L
        u_t = (lambda x, *d: x.permute(*d))(u, 0, 2, 1)
        Kf = (lambda x, *a, **k: torch.fft.rfft(x.float(), *a, **k))(K, L2)
        Uf = (lambda x, *a, **k: torch.fft.rfft(x.float(), *a, **k))(u_t, L2)
        y = (lambda x, *a, **k: torch.fft.irfft(x, *a, **k).to(torch.bfloat16))(Uf * Kf[None, :, :], L2)[:, :, :L]
        y = (lambda x, *d: x.permute(*d))(y, 0, 2, 1)
        return y + u * D_skip[None, None, :]

    def _B_ref(x, w_r, w_gate, w_up, w_down):
        B, S, D = x.shape
        C = 8
        r = x @ w_r
        idx = torch.argsort(-r, axis=-1)[:, :C]
        idx_e = (lambda x, n, axis: torch.repeat_interleave(x, n, dim=axis))(idx.reshape(B, C, 1), D, axis=2)
        x_sel = (lambda x, i, axis: torch.take_along_dim(x, i, dim=axis))(x, idx_e, axis=1)
        g = _silu(x_sel @ w_gate)
        u = x_sel @ w_up
        y = (g * u) @ w_down
        r_sel = _sigmoid((lambda x, i, axis: torch.take_along_dim(x, i, dim=axis))(r, idx, axis=1))
        y = y * r_sel.reshape(B, C, 1)
        b_off = (torch.arange(B) * S).reshape(B, 1)
        flat_idx = (idx + b_off).reshape(B * C)
        zero = (x * 0.0).reshape(B * S, D)
        upd = _scatter_add(zero, flat_idx, y.reshape(B * C, D), axis=0)
        return x + upd.reshape(B, S, D)

    x = A_u
    h = x + _A_ref(_layernorm(x, axis=-1), A_log_A_real, A_A_imag, A_C_real, A_C_imag, A_log_dt, A_D_skip)
    h2 = h + _B_ref(_layernorm(h, axis=-1), B_w_r, B_w_gate, B_w_up, B_w_down)
    return h2
```

```cpp
#include <cuda_runtime.h>
#include <cuda.h>
#include <cuda_fp16.h>
#include <cuda_bf16.h>
#include <stdint.h>

#define LSEQ 2048
#define DM 576
#define NST 128
#define FF 4608
#define NSEL 8
#define NCTA 128
#define NTHR 640
#define NWRK 640

typedef __nv_bfloat16 bf16;

#define SM_WG 0
#define SM_WU 41472
#define SM_WD 82944
#define W_PITCH 144
#define SM_XC 50176
#define SM_ZERO SM_WD
#define SM_TB (SM_WD + 9216)
#define SM_PL 124416
#define PL_B 10752
#define SM_XT (SM_TB + 20 * TBW)
#define SM_U (SM_XT + 18432)
#define UPAD 8
#define ULO_B ((UPAD + 128) * 16)
#define USLOT_B (2 * ULO_B)
#define SM_KW (SM_U + 5 * USLOT_B)
#define KW_B 3600
#define KW_T2 1152
#define KW_KH 656
#define KW_T3 2464
#define SM_MISC (SM_KW + 5 * KW_B)
#define SM_LNP (SM_MISC + 576)
#define SMEM_TOTAL (SM_LNP + 4096)
#define TBP 112
#define TBW (32 * TBP)
#define SM_OUT SM_PL
#define OUT_PITCH 1216
#define SM_XS (SM_PL + 19456)
#define XS_PITCH 592
#define SM_EX (SM_PL + 24320)
#define SM_GU (SM_PL + 42752)
#define SM_CAND SM_KW

struct __align__(128) Scratch {
    unsigned hint[8 * 32];
    unsigned flag[32];
    unsigned short sc[LSEQ];
    uint32_t st[LSEQ * 2];
    uint32_t uT[64 * (LSEQ / 2)];
    uint32_t y[NCTA * DM * 8];
    uint32_t part[72 * 64 * 64];
    uint32_t rows[(2 * NCTA + NSEL) * DM];
};
__device__ Scratch g_scratch;
#define STAMP(i)
#define DBG(i, v)

__device__ __forceinline__ float rbf(float x) {
    uint32_t r;
    asm("cvt.rn.bf16x2.f32 %0, %1, %2;\n" : "=r"(r) : "f"(x), "f"(0.f));
    return __uint_as_float(r & 0xffff0000u);
}
__device__ __forceinline__ uint32_t pack_bf16(float lo, float hi) {
    uint32_t r;
    asm("cvt.rn.bf16x2.f32 %0, %1, %2;\n" : "=r"(r) : "f"(hi), "f"(lo));
    return r;
}
__device__ __forceinline__ uint32_t pack_f16(float lo, float hi) {
    uint32_t r;
    asm("cvt.rn.f16x2.f32 %0, %1, %2;\n" : "=r"(r) : "f"(hi), "f"(lo));
    return r;
}
__device__ __forceinline__ uint32_t pack_f16_rz(float lo, float hi) {
    uint32_t r;
    asm("cvt.rz.f16x2.f32 %0, %1, %2;\n" : "=r"(r) : "f"(hi), "f"(lo));
    return r;
}
__device__ __forceinline__ float bf_lo(uint32_t w) { return __uint_as_float(w << 16); }
__device__ __forceinline__ float bf_hi(uint32_t w) { return __uint_as_float(w & 0xffff0000u); }
__device__ __forceinline__ uint32_t hadd2_bf(uint32_t a, uint32_t b) {
    __nv_bfloat162 r = __hadd2_rn(*reinterpret_cast<__nv_bfloat162*>(&a), *reinterpret_cast<__nv_bfloat162*>(&b));
    return *reinterpret_cast<uint32_t*>(&r);
}
__device__ __forceinline__ uint32_t hsub2_bf(uint32_t a, uint32_t b) {
    __nv_bfloat162 r = __hsub2_rn(*reinterpret_cast<__nv_bfloat162*>(&a), *reinterpret_cast<__nv_bfloat162*>(&b));
    return *reinterpret_cast<uint32_t*>(&r);
}
__device__ __forceinline__ uint32_t hmul2_bf(uint32_t a, uint32_t b) {
    __nv_bfloat162 r = __hmul2_rn(*reinterpret_cast<__nv_bfloat162*>(&a), *reinterpret_cast<__nv_bfloat162*>(&b));
    return *reinterpret_cast<uint32_t*>(&r);
}
__device__ __forceinline__ uint32_t hfma2_bf(uint32_t a, uint32_t b, uint32_t c) { uint32_t r; asm("fma.rn.bf16x2 %0, %1, %2, %3;\n" : "=r"(r) : "r"(a), "r"(b), "r"(c)); return r; }
__device__ __forceinline__ uint32_t hmul2(uint32_t a, uint32_t b) { uint32_t r; asm("mul.rn.f16x2 %0, %1, %2;\n" : "=r"(r) : "r"(a), "r"(b)); return r; }
__device__ __forceinline__ uint32_t hadd2(uint32_t a, uint32_t b) { uint32_t r; asm("add.rn.f16x2 %0, %1, %2;\n" : "=r"(r) : "r"(a), "r"(b)); return r; }
__device__ __forceinline__ uint32_t hfma2(uint32_t a, uint32_t b, uint32_t c) { uint32_t r; asm("fma.rn.f16x2 %0, %1, %2, %3;\n" : "=r"(r) : "r"(a), "r"(b), "r"(c)); return r; }
__device__ __forceinline__ uint32_t nzw(uint32_t w) { return w ? w : 0x8000u; }
__device__ __forceinline__ uint32_t nzf(float f) { const uint32_t w = __float_as_uint(f); return w ? w : 0x80000000u; }
__device__ __forceinline__ uint32_t smem_u32(const void* p) { return (uint32_t)__cvta_generic_to_shared(p); }
__device__ __forceinline__ uint32_t lds32(uint32_t addr) {
    uint32_t v;
    asm volatile("ld.shared.u32 %0, [%1];\n" : "=r"(v) : "r"(addr) : "memory");
    return v;
}
__device__ __forceinline__ uint32_t lds16(uint32_t addr) {
    unsigned short v;
    asm volatile("ld.shared.u16 %0, [%1];\n" : "=h"(v) : "r"(addr) : "memory");
    return v;
}
__device__ __forceinline__ uint2 lds64(uint32_t addr) {
    uint2 v;
    asm volatile("ld.shared.v2.u32 {%0,%1}, [%2];\n" : "=r"(v.x), "=r"(v.y) : "r"(addr) : "memory");
    return v;
}
__device__ __forceinline__ uint4 lds128(uint32_t addr) {
    uint4 v;
    asm volatile("ld.shared.v4.u32 {%0,%1,%2,%3}, [%4];\n" : "=r"(v.x), "=r"(v.y), "=r"(v.z), "=r"(v.w) : "r"(addr) : "memory");
    return v;
}
__device__ __forceinline__ float ldsf(uint32_t addr) { return __uint_as_float(lds32(addr)); }
__device__ __forceinline__ void sts32(uint32_t addr, uint32_t v) { asm volatile("st.shared.u32 [%0], %1;\n" ::"r"(addr), "r"(v) : "memory"); }
__device__ __forceinline__ void stsf(uint32_t addr, float v) { sts32(addr, __float_as_uint(v)); }
__device__ __forceinline__ void sts64(uint32_t addr, uint32_t a, uint32_t b) { asm volatile("st.shared.v2.u32 [%0], {%1,%2};\n" ::"r"(addr), "r"(a), "r"(b) : "memory"); }
__device__ __forceinline__ void sts64f(uint32_t addr, float a, float b) { sts64(addr, __float_as_uint(a), __float_as_uint(b)); }
__device__ __forceinline__ void sts128(uint32_t addr, uint32_t a, uint32_t b, uint32_t c, uint32_t d) {
    asm volatile("st.shared.v4.u32 [%0], {%1,%2,%3,%4};\n" ::"r"(addr), "r"(a), "r"(b), "r"(c), "r"(d) : "memory");
}
__device__ __forceinline__ void sts128f(uint32_t addr, const float (&v)[4]) {
    sts128(addr, __float_as_uint(v[0]), __float_as_uint(v[1]), __float_as_uint(v[2]), __float_as_uint(v[3]));
}
__device__ __forceinline__ void ldsm_x4(uint32_t& r0, uint32_t& r1, uint32_t& r2, uint32_t& r3, uint32_t addr) {
    asm volatile("ldmatrix.sync.aligned.m8n8.x4.shared.b16 {%0,%1,%2,%3}, [%4];\n"
                 : "=r"(r0), "=r"(r1), "=r"(r2), "=r"(r3) : "r"(addr) : "memory");
}
__device__ __forceinline__ void ldsm_x4_t(uint32_t& r0, uint32_t& r1, uint32_t& r2, uint32_t& r3, uint32_t addr) {
    asm volatile("ldmatrix.sync.aligned.m8n8.x4.trans.shared.b16 {%0,%1,%2,%3}, [%4];\n"
                 : "=r"(r0), "=r"(r1), "=r"(r2), "=r"(r3) : "r"(addr) : "memory");
}
__device__ __forceinline__ void ldsm_x2_t(uint32_t& r0, uint32_t& r1, uint32_t addr) {
    asm volatile("ldmatrix.sync.aligned.m8n8.x2.trans.shared.b16 {%0,%1}, [%2];\n" : "=r"(r0), "=r"(r1) : "r"(addr) : "memory");
}
__device__ __forceinline__ void ldsm_x1_t(uint32_t& r0, uint32_t addr) {
    asm volatile("ldmatrix.sync.aligned.m8n8.x1.trans.shared.b16 {%0}, [%1];\n" : "=r"(r0) : "r"(addr) : "memory");
}
__device__ __forceinline__ uint32_t movm(uint32_t a) {
    uint32_t d;
    asm volatile("movmatrix.sync.aligned.m8n8.trans.b16 %0, %1;\n" : "=r"(d) : "r"(a));
    return d;
}
__device__ __forceinline__ void mma_f16(float (&c)[4], uint32_t a0, uint32_t a1, uint32_t a2, uint32_t a3, uint32_t b0, uint32_t b1) {
    asm volatile(
        "mma.sync.aligned.m16n8k16.row.col.f32.f16.f16.f32 {%0,%1,%2,%3}, {%4,%5,%6,%7}, {%8,%9}, {%0,%1,%2,%3};\n"
        : "+f"(c[0]), "+f"(c[1]), "+f"(c[2]), "+f"(c[3])
        : "r"(a0), "r"(a1), "r"(a2), "r"(a3), "r"(b0), "r"(b1));
}
__device__ __forceinline__ void mma_bf16(float (&c)[4], uint32_t a0, uint32_t a1, uint32_t a2, uint32_t a3, uint32_t b0, uint32_t b1) {
    asm volatile(
        "mma.sync.aligned.m16n8k16.row.col.f32.bf16.bf16.f32 {%0,%1,%2,%3}, {%4,%5,%6,%7}, {%8,%9}, {%0,%1,%2,%3};\n"
        : "+f"(c[0]), "+f"(c[1]), "+f"(c[2]), "+f"(c[3])
        : "r"(a0), "r"(a1), "r"(a2), "r"(a3), "r"(b0), "r"(b1));
}
__device__ __forceinline__ void bar_sync(int id, int n) { asm volatile("bar.sync %0, %1;\n" ::"r"(id), "r"(n) : "memory"); }
__device__ __forceinline__ void bar_arrive(int id, int n) { asm volatile("bar.arrive %0, %1;\n" ::"r"(id), "r"(n) : "memory"); }
__device__ __forceinline__ uint4 ld_poll(const void* p) {
    uint4 v;
    asm volatile("ld.relaxed.gpu.global.v4.u32 {%0,%1,%2,%3}, [%4];\n" : "=r"(v.x), "=r"(v.y), "=r"(v.z), "=r"(v.w) : "l"(p) : "memory");
    return v;
}
__device__ __forceinline__ uint2 ld_poll64(const void* p) {
    uint2 v;
    asm volatile("ld.relaxed.gpu.global.v2.u32 {%0,%1}, [%2];\n" : "=r"(v.x), "=r"(v.y) : "l"(p) : "memory");
    return v;
}
__device__ __forceinline__ uint32_t ld_poll32(const void* p) {
    uint32_t v;
    asm volatile("ld.relaxed.gpu.global.u32 %0, [%1];\n" : "=r"(v) : "l"(p) : "memory");
    return v;
}
__device__ __forceinline__ uint4 ldg128(const void* p) {
    uint4 v;
    asm volatile("ld.global.nc.v4.u32 {%0,%1,%2,%3}, [%4];\n" : "=r"(v.x), "=r"(v.y), "=r"(v.z), "=r"(v.w) : "l"(p));
    return v;
}
__device__ __forceinline__ uint2 ldg64(const void* p) {
    uint2 v;
    asm volatile("ld.global.nc.v2.u32 {%0,%1}, [%2];\n" : "=r"(v.x), "=r"(v.y) : "l"(p));
    return v;
}
__device__ __forceinline__ uint32_t ldg16(const void* p) {
    uint32_t v;
    asm volatile("ld.global.nc.u16 %0, [%1];\n" : "=r"(v) : "l"(p));
    return v;
}
__device__ __forceinline__ void stg128(void* p, uint32_t a, uint32_t b, uint32_t c, uint32_t d) {
    asm volatile("st.global.v4.u32 [%0], {%1,%2,%3,%4};\n" ::"l"(p), "r"(a), "r"(b), "r"(c), "r"(d) : "memory");
}
__device__ __forceinline__ void stg64(void* p, uint32_t a, uint32_t b) { asm volatile("st.global.v2.u32 [%0], {%1,%2};\n" ::"l"(p), "r"(a), "r"(b) : "memory"); }
__device__ __forceinline__ bool all_nz(const uint4& v) { return v.x && v.y && v.z && v.w; }
#define SPIN_LIMIT (1 << 21)
#define TRAP() __trap()
__device__ __forceinline__ void hint_arrive(unsigned* g_hint, int idx, int sub) {
    asm volatile("red.relaxed.gpu.global.add.u32 [%0], 1;\n" ::"l"(&g_hint[sub * 32 + idx]) : "memory");
}
__device__ __forceinline__ void hint_wait(const unsigned* g_hint, int idx, unsigned target) {
    unsigned l;
    asm volatile("mov.u32 %0, %%laneid;" : "=r"(l));
    const unsigned* c = &g_hint[(l & 7) * 32 + idx];
    int it = 0;
    while (__any_sync(0xffffffffu, (int)(ld_poll32(c) - target) < 0)) { if (++it > SPIN_LIMIT) TRAP(); }
}
__device__ __forceinline__ void mbar_init(uint32_t bar, uint32_t cnt) { asm volatile("mbarrier.init.shared::cta.b64 [%0], %1;\n" ::"r"(bar), "r"(cnt) : "memory"); }
__device__ __forceinline__ void mbar_expect(uint32_t bar, uint32_t bytes) {
    asm volatile("mbarrier.arrive.expect_tx.shared::cta.b64 _, [%0], %1;\n" ::"r"(bar), "r"(bytes) : "memory");
}
__device__ __forceinline__ void mbar_arrive(uint32_t bar) { asm volatile("mbarrier.arrive.shared::cta.b64 _, [%0];\n" ::"r"(bar) : "memory"); }
__device__ __forceinline__ void mbar_wait_cluster(uint32_t bar) {
    asm volatile(
        "{\n.reg .pred p;\n"
        "W_%=:\n"
        "mbarrier.try_wait.parity.acquire.cluster.shared::cta.b64 p, [%0], 0;\n"
        "@!p bra W_%=;\n}\n" ::"r"(bar) : "memory");
}
__device__ __forceinline__ void mbar_wait(uint32_t bar) {
    asm volatile(
        "{\n.reg .pred p;\n"
        "W_%=:\n"
        "mbarrier.try_wait.parity.shared::cta.b64 p, [%0], 0;\n"
        "@!p bra W_%=;\n}\n" ::"r"(bar) : "memory");
}
__device__ __forceinline__ bool mbar_test(uint32_t bar) {
    uint32_t r;
    asm volatile("{\n.reg .pred p;\nmbarrier.test_wait.parity.shared::cta.b64 p, [%1], 0;\nselp.u32 %0, 1, 0, p;\n}\n" : "=r"(r) : "r"(bar) : "memory");
    return __any_sync(0xffffffffu, r);
}
__device__ __forceinline__ void bulk_g2s(uint32_t dst, const void* src, uint32_t bytes, uint32_t bar) {
    asm volatile("cp.async.bulk.shared::cluster.global.mbarrier::complete_tx::bytes [%0], [%1], %2, [%3];\n" ::"r"(dst), "l"(src), "r"(bytes), "r"(bar) : "memory");
}
__device__ __forceinline__ void bulk_s2g(void* dst, uint32_t src, uint32_t bytes) {
    asm volatile("cp.async.bulk.global.shared::cta.bulk_group [%0], [%1], %2;\ncp.async.bulk.commit_group;\n" ::"l"(dst), "r"(src), "r"(bytes) : "memory");
}
__device__ __forceinline__ void tma_2d(uint32_t dst, const CUtensorMap* tm, int c0, int c1, uint32_t bar) {
    asm volatile("cp.async.bulk.tensor.2d.shared::cluster.global.mbarrier::complete_tx::bytes [%0], [%1, {%3, %4}], [%2];\n"
                 ::"r"(dst), "l"(tm), "r"(bar), "r"(c0), "r"(c1) : "memory");
}
__device__ __forceinline__ void tma_3d(uint32_t dst, const CUtensorMap* tm, int c0, int c1, int c2, uint32_t bar) {
    asm volatile("cp.async.bulk.tensor.3d.shared::cluster.global.mbarrier::complete_tx::bytes [%0], [%1, {%3, %4, %5}], [%2];\n"
                 ::"r"(dst), "l"(tm), "r"(bar), "r"(c0), "r"(c1), "r"(c2) : "memory");
}
__device__ __forceinline__ void tma_3d_mc(uint32_t dst, const CUtensorMap* tm, int c0, int c1, int c2, uint32_t bar) {
    asm volatile("cp.async.bulk.tensor.3d.shared::cluster.global.mbarrier::complete_tx::bytes.multicast::cluster [%0], [%1, {%3, %4, %5}], [%2], %6;\n"
                 ::"r"(dst), "l"(tm), "r"(bar), "r"(c0), "r"(c1), "r"(c2), "h"((unsigned short)3) : "memory");
}
__device__ __forceinline__ void tma_st_3d(const CUtensorMap* tm, uint32_t src, int c0, int c1, int c2) {
    asm volatile("cp.async.bulk.tensor.3d.global.shared::cta.bulk_group [%0, {%2, %3, %4}], [%1];\ncp.async.bulk.commit_group;\n"
                 ::"l"(tm), "r"(src), "r"(c0), "r"(c1), "r"(c2) : "memory");
}
__device__ __forceinline__ void l2_prefetch(const void* src, uint32_t bytes) {
    asm volatile("cp.async.bulk.prefetch.L2.global [%0], %1;\n" ::"l"(src), "r"(bytes) : "memory");
}
__device__ __forceinline__ bool elect_one() {
    uint32_t r;
    asm volatile("{\n.reg .pred p;\nelect.sync _|p, 0xffffffff;\nselp.u32 %0, 1, 0, p;\n}\n" : "=r"(r));
    return r;
}
__device__ __forceinline__ void fence_async() { asm volatile("fence.proxy.async.shared::cta;\n" ::: "memory"); }

__device__ __forceinline__ float2 cmul(float2 a, float2 b) {
    return make_float2(fmaf(a.x, b.x, -a.y * b.y), fmaf(a.x, b.y, a.y * b.x));
}
__device__ __forceinline__ float2 csq(float2 a) {
    float p = a.x * a.y;
    return make_float2(fmaf(a.x, a.x, -a.y * a.y), p + p);
}
__device__ __forceinline__ float2 cexp_e(float lr2, float rh, float rl, float e) {
    float m;
    asm("ex2.approx.ftz.f32 %0, %1;\n" : "=f"(m) : "f"(lr2 * e));
    const float a = rh * e;
    const float r = fmaf(rl, e, a - rintf(a)) * 6.283185307179586f;
    return make_float2(m * __cosf(r), m * __sinf(r));
}
__device__ __forceinline__ float rcp_approx(float x) { float r; asm("rcp.approx.ftz.f32 %0, %1;\n" : "=f"(r) : "f"(x)); return r; }
__device__ __forceinline__ float sqrt_approx(float x) { float r; asm("sqrt.approx.f32 %0, %1;\n" : "=f"(r) : "f"(x)); return r; }

__device__ __forceinline__ void wg_fence() { asm volatile("wgmma.fence.sync.aligned;\n" ::: "memory"); }
__device__ __forceinline__ void wg_commit() { asm volatile("wgmma.commit_group.sync.aligned;\n" ::: "memory"); }
__device__ __forceinline__ void wg_wait0() { asm volatile("wgmma.wait_group.sync.aligned 0;\n" ::: "memory"); }
template <int T0, int NT> __device__ __forceinline__ void wg_h(uint32_t (&acc)[32], const uint32_t (&a)[4], uint64_t desc);
template <> __device__ __forceinline__ void wg_h<0, 16>(uint32_t (&acc)[32], const uint32_t (&a)[4], uint64_t desc) {
    asm volatile("wgmma.mma_async.sync.aligned.m64n128k16.f16.f16.f16 {%0,%1,%2,%3,%4,%5,%6,%7,%8,%9,%10,%11,%12,%13,%14,%15,%16,%17,%18,%19,%20,%21,%22,%23,%24,%25,%26,%27,%28,%29,%30,%31}, {%32,%33,%34,%35}, %36, 1, 1, 1, 0;\n"
                 : "+r"(acc[0]), "+r"(acc[1]), "+r"(acc[2]), "+r"(acc[3]), "+r"(acc[4]), "+r"(acc[5]), "+r"(acc[6]), "+r"(acc[7]), "+r"(acc[8]), "+r"(acc[9]), "+r"(acc[10]), "+r"(acc[11]), "+r"(acc[12]), "+r"(acc[13]), "+r"(acc[14]), "+r"(acc[15]), "+r"(acc[16]), "+r"(acc[17]), "+r"(acc[18]), "+r"(acc[19]), "+r"(acc[20]), "+r"(acc[21]), "+r"(acc[22]), "+r"(acc[23]), "+r"(acc[24]), "+r"(acc[25]), "+r"(acc[26]), "+r"(acc[27]), "+r"(acc[28]), "+r"(acc[29]), "+r"(acc[30]), "+r"(acc[31])
                 : "r"(a[0]), "r"(a[1]), "r"(a[2]), "r"(a[3]), "l"(desc));
}
template <> __device__ __forceinline__ void wg_h<4, 4>(uint32_t (&acc)[32], const uint32_t (&a)[4], uint64_t desc) {
    asm volatile("wgmma.mma_async.sync.aligned.m64n32k16.f16.f16.f16 {%0,%1,%2,%3,%4,%5,%6,%7}, {%8,%9,%10,%11}, %12, 1, 1, 1, 0;\n"
                 : "+r"(acc[8]), "+r"(acc[9]), "+r"(acc[10]), "+r"(acc[11]), "+r"(acc[12]), "+r"(acc[13]), "+r"(acc[14]), "+r"(acc[15])
                 : "r"(a[0]), "r"(a[1]), "r"(a[2]), "r"(a[3]), "l"(desc));
}
template <> __device__ __forceinline__ void wg_h<8, 4>(uint32_t (&acc)[32], const uint32_t (&a)[4], uint64_t desc) {
    asm volatile("wgmma.mma_async.sync.aligned.m64n32k16.f16.f16.f16 {%0,%1,%2,%3,%4,%5,%6,%7}, {%8,%9,%10,%11}, %12, 1, 1, 1, 0;\n"
                 : "+r"(acc[16]), "+r"(acc[17]), "+r"(acc[18]), "+r"(acc[19]), "+r"(acc[20]), "+r"(acc[21]), "+r"(acc[22]), "+r"(acc[23])
                 : "r"(a[0]), "r"(a[1]), "r"(a[2]), "r"(a[3]), "l"(desc));
}
template <> __device__ __forceinline__ void wg_h<12, 4>(uint32_t (&acc)[32], const uint32_t (&a)[4], uint64_t desc) {
    asm volatile("wgmma.mma_async.sync.aligned.m64n32k16.f16.f16.f16 {%0,%1,%2,%3,%4,%5,%6,%7}, {%8,%9,%10,%11}, %12, 1, 1, 1, 0;\n"
                 : "+r"(acc[24]), "+r"(acc[25]), "+r"(acc[26]), "+r"(acc[27]), "+r"(acc[28]), "+r"(acc[29]), "+r"(acc[30]), "+r"(acc[31])
                 : "r"(a[0]), "r"(a[1]), "r"(a[2]), "r"(a[3]), "l"(desc));
}
template <> __device__ __forceinline__ void wg_h<0, 8>(uint32_t (&acc)[32], const uint32_t (&a)[4], uint64_t desc) {
    asm volatile("wgmma.mma_async.sync.aligned.m64n64k16.f16.f16.f16 {%0,%1,%2,%3,%4,%5,%6,%7,%8,%9,%10,%11,%12,%13,%14,%15}, {%16,%17,%18,%19}, %20, 1, 1, 1, 0;\n"
                 : "+r"(acc[0]), "+r"(acc[1]), "+r"(acc[2]), "+r"(acc[3]), "+r"(acc[4]), "+r"(acc[5]), "+r"(acc[6]), "+r"(acc[7]), "+r"(acc[8]), "+r"(acc[9]), "+r"(acc[10]), "+r"(acc[11]), "+r"(acc[12]), "+r"(acc[13]), "+r"(acc[14]), "+r"(acc[15])
                 : "r"(a[0]), "r"(a[1]), "r"(a[2]), "r"(a[3]), "l"(desc));
}
template <> __device__ __forceinline__ void wg_h<4, 12>(uint32_t (&acc)[32], const uint32_t (&a)[4], uint64_t desc) {
    asm volatile("wgmma.mma_async.sync.aligned.m64n96k16.f16.f16.f16 {%0,%1,%2,%3,%4,%5,%6,%7,%8,%9,%10,%11,%12,%13,%14,%15,%16,%17,%18,%19,%20,%21,%22,%23}, {%24,%25,%26,%27}, %28, 1, 1, 1, 0;\n"
                 : "+r"(acc[8]), "+r"(acc[9]), "+r"(acc[10]), "+r"(acc[11]), "+r"(acc[12]), "+r"(acc[13]), "+r"(acc[14]), "+r"(acc[15]), "+r"(acc[16]), "+r"(acc[17]), "+r"(acc[18]), "+r"(acc[19]), "+r"(acc[20]), "+r"(acc[21]), "+r"(acc[22]), "+r"(acc[23]), "+r"(acc[24]), "+r"(acc[25]), "+r"(acc[26]), "+r"(acc[27]), "+r"(acc[28]), "+r"(acc[29]), "+r"(acc[30]), "+r"(acc[31])
                 : "r"(a[0]), "r"(a[1]), "r"(a[2]), "r"(a[3]), "l"(desc));
}

#define EARLYN 2
#define PAUSE 2
#define PCNT (32 + ((PAUSE & 1) ? 288 : 0) + ((PAUSE & 6) ? 320 : 64))
#define LNAT 2
#define UW 4
#define FINAT 3
#define UAT 2
#define PF1 0
#define PF2 0
#define PFW 11
#define HK 9
#define TOKEN_OF(g) (16 * ((g) & 1) + ((g) >> 2) + 2 * ((g) & 2))
#define HI2(a, b) (pack_f16_rz(__uint_as_float(a), __uint_as_float(b)) & 0xfff8fff8u)
struct Params {
    const bf16 *x, *lar, *aim, *cre, *cim, *ldt, *dsk;
    Scratch* s;
    const bf16 *wr, *wpf;
    bf16* out;
};

template <int NK>
__device__ __forceinline__ void ln_partial(const uint32_t (&H)[2][NK], uint32_t lp, int warp, int g, int t) {
    float cs[4] = {0.f, 0.f, 0.f, 0.f}, cl[4] = {0.f, 0.f, 0.f, 0.f}, ch[4] = {0.f, 0.f, 0.f, 0.f};
#pragma unroll
    for (int k = 0; k < NK; k += 2) {
        uint32_t a0, a1, a2, a3;
        asm volatile("prmt.b32 %0, %4, %4, %8;\nprmt.b32 %1, %5, %5, %8;\nprmt.b32 %2, %6, %6, %8;\nprmt.b32 %3, %7, %7, %8;\n"
                     : "=r"(a0), "=r"(a1), "=r"(a2), "=r"(a3) : "r"(H[0][k]), "r"(H[1][k]), "r"(H[0][k + 1]), "r"(H[1][k + 1]), "r"(0x3210u + (warp >> 8)));
        mma_bf16(cl, a0, a1, a2, a3, H[0][k], H[0][k + 1]);
        mma_bf16(ch, a0, a1, a2, a3, H[1][k], H[1][k + 1]);
        mma_bf16(cs, a0, a1, a2, a3, 0x3f803f80u, 0x3f803f80u);
    }
    const uint32_t a = lp + (g * 20 + warp) * 4;
    if (t == 0) {
        stsf(a, cs[0]); stsf(a + 8 * 80, cs[2]);
    }
    if (t == (g >> 1)) { stsf(a + 16 * 80, (g & 1) ? cl[1] : cl[0]); stsf(a + 24 * 80, (g & 1) ? ch[3] : ch[2]); }
}
__device__ __forceinline__ float sum18(uint32_t a) {
    const uint4 p = lds128(a), q = lds128(a + 16), r = lds128(a + 32), s = lds128(a + 48);
    const uint2 u = lds64(a + 64);
#define F(x) __uint_as_float(x)
    return (((F(p.x) + F(p.y)) + (F(p.z) + F(p.w))) + ((F(q.x) + F(q.y)) + (F(q.z) + F(q.w)))) +
           (((F(r.x) + F(r.y)) + (F(r.z) + F(r.w))) + ((F(s.x) + F(s.y)) + (F(s.z) + F(s.w))) + (F(u.x) + F(u.y)));
#undef F
}
__device__ __forceinline__ float sum9(uint32_t a) {
    const uint4 p = lds128(a), q = lds128(a + 16);
#define F(x) __uint_as_float(x)
    return (((F(p.x) + F(p.y)) + (F(p.z) + F(p.w))) + ((F(q.x) + F(q.y)) + (F(q.z) + F(q.w)))) + ldsf(a + 32);
#undef F
}
template <int N>
__device__ __forceinline__ void ln_finish(uint32_t lp, int lane, float& mb, float& rc) {
    const float v = N == 9 ? sum9(lp + lane * 80) : sum18(lp + lane * 80);
    const float o = __shfl_xor_sync(0xffffffffu, v, 16);
    const float sm = lane < 16 ? v : o, m0 = sm * (1.0f / 576.0f);
    const float mean = fmaf(fmaf(-m0, 576.0f, sm), 1.0f / 576.0f, m0);
    const float var = fmaxf(fmaf(-mean, mean, (lane < 16 ? o : v) * (1.0f / 576.0f)), 0.f);
    mb = rbf(mean);
    rc = rcp_approx(rbf(sqrt_approx(rbf(rbf(var) + 1e-5f))));
}
__device__ __forceinline__ uint32_t ln_apply(uint32_t w, const uint2& st) {
    uint32_t r;
    asm("{\n.reg .b16 m, t, h, l;\n.reg .b32 mm, hh, ll, d, e;\nmov.b32 {m, t}, %2;\nmov.b32 {h, l}, %3;\nmov.b32 mm, {m, m};\nmov.b32 hh, {h, h};\nmov.b32 ll, {l, l};\n"
        "sub.rn.bf16x2 d, %1, mm;\nmul.rn.bf16x2 e, d, ll;\nfma.rn.bf16x2 %0, d, hh, e;\n}\n" : "=r"(r) : "r"(w), "r"(st.x), "r"(st.y));
    return r;
}
__device__ __forceinline__ void stat_store(uint32_t a, float mb, float rc, uint32_t extra) {
    const float rh = rbf(rc);
    sts64(a, (__float_as_uint(mb) >> 16) | (extra << 16), pack_bf16(rh, rc - rh));
}

__device__ __forceinline__ void hcmul(uint32_t re, uint32_t im, uint32_t z, uint32_t& ore, uint32_t& oim) {
    asm("{\n.reg .b16 x, y;\n.reg .b32 xx, yy, ny, a, b;\nmov.b32 {x, y}, %4;\nmov.b32 xx, {x, x};\nmov.b32 yy, {y, y};\nneg.f16x2 ny, yy;\n"
        "mul.rn.f16x2 a, %2, xx;\nfma.rn.f16x2 %0, %3, ny, a;\nmul.rn.f16x2 b, %3, xx;\nfma.rn.f16x2 %1, %2, yy, b;\n}\n" : "=&r"(ore), "=r"(oim) : "r"(re), "r"(im), "r"(z));
}
__device__ __forceinline__ void hcmul(uint32_t re, uint32_t im, uint32_t zx, uint32_t zy, uint32_t& ore, uint32_t& oim) {
    asm("{\n.reg .b32 ny, a, b;\nneg.f16x2 ny, %5;\n"
        "mul.rn.f16x2 a, %2, %4;\nfma.rn.f16x2 %0, %3, ny, a;\nmul.rn.f16x2 b, %3, %4;\nfma.rn.f16x2 %1, %2, %5, b;\n}\n" : "=&r"(ore), "=r"(oim) : "r"(re), "r"(im), "r"(zx), "r"(zy));
}

struct KGen {
    uint32_t Af[4][4];
    float2 z1, z8, z64, z128, T[9];
    uint32_t zw;
};
__device__ __forceinline__ void kgen_setup(KGen& k, uint32_t pa, float dt) {
    const float A = rbf(expf(bf_lo(pa)));
    const float lr2 = -(A * dt) * 1.4426950408889634f;
    const float li = bf_hi(pa) * dt;
    const float rh = li * 0.15915494309189535f;
    const float rl = fmaf(li, 6.4206382986e-9f, fmaf(li, 0.15915494309189535f, -rh));
    k.z1 = cexp_e(lr2, rh, rl, 1.0f);
    k.z8 = cexp_e(lr2, rh, rl, 8.0f);
    k.z64 = cexp_e(lr2, rh, rl, 64.0f);
}
__device__ __forceinline__ void kgen_rows(KGen& k, uint32_t tb, int lane) {
    const float2 z8 = k.z8, z64 = k.z64;
    const uint32_t row = tb + lane * TBP;
    k.z128 = csq(z64);
    const float2 z16 = csq(z8), z32 = csq(z16), z48 = cmul(z32, z16), z80 = cmul(z64, z16), z96 = cmul(z64, z32), z112 = cmul(z64, z48);
    uint32_t re[4], im[4], a[4], b[4];
    re[0] = pack_f16(1.0f, z16.x); im[0] = pack_f16(0.0f, z16.y);
    re[1] = pack_f16(z32.x, z48.x); im[1] = pack_f16(z32.y, z48.y);
    re[2] = pack_f16(z64.x, z80.x); im[2] = pack_f16(z64.y, z80.y);
    re[3] = pack_f16(z96.x, z112.x); im[3] = pack_f16(z96.y, z112.y);
    sts128(row, re[0], re[1], re[2], re[3]);
    sts128(row + 32, im[0], im[1], im[2], im[3]);
    const uint32_t zz = pack_f16(z8.x, z8.y);
#pragma unroll
    for (int j = 0; j < 4; j++) hcmul(re[j], im[j], zz, a[j], b[j]);
    sts128(row + 16, a[0], a[1], a[2], a[3]);
    sts128(row + 48, b[0], b[1], b[2], b[3]);
    __syncwarp();
    const int mi = lane >> 3;
    const uint32_t ad = tb + (lane & 7) * TBP + mi * 16;
#pragma unroll
    for (int ks = 0; ks < 4; ks++) ldsm_x4_t(k.Af[ks][0], k.Af[ks][1], k.Af[ks][2], k.Af[ks][3], ad + ks * 8 * TBP);
}
__device__ __forceinline__ void kgen_chain(KGen& k, uint32_t pc, float cs) {
    k.T[0] = make_float2(bf_lo(pc) * cs, -bf_hi(pc) * cs);
    const float2 y1 = make_float2(k.z1.x, -k.z1.y);
#pragma unroll
    for (int c = 1; c < 8; c++) k.T[c] = cmul(k.T[c - 1], y1);
    k.T[8] = cmul(k.T[0], make_float2(k.z8.x, -k.z8.y));
}
__device__ __forceinline__ void kgen_cols(KGen& k, uint32_t tb, int lane) {
    const uint32_t row = tb + lane * TBP;
    const float2 (&T)[9] = k.T;
    const uint32_t zv = pack_f16(k.z128.x, k.z128.y), zo = __shfl_xor_sync(0xffffffffu, zv, 1);
    k.zw = (lane & 1) ? __byte_perm(zo, zv, 0x7632) : __byte_perm(zv, zo, 0x5410);
    const float2 y256 = csq(make_float2(k.z128.x, -k.z128.y)), y512 = csq(y256), y768 = cmul(y512, y256), y1024 = csq(y512);
    const float2 c1032 = cmul(T[8], y1024);
    const uint32_t r04 = pack_f16(T[0].x, T[4].x), i04 = pack_f16(T[0].y, T[4].y), r26 = pack_f16(T[2].x, T[6].x), i26 = pack_f16(T[2].y, T[6].y);
    const uint32_t r48 = pack_f16(T[4].x, T[8].x), i48 = pack_f16(T[4].y, T[8].y);
    __syncwarp();
    sts128(row, r04, pack_f16(T[1].x, T[5].x), r26, pack_f16(T[3].x, T[7].x));
    sts128(row + 16, i04, pack_f16(T[1].y, T[5].y), i26, pack_f16(T[3].y, T[7].y));
    uint32_t a[4], b[4];
    {
        const uint32_t zz = pack_f16(y256.x, y256.y);
        hcmul(r04, i04, zz, a[0], b[0]);
        hcmul(r26, i26, zz, a[2], b[2]);
        hcmul(r48, i48, zz, a[3], b[3]);
    }
    sts128(row + 32, a[0], a[0], a[2], a[3]);
    sts128(row + 48, b[0], b[0], b[2], b[3]);
    {
        hcmul(r48, i48, pack_f16(y512.x, y512.y), a[0], b[0]);
        hcmul(r48, i48, pack_f16(y768.x, y768.y), a[1], b[1]);
        const uint32_t zz = pack_f16(c1032.x, c1032.y);
        hcmul(pack_f16(1.0f, y256.x), pack_f16(0.0f, y256.y), zz, a[2], b[2]);
        hcmul(pack_f16(y512.x, y768.x), pack_f16(y512.y, y768.y), zz, a[3], b[3]);
    }
    sts128(row + 64, a[0], a[1], a[2], a[3]);
    sts128(row + 80, b[0], b[1], b[2], b[3]);
}
__device__ __forceinline__ void kgen_mma(const KGen& k, uint32_t tb, int lane) {
    const int t = lane & 3;
    const uint32_t zw = k.zw;
    uint32_t zx[4], zy[4];
#pragma unroll
    for (int ks = 0; ks < 4; ks++) { zx[ks] = __shfl_sync(0xffffffffu, zw, 8 * ks + 2 * t); zy[ks] = __shfl_sync(0xffffffffu, zw, 8 * ks + 2 * t + 1); }
    __syncwarp();
    float acc[2][3][4];
#pragma unroll
    for (int i = 0; i < 6; i++)
#pragma unroll
        for (int j = 0; j < 4; j++) acc[i / 3][i % 3][j] = 0.f;
    {
        const int mi = lane >> 3;
        const uint32_t bd = tb + ((lane & 7) + 8 * (mi >> 1)) * TBP + (mi & 1) * 16;
#pragma unroll
        for (int kp = 0; kp < 2; kp++) {
            uint32_t b[3][4];
#pragma unroll
            for (int j = 0; j < 3; j++) ldsm_x4_t(b[j][0], b[j][1], b[j][2], b[j][3], bd + kp * 16 * TBP + j * 32);
#pragma unroll
            for (int h = 0; h < 2; h++) {
                const int ks = 2 * kp + h;
                uint32_t d[4];
                hcmul(k.Af[ks][0], k.Af[ks][2], zx[ks], zy[ks], d[0], d[2]);
                hcmul(k.Af[ks][1], k.Af[ks][3], zx[ks], zy[ks], d[1], d[3]);
#pragma unroll
                for (int j = 0; j < 3; j++) {
                    mma_f16(acc[0][j], k.Af[ks][0], k.Af[ks][1], k.Af[ks][2], k.Af[ks][3], b[j][2 * h], b[j][2 * h + 1]);
                    mma_f16(acc[1][j], d[0], d[1], d[2], d[3], b[j][2 * h], b[j][2 * h + 1]);
                }
            }
        }
    }
    __syncwarp();
#pragma unroll
    for (int h = 0; h < 2; h++) {
        sts64(tb + h * 256 + lane * 8, pack_f16(acc[h][0][0], acc[h][0][1]), pack_f16(acc[h][0][2], acc[h][0][3]));
        sts64(tb + 512 + h * 256 + lane * 8, pack_f16(acc[h][1][0], acc[h][1][1]), pack_f16(acc[h][1][2], acc[h][1][3]));
        sts32(tb + 1024 + h * 256 + lane * 4, pack_f16(acc[h][2][0], t < 2 ? acc[h][2][1] : acc[h][2][2]));
        sts32(tb + 1152 + h * 256 + lane * 4, pack_f16(t < 2 ? acc[h][2][2] : acc[h][2][1], acc[h][2][3]));
    }
}
__device__ __forceinline__ uint32_t table_buf(uint32_t sb, int warp) { return sb + SM_TB + warp * TBW; }

__device__ __forceinline__ void kgen_combine(uint32_t sb, int warp, int lane, uint32_t kw, uint32_t ao) {
    const int wq = warp & 3;
    const uint32_t a = table_buf(sb, warp & ~3) + wq * 256 + lane * 8, c = table_buf(sb, warp & ~3) + 1024 + wq * 128 + lane * 4;
    const int t = lane & 3;
    const uint32_t o0 = (t < 2 ? KW_T2 + KW_KH + 16 + t * 256 - (wq & 1) * KW_KH : KW_T3 + 16 - 1024 + t * 512 + (wq & 1) * 256) + (lane >> 2) * 16;
    const uint4 o = make_uint4(o0 + t * 36, o0 + (t ^ 1) * 36, o0 + (t ^ 2) * 36, o0 + (t ^ 3) * 36);
    const uint2 u = lds64(a), v = lds64(a + TBW), w = lds64(a + 2 * TBW), x = lds64(a + 3 * TBW);
    const uint32_t kt = hadd2(hadd2(lds32(c), lds32(c + TBW)), hadd2(lds32(c + 2 * TBW), lds32(c + 3 * TBW)));
    const uint32_t k23 = hadd2(hadd2(u.y, v.y), hadd2(w.y, x.y));
    sts64(kw + wq * 64 + ao, hadd2(hadd2(u.x, v.x), hadd2(w.x, x.x)), k23);
    const uint32_t d = kw + (wq >> 1) * 128;
    const uint32_t kh = hmul2(kt, 0x38003800u);
    sts32(d + o.x, kh); sts32(d + o.y, kh); sts32(d + o.z, kh); sts32(d + o.w, kh);
    if (wq == 3) {
        if (lane == 31) { sts32(kw + 264, k23 >> 16); sts32(kw + 288 + 264, k23 >> 16); sts32(kw + 576 + 264, k23 >> 16); }
        if (lane == 29) { sts32(kw + 864 + 280, kt >> 16); sts32(kw + 280, kt & 0xffff0000u); }
    }
}

__device__ __forceinline__ int c_exponent(const uint2& r, const uint2& i) {
    uint32_t mx = __vmaxu2(__vmaxu2(r.x & 0x7fff7fffu, r.y & 0x7fff7fffu), __vmaxu2(i.x & 0x7fff7fffu, i.y & 0x7fff7fffu));
    mx = __reduce_max_sync(0xffffffffu, max(mx & 0xffffu, mx >> 16));
    return min(max((int)(mx >> 7), 4), 240);
}

__device__ __forceinline__ int warp_v() { int l; asm volatile("mov.u32 %0, %%tid.x;" : "=r"(l)); return __shfl_sync(0xffffffffu, l >> 5, 0); }
__device__ __forceinline__ int lane_v() { int l; asm volatile("mov.u32 %0, %%laneid;" : "=r"(l)); return l; }
__device__ __forceinline__ uint32_t prmt(uint32_t a, uint32_t b, uint32_t s) { uint32_t d; asm("prmt.b32 %0, %1, %2, %3;\n" : "=r"(d) : "r"(a), "r"(b), "r"(s)); return d; }
__device__ __forceinline__ uint32_t prmt_v(uint32_t a, uint32_t b, uint32_t s) { uint32_t d; asm volatile("prmt.b32 %0, %1, %2, %3;\n" : "=r"(d) : "r"(a), "r"(b), "r"(s)); return d; }
__device__ __forceinline__ void mmah16(uint32_t& d0, uint32_t& d1, uint32_t a0, uint32_t a1, uint32_t a2, uint32_t a3, uint32_t b0, uint32_t b1, uint32_t c0, uint32_t c1) {
    asm volatile("mma.sync.aligned.m16n8k16.row.col.f16.f16.f16.f16 {%0,%1}, {%2,%3,%4,%5}, {%6,%7}, {%8,%9};\n"
                 : "=r"(d0), "=r"(d1) : "r"(a0), "r"(a1), "r"(a2), "r"(a3), "r"(b0), "r"(b1), "r"(c0), "r"(c1));
}
__device__ __forceinline__ void mmah8(uint32_t& d0, uint32_t& d1, uint32_t a0, uint32_t a1, uint32_t b0, uint32_t c0, uint32_t c1) {
    asm volatile("mma.sync.aligned.m16n8k8.row.col.f16.f16.f16.f16 {%0,%1}, {%2,%3}, {%4}, {%5,%6};\n"
                 : "=r"(d0), "=r"(d1) : "r"(a0), "r"(a1), "r"(b0), "r"(c0), "r"(c1));
}
template <int A = 8, int B = 32>
__device__ __forceinline__ void conv_rename(uint32_t (&acc)[32]) {
#pragma unroll
    for (int i = A; i < B; i++) { uint32_t v; asm volatile("mov.b32 %0, %1;\n" : "=r"(v) : "r"(acc[i])); acc[i] = v; }
}
__host__ __device__ constexpr uint32_t band_bits(int hw, int sh) {
    uint32_t c = 0;
    for (int s = 0; s <= 10; s++)
        for (int e = 0; e < 2; e++) {
            const int v = s - 3 + sh - 4 * e;
            if (v <= hw && v >= -hw) c |= 1u << (14 + 16 * e - s);
        }
    return c;
}
template <int HW, int SH, int J> __device__ __forceinline__ uint32_t band(uint32_t p2) {
    uint32_t d;
    asm volatile("{\n.reg .b32 t;\nmul.lo.u32 t, %1, %2;\nand.b32 %0, t, 0x40004000;\n}\n" : "=r"(d) : "r"(p2), "n"(band_bits(HW, SH) | J));
    return d;
}
template <int H0, int SH> __device__ __forceinline__ void band_pair(uint4& l, uint4& u, uint32_t p2) {
    l = make_uint4(band<H0, 8, 1>(p2), band<H0 - 1, SH + 8, 2>(p2), band<H0, 0, 1>(p2), band<H0 - 1, SH, 1>(p2));
    u = make_uint4(band<H0, 0, 2>(p2), band<H0 - 1, SH, 2>(p2), band<H0, -8, 1>(p2), band<H0 - 1, SH - 8, 1>(p2));
}
__device__ __forceinline__ void run_sums(uint32_t (&G)[3][2], const uint32_t (&c)[5], const uint4& l, const uint4& u) {
    mmah8(G[0][0], G[0][1], l.x, l.y, c[0], 0u, 0u);
    mmah8(G[1][0], G[1][1], u.z, u.w, c[3], 0u, 0u);
    mmah8(G[2][0], G[2][1], l.x, l.y, c[2], 0u, 0u);
    mmah16(G[0][0], G[0][1], u.x, u.y, u.z, u.w, c[1], c[2], G[0][0], G[0][1]);
    mmah16(G[1][0], G[1][1], l.x, l.y, l.z, l.w, c[1], c[2], G[1][0], G[1][1]);
    mmah16(G[2][0], G[2][1], u.x, u.y, u.z, u.w, c[3], c[4], G[2][0], G[2][1]);
}
__device__ __forceinline__ float h_lo(uint32_t w) { return __half2float(__ushort_as_half((unsigned short)(w & 0xffffu))); }
__device__ __forceinline__ float h_hi(uint32_t w) { return __half2float(__ushort_as_half((unsigned short)(w >> 16))); }
__device__ __forceinline__ uint64_t smem_desc(uint32_t sb, uint32_t o16, uint32_t lbo) {
    uint64_t d;
    asm("mov.b64 %0, {%1, %2};" : "=l"(d) : "r"(((sb & 0x3FFFF) >> 4) + o16 + (lbo << 12)), "r"(8));
    return d;
}
template <int I> struct IC { static constexpr int value = I; };

struct Conv {
    uint32_t u[3][5];
    uint32_t q2[3][2][4];
    uint32_t q3[2][4];
    uint32_t r[18];
};
__device__ __forceinline__ void conv_sums(Conv& c, uint32_t a0, uint32_t a1, const uint4 (&bd)[4]) {
    {
        uint32_t x;
        ldsm_x4(c.u[0][1], c.u[0][2], c.u[0][3], c.u[0][4], a1);
        ldsm_x4(c.u[0][0], c.u[1][0], c.u[2][0], x, a0);
#pragma unroll
        for (int q = 1; q < 3; q++) ldsm_x4(c.u[q][1], c.u[q][2], c.u[q][3], c.u[q][4], a1 + q * 512);
    }
    uint32_t G[3][2];
#pragma unroll
    for (int q = 0; q < 3; q++) {
        run_sums(G, c.u[q], bd[0], bd[1]);
#pragma unroll
        for (int e = 0; e < 2; e++) {
            const uint32_t s = e ? 0x7632u : 0x5410u;
            c.q2[q][e][0] = prmt(G[0][1], G[0][0], s); c.q2[q][e][1] = prmt(G[1][1], G[1][0], s);
            c.q2[q][e][2] = prmt(G[1][0], G[1][1], s ^ 0x4444u); c.q2[q][e][3] = prmt(G[2][1], G[2][0], s);
        }
    }
#pragma unroll
    for (int q = 0; q < 2; q++) {
        run_sums(G, c.u[q], bd[2], bd[3]);
        c.q3[q][0] = prmt(G[1][1], G[0][0], 0x7632u); c.q3[q][1] = prmt(G[2][1], G[1][0], 0x7632u);
        c.q3[q][2] = prmt(G[1][1], G[0][0], 0x5410u); c.q3[q][3] = prmt(G[2][1], G[1][0], 0x5410u);
    }
}
__device__ __forceinline__ void conv_edges(Conv& c, uint32_t (&acc)[32], uint32_t ka, uint32_t ks, uint32_t sel, int wq) {
#pragma unroll
    for (int i = 0; i < 32; i++) acc[i] = 0u;
    const uint4 r = lds128(ka + 256), s = lds128(ka + 272);
    const uint32_t a0 = prmt(r.x, r.y, sel), a1 = prmt(r.y, r.z, sel), a2 = prmt(r.z, r.w, sel), b1 = prmt(s.y, s.z, sel), b2 = prmt(s.z, s.w, sel);
    const uint32_t sw = sel ^ 0x4444u, a3 = prmt(r.z, r.y, sw), a4 = prmt(r.w, r.z, sw), b0 = prmt(s.x, s.y, sel), b3 = prmt(s.z, s.y, sw), b4 = prmt(s.w, s.z, sw);
#pragma unroll
    for (int q = 0; q < 3; q++) mmah8(acc[8 * q + 8], acc[8 * q + 9], a2, 0u, c.u[q][2], 0u, 0u);
#pragma unroll
    for (int q = 0; q < 2; q++) mmah8(acc[8 * q + 16], acc[8 * q + 17], b2, 0u, c.u[q][2], acc[8 * q + 16], acc[8 * q + 17]);
#pragma unroll
    for (int q = 0; q < 3; q++) mmah16(acc[8 * q + 8], acc[8 * q + 9], a1, a4, a0, a3, c.u[q][3], c.u[q][4], acc[8 * q + 8], acc[8 * q + 9]);
#pragma unroll
    for (int q = 0; q < 2; q++) mmah16(acc[8 * q + 16], acc[8 * q + 17], b1, b4, b0, b3, c.u[q][3], c.u[q][4], acc[8 * q + 16], acc[8 * q + 17]);
    {
        uint32_t t0, t1, t2, t3;
        ldsm_x4(t0, t1, t2, t3, ks);
#pragma unroll
        for (int q = 0; q < 2; q++) mmah16(acc[8 * q + 16], acc[8 * q + 17], c.q2[q][0][0], c.q2[q][0][1], c.q2[q][0][2], c.q2[q][0][3], t0, t1, acc[8 * q + 16], acc[8 * q + 17]);
#pragma unroll
        for (int q = 0; q < 2; q++) mmah16(acc[8 * q + 16], acc[8 * q + 17], c.q2[q][1][0], c.q2[q][1][1], c.q2[q][1][2], c.q2[q][1][3], t2, t3, acc[8 * q + 16], acc[8 * q + 17]);
    }
    {
        const uint32_t a = ka + wq * 64;
#pragma unroll
        for (int i = 0; i < 4; i++) { const uint4 v = lds128(a + i * 16); c.r[4 * i] = v.x; c.r[4 * i + 1] = v.y; c.r[4 * i + 2] = v.z; c.r[4 * i + 3] = v.w; }
        const uint2 v = lds64(a + 64);
        c.r[16] = v.x; c.r[17] = v.y;
    }
    if (sel == 0u) {
#pragma unroll
        for (int i = 0; i < 6; i++) sts128(ka + i * 16, c.q2[i >> 1][i & 1][0], c.q2[i >> 1][i & 1][1], c.q2[i >> 1][i & 1][2], c.q2[i >> 1][i & 1][3]);
#pragma unroll
        for (int i = 0; i < 2; i++) sts128(ka + i * 16, c.q3[i][0], c.q3[i][1], c.q3[i][2], c.q3[i][3]);
#pragma unroll
        for (int i = 1; i < 4; i++) sts64(ka + i * 16, acc[8 * i], acc[8 * i + 1]);
    }
    conv_rename(acc);
}
#define GATE 2
#define HAND 2
#define GA 6
#define GB 4
template <int TA, int TB, int IA, class FG>
__device__ __forceinline__ void conv_tail(uint32_t (&acc)[32], const uint32_t (&a)[8][4], uint32_t sb, unsigned char* gy0, int warp, size_t ycopy, FG fg) {
    const int wg = warp >> 2, wq = warp & 3, ord = TA == 0 && TB == 16 ? 3 - wg : 4;
    const uint32_t ub = sb + SM_U + wg * USLOT_B + UPAD * 16, turn = sb + SM_MISC + 376 + ord * 8, sfs = sb + SM_MISC + 256 + wg * 8;
    const uint32_t du = wg * (USLOT_B / 16) + (SM_U / 16 + UPAD + TA * 8);
    uint32_t ud[8], fs;
    auto skip = [&]() {
        const int lane = lane_v();
        const uint32_t ua = ub + ((lane >> 3) & 1) * ULO_B + (8 * wq + (lane & 7)) * 16 + (lane >> 4) * 512;
        if (IA == 0) ldsm_x4_t(ud[0], ud[1], ud[2], ud[3], ua);
        if (TB == 16) ldsm_x4_t(ud[4], ud[5], ud[6], ud[7], ua + 1024);
        const uint2 fd = lds64(sfs);
        fs = fd.x;
        const float dsk = __uint_as_float(fd.y);
#pragma unroll
        for (int i = 2 * IA; i < TB / 2; i++) ud[i] = pack_bf16(h_lo(ud[i]) * dsk, h_hi(ud[i]) * dsk);
    };
    conv_rename<2 * TA, 2 * TB>(acc);
    if (__builtin_expect(ord != 0, 0)) {
        skip();
        mbar_wait(turn);
    }
    if (TA == 0 && TB == 16) asm volatile("{\n.reg .pred p;\nelect.sync _|p, 0xffffffff;\n@p mbarrier.arrive.shared::cta.b64 _, [%0];\n}\n" ::"r"(turn + 40) : "memory");
    fg(IC<8>());
    wg_fence();
#pragma unroll
    for (int m = 7; m >= 0; m--) {
        wg_h<TA, TB - TA>(acc, a[m], smem_desc(sb, du - m, ULO_B));
        if (m == GA || m == GB || m == HAND) wg_commit();
        if (m == GB) asm volatile("wgmma.wait_group.sync.aligned 1;\n" ::: "memory");
    }
    wg_commit();
    if (TA == 0 && TB == 16) {
        asm volatile("wgmma.wait_group.sync.aligned 1;\n" ::: "memory");
        asm volatile("{\n.reg .pred p;\nelect.sync _|p, 0xffffffff;\n@p mbarrier.arrive.shared::cta.b64 _, [%0];\n}\n" ::"r"(turn + 8) : "memory");
    }
    __syncwarp();
    fg(IC<3>());
    if (!ord) skip();
    fg(IC<4>());
    const int lane = lane_v();
    const uint32_t lp = sb + SM_PL + (ord >= 3 ? ord - 3 : ord) * PL_B + lane * 8;
    unsigned char* gy = gy0 + ((4 * wq + (lane & 3)) * DM + (TA == 0 && TB == 16 ? 4 * blockIdx.x + wg : 512 + (blockIdx.x >> 1))) * 64 + (lane >> 2) * 8;
    const uint32_t st = lp + (wq * 12 - ((wq * (wq - 1)) >> 1)) * 256;
    uint32_t ld[3];
#pragma unroll
    for (int s = 1; s < 4; s++) {
        const int w = (wq - s) & 3;
        ld[s - 1] = lp + (w * 12 - ((w * (w - 1)) >> 1) + s - 1 - (wq < s ? 3 : 0)) * 256;
    }
    if (ord >= 3) bar_sync(9 + ord, 256);
    wg_wait0();
    fg(IC<6>());
#pragma unroll
    for (int j = TA; j < TB; j++)
        if ((j & 3) && j + 3 >= 4 * IA && (j + 3 < TB || j + wq < TB)) sts64(st + (j - 1 - (j >> 2)) * 256, acc[2 * j], acc[2 * j + 1]);
    bar_sync(1 + wg, 128);
    fg(IC<7>());
    uint2 v[4][3];
#pragma unroll
    for (int i = IA; i < TB / 4; i++)
#pragma unroll
        for (int s = 0; s < 3; s++) {
            if (i == 0) { v[i][s] = make_uint2(0u, 0u); if (wq > s) v[i][s] = lds64(ld[s]); }
            else v[i][s] = lds64(ld[s] + i * 768);
        }
    fg(IC<5>());
#pragma unroll
    for (int i = IA; i < TB / 4; i++) {
        const uint32_t x0 = hadd2(v[i][0].x, acc[8 * i]), x1 = hadd2(v[i][1].x, v[i][2].x), y0 = hadd2(v[i][0].y, acc[8 * i + 1]), y1 = hadd2(v[i][1].y, v[i][2].y);
        const uint32_t x = hadd2(x0, x1), y = hadd2(y0, y1);
        const uint32_t lo = pack_bf16(h_lo(x), h_hi(x)), hi = pack_bf16(h_lo(y), h_hi(y));
        const uint32_t o0 = max(hfma2_bf(lo, fs, ud[2 * i]), 1u), o1 = hfma2_bf(hi, fs, ud[2 * i + 1]);
        stg64(gy + i * 16 * DM * 64, o0, o1);
    }
    if (TA == 0 && TB == 16 && ord < 2) bar_arrive(12 + ord, 256);
}
template <int M0, int M1>
__device__ __forceinline__ void conv_frags(uint32_t (&a)[8][4], const uint32_t (&r)[18], uint32_t sel, uint32_t dep, int warp) {
    const uint32_t s = prmt_v(sel, dep, 0x3210u + (warp >> 8)), sw = s ^ 0x4444u;
#pragma unroll
    for (int m = M0; m < M1; m++) {
        a[m][0] = prmt_v(r[2 * m + 1], r[2 * m + 2], s); a[m][1] = prmt_v(r[2 * m + 2], r[2 * m + 3], s);
        a[m][2] = prmt_v(r[2 * m + 1], r[2 * m], sw); a[m][3] = prmt_v(r[2 * m + 2], r[2 * m + 1], sw);
    }
}
template <class FG>
__device__ __forceinline__ void conv_main(const Conv& c, uint32_t (&acc)[32], uint32_t sb, uint32_t sel, unsigned char* gy, int warp, size_t ycopy, FG fg) {
    const uint32_t kw = (warp >> 2) * (KW_B / 16) + SM_KW / 16;
    const uint64_t d2 = smem_desc(sb, kw + KW_T2 / 16, KW_KH), d2b = smem_desc(sb, kw + KW_T2 / 16 + 1, KW_KH), d3 = smem_desc(sb, kw + KW_T3 / 16, 16), d3b = smem_desc(sb, kw + KW_T3 / 16 + 32, 16);
    uint32_t a[8][4];
    {
        const int ord = warp < 16 ? 3 - (warp >> 2) : 4;
        if (__builtin_expect(ord >= GATE, 0)) {
            fg(IC<1>());
            mbar_wait(sb + SM_MISC + 376 + 40 + (ord - GATE) * 8);
        }
    }
    wg_fence();
    wg_h<12, 4>(acc, c.q3[0], d3b); wg_h<8, 4>(acc, c.q3[0], d3); wg_h<4, 4>(acc, c.q2[0][0], d2b);
    wg_h<12, 4>(acc, c.q3[1], d3); wg_h<8, 4>(acc, c.q2[1][0], d2b);
    wg_h<12, 4>(acc, c.q2[2][0], d2b); wg_h<4, 4>(acc, c.q2[0][1], d2); wg_h<8, 4>(acc, c.q2[1][1], d2);
    wg_h<12, 4>(acc, c.q2[2][1], d2);
    wg_commit(); __syncwarp();
    fg(IC<0>());
    wg_wait0();
    conv_frags<0, 8>(a, c.r, sel, acc[16], warp);
    fg(IC<2>());
    if (warp >= 16) {
        if (blockIdx.x & 1) conv_tail<4, 16, 2>(acc, a, sb, gy, warp, ycopy, fg);
        else conv_tail<0, 8, 0>(acc, a, sb, gy, warp, ycopy, fg);
    } else {
        conv_tail<0, 16, 0>(acc, a, sb, gy, warp, ycopy, fg);
    }
}
#define CONV_LT6 const int dd = (lane >> 3) + (lane & 4) - (lane & 3); \
        const uint4 lt6 = make_uint4(prmt_v((dd & 3) * 288, 0u, idn), prmt_v(0x3254u + (dd >> 2) * 0x2222u, 0u, idn), \
            prmt_v(UPAD * 16 + (lane & 7) * 16 + ULO_B - 32 + (lane >> 3) * 512, 0u, idn), prmt_v(UPAD * 16 + (lane & 7) * 16 + ((lane >> 3) & 1) * ULO_B - 16 + (lane & 16), 0u, idn));
#define CONV_PRE \
        CONV_LT6 \
        const uint32_t ka = kw + lt6.x, sel = lt6.y, ks = kw + lt7.x; \
        const uint32_t ca0 = sb + SM_U + wg * USLOT_B + (warp & 3) * 128 + lt6.z, ca1 = sb + SM_U + wg * USLOT_B + (warp & 3) * 128 + lt6.w; \
        uint4 bd[4]; \
        band_pair<2, 4>(bd[0], bd[1], lt7.w); band_pair<4, 0>(bd[2], bd[3], lt7.w);
#define CONV_BODY \
        Conv c; \
        uint32_t acc[32]; \
        conv_sums(c, ca0, ca1, bd); \
        conv_edges(c, acc, ka, ks, sel, warp & 3);
template <int U0, int U1>
__device__ __forceinline__ void weight_units(uint32_t sb, const CUtensorMap* tg, const CUtensorMap* tu, const CUtensorMap* td, int w) {
    if constexpr (U0 < U1) {
        if (w == 0 && elect_one()) {
            if constexpr (U0 < 12) tma_2d(sb + SM_WG + U0 * 6912, U0 < 6 ? tg : tu, 72 * (blockIdx.x >> 1), 288 * (blockIdx.x & 1) + (U0 % 6) * 48, sb + SM_MISC + 328);
            else tma_2d(sb + SM_WD + (15 - U0) * 10368, td, 288 * (blockIdx.x & 1) + 72 * (15 - U0), 72 * (blockIdx.x >> 1), sb + SM_MISC + 336);
        }
        weight_units<U0 + 1, U1>(sb, tg, tu, td, w - 1);
    }
}
#define WS x0012468899abcdddefg
#define WS_STR2(x) #x
#define WS_STR(x) WS_STR2(x)
__device__ constexpr int wsched(int i) { constexpr char t[] = WS_STR(WS); return i == 0 ? 0 : (t[i] <= '9' ? t[i] - '0' : t[i] - 'a' + 10); }
#define WPOINT(i, w) do { weight_units<wsched(i), wsched(i + 1)>(sb, &tm_g, &tm_u, &tm_d, w); } while (0)

__global__ void __launch_bounds__(NTHR, 1) __cluster_dims__(2, 1, 1)
fused_kernel(const Params p, const __grid_constant__ CUtensorMap tm_g, const __grid_constant__ CUtensorMap tm_u, const __grid_constant__ CUtensorMap tm_d, const __grid_constant__ CUtensorMap tm_x,
             const __grid_constant__ CUtensorMap tm_y, const __grid_constant__ CUtensorMap tm_z) {
    extern __shared__ __align__(1024) unsigned char smem[];
    const uint32_t sb = smem_u32(smem);
    const int tid = threadIdx.x, warp = __shfl_sync(0xffffffffu, tid >> 5, 0), lane = tid & 31;
    const int b = blockIdx.x, P = b >> 1, odd = b & 1;
    const int g = lane >> 2, t = lane & 3;
    const int wg = warp >> 2, t128 = tid & 127;
    const uint32_t s_stat = sb + SM_MISC;
    const uint32_t s_key = sb + SM_MISC + 128;
    const uint32_t s_wm = sb + SM_MISC + 160;
    const uint32_t s_k16 = sb + SM_MISC + 192;
    const uint32_t s_fs = sb + SM_MISC + 256;
    const uint32_t s_cnt = sb + SM_MISC + 320;
    const uint32_t bar_w = sb + SM_MISC + 328, bar_d = bar_w + 8, bar_g = bar_w + 16, bar_h = bar_w + 40, bar_x = bar_w + 48;
    STAMP(0);

    const bool lnw = (unsigned)(warp - 10) < 9u;
    const unsigned pm = tid + (tid < 512 ? 512 * b : 65024 + 128 * P), pq = (pm & ~127u) + 4 * lane;
    uint32_t pl = ldg16(p.lar + pm), ldt = ldg16(p.ldt + (pm >> 7));
    const uint32_t pa2 = ldg16(p.aim + pm), pc = ldg16(p.cre + pm), pi = ldg16(p.cim + pm);
    const uint2 call_re = ldg64(p.cre + pq), call_im = ldg64(p.cim + pq);
    const uint32_t dskl = ldg16(p.dsk + (pm >> 7));
    const uint32_t ep = ld_poll32(p.s->hint + (b & 7) * 32 + 1 + (lane >> 5));
    if ((unsigned)(tid - 320) < 288u) {
        const bf16* xp = p.x + (unsigned)((32 * P + 2 * odd + TOKEN_OF(g)) * DM + ((tid - 320) & ~31) + 8 * t);
        const uint32_t xt = sb + SM_XT + ((tid - 320) & ~31) * 32 + lane * 16;
        asm volatile("cp.async.cg.shared.global [%0], [%1], 16;\ncp.async.cg.shared.global [%0 + 512], [%1 + 9216], 16;\n"
                     "cp.async.cg.shared.global [%0 + 9216], [%1 + 576], 16;\ncp.async.cg.shared.global [%0 + 9728], [%1 + 9792], 16;\n" ::"r"(xt), "l"(xp) : "memory");
    }
    uint32_t* const std_ = p.s->st + ((lane & 12) * 128 + odd * 256 + 4 * P + 2 * (lane & 1) + ((lane >> 1) & 1)) * 2;
    unsigned char* const ud = reinterpret_cast<unsigned char*>(p.s->uT) + (32 * (warp - UW) + 8 * (g >> 1) + (g & 1)) * 4096 + b * 32 + t * 8;
    if (warp == 0) {
        if (lane == 0) {
            mbar_init(bar_x, 1); mbar_init(bar_w, 1); mbar_init(bar_d, 1); mbar_init(bar_g, 1); mbar_init(bar_h, 3);
            #pragma unroll
            for (int i = 1; i < 9; i++) mbar_init(bar_x + 8 * i, 4);
            asm volatile("fence.mbarrier_init.release.cluster;\n" ::: "memory");
            mbar_expect(bar_x, 32768);
            mbar_expect(bar_w, 2 * 41472); mbar_expect(bar_d, 41472); mbar_expect(bar_g, 18 * 512); sts32(s_cnt, 0);
        }
        __syncwarp();
        bar_arrive(0, NWRK);
    }
    asm volatile("barrier.cluster.arrive.relaxed.aligned;\n" ::: "memory");
    if (warp == 0) {
        asm volatile("barrier.cluster.wait.acquire.aligned;\n" ::: "memory");
        if (elect_one()) tma_3d_mc(sb + SM_XC + 16384 * odd, &tm_x, 8 * P, 0, 8 * odd, bar_x);
    }
    const uint32_t kw = sb + SM_KW + wg * KW_B;
    if (t128 < 2 * UPAD) sts128(sb + SM_U + wg * USLOT_B + (t128 & 1) * ULO_B + (t128 >> 1) * 16, 0u, 0u, 0u, 0u);
    sts128(kw + t128 * 16, 0u, 0u, 0u, 0u);
    if (t128 < KW_B / 16 - 128) sts128(kw + 2048 + t128 * 16, 0u, 0u, 0u, 0u);
    if (tid < 96) {
#pragma unroll
        for (int i = 0; i < 6; i++) sts128(sb + SM_ZERO + i * 1536 + tid * 16, 0u, 0u, 0u, 0u);
    }
    if (warp != 0) bar_sync(0, NWRK);
    STAMP(1);
    if (warp == 19 || warp == UW || warp == UW + 1) {
        if (warp == 19) {
            if (lane < 16) stg64(std_, 0u, 0u);
            if (lane < 9) asm volatile("prefetch.global.L2 [%0];\n" ::"l"(p.wr + lane * 64));
        } else {
#pragma unroll
            for (int k = 0; k < 4; k++) stg64(ud + k * 8192, 0u, 0u);
        }
    }
    uint32_t X[2][8];
    auto partial = [&]() {
        const uint32_t xt = sb + SM_XT + (warp - 10) * 1024 + lane * 16;
        asm volatile("cp.async.wait_all;\n" ::: "memory");
        STAMP(23);
        const uint4 a = lds128(xt), c = lds128(xt + 512), d = lds128(xt + 9216), e = lds128(xt + 9728);
        X[0][0] = a.x; X[0][1] = a.y; X[0][2] = a.z; X[0][3] = a.w; X[0][4] = d.x; X[0][5] = d.y; X[0][6] = d.z; X[0][7] = d.w;
        X[1][0] = c.x; X[1][1] = c.y; X[1][2] = c.z; X[1][3] = c.w; X[1][4] = e.x; X[1][5] = e.y; X[1][6] = e.z; X[1][7] = e.w;
        ln_partial<8>(X, sb + SM_LNP, warp - 10, g, t);
        bar_arrive(6, 320);
        if (PAUSE & 1) bar_sync(7, PCNT);
    };
    if (LNAT == 0 && lnw) {
        partial();
        pl = prmt_v(pl, X[0][0], 0x3210u + (warp >> 8)); ldt = prmt_v(ldt, X[0][0], 0x3210u + (warp >> 8));
    }
    auto finish = [&]() {
        bar_sync(6, 320);
        float mb, rc;
        ln_finish<9>(sb + SM_LNP, lane, mb, rc);
        const float rh = rbf(rc);
        const uint32_t s0 = (__float_as_uint(mb) >> 16) | (((ep & 0x7fffu) + 1u) << 16), s1 = pack_bf16(rh, rc - rh);
        if (lane < 16) { stg64(std_, s0, s1); sts64(s_stat + lane * 8, s0, s1); }
        if (lane == 16) sts32(s_cnt + 4, ep);
        bar_arrive(7, PCNT);
        STAMP(28);
    };
    auto upub = [&]() {
        if (!(PAUSE & 6)) bar_sync(7, PCNT);
        const uint32_t utag = ((ep & 3u) + 1u) * 0x10001u;
        uint32_t U[2][4];
#pragma unroll
        for (int hf = 0; hf < 2; hf++) {
            const uint2 st = lds64(s_stat + (g + 8 * hf) * 8);
            const uint4 xv = lds128(sb + SM_XT + (16 + warp - UW) * 1024 + hf * 512 + lane * 16);
            const uint32_t xs[4] = {xv.x, xv.y, xv.z, xv.w};
#pragma unroll
            for (int k = 0; k < 4; k++) {
                const uint32_t u = ln_apply(xs[k], st);
                U[hf][k] = movm((pack_f16_rz(bf_lo(u), __uint_as_float(u)) & 0xfff8fff8u) | utag);
            }
        }
#pragma unroll
        for (int k = 0; k < 4; k++) stg64(ud + k * 8192, U[0][k], U[1][k]);
    };
    STAMP(27);
    if (FINAT == 0 && warp == 19) finish();
    const uint32_t tb = table_buf(sb, warp);
    const float dt = rbf(expf(bf_lo(ldt)));
    KGen kg;
    kgen_setup(kg, pl | (pa2 << 16), dt);
    if (LNAT == 1 && lnw) {
        partial();
        kg.z8.x = __uint_as_float(prmt_v(__float_as_uint(kg.z8.x), X[0][0], 0x3210u + (warp >> 8)));
        kg.z1.x = __uint_as_float(prmt_v(__float_as_uint(kg.z1.x), X[0][0], 0x3210u + (warp >> 8)));
    }
    if (FINAT == 1 && warp == 19) finish();
    if (UAT == 0 && (warp == UW || warp == UW + 1)) upub();
    kgen_rows(kg, tb, lane);
    if (wg == 0) fence_async();
    if (LNAT == 2 && lnw) {
        partial();
        kg.z128.x = __uint_as_float(prmt_v(__float_as_uint(kg.z128.x), X[0][0], 0x3210u + (warp >> 8)));
        kg.z1.x = __uint_as_float(prmt_v(__float_as_uint(kg.z1.x), X[0][0], 0x3210u + (warp >> 8)));
    }
    if (FINAT == 2 && warp == 19) finish();
    if (UAT == 1 && (warp == UW || warp == UW + 1)) upub();
    STAMP(2);
    WPOINT(0, warp - 4);
    const int ce = c_exponent(call_re, call_im);
    if (t128 == 0) sts64(s_fs + wg * 8, (uint32_t)min(max(ce + (int)(__float_as_uint(dt) >> 23) - 116, 0), 254) * 0x800080u, dskl << 16);
    kgen_chain(kg, pc | (pi << 16), __uint_as_float(((uint32_t)(244 - ce) << 23) | (__float_as_uint(dt) & 0x7fffffu)));
    if ((PAUSE & 4) && warp < 10) bar_sync(7, PCNT);
    if (UAT == 4 && (warp == UW || warp == UW + 1)) upub();
    STAMP(3);
    WPOINT(1, warp - 6);
    kgen_cols(kg, tb, lane);
    if (LNAT == 3 && lnw) partial();
    if (FINAT == 3 && warp == 19) finish();
    if ((PAUSE & 2) && warp < 10) bar_sync(7, PCNT);
    if (UAT == 2 && (warp == UW || warp == UW + 1)) upub();
    STAMP(4);
    WPOINT(2, warp - 8);
    const uint4* usrc = wg < 4 ? reinterpret_cast<const uint4*>(p.s->st) + (warp & 1) * 512 + (lane & 1) * 128 + 16 * (warp >> 1) + (lane >> 1)
                               : reinterpret_cast<const uint4*>(p.s->uT) + P * 256 + 2 * t128;
    const int ustep = wg < 4 ? 256 : 1;
    uint4 uv0, uv1;
    kgen_mma(kg, tb, lane);
    if (UAT == 3 && (warp == UW || warp == UW + 1)) upub();
    STAMP(26);
    WPOINT(3, warp - 5);
    const uint32_t idn = 0x3210u + (warp >> 8);
    const uint4 lt7 = make_uint4(prmt_v(KW_T2 + ((lane >> 3) & 1) * KW_KH + (33 + (lane & 7)) * 16 - (lane & 16), 0u, idn), t * 288 + g * 8 + 8, (lane & 1) * 4096 + (lane >> 1) * 16,
                                 prmt_v(8u << ((lane >> 3) + (lane & 4)) >> (lane & 3), 0u, idn));
    bar_sync(1 + wg, 128);
    uv0 = ld_poll(usrc); uv1 = ld_poll(usrc + ustep);
    kgen_combine(sb, warp, lane, kw, lt7.y);
    CONV_PRE
    STAMP(5);
    WPOINT(4, warp - 7);
    if (wg < 4) {
        mbar_wait(bar_x);
        const uint32_t xa = sb + SM_XC + (warp & 1) * 16384 + (warp >> 1) * 256 + odd * 8 + lt7.z;
        uint2 xv[4] = {lds64(xa), lds64(xa + 8192), lds64(xa + 2048), lds64(xa + 10240)};
        const uint32_t tag = ((ep & 0x7fffu) + 1u) << 16;
        int it = 0;
        while (true) {
            const bool bad = (((uv0.x ^ tag) | (uv0.z ^ tag)) | ((uv1.x ^ tag) | (uv1.z ^ tag))) >> 16;
            if (!__any_sync(0xffffffffu, bad)) break;
            if (++it > SPIN_LIMIT) TRAP();
            if (bad) { uv0 = ld_poll(usrc); uv1 = ld_poll(usrc + 256); }
        }
        STAMP(6);
        DBG(wg, it);
        const uint2 st[4] = {make_uint2(uv0.x, uv0.y), make_uint2(uv0.z, uv0.w), make_uint2(uv1.x, uv1.y), make_uint2(uv1.z, uv1.w)};
#pragma unroll
        for (int i = 0; i < 4; i++) {
            xv[i].x = ln_apply(xv[i].x, st[i]);
            xv[i].y = ln_apply(xv[i].y, st[i]);
        }
        const uint32_t ub = sb + SM_U + UPAD * 16 + (warp & 1) * ULO_B + (warp >> 1) * 256 + lane * 8;
        sts64(ub, pack_f16(bf_lo(xv[0].x), bf_lo(xv[1].x)), pack_f16(bf_lo(xv[2].x), bf_lo(xv[3].x)));
        sts64(ub + USLOT_B, HI2(xv[0].x, xv[1].x), HI2(xv[2].x, xv[3].x));
        sts64(ub + 2 * USLOT_B, pack_f16(bf_lo(xv[0].y), bf_lo(xv[1].y)), pack_f16(bf_lo(xv[2].y), bf_lo(xv[3].y)));
        sts64(ub + 3 * USLOT_B, HI2(xv[0].y, xv[1].y), HI2(xv[2].y, xv[3].y));
    } else {
        const uint32_t utag = ((ep & 3u) + 1u) * 0x10001u;
        int it = 0;
        while (true) {
            const bool bad = (((uv0.x ^ utag) | (uv0.y ^ utag) | (uv0.z ^ utag) | (uv0.w ^ utag)) | ((uv1.x ^ utag) | (uv1.y ^ utag) | (uv1.z ^ utag) | (uv1.w ^ utag))) & 0x70007u;
            if (!__any_sync(0xffffffffu, bad)) break;
            if (++it > SPIN_LIMIT) TRAP();
            if (bad) { uv0 = ld_poll(usrc); uv1 = ld_poll(usrc + 1); }
        }
        STAMP(6);
        DBG(4, it);
        const uint32_t ub = sb + SM_U + UPAD * 16 + 4 * USLOT_B + (t128 >> 1) * 32 + (t128 & 1) * 8;
        sts64(ub, prmt(uv0.x, uv0.z, 0x5410u) ^ utag, prmt(uv1.x, uv1.z, 0x5410u) ^ utag);
        sts64(ub + 16, prmt(uv0.x, uv0.z, 0x7632u) ^ utag, prmt(uv1.x, uv1.z, 0x7632u) ^ utag);
        sts64(ub + ULO_B, prmt(uv0.y, uv0.w, 0x5410u) ^ utag, prmt(uv1.y, uv1.w, 0x5410u) ^ utag);
        sts64(ub + ULO_B + 16, prmt(uv0.y, uv0.w, 0x7632u) ^ utag, prmt(uv1.y, uv1.w, 0x7632u) ^ utag);
    }
    fence_async();
    WPOINT(5, warp - 3);
    if (warp < 3 && elect_one()) tma_st_3d(warp < 2 ? &tm_y : &tm_z, sb + SM_ZERO, warp < 2 ? 128 * b : 32 * (512 + P), 0, 2 * (warp < 2 ? warp : odd));
    if (warp != 0) asm volatile("barrier.cluster.wait.acquire.aligned;\n" ::: "memory");
    bar_sync(0, NWRK);
    STAMP(7);
    {
        CONV_BODY
        WPOINT(6, 19 - warp);
        bar_sync(0, NWRK);
        STAMP(8);
        size_t ycopy = 0;
        auto hook = [&](auto gi) {
                     constexpr int G = decltype(gi)::value;
                     if (G == 5) mbar_wait(bar_h);
                     if (G < 3) WPOINT(7 + G, warp - 16 - G);
                     if (G == 3) { WPOINT(10, warp - 12); WPOINT(12, warp - 8); WPOINT(14, warp - 4); }
                     if (G == 5) { WPOINT(11, warp - 13); WPOINT(13, warp - 9); WPOINT(15, warp - 5); }
                     if (G == 1 && warp < 4) {
                         if (elect_one()) {
                             if (warp == 3) {
                                 bulk_s2g(reinterpret_cast<unsigned char*>(p.s->part) + b * 9216, sb + SM_ZERO, 9216);
                                 bulk_s2g(reinterpret_cast<unsigned char*>(p.s->rows) + b * 4608, sb + SM_ZERO, 4608);
                                 bulk_s2g(reinterpret_cast<unsigned char*>(p.s->sc) + b * 32, sb + SM_ZERO, 32);
                             }
                             asm volatile("cp.async.bulk.wait_group 0;\n" ::: "memory");
                             if (warp < 3) mbar_arrive(bar_h);
                             hint_arrive(p.s->hint, 0, b & 7);
                         }
                         __syncwarp();
                     }
                 };
        conv_main(c, acc, sb, sel, reinterpret_cast<unsigned char*>(p.s->y), warp, ycopy, hook);
        STAMP(10);
    }
    {
    const int warp = warp_v(), lane = lane_v(), tid = 32 * warp + lane, g = lane >> 2, t = lane & 3;
    uint4 wr = make_uint4(0u, 0u, 0u, 0u);
    if (warp == 12) hint_wait(p.s->hint, 0, (lds32(s_cnt + 4) + 1u) * 64u);
    bar_sync(0, NWRK);
    STAMP(11);
    uint32_t H[2][4], U2[2][4] = {};
    uint32_t WA[9][4];
    const int fkh = warp >= 9, fmt = warp - 9 * fkh;
    auto load_wa = [&]() {
        mbar_wait(bar_w);
        const int mi = lane >> 3, rr = lane & 7;
        const uint32_t aad = sb + SM_WG + (mi & 1) * SM_WU + (fkh * 144 + rr + 8 * (mi >> 1)) * W_PITCH + fmt * 16;
#pragma unroll
        for (int k = 0; k < 9; k++) ldsm_x4_t(WA[k][0], WA[k][1], WA[k][2], WA[k][3], aad + k * 16 * W_PITCH);
    };
    if (warp < 18) {
        if (g == 0) wr = ldg128(p.wr + 32 * warp + 8 * t);
        const unsigned char* ys = reinterpret_cast<const unsigned char*>(p.s->y) + ((size_t)P * DM + 32 * warp + 8 * (g >> 1) + (g & 1)) * 64 + odd * 32 + t * 8;
        uint2 yv[4];
#pragma unroll
        for (int k = 0; k < 4; k++) yv[k] = ld_poll64(ys + k * 128);
        const uint4 x0 = lds128(sb + SM_XT + warp * 1024 + lane * 16), x1 = lds128(sb + SM_XT + warp * 1024 + 512 + lane * 16);
        int it = 0;
        while (!__all_sync(0xffffffffu, yv[0].x && yv[1].x && yv[2].x && yv[3].x)) {
#pragma unroll
            for (int k = 0; k < 4; k++) yv[k] = ld_poll64(ys + k * 128);
            if (++it > SPIN_LIMIT) TRAP();
        }
        STAMP(12);
        const uint32_t Z[2][4] = {{x0.x, x0.y, x0.z, x0.w}, {x1.x, x1.y, x1.z, x1.w}};
#pragma unroll
        for (int k = 0; k < 4; k++) {
            H[0][k] = hadd2_bf(Z[0][k], movm(yv[k].x));
            H[1][k] = hadd2_bf(Z[1][k], movm(yv[k].y));
        }
        ln_partial<4>(H, sb + SM_LNP, warp, g, t);
    } else if (warp == 19) {
#pragma unroll 1
        for (int i = lane; i < 520; i += 32) sts128(sb + SM_CAND + i * 16, 0u, 0u, 0u, 0u);
    }
    bar_sync(0, NWRK);
    STAMP(13);
    WPOINT(16, warp == 19 ? 0 : -1);
    if (warp == 18) {
        float mb, rc;
        ln_finish<18>(sb + SM_LNP, lane, mb, rc);
        if (lane < 16) stat_store(s_stat + lane * 8, mb, rc, 0u);
    }
    bar_sync(0, NWRK);
    STAMP(14);
    WPOINT(17, warp == 19 ? 0 : -1);
    auto publish = [&](bool hi, int slot) {
        uint4* rowp = reinterpret_cast<uint4*>(p.s->rows) + slot * 144 + warp * 4 + t;
        stg128(rowp, nzw(hi ? U2[1][0] : U2[0][0]), nzw(hi ? U2[1][1] : U2[0][1]), nzw(hi ? U2[1][2] : U2[0][2]), nzw(hi ? U2[1][3] : U2[0][3]));
        stg128(rowp + 72, nzw(hi ? H[1][0] : H[0][0]), nzw(hi ? H[1][1] : H[0][1]), nzw(hi ? H[1][2] : H[0][2]), nzw(hi ? H[1][3] : H[0][3]));
    };
    uint4 kv = make_uint4(1, 1, 1, 1);
    const uint4* ksrc = reinterpret_cast<const uint4*>(p.s->sc) + tid;
    if (warp < 18) {
#pragma unroll
        for (int hf = 0; hf < 2; hf++) {
            const uint2 st = lds64(s_stat + (g + 8 * hf) * 8);
#pragma unroll
            for (int k = 0; k < 4; k++) U2[hf][k] = ln_apply(H[hf][k], st);
        }
        {
            float cs[4] = {0.f, 0.f, 0.f, 0.f};
            mma_bf16(cs, U2[0][0], U2[1][0], U2[0][1], U2[1][1], wr.x, wr.y);
            mma_bf16(cs, U2[0][2], U2[1][2], U2[0][3], U2[1][3], wr.z, wr.w);
            if (t == 0) { stsf(sb + SM_LNP + ((32 + g) * 20 + warp) * 4, cs[0]); stsf(sb + SM_LNP + ((40 + g) * 20 + warp) * 4, cs[2]); }
            bar_arrive(10, 608);
        }
        bar_sync(11, 608);
#pragma unroll
        for (int hf = 0; hf < 2; hf++)
            sts128(sb + SM_OUT + (g + 8 * hf) * OUT_PITCH + warp * 64 + t * 16,
                   hadd2_bf(H[hf][0], U2[hf][0]), hadd2_bf(H[hf][1], U2[hf][1]), hadd2_bf(H[hf][2], U2[hf][2]), hadd2_bf(H[hf][3], U2[hf][3]));
        fence_async();
        bar_arrive(9, 608);
        if (tid < 256) kv = ld_poll(ksrc);
        const uint32_t rk[2] = {lds32(s_wm + 32 + 64 + g * 4), lds32(s_wm + 32 + 64 + 32 + g * 4)};
        uint32_t lo = min(rk[0], rk[1]), hi = max(rk[0], rk[1]);
#pragma unroll 1
        while (lo < EARLYN) { publish(lo == rk[1], 2 * b + lo); lo = hi; hi = 16; }
        if (warp >= 8) load_wa();
    } else if (warp == 18) {
        bar_sync(10, 608);
        const float r = sum18(sb + SM_LNP + (32 + (lane & 15)) * 80);
        const uint32_t bits = pack_bf16(r, 0.f) & 0xffffu;
        const uint32_t k = max((bits & 0x8000u) ? (~bits & 0xffffu) : (bits | 0x8000u), 1u);
        const uint32_t me = (k << 16) | (uint32_t)(15 - (lane & 15));
        if (lane < 16) {
            p.s->sc[16 * b + lane] = (unsigned short)k;
            sts32(s_k16 + lane * 4, me);
        }
        __syncwarp();
        int rank = 0;
#pragma unroll
        for (int q = 0; q < 4; q++) {
            const uint4 v = lds128(s_k16 + q * 16);
            rank += (v.x > me) + (v.y > me) + (v.z > me) + (v.w > me);
        }
        if (lane < 16) sts32(s_wm + 32 + 64 + lane * 4, rank);
        bar_arrive(11, 608);
    } else if (warp == 19) {
        bar_sync(9, 608);
        if (lane < 16) bulk_s2g(p.out + (size_t)(32 * P + 2 * odd + TOKEN_OF(lane & 7) + (lane & 8)) * DM, sb + SM_OUT + lane * OUT_PITCH, DM * 2);
        __syncwarp();
    }
    STAMP(15);
    WPOINT(18, warp == 19 ? 0 : -1);
    uint32_t kmax = 0;
    if (tid < 256) {
        int it = 0;
        while (true) {
            const uint32_t mn = __vminu2(__vminu2(kv.x, kv.y), __vminu2(kv.z, kv.w));
            if ((mn & 0xffffu) && (mn >> 16)) break;
            if (++it > SPIN_LIMIT) TRAP();
            kv = ld_poll(ksrc);
        }
        const uint32_t mx = __vmaxu2(__vmaxu2(kv.x, kv.y), __vmaxu2(kv.z, kv.w));
        kmax = max(mx & 0xffffu, mx >> 16);
        const uint32_t m = __reduce_max_sync(0xffffffffu, kmax);
        if (lane == 0) sts32(s_wm + warp * 4, m);
    }
    if (warp < 8) bar_sync(8, 256);
    STAMP(16);
    if (tid < 256) {
        const uint4 m0 = lds128(s_wm), m1 = lds128(s_wm + 16);
        const uint32_t T = min(min(min(m0.x, m0.y), min(m0.z, m0.w)), min(min(m1.x, m1.y), min(m1.z, m1.w)));
        if (kmax >= T) {
            const uint32_t kk[4] = {kv.x, kv.y, kv.z, kv.w};
            uint32_t m = 0;
#pragma unroll
            for (int i = 0; i < 8; i++) m |= (((i & 1) ? kk[i >> 1] >> 16 : kk[i >> 1] & 0xffffu) >= T ? 1u : 0u) << i;
            uint32_t pos;
            asm volatile("atom.shared.add.u32 %0, [%1], %2;\n" : "=r"(pos) : "r"(s_cnt), "r"(__popc(m)) : "memory");
            pos = sb + SM_CAND + pos * 4;
#pragma unroll 1
            while (m) {
                const int i = __ffs(m) - 1;
                m &= m - 1;
                const uint32_t w = (i & 4) ? ((i & 2) ? kv.w : kv.z) : ((i & 2) ? kv.y : kv.x);
                sts32(pos, __byte_perm(w, 2047 - 8 * tid - i, (i & 1) ? 0x3254 : 0x1054));
                pos += 4;
            }
        }
    }
    if (warp < 8) bar_sync(8, 256);
    STAMP(17);
    if (warp < 8) {
        const int n = (int)lds32(s_cnt);
#pragma unroll 1
        for (int i = tid; i < n; i += 256) {
            const uint32_t k = lds32(sb + SM_CAND + i * 4);
            int r0 = 0, r1 = 0;
            int j = 0;
#pragma unroll 1
            do {
#pragma unroll
                for (int q = 0; q < 4; q++) {
                    const uint4 v = lds128(sb + SM_CAND + (j + 4 * q) * 4);
                    r0 += (v.x > k) + (v.y > k); r1 += (v.z > k) + (v.w > k);
                }
                j += 16;
            } while (j < n && r0 + r1 < NSEL);
            if (r0 + r1 < NSEL) sts32(s_key + (r0 + r1) * 4, k);
        }
    }
    bar_sync(0, NWRK);
    STAMP(18);
    const int gs = tid / 36;
    int slot, tok;
    {
        const uint4 ka = lds128(s_key), kb = lds128(s_key + 16);
        const uint32_t k = lds32(s_key + (lane & 7) * 4);
        tok = 2047 - (int)(k & 0x7ffu);
#define SAME(v) ((v) > k && (((v) ^ k) & 0x7f0u) == 0)
        const int lr = (SAME(ka.x) + SAME(ka.y)) + (SAME(ka.z) + SAME(ka.w)) + (SAME(kb.x) + SAME(kb.y)) + SAME(kb.z);
#undef SAME
        slot = lr < EARLYN ? 2 * (tok >> 4) + lr : 2 * NCTA + (lane & 7);
        const uint32_t late = __ballot_sync(0xffffffffu, lr >= EARLYN) & 0xffu;
        if (late) {
            const uint32_t ep = lds32(s_cnt + 4);
            const bool mine = lr >= EARLYN && (tok >> 4) == b;
            uint32_t todo = __ballot_sync(0xffffffffu, mine) & 0xffu;
            if (todo) {
#pragma unroll 1
                while (todo) {
                    const int s = __ffs(todo) - 1, tk = __shfl_sync(0xffffffffu, tok, s);
                    todo &= todo - 1;
                    if (warp < 18 && (tk & 7) == g) publish(tk & 8, 2 * NCTA + s);
                }
                __threadfence();
                bar_sync(0, NWRK);
                if (tid < NSEL && mine) *reinterpret_cast<volatile unsigned*>(p.s->flag + tid) = ep + 1u;
            }
            int it = 0;
            while (__any_sync(0xffffffffu, lr >= EARLYN && ld_poll32(p.s->flag + (lane & 7)) != ep + 1u)) { if (++it > SPIN_LIMIT) TRAP(); }
            __threadfence();
        }
    }
    const uint4* src0 = reinterpret_cast<const uint4*>(p.s->rows) + __shfl_sync(0xffffffffu, slot, gs & 7) * 144 + 36 * odd + (tid - gs * 36);
    uint4 v0 = make_uint4(1, 1, 1, 1);
    if (tid < 288) v0 = ld_poll(src0);
    uint32_t WD[18];
    if (warp < 18) {
        if (warp < 8) load_wa();
        mbar_wait(bar_d);
        const int mi = lane >> 3, rr = lane & 7;
        const int c8 = 2 * warp + (mi & 1), bx = c8 / 9;
        const uint32_t base = sb + SM_WD + bx * 10368 + (c8 - 9 * bx) * 16 + rr * W_PITCH;
#pragma unroll
        for (int k = 0; k < 4; k++) ldsm_x4_t(WD[4 * k], WD[4 * k + 1], WD[4 * k + 2], WD[4 * k + 3], base + (k * 16 + 8 * (mi >> 1)) * W_PITCH);
        ldsm_x2_t(WD[16], WD[17], base + 64 * W_PITCH);
    }
    float hv = 0.f, uv = 0.f, rs = 0.f;
    const int fl = 16 * (b & 1) + ((tid >> 2) & 15), fc = 16 * (b >> 1) + (fl >> 2) + 8 * ((tid >> 1) & 1), fsl = 2 * (fl & 3) + (tid & 1);
    int ftok = 0;
    if (warp >= 18) {
        const int fslot = __shfl_sync(0xffffffffu, slot, fsl);
        if (b < 72) {
            const uint32_t kk = lds32(s_key + fsl * 4);
            ftok = 2047 - (int)(kk & 0x7ffu);
            ftok = (ftok & ~23) + ((ftok >> 3) & 2) + TOKEN_OF(ftok & 7);
            uint32_t hw, uw;
            int it = 0;
            do { uw = ld_poll32(p.s->rows + fslot * DM + (fc >> 1)); hw = ld_poll32(p.s->rows + fslot * DM + 288 + (fc >> 1)); if (++it > SPIN_LIMIT) TRAP(); } while (!hw || !uw);
            uv = (fc & 1) ? bf_hi(uw) : bf_lo(uw);
            const unsigned k16 = kk >> 16;
            const unsigned bits = (k16 & 0x8000u) ? (k16 & 0x7fffu) : (~k16 & 0xffffu);
            rs = rbf(__fdividef(1.0f, 1.0f + __expf(-__uint_as_float(bits << 16))));
            hv = (fc & 1) ? bf_hi(hw) : bf_lo(hw);
        }
    } else if (warp < 9) {
        int it = 0;
        while (!all_nz(v0)) {
            if (++it > SPIN_LIMIT) TRAP();
            v0 = ld_poll(src0);
        }
        sts128(sb + SM_XS + gs * XS_PITCH + (tid - gs * 36) * 16, v0.x, v0.y, v0.z, v0.w);
    }
    bar_sync(0, NWRK);
    STAMP(19);
    if (warp < 18) {
        float c4[3][4];
#pragma unroll
        for (int i = 0; i < 3; i++)
#pragma unroll
            for (int j = 0; j < 4; j++) c4[i][j] = 0.f;
        const uint32_t bad = sb + SM_XS + (lane & 7) * XS_PITCH + (fkh * 144 + 8 * (lane >> 3)) * 2;
#pragma unroll
        for (int k = 0; k < 10; k += 2) {
            uint32_t b0, b1, b2, b3;
            ldsm_x4(b0, b1, b2, b3, bad + k * 32);
            mma_bf16(c4[k % 3], WA[k][0], WA[k][1], WA[k][2], WA[k][3], b0, b1);
            if (k < 8) mma_bf16(c4[(k + 1) % 3], WA[k + 1][0], WA[k + 1][1], WA[k + 1][2], WA[k + 1][3], b2, b3);
        }
#pragma unroll
        for (int j = 0; j < 4; j++) c4[0][j] += c4[1][j] + c4[2][j];
        const uint32_t ex = sb + SM_EX + (18 * odd + warp) * 512 + lane * 16;
        asm volatile("st.async.shared::cluster.mbarrier::complete_tx::bytes.v4.b32 [%0], {%1,%2,%3,%4}, [%5];\n"
                     ::"r"(ex ^ 0x1000000u), "r"(__float_as_uint(c4[0][0])), "r"(__float_as_uint(c4[0][1])), "r"(__float_as_uint(c4[0][2])), "r"(__float_as_uint(c4[0][3])), "r"(bar_g ^ 0x1000000u) : "memory");
        sts128f(ex, c4[0]);
        if (warp >= 9) bar_arrive(6, 576);
    }
    STAMP(20);
    if (warp < 9) {
        bar_sync(6, 576);
        mbar_wait(bar_g);
        const uint32_t ex = sb + SM_EX + tid * 16;
        const uint4 u = lds128(ex), v = lds128(ex + 4608), w = lds128(ex + 9216), x = lds128(ex + 13824);
#define S4(f) rbf((__uint_as_float(u.f) + __uint_as_float(v.f)) + (__uint_as_float(w.f) + __uint_as_float(x.f)))
        const float G0 = S4(x), G1 = S4(y), U0 = S4(z), U1 = S4(w);
#undef S4
        sts32(sb + SM_GU + tid * 4, pack_bf16(rbf(__fdividef(G0, 1.0f + __expf(-G0))) * U0, rbf(__fdividef(G1, 1.0f + __expf(-G1))) * U1));
    }
    if (warp == 19 && __any_sync(0xffffffffu, (tok >> 4) == b)) asm volatile("cp.async.bulk.wait_group 0;\n" ::: "memory");
    if (warp != 18) bar_sync(7, 608);
    STAMP(21);
    if (warp < 18) {
        uint32_t gb[9];
        ldsm_x4_t(gb[0], gb[1], gb[2], gb[3], sb + SM_GU + lane * 16);
        ldsm_x4_t(gb[4], gb[5], gb[6], gb[7], sb + SM_GU + 512 + lane * 16);
        ldsm_x1_t(gb[8], sb + SM_GU + 1024 + (lane & 7) * 16);
        float c4[4] = {0.f, 0.f, 0.f, 0.f}, d4[4] = {0.f, 0.f, 0.f, 0.f};
        mma_bf16(c4, WD[0], WD[1], WD[2], WD[3], gb[0], gb[1]);
        mma_bf16(d4, WD[4], WD[5], WD[6], WD[7], gb[2], gb[3]);
        mma_bf16(c4, WD[8], WD[9], WD[10], WD[11], gb[4], gb[5]);
        mma_bf16(d4, WD[12], WD[13], WD[14], WD[15], gb[6], gb[7]);
        mma_bf16(c4, WD[16], WD[17], 0u, 0u, gb[8], 0u);
        stg128(p.s->part + ((size_t)(2 * (18 * odd + warp) + (lane >> 4)) * 64 + P) * 64 + (lane & 15) * 4,
               nzf(c4[0] + d4[0]), nzf(c4[1] + d4[1]), nzf(c4[2] + d4[2]), nzf(c4[3] + d4[3]));
    }
    STAMP(22);
    if (b < 72) {
        if (tid < 512) {
            const uint4* src = reinterpret_cast<const uint4*>(p.s->part) + (size_t)b * 1024 + tid;
            uint4 a, c;
            int it = 0;
            while (true) {
                a = ld_poll(src); c = ld_poll(src + 512);
                if (all_nz(a) && all_nz(c)) break;
                if (++it > SPIN_LIMIT) TRAP();
            }
            STAMP(24);
            const float s0 = __uint_as_float(a.x) + __uint_as_float(c.x), s1 = __uint_as_float(a.y) + __uint_as_float(c.y);
            const float s2 = __uint_as_float(a.z) + __uint_as_float(c.z), s3 = __uint_as_float(a.w) + __uint_as_float(c.w);
            const bool up = lane & 16;
            const float r0 = __shfl_xor_sync(0xffffffffu, up ? s0 : s2, 16), r1 = __shfl_xor_sync(0xffffffffu, up ? s1 : s3, 16);
            sts64f(sb + SM_EX + warp * 256 + (lane & 15) * 16 + (up ? 8 : 0), (up ? s2 : s0) + r0, (up ? s3 : s1) + r1);
        }
        bar_sync(0, NWRK);
        if (warp >= 18) {
            float v0 = 0.f, v1 = 0.f, v2 = 0.f, v3 = 0.f;
            const uint32_t a = sb + SM_EX + (tid - 576) * 4;
#pragma unroll
            for (int i = 0; i < 16; i += 4) { v0 += ldsf(a + i * 256); v1 += ldsf(a + i * 256 + 256); v2 += ldsf(a + i * 256 + 512); v3 += ldsf(a + i * 256 + 768); }
            const float y3 = rbf(rbf((v0 + v1) + (v2 + v3)) * rs);
            p.out[(size_t)ftok * DM + fc] = __float2bfloat16_rn(hv + rbf(uv + y3));
        }
    }
    if (warp == 19) asm volatile("cp.async.bulk.wait_group.read 0;\n" ::: "memory");
    if (b == 0 && tid < 8) *reinterpret_cast<volatile unsigned*>(p.s->hint + tid * 32 + 1) = lds32(s_cnt + 4) + 1u;
    STAMP(25);
    }
}

typedef CUresult (*PFN_tmEncode)(CUtensorMap*, CUtensorMapDataType, cuuint32_t, void*, const cuuint64_t*, const cuuint64_t*, const cuuint32_t*,
                                 const cuuint32_t*, CUtensorMapInterleave, CUtensorMapSwizzle, CUtensorMapL2promotion, CUtensorMapFloatOOBfill);

extern "C" void kernel_launch(void* const* d_in, const int* in_sizes, int n_in, void* d_out, int out_size) {
    Params p;
    p.x = (const bf16*)d_in[0];
    p.lar = (const bf16*)d_in[1];
    p.aim = (const bf16*)d_in[2];
    p.cre = (const bf16*)d_in[3];
    p.cim = (const bf16*)d_in[4];
    p.ldt = (const bf16*)d_in[5];
    p.dsk = (const bf16*)d_in[6];
    p.wr = (const bf16*)d_in[8];
    p.wpf = (const bf16*)d_in[PFW];
    p.out = (bf16*)d_out;
    static PFN_tmEncode enc = nullptr;
    static void* scratch = nullptr;
    if (!enc) {
        cudaFuncSetAttribute(fused_kernel, cudaFuncAttributeMaxDynamicSharedMemorySize, SMEM_TOTAL);
        void* fn = nullptr;
        cudaDriverEntryPointQueryResult qr;
        cudaGetDriverEntryPoint("cuTensorMapEncodeTiled", &fn, cudaEnableDefault, &qr);
        enc = (PFN_tmEncode)fn;
        cudaGetSymbolAddress(&scratch, g_scratch);
    }
    p.s = (Scratch*)scratch;
    CUtensorMap tm_g, tm_u, tm_d, tm_x, tm_y, tm_z;
    const cuuint64_t dims[2] = {FF, DM}, strides[1] = {FF * 2};
    const cuuint32_t box[2] = {72, 48}, es[2] = {1, 1};
    enc(&tm_g, CU_TENSOR_MAP_DATA_TYPE_BFLOAT16, 2, d_in[9], dims, strides, box, es, CU_TENSOR_MAP_INTERLEAVE_NONE, CU_TENSOR_MAP_SWIZZLE_NONE,
        CU_TENSOR_MAP_L2_PROMOTION_NONE, CU_TENSOR_MAP_FLOAT_OOB_FILL_NONE);
    enc(&tm_u, CU_TENSOR_MAP_DATA_TYPE_BFLOAT16, 2, d_in[10], dims, strides, box, es, CU_TENSOR_MAP_INTERLEAVE_NONE, CU_TENSOR_MAP_SWIZZLE_NONE,
        CU_TENSOR_MAP_L2_PROMOTION_NONE, CU_TENSOR_MAP_FLOAT_OOB_FILL_NONE);
    const cuuint64_t ddims[2] = {DM, FF}, dstrides[1] = {DM * 2};
    const cuuint32_t dbox[2] = {72, 72};
    enc(&tm_d, CU_TENSOR_MAP_DATA_TYPE_BFLOAT16, 2, d_in[11], ddims, dstrides, dbox, es, CU_TENSOR_MAP_INTERLEAVE_NONE, CU_TENSOR_MAP_SWIZZLE_NONE,
        CU_TENSOR_MAP_L2_PROMOTION_NONE, CU_TENSOR_MAP_FLOAT_OOB_FILL_NONE);
    const cuuint64_t xdims[3] = {DM, LSEQ / 16, 16}, xstrides[2] = {16 * DM * 2, DM * 2};
    const cuuint32_t xbox[3] = {8, LSEQ / 16, 8}, es3[3] = {1, 1, 1};
    enc(&tm_x, CU_TENSOR_MAP_DATA_TYPE_BFLOAT16, 3, d_in[0], xdims, xstrides, xbox, es3, CU_TENSOR_MAP_INTERLEAVE_NONE, CU_TENSOR_MAP_SWIZZLE_NONE,
        CU_TENSOR_MAP_L2_PROMOTION_NONE, CU_TENSOR_MAP_FLOAT_OOB_FILL_NONE);
    const cuuint64_t ydims[3] = {DM * 32, 16, 4}, ystrides[2] = {DM * 64, 16 * DM * 64};
    const cuuint32_t ybox[3] = {128, 16, 2}, zbox[3] = {32, 16, 2};
    enc(&tm_y, CU_TENSOR_MAP_DATA_TYPE_BFLOAT16, 3, p.s->y, ydims, ystrides, ybox, es3, CU_TENSOR_MAP_INTERLEAVE_NONE, CU_TENSOR_MAP_SWIZZLE_NONE,
        CU_TENSOR_MAP_L2_PROMOTION_NONE, CU_TENSOR_MAP_FLOAT_OOB_FILL_NONE);
    enc(&tm_z, CU_TENSOR_MAP_DATA_TYPE_BFLOAT16, 3, p.s->y, ydims, ystrides, zbox, es3, CU_TENSOR_MAP_INTERLEAVE_NONE, CU_TENSOR_MAP_SWIZZLE_NONE,
        CU_TENSOR_MAP_L2_PROMOTION_NONE, CU_TENSOR_MAP_FLOAT_OOB_FILL_NONE);
    fused_kernel<<<NCTA, NTHR, SMEM_TOTAL>>>(p, tm_g, tm_u, tm_d, tm_x, tm_y, tm_z);
}
```

```cpp
#include <cuda_runtime.h>
#include <cuda.h>
#include <cuda_fp16.h>
#include <cuda_bf16.h>
#include <stdint.h>

#define LSEQ 2048
#define DM 576
#define NST 128
#define FF 4608
#define NSEL 8
#define NCTA 128
#define NTHR 640
#define NWRK 640

typedef __nv_bfloat16 bf16;

#define SM_WG 0
#define SM_WU 41472
#define SM_WD 82944
#define W_PITCH 144
#define SM_XC 50176
#define SM_ZERO SM_WD
#define SM_TB (SM_WD + 9216)
#define SM_PL 124416
#define PL_B 10752
#define SM_XT (SM_TB + 20 * TBW)
#define SM_U (SM_XT + 18432)
#define UPAD 8
#define ULO_B ((UPAD + 128) * 16)
#define USLOT_B (2 * ULO_B)
#define SM_KW (SM_U + 5 * USLOT_B)
#define KW_B 3600
#define KW_T2 1152
#define KW_KH 656
#define KW_T3 2464
#define SM_MISC (SM_KW + 5 * KW_B)
#define SM_LNP (SM_MISC + 576)
#define SMEM_TOTAL (SM_LNP + 4096)
#define TBP 112
#define TBW (32 * TBP)
#define SM_OUT SM_PL
#define OUT_PITCH 1216
#define SM_XS (SM_PL + 19456)
#define XS_PITCH 592
#define SM_EX (SM_PL + 24320)
#define SM_GU (SM_PL + 42752)

struct __align__(128) Scratch {
    unsigned hint[8 * 32];
    unsigned flag[32];
    uint32_t sc[NCTA * 32];
    uint32_t st[LSEQ * 2];
    uint32_t uT[64 * (LSEQ / 2)];
    uint32_t y[NCTA * DM * 8];
    uint32_t part[72 * 64 * 64];
    uint32_t rows[(2 * NCTA + NSEL) * DM];
};
__device__ Scratch g_scratch;
#define STAMP(i)
#define DBG(i, v)

__device__ __forceinline__ float rbf(float x) {
    uint32_t r;
    asm("cvt.rn.bf16x2.f32 %0, %1, %2;\n" : "=r"(r) : "f"(x), "f"(0.f));
    return __uint_as_float(r & 0xffff0000u);
}
__device__ __forceinline__ uint32_t pack_bf16(float lo, float hi) {
    uint32_t r;
    asm("cvt.rn.bf16x2.f32 %0, %1, %2;\n" : "=r"(r) : "f"(hi), "f"(lo));
    return r;
}
__device__ __forceinline__ uint32_t pack_f16(float lo, float hi) {
    uint32_t r;
    asm("cvt.rn.f16x2.f32 %0, %1, %2;\n" : "=r"(r) : "f"(hi), "f"(lo));
    return r;
}
__device__ __forceinline__ uint32_t pack_f16_rz(float lo, float hi) {
    uint32_t r;
    asm("cvt.rz.f16x2.f32 %0, %1, %2;\n" : "=r"(r) : "f"(hi), "f"(lo));
    return r;
}
__device__ __forceinline__ float bf_lo(uint32_t w) { return __uint_as_float(w << 16); }
__device__ __forceinline__ float bf_hi(uint32_t w) { return __uint_as_float(w & 0xffff0000u); }
__device__ __forceinline__ uint32_t hadd2_bf(uint32_t a, uint32_t b) {
    __nv_bfloat162 r = __hadd2_rn(*reinterpret_cast<__nv_bfloat162*>(&a), *reinterpret_cast<__nv_bfloat162*>(&b));
    return *reinterpret_cast<uint32_t*>(&r);
}
__device__ __forceinline__ uint32_t hsub2_bf(uint32_t a, uint32_t b) {
    __nv_bfloat162 r = __hsub2_rn(*reinterpret_cast<__nv_bfloat162*>(&a), *reinterpret_cast<__nv_bfloat162*>(&b));
    return *reinterpret_cast<uint32_t*>(&r);
}
__device__ __forceinline__ uint32_t hmul2_bf(uint32_t a, uint32_t b) {
    __nv_bfloat162 r = __hmul2_rn(*reinterpret_cast<__nv_bfloat162*>(&a), *reinterpret_cast<__nv_bfloat162*>(&b));
    return *reinterpret_cast<uint32_t*>(&r);
}
__device__ __forceinline__ uint32_t hfma2_bf(uint32_t a, uint32_t b, uint32_t c) { uint32_t r; asm("fma.rn.bf16x2 %0, %1, %2, %3;\n" : "=r"(r) : "r"(a), "r"(b), "r"(c)); return r; }
__device__ __forceinline__ uint32_t hmul2(uint32_t a, uint32_t b) { uint32_t r; asm("mul.rn.f16x2 %0, %1, %2;\n" : "=r"(r) : "r"(a), "r"(b)); return r; }
__device__ __forceinline__ uint32_t hadd2(uint32_t a, uint32_t b) { uint32_t r; asm("add.rn.f16x2 %0, %1, %2;\n" : "=r"(r) : "r"(a), "r"(b)); return r; }
__device__ __forceinline__ uint32_t hfma2(uint32_t a, uint32_t b, uint32_t c) { uint32_t r; asm("fma.rn.f16x2 %0, %1, %2, %3;\n" : "=r"(r) : "r"(a), "r"(b), "r"(c)); return r; }
__device__ __forceinline__ uint32_t nzw(uint32_t w) { return w ? w : 0x8000u; }
__device__ __forceinline__ uint32_t nzf(float f) { const uint32_t w = __float_as_uint(f); return w ? w : 0x80000000u; }
__device__ __forceinline__ uint32_t smem_u32(const void* p) { return (uint32_t)__cvta_generic_to_shared(p); }
__device__ __forceinline__ uint32_t lds32(uint32_t addr) {
    uint32_t v;
    asm volatile("ld.shared.u32 %0, [%1];\n" : "=r"(v) : "r"(addr) : "memory");
    return v;
}
__device__ __forceinline__ uint32_t lds16(uint32_t addr) {
    unsigned short v;
    asm volatile("ld.shared.u16 %0, [%1];\n" : "=h"(v) : "r"(addr) : "memory");
    return v;
}
__device__ __forceinline__ uint2 lds64(uint32_t addr) {
    uint2 v;
    asm volatile("ld.shared.v2.u32 {%0,%1}, [%2];\n" : "=r"(v.x), "=r"(v.y) : "r"(addr) : "memory");
    return v;
}
__device__ __forceinline__ uint4 lds128(uint32_t addr) {
    uint4 v;
    asm volatile("ld.shared.v4.u32 {%0,%1,%2,%3}, [%4];\n" : "=r"(v.x), "=r"(v.y), "=r"(v.z), "=r"(v.w) : "r"(addr) : "memory");
    return v;
}
__device__ __forceinline__ float ldsf(uint32_t addr) { return __uint_as_float(lds32(addr)); }
__device__ __forceinline__ void sts32(uint32_t addr, uint32_t v) { asm volatile("st.shared.u32 [%0], %1;\n" ::"r"(addr), "r"(v) : "memory"); }
__device__ __forceinline__ void stsf(uint32_t addr, float v) { sts32(addr, __float_as_uint(v)); }
__device__ __forceinline__ void sts64(uint32_t addr, uint32_t a, uint32_t b) { asm volatile("st.shared.v2.u32 [%0], {%1,%2};\n" ::"r"(addr), "r"(a), "r"(b) : "memory"); }
__device__ __forceinline__ void sts64f(uint32_t addr, float a, float b) { sts64(addr, __float_as_uint(a), __float_as_uint(b)); }
__device__ __forceinline__ void sts128(uint32_t addr, uint32_t a, uint32_t b, uint32_t c, uint32_t d) {
    asm volatile("st.shared.v4.u32 [%0], {%1,%2,%3,%4};\n" ::"r"(addr), "r"(a), "r"(b), "r"(c), "r"(d) : "memory");
}
__device__ __forceinline__ void sts128f(uint32_t addr, const float (&v)[4]) {
    sts128(addr, __float_as_uint(v[0]), __float_as_uint(v[1]), __float_as_uint(v[2]), __float_as_uint(v[3]));
}
__device__ __forceinline__ void ldsm_x4(uint32_t& r0, uint32_t& r1, uint32_t& r2, uint32_t& r3, uint32_t addr) {
    asm volatile("ldmatrix.sync.aligned.m8n8.x4.shared.b16 {%0,%1,%2,%3}, [%4];\n"
                 : "=r"(r0), "=r"(r1), "=r"(r2), "=r"(r3) : "r"(addr) : "memory");
}
__device__ __forceinline__ void ldsm_x4_t(uint32_t& r0, uint32_t& r1, uint32_t& r2, uint32_t& r3, uint32_t addr) {
    asm volatile("ldmatrix.sync.aligned.m8n8.x4.trans.shared.b16 {%0,%1,%2,%3}, [%4];\n"
                 : "=r"(r0), "=r"(r1), "=r"(r2), "=r"(r3) : "r"(addr) : "memory");
}
__device__ __forceinline__ void ldsm_x2_t(uint32_t& r0, uint32_t& r1, uint32_t addr) {
    asm volatile("ldmatrix.sync.aligned.m8n8.x2.trans.shared.b16 {%0,%1}, [%2];\n" : "=r"(r0), "=r"(r1) : "r"(addr) : "memory");
}
__device__ __forceinline__ void ldsm_x1_t(uint32_t& r0, uint32_t addr) {
    asm volatile("ldmatrix.sync.aligned.m8n8.x1.trans.shared.b16 {%0}, [%1];\n" : "=r"(r0) : "r"(addr) : "memory");
}
__device__ __forceinline__ uint32_t movm(uint32_t a) {
    uint32_t d;
    asm volatile("movmatrix.sync.aligned.m8n8.trans.b16 %0, %1;\n" : "=r"(d) : "r"(a));
    return d;
}
__device__ __forceinline__ void mma_f16(float (&c)[4], uint32_t a0, uint32_t a1, uint32_t a2, uint32_t a3, uint32_t b0, uint32_t b1) {
    asm volatile(
        "mma.sync.aligned.m16n8k16.row.col.f32.f16.f16.f32 {%0,%1,%2,%3}, {%4,%5,%6,%7}, {%8,%9}, {%0,%1,%2,%3};\n"
        : "+f"(c[0]), "+f"(c[1]), "+f"(c[2]), "+f"(c[3])
        : "r"(a0), "r"(a1), "r"(a2), "r"(a3), "r"(b0), "r"(b1));
}
__device__ __forceinline__ void mma_bf16(float (&c)[4], uint32_t a0, uint32_t a1, uint32_t a2, uint32_t a3, uint32_t b0, uint32_t b1) {
    asm volatile(
        "mma.sync.aligned.m16n8k16.row.col.f32.bf16.bf16.f32 {%0,%1,%2,%3}, {%4,%5,%6,%7}, {%8,%9}, {%0,%1,%2,%3};\n"
        : "+f"(c[0]), "+f"(c[1]), "+f"(c[2]), "+f"(c[3])
        : "r"(a0), "r"(a1), "r"(a2), "r"(a3), "r"(b0), "r"(b1));
}
__device__ __forceinline__ void bar_sync(int id, int n) { asm volatile("bar.sync %0, %1;\n" ::"r"(id), "r"(n) : "memory"); }
__device__ __forceinline__ void bar_arrive(int id, int n) { asm volatile("bar.arrive %0, %1;\n" ::"r"(id), "r"(n) : "memory"); }
__device__ __forceinline__ bool bar_or(int id, int n, bool v) {
    uint32_t r;
    asm volatile("{\n.reg .pred p, q;\nsetp.ne.u32 p, %3, 0;\nbar.red.or.pred q, %1, %2, p;\nselp.u32 %0, 1, 0, q;\n}\n" : "=r"(r) : "r"(id), "r"(n), "r"((uint32_t)v) : "memory");
    return r;
}
__device__ __forceinline__ uint4 ld_poll(const void* p) {
    uint4 v;
    asm volatile("ld.relaxed.gpu.global.v4.u32 {%0,%1,%2,%3}, [%4];\n" : "=r"(v.x), "=r"(v.y), "=r"(v.z), "=r"(v.w) : "l"(p) : "memory");
    return v;
}
template <class T> __device__ __forceinline__ T* pin(T* p, uint32_t z) {
    uint32_t lo, hi;
    asm volatile("mov.b64 {%0, %1}, %2;\n" : "=r"(lo), "=r"(hi) : "l"(p));
    asm volatile("xor.b32 %0, %0, %1;\n" : "+r"(lo) : "r"(z));
    asm volatile("xor.b32 %0, %0, %1;\n" : "+r"(hi) : "r"(z));
    asm volatile("mov.b64 %0, {%1, %2};\n" : "=l"(p) : "r"(lo), "r"(hi));
    return p;
}
__device__ __forceinline__ uint32_t pin(uint32_t a, uint32_t z) { asm volatile("xor.b32 %0, %0, %1;\n" : "+r"(a) : "r"(z)); return a; }
__device__ __forceinline__ uint2 ld_poll64(const void* p) {
    uint2 v;
    asm volatile("ld.relaxed.gpu.global.v2.u32 {%0,%1}, [%2];\n" : "=r"(v.x), "=r"(v.y) : "l"(p) : "memory");
    return v;
}
__device__ __forceinline__ uint32_t ld_poll32(const void* p) {
    uint32_t v;
    asm volatile("ld.relaxed.gpu.global.u32 %0, [%1];\n" : "=r"(v) : "l"(p) : "memory");
    return v;
}
__device__ __forceinline__ uint4 ldg128(const void* p) {
    uint4 v;
    asm volatile("ld.global.nc.v4.u32 {%0,%1,%2,%3}, [%4];\n" : "=r"(v.x), "=r"(v.y), "=r"(v.z), "=r"(v.w) : "l"(p));
    return v;
}
__device__ __forceinline__ uint2 ldg64(const void* p) {
    uint2 v;
    asm volatile("ld.global.nc.v2.u32 {%0,%1}, [%2];\n" : "=r"(v.x), "=r"(v.y) : "l"(p));
    return v;
}
__device__ __forceinline__ uint32_t ldg16(const void* p) {
    uint32_t v;
    asm volatile("ld.global.nc.u16 %0, [%1];\n" : "=r"(v) : "l"(p));
    return v;
}
__device__ __forceinline__ void stg128(void* p, uint32_t a, uint32_t b, uint32_t c, uint32_t d) {
    asm volatile("st.global.v4.u32 [%0], {%1,%2,%3,%4};\n" ::"l"(p), "r"(a), "r"(b), "r"(c), "r"(d) : "memory");
}
__device__ __forceinline__ void stg64(void* p, uint32_t a, uint32_t b) { asm volatile("st.global.v2.u32 [%0], {%1,%2};\n" ::"l"(p), "r"(a), "r"(b) : "memory"); }
__device__ __forceinline__ void stg32(void* p, uint32_t a) { asm volatile("st.global.u32 [%0], %1;\n" ::"l"(p), "r"(a) : "memory"); }
__device__ __forceinline__ bool all_nz(const uint4& v) { return v.x && v.y && v.z && v.w; }
#define SPIN_LIMIT (1 << 21)
#define TRAP() __trap()
__device__ __forceinline__ void hint_arrive(unsigned* g_hint, int idx, int sub) {
    asm volatile("red.relaxed.gpu.global.add.u32 [%0], 1;\n" ::"l"(&g_hint[sub * 32 + idx]) : "memory");
}
__device__ __forceinline__ void hint_wait(const unsigned* g_hint, int idx, unsigned target) {
    unsigned l;
    asm volatile("mov.u32 %0, %%laneid;" : "=r"(l));
    const unsigned* c = &g_hint[(l & 7) * 32 + idx];
    int it = 0;
    while (__any_sync(0xffffffffu, (int)(ld_poll32(c) - target) < 0)) { if (++it > SPIN_LIMIT) TRAP(); }
}
__device__ __forceinline__ void mbar_init(uint32_t bar, uint32_t cnt) { asm volatile("mbarrier.init.shared::cta.b64 [%0], %1;\n" ::"r"(bar), "r"(cnt) : "memory"); }
__device__ __forceinline__ void mbar_expect(uint32_t bar, uint32_t bytes) {
    asm volatile("mbarrier.arrive.expect_tx.shared::cta.b64 _, [%0], %1;\n" ::"r"(bar), "r"(bytes) : "memory");
}
__device__ __forceinline__ void mbar_arrive(uint32_t bar) { asm volatile("mbarrier.arrive.shared::cta.b64 _, [%0];\n" ::"r"(bar) : "memory"); }
__device__ __forceinline__ void mbar_wait_cluster(uint32_t bar) {
    asm volatile(
        "{\n.reg .pred p;\n"
        "W_%=:\n"
        "mbarrier.try_wait.parity.acquire.cluster.shared::cta.b64 p, [%0], 0;\n"
        "@!p bra W_%=;\n}\n" ::"r"(bar) : "memory");
}
__device__ __forceinline__ void mbar_wait(uint32_t bar) {
    asm volatile(
        "{\n.reg .pred p;\n"
        "W_%=:\n"
        "mbarrier.try_wait.parity.shared::cta.b64 p, [%0], 0;\n"
        "@!p bra W_%=;\n}\n" ::"r"(bar) : "memory");
}
__device__ __forceinline__ bool mbar_test(uint32_t bar) {
    uint32_t r;
    asm volatile("{\n.reg .pred p;\nmbarrier.test_wait.parity.shared::cta.b64 p, [%1], 0;\nselp.u32 %0, 1, 0, p;\n}\n" : "=r"(r) : "r"(bar) : "memory");
    return __any_sync(0xffffffffu, r);
}
__device__ __forceinline__ void bulk_g2s(uint32_t dst, const void* src, uint32_t bytes, uint32_t bar) {
    asm volatile("cp.async.bulk.shared::cluster.global.mbarrier::complete_tx::bytes [%0], [%1], %2, [%3];\n" ::"r"(dst), "l"(src), "r"(bytes), "r"(bar) : "memory");
}
__device__ __forceinline__ void bulk_s2g(void* dst, uint32_t src, uint32_t bytes) {
    asm volatile("cp.async.bulk.global.shared::cta.bulk_group [%0], [%1], %2;\ncp.async.bulk.commit_group;\n" ::"l"(dst), "r"(src), "r"(bytes) : "memory");
}
__device__ __forceinline__ void tma_2d(uint32_t dst, const CUtensorMap* tm, int c0, int c1, uint32_t bar) {
    asm volatile("cp.async.bulk.tensor.2d.shared::cluster.global.mbarrier::complete_tx::bytes [%0], [%1, {%3, %4}], [%2];\n"
                 ::"r"(dst), "l"(tm), "r"(bar), "r"(c0), "r"(c1) : "memory");
}
__device__ __forceinline__ void tma_3d(uint32_t dst, const CUtensorMap* tm, int c0, int c1, int c2, uint32_t bar) {
    asm volatile("cp.async.bulk.tensor.3d.shared::cluster.global.mbarrier::complete_tx::bytes [%0], [%1, {%3, %4, %5}], [%2];\n"
                 ::"r"(dst), "l"(tm), "r"(bar), "r"(c0), "r"(c1), "r"(c2) : "memory");
}
__device__ __forceinline__ void tma_3d_mc(uint32_t dst, const CUtensorMap* tm, int c0, int c1, int c2, uint32_t bar) {
    asm volatile("cp.async.bulk.tensor.3d.shared::cluster.global.mbarrier::complete_tx::bytes.multicast::cluster [%0], [%1, {%3, %4, %5}], [%2], %6;\n"
                 ::"r"(dst), "l"(tm), "r"(bar), "r"(c0), "r"(c1), "r"(c2), "h"((unsigned short)3) : "memory");
}
__device__ __forceinline__ void tma_st_3d(const CUtensorMap* tm, uint32_t src, int c0, int c1, int c2) {
    asm volatile("cp.async.bulk.tensor.3d.global.shared::cta.bulk_group [%0, {%2, %3, %4}], [%1];\ncp.async.bulk.commit_group;\n"
                 ::"l"(tm), "r"(src), "r"(c0), "r"(c1), "r"(c2) : "memory");
}
__device__ __forceinline__ void l2_prefetch(const void* src, uint32_t bytes) {
    asm volatile("cp.async.bulk.prefetch.L2.global [%0], %1;\n" ::"l"(src), "r"(bytes) : "memory");
}
__device__ __forceinline__ bool elect_one() {
    uint32_t r;
    asm volatile("{\n.reg .pred p;\nelect.sync _|p, 0xffffffff;\nselp.u32 %0, 1, 0, p;\n}\n" : "=r"(r));
    return r;
}
__device__ __forceinline__ void fence_async() { asm volatile("fence.proxy.async.shared::cta;\n" ::: "memory"); }

__device__ __forceinline__ float2 cmul(float2 a, float2 b) {
    return make_float2(fmaf(a.x, b.x, -a.y * b.y), fmaf(a.x, b.y, a.y * b.x));
}
__device__ __forceinline__ float2 csq(float2 a) {
    float p = a.x * a.y;
    return make_float2(fmaf(a.x, a.x, -a.y * a.y), p + p);
}
__device__ __forceinline__ float2 cexp_e(float lr2, float rh, float rl, float e) {
    float m;
    asm("ex2.approx.ftz.f32 %0, %1;\n" : "=f"(m) : "f"(lr2 * e));
    const float a = rh * e;
    const float r = fmaf(rl, e, a - rintf(a)) * 6.283185307179586f;
    return make_float2(m * __cosf(r), m * __sinf(r));
}
__device__ __forceinline__ float rcp_approx(float x) { float r; asm("rcp.approx.ftz.f32 %0, %1;\n" : "=f"(r) : "f"(x)); return r; }
__device__ __forceinline__ float sqrt_approx(float x) { float r; asm("sqrt.approx.ftz.f32 %0, %1;\n" : "=f"(r) : "f"(x)); return r; }

__device__ __forceinline__ void wg_fence() { asm volatile("wgmma.fence.sync.aligned;\n" ::: "memory"); }
__device__ __forceinline__ void wg_commit() { asm volatile("wgmma.commit_group.sync.aligned;\n" ::: "memory"); }
__device__ __forceinline__ void wg_wait0() { asm volatile("wgmma.wait_group.sync.aligned 0;\n" ::: "memory"); }
template <int T0, int NT> __device__ __forceinline__ void wg_h(uint32_t (&acc)[32], const uint32_t (&a)[4], uint64_t desc);
template <> __device__ __forceinline__ void wg_h<0, 16>(uint32_t (&acc)[32], const uint32_t (&a)[4], uint64_t desc) {
    asm volatile("wgmma.mma_async.sync.aligned.m64n128k16.f16.f16.f16 {%0,%1,%2,%3,%4,%5,%6,%7,%8,%9,%10,%11,%12,%13,%14,%15,%16,%17,%18,%19,%20,%21,%22,%23,%24,%25,%26,%27,%28,%29,%30,%31}, {%32,%33,%34,%35}, %36, 1, 1, 1, 0;\n"
                 : "+r"(acc[0]), "+r"(acc[1]), "+r"(acc[2]), "+r"(acc[3]), "+r"(acc[4]), "+r"(acc[5]), "+r"(acc[6]), "+r"(acc[7]), "+r"(acc[8]), "+r"(acc[9]), "+r"(acc[10]), "+r"(acc[11]), "+r"(acc[12]), "+r"(acc[13]), "+r"(acc[14]), "+r"(acc[15]), "+r"(acc[16]), "+r"(acc[17]), "+r"(acc[18]), "+r"(acc[19]), "+r"(acc[20]), "+r"(acc[21]), "+r"(acc[22]), "+r"(acc[23]), "+r"(acc[24]), "+r"(acc[25]), "+r"(acc[26]), "+r"(acc[27]), "+r"(acc[28]), "+r"(acc[29]), "+r"(acc[30]), "+r"(acc[31])
                 : "r"(a[0]), "r"(a[1]), "r"(a[2]), "r"(a[3]), "l"(desc));
}
template <> __device__ __forceinline__ void wg_h<4, 4>(uint32_t (&acc)[32], const uint32_t (&a)[4], uint64_t desc) {
    asm volatile("wgmma.mma_async.sync.aligned.m64n32k16.f16.f16.f16 {%0,%1,%2,%3,%4,%5,%6,%7}, {%8,%9,%10,%11}, %12, 1, 1, 1, 0;\n"
                 : "+r"(acc[8]), "+r"(acc[9]), "+r"(acc[10]), "+r"(acc[11]), "+r"(acc[12]), "+r"(acc[13]), "+r"(acc[14]), "+r"(acc[15])
                 : "r"(a[0]), "r"(a[1]), "r"(a[2]), "r"(a[3]), "l"(desc));
}
template <> __device__ __forceinline__ void wg_h<8, 4>(uint32_t (&acc)[32], const uint32_t (&a)[4], uint64_t desc) {
    asm volatile("wgmma.mma_async.sync.aligned.m64n32k16.f16.f16.f16 {%0,%1,%2,%3,%4,%5,%6,%7}, {%8,%9,%10,%11}, %12, 1, 1, 1, 0;\n"
                 : "+r"(acc[16]), "+r"(acc[17]), "+r"(acc[18]), "+r"(acc[19]), "+r"(acc[20]), "+r"(acc[21]), "+r"(acc[22]), "+r"(acc[23])
                 : "r"(a[0]), "r"(a[1]), "r"(a[2]), "r"(a[3]), "l"(desc));
}
template <> __device__ __forceinline__ void wg_h<12, 4>(uint32_t (&acc)[32], const uint32_t (&a)[4], uint64_t desc) {
    asm volatile("wgmma.mma_async.sync.aligned.m64n32k16.f16.f16.f16 {%0,%1,%2,%3,%4,%5,%6,%7}, {%8,%9,%10,%11}, %12, 1, 1, 1, 0;\n"
                 : "+r"(acc[24]), "+r"(acc[25]), "+r"(acc[26]), "+r"(acc[27]), "+r"(acc[28]), "+r"(acc[29]), "+r"(acc[30]), "+r"(acc[31])
                 : "r"(a[0]), "r"(a[1]), "r"(a[2]), "r"(a[3]), "l"(desc));
}
template <> __device__ __forceinline__ void wg_h<0, 8>(uint32_t (&acc)[32], const uint32_t (&a)[4], uint64_t desc) {
    asm volatile("wgmma.mma_async.sync.aligned.m64n64k16.f16.f16.f16 {%0,%1,%2,%3,%4,%5,%6,%7,%8,%9,%10,%11,%12,%13,%14,%15}, {%16,%17,%18,%19}, %20, 1, 1, 1, 0;\n"
                 : "+r"(acc[0]), "+r"(acc[1]), "+r"(acc[2]), "+r"(acc[3]), "+r"(acc[4]), "+r"(acc[5]), "+r"(acc[6]), "+r"(acc[7]), "+r"(acc[8]), "+r"(acc[9]), "+r"(acc[10]), "+r"(acc[11]), "+r"(acc[12]), "+r"(acc[13]), "+r"(acc[14]), "+r"(acc[15])
                 : "r"(a[0]), "r"(a[1]), "r"(a[2]), "r"(a[3]), "l"(desc));
}
template <> __device__ __forceinline__ void wg_h<4, 12>(uint32_t (&acc)[32], const uint32_t (&a)[4], uint64_t desc) {
    asm volatile("wgmma.mma_async.sync.aligned.m64n96k16.f16.f16.f16 {%0,%1,%2,%3,%4,%5,%6,%7,%8,%9,%10,%11,%12,%13,%14,%15,%16,%17,%18,%19,%20,%21,%22,%23}, {%24,%25,%26,%27}, %28, 1, 1, 1, 0;\n"
                 : "+r"(acc[8]), "+r"(acc[9]), "+r"(acc[10]), "+r"(acc[11]), "+r"(acc[12]), "+r"(acc[13]), "+r"(acc[14]), "+r"(acc[15]), "+r"(acc[16]), "+r"(acc[17]), "+r"(acc[18]), "+r"(acc[19]), "+r"(acc[20]), "+r"(acc[21]), "+r"(acc[22]), "+r"(acc[23]), "+r"(acc[24]), "+r"(acc[25]), "+r"(acc[26]), "+r"(acc[27]), "+r"(acc[28]), "+r"(acc[29]), "+r"(acc[30]), "+r"(acc[31])
                 : "r"(a[0]), "r"(a[1]), "r"(a[2]), "r"(a[3]), "l"(desc));
}

#define WAAT 2
#define WDAT 1
#define PAUSE 2
#define PCNT (32 + ((PAUSE & 1) ? 288 : 0) + ((PAUSE & 6) ? 320 : 64))
#define LNAT 2
#define UW 4
#define FINAT 3
#define UAT 2
#define PF1 0
#define PF2 0
#define PFW 11
#define HK 9
#define TOKEN_OF(g) (16 * ((g) & 1) + ((g) >> 2) + 2 * ((g) & 2))
#define HI2(a, b) (pack_f16_rz(__uint_as_float(a), __uint_as_float(b)) & 0xfff8fff8u)
struct Params {
    const bf16 *x, *lar, *aim, *cre, *cim, *ldt, *dsk;
    Scratch* s;
    const bf16 *wr, *wpf;
    bf16* out;
};

template <int NK>
__device__ __forceinline__ void ln_partial(const uint32_t (&H)[2][NK], uint32_t lp, int warp, int g, int t) {
    float cs[4] = {0.f, 0.f, 0.f, 0.f}, cl[4] = {0.f, 0.f, 0.f, 0.f}, ch[4] = {0.f, 0.f, 0.f, 0.f};
#pragma unroll
    for (int k = 0; k < NK; k += 2) {
        uint32_t a0, a1, a2, a3;
        asm volatile("prmt.b32 %0, %4, %4, %8;\nprmt.b32 %1, %5, %5, %8;\nprmt.b32 %2, %6, %6, %8;\nprmt.b32 %3, %7, %7, %8;\n"
                     : "=r"(a0), "=r"(a1), "=r"(a2), "=r"(a3) : "r"(H[0][k]), "r"(H[1][k]), "r"(H[0][k + 1]), "r"(H[1][k + 1]), "r"(0x3210u + (warp >> 8)));
        mma_bf16(cl, a0, a1, a2, a3, H[0][k], H[0][k + 1]);
        mma_bf16(ch, a0, a1, a2, a3, H[1][k], H[1][k + 1]);
        mma_bf16(cs, a0, a1, a2, a3, 0x3f803f80u, 0x3f803f80u);
    }
    const uint32_t a = lp + (g * 20 + warp) * 4;
    if (t == 0) {
        stsf(a, cs[0]); stsf(a + 8 * 80, cs[2]);
    }
    if (t == (g >> 1)) { stsf(a + 16 * 80, (g & 1) ? cl[1] : cl[0]); stsf(a + 24 * 80, (g & 1) ? ch[3] : ch[2]); }
}
__device__ __forceinline__ float sum18(uint32_t a) {
    const uint4 p = lds128(a), q = lds128(a + 16), r = lds128(a + 32), s = lds128(a + 48);
    const uint2 u = lds64(a + 64);
#define F(x) __uint_as_float(x)
    return (((F(p.x) + F(p.y)) + (F(p.z) + F(p.w))) + ((F(q.x) + F(q.y)) + (F(q.z) + F(q.w)))) +
           (((F(r.x) + F(r.y)) + (F(r.z) + F(r.w))) + ((F(s.x) + F(s.y)) + (F(s.z) + F(s.w))) + (F(u.x) + F(u.y)));
#undef F
}
__device__ __forceinline__ float sum9(uint32_t a) {
    const uint4 p = lds128(a), q = lds128(a + 16);
#define F(x) __uint_as_float(x)
    return (((F(p.x) + F(p.y)) + (F(p.z) + F(p.w))) + ((F(q.x) + F(q.y)) + (F(q.z) + F(q.w)))) + ldsf(a + 32);
#undef F
}
template <int N>
__device__ __forceinline__ void ln_finish(uint32_t lp, int lane, float& mb, float& rc) {
    const float v = N == 9 ? sum9(lp + lane * 80) : sum18(lp + lane * 80);
    const float o = __shfl_xor_sync(0xffffffffu, v, 16);
    const float m0 = v * (1.0f / 576.0f);
    const float mean = fmaf(fmaf(-m0, 576.0f, v), 1.0f / 576.0f, m0);
    const float var = fmaxf(fmaf(-mean, mean, o * (1.0f / 576.0f)), 0.f);
    mb = rbf(mean);
    rc = rcp_approx(rbf(sqrt_approx(rbf(rbf(var) + 1e-5f))));
}
__device__ __forceinline__ uint32_t ln_apply(uint32_t w, const uint2& st) {
    uint32_t r;
    asm("{\n.reg .b16 m, t, h, l;\n.reg .b32 mm, hh, ll, d, e;\nmov.b32 {m, t}, %2;\nmov.b32 {h, l}, %3;\nmov.b32 mm, {m, m};\nmov.b32 hh, {h, h};\nmov.b32 ll, {l, l};\n"
        "sub.rn.bf16x2 d, %1, mm;\nmul.rn.bf16x2 e, d, ll;\nfma.rn.bf16x2 %0, d, hh, e;\n}\n" : "=r"(r) : "r"(w), "r"(st.x), "r"(st.y));
    return r;
}
__device__ __forceinline__ void stat_store(uint32_t a, float mb, float rc, uint32_t extra) {
    const float rh = rbf(rc);
    sts64(a, (__float_as_uint(mb) >> 16) | (extra << 16), pack_bf16(rh, rc - rh));
}

__device__ __forceinline__ void hcmul(uint32_t re, uint32_t im, uint32_t z, uint32_t& ore, uint32_t& oim) {
    asm("{\n.reg .b16 x, y;\n.reg .b32 xx, yy, ny, a, b;\nmov.b32 {x, y}, %4;\nmov.b32 xx, {x, x};\nmov.b32 yy, {y, y};\nneg.f16x2 ny, yy;\n"
        "mul.rn.f16x2 a, %2, xx;\nfma.rn.f16x2 %0, %3, ny, a;\nmul.rn.f16x2 b, %3, xx;\nfma.rn.f16x2 %1, %2, yy, b;\n}\n" : "=&r"(ore), "=r"(oim) : "r"(re), "r"(im), "r"(z));
}
__device__ __forceinline__ void hcmul(uint32_t re, uint32_t im, uint32_t zx, uint32_t zy, uint32_t& ore, uint32_t& oim) {
    asm("{\n.reg .b32 ny, a, b;\nneg.f16x2 ny, %5;\n"
        "mul.rn.f16x2 a, %2, %4;\nfma.rn.f16x2 %0, %3, ny, a;\nmul.rn.f16x2 b, %3, %4;\nfma.rn.f16x2 %1, %2, %5, b;\n}\n" : "=&r"(ore), "=r"(oim) : "r"(re), "r"(im), "r"(zx), "r"(zy));
}

struct KGen {
    uint32_t Af[4][4];
    float2 z1, z8, z64, z128, T[9];
    uint32_t zw;
};
__device__ __forceinline__ void kgen_setup(KGen& k, uint32_t pa, float dt) {
    const float A = rbf(expf(bf_lo(pa)));
    const float lr2 = -(A * dt) * 1.4426950408889634f;
    const float li = bf_hi(pa) * dt;
    const float rh = li * 0.15915494309189535f;
    const float rl = fmaf(li, 6.4206382986e-9f, fmaf(li, 0.15915494309189535f, -rh));
    k.z1 = cexp_e(lr2, rh, rl, 1.0f);
    k.z8 = cexp_e(lr2, rh, rl, 8.0f);
    k.z64 = cexp_e(lr2, rh, rl, 64.0f);
}
__device__ __forceinline__ void kgen_rows(KGen& k, uint32_t tb, int lane) {
    const float2 z8 = k.z8, z64 = k.z64;
    const uint32_t row = tb + lane * TBP;
    k.z128 = csq(z64);
    const float2 z16 = csq(z8), z32 = csq(z16), z48 = cmul(z32, z16), z80 = cmul(z64, z16), z96 = cmul(z64, z32), z112 = cmul(z64, z48);
    uint32_t re[4], im[4], a[4], b[4];
    re[0] = pack_f16(1.0f, z16.x); im[0] = pack_f16(0.0f, z16.y);
    re[1] = pack_f16(z32.x, z48.x); im[1] = pack_f16(z32.y, z48.y);
    re[2] = pack_f16(z64.x, z80.x); im[2] = pack_f16(z64.y, z80.y);
    re[3] = pack_f16(z96.x, z112.x); im[3] = pack_f16(z96.y, z112.y);
    sts128(row, re[0], re[1], re[2], re[3]);
    sts128(row + 32, im[0], im[1], im[2], im[3]);
    const uint32_t zz = pack_f16(z8.x, z8.y);
#pragma unroll
    for (int j = 0; j < 4; j++) hcmul(re[j], im[j], zz, a[j], b[j]);
    sts128(row + 16, a[0], a[1], a[2], a[3]);
    sts128(row + 48, b[0], b[1], b[2], b[3]);
    __syncwarp();
    const int mi = lane >> 3;
    const uint32_t ad = tb + (lane & 7) * TBP + mi * 16;
#pragma unroll
    for (int ks = 0; ks < 4; ks++) ldsm_x4_t(k.Af[ks][0], k.Af[ks][1], k.Af[ks][2], k.Af[ks][3], ad + ks * 8 * TBP);
}
__device__ __forceinline__ void kgen_chain(KGen& k, uint32_t pc, float cs) {
    k.T[0] = make_float2(bf_lo(pc) * cs, -bf_hi(pc) * cs);
    const float2 y1 = make_float2(k.z1.x, -k.z1.y);
#pragma unroll
    for (int c = 1; c < 8; c++) k.T[c] = cmul(k.T[c - 1], y1);
    k.T[8] = cmul(k.T[0], make_float2(k.z8.x, -k.z8.y));
}
__device__ __forceinline__ void kgen_cols(KGen& k, uint32_t tb, int lane) {
    const uint32_t row = tb + lane * TBP;
    const float2 (&T)[9] = k.T;
    const uint32_t zv = pack_f16(k.z128.x, k.z128.y), zo = __shfl_xor_sync(0xffffffffu, zv, 1);
    k.zw = (lane & 1) ? __byte_perm(zo, zv, 0x7632) : __byte_perm(zv, zo, 0x5410);
    const float2 y256 = csq(make_float2(k.z128.x, -k.z128.y)), y512 = csq(y256), y768 = cmul(y512, y256), y1024 = csq(y512);
    const float2 c1032 = cmul(T[8], y1024);
    const uint32_t r04 = pack_f16(T[0].x, T[4].x), i04 = pack_f16(T[0].y, T[4].y), r26 = pack_f16(T[2].x, T[6].x), i26 = pack_f16(T[2].y, T[6].y);
    const uint32_t r48 = pack_f16(T[4].x, T[8].x), i48 = pack_f16(T[4].y, T[8].y);
    __syncwarp();
    sts128(row, r04, pack_f16(T[1].x, T[5].x), r26, pack_f16(T[3].x, T[7].x));
    sts128(row + 16, i04, pack_f16(T[1].y, T[5].y), i26, pack_f16(T[3].y, T[7].y));
    uint32_t a[4], b[4];
    {
        const uint32_t zz = pack_f16(y256.x, y256.y);
        hcmul(r04, i04, zz, a[0], b[0]);
        hcmul(r26, i26, zz, a[2], b[2]);
        hcmul(r48, i48, zz, a[3], b[3]);
    }
    sts128(row + 32, a[0], a[0], a[2], a[3]);
    sts128(row + 48, b[0], b[0], b[2], b[3]);
    {
        hcmul(r48, i48, pack_f16(y512.x, y512.y), a[0], b[0]);
        hcmul(r48, i48, pack_f16(y768.x, y768.y), a[1], b[1]);
        const uint32_t zz = pack_f16(c1032.x, c1032.y);
        hcmul(pack_f16(1.0f, y256.x), pack_f16(0.0f, y256.y), zz, a[2], b[2]);
        hcmul(pack_f16(y512.x, y768.x), pack_f16(y512.y, y768.y), zz, a[3], b[3]);
    }
    sts128(row + 64, a[0], a[1], a[2], a[3]);
    sts128(row + 80, b[0], b[1], b[2], b[3]);
}
__device__ __forceinline__ void kgen_mma(const KGen& k, uint32_t tb, int lane) {
    const int t = lane & 3;
    const uint32_t zw = k.zw;
    uint32_t zx[4], zy[4];
#pragma unroll
    for (int ks = 0; ks < 4; ks++) { zx[ks] = __shfl_sync(0xffffffffu, zw, 8 * ks + 2 * t); zy[ks] = __shfl_sync(0xffffffffu, zw, 8 * ks + 2 * t + 1); }
    __syncwarp();
    float acc[2][3][4];
#pragma unroll
    for (int i = 0; i < 6; i++)
#pragma unroll
        for (int j = 0; j < 4; j++) acc[i / 3][i % 3][j] = 0.f;
    {
        const int mi = lane >> 3;
        const uint32_t bd = tb + ((lane & 7) + 8 * (mi >> 1)) * TBP + (mi & 1) * 16;
#pragma unroll
        for (int kp = 0; kp < 2; kp++) {
            uint32_t b[3][4];
#pragma unroll
            for (int j = 0; j < 3; j++) ldsm_x4_t(b[j][0], b[j][1], b[j][2], b[j][3], bd + kp * 16 * TBP + j * 32);
#pragma unroll
            for (int h = 0; h < 2; h++) {
                const int ks = 2 * kp + h;
                uint32_t d[4];
                hcmul(k.Af[ks][0], k.Af[ks][2], zx[ks], zy[ks], d[0], d[2]);
                hcmul(k.Af[ks][1], k.Af[ks][3], zx[ks], zy[ks], d[1], d[3]);
#pragma unroll
                for (int j = 0; j < 3; j++) {
                    mma_f16(acc[0][j], k.Af[ks][0], k.Af[ks][1], k.Af[ks][2], k.Af[ks][3], b[j][2 * h], b[j][2 * h + 1]);
                    mma_f16(acc[1][j], d[0], d[1], d[2], d[3], b[j][2 * h], b[j][2 * h + 1]);
                }
            }
        }
    }
    __syncwarp();
#pragma unroll
    for (int h = 0; h < 2; h++) {
        sts64(tb + h * 256 + lane * 8, pack_f16(acc[h][0][0], acc[h][0][1]), pack_f16(acc[h][0][2], acc[h][0][3]));
        sts64(tb + 512 + h * 256 + lane * 8, pack_f16(acc[h][1][0], acc[h][1][1]), pack_f16(acc[h][1][2], acc[h][1][3]));
        sts32(tb + 1024 + h * 256 + lane * 4, pack_f16(acc[h][2][0], t < 2 ? acc[h][2][1] : acc[h][2][2]));
        sts32(tb + 1152 + h * 256 + lane * 4, pack_f16(t < 2 ? acc[h][2][2] : acc[h][2][1], acc[h][2][3]));
    }
}
__device__ __forceinline__ uint32_t table_buf(uint32_t sb, int warp) { return sb + SM_TB + warp * TBW; }

__device__ __forceinline__ void kgen_combine(uint32_t sb, int warp, int lane, uint32_t kw, uint32_t ao) {
    const int wq = warp & 3;
    const uint32_t a = table_buf(sb, warp & ~3) + wq * 256 + lane * 8, c = table_buf(sb, warp & ~3) + 1024 + wq * 128 + lane * 4;
    const int t = lane & 3;
    const uint32_t o0 = (t < 2 ? KW_T2 + KW_KH + 16 + t * 256 - (wq & 1) * KW_KH : KW_T3 + 16 - 1024 + t * 512 + (wq & 1) * 256) + (lane >> 2) * 16;
    const uint4 o = make_uint4(o0 + t * 36, o0 + (t ^ 1) * 36, o0 + (t ^ 2) * 36, o0 + (t ^ 3) * 36);
    const uint2 u = lds64(a), v = lds64(a + TBW), w = lds64(a + 2 * TBW), x = lds64(a + 3 * TBW);
    const uint32_t kt = hadd2(hadd2(lds32(c), lds32(c + TBW)), hadd2(lds32(c + 2 * TBW), lds32(c + 3 * TBW)));
    const uint32_t k23 = hadd2(hadd2(u.y, v.y), hadd2(w.y, x.y));
    sts64(kw + wq * 64 + ao, hadd2(hadd2(u.x, v.x), hadd2(w.x, x.x)), k23);
    const uint32_t d = kw + (wq >> 1) * 128;
    const uint32_t kh = hmul2(kt, 0x38003800u);
    sts32(d + o.x, kh); sts32(d + o.y, kh); sts32(d + o.z, kh); sts32(d + o.w, kh);
    if (wq == 3) {
        if (lane == 31) { sts32(kw + 264, k23 >> 16); sts32(kw + 288 + 264, k23 >> 16); sts32(kw + 576 + 264, k23 >> 16); }
        if (lane == 29) { sts32(kw + 864 + 280, kt >> 16); sts32(kw + 280, kt & 0xffff0000u); }
    }
}

__device__ __forceinline__ int c_exponent(const uint2& r, const uint2& i) {
    uint32_t mx = __vmaxu2(__vmaxu2(r.x & 0x7fff7fffu, r.y & 0x7fff7fffu), __vmaxu2(i.x & 0x7fff7fffu, i.y & 0x7fff7fffu));
    mx = __reduce_max_sync(0xffffffffu, max(mx & 0xffffu, mx >> 16));
    return min(max((int)(mx >> 7), 4), 240);
}

__device__ __forceinline__ int warp_v() { int l; asm volatile("mov.u32 %0, %%tid.x;" : "=r"(l)); return __shfl_sync(0xffffffffu, l >> 5, 0); }
__device__ __forceinline__ int lane_v() { int l; asm volatile("mov.u32 %0, %%laneid;" : "=r"(l)); return l; }
__device__ __forceinline__ uint32_t prmt(uint32_t a, uint32_t b, uint32_t s) { uint32_t d; asm("prmt.b32 %0, %1, %2, %3;\n" : "=r"(d) : "r"(a), "r"(b), "r"(s)); return d; }
__device__ __forceinline__ uint32_t prmt_v(uint32_t a, uint32_t b, uint32_t s) { uint32_t d; asm volatile("prmt.b32 %0, %1, %2, %3;\n" : "=r"(d) : "r"(a), "r"(b), "r"(s)); return d; }
__device__ __forceinline__ void mmah16(uint32_t& d0, uint32_t& d1, uint32_t a0, uint32_t a1, uint32_t a2, uint32_t a3, uint32_t b0, uint32_t b1, uint32_t c0, uint32_t c1) {
    asm volatile("mma.sync.aligned.m16n8k16.row.col.f16.f16.f16.f16 {%0,%1}, {%2,%3,%4,%5}, {%6,%7}, {%8,%9};\n"
                 : "=r"(d0), "=r"(d1) : "r"(a0), "r"(a1), "r"(a2), "r"(a3), "r"(b0), "r"(b1), "r"(c0), "r"(c1));
}
__device__ __forceinline__ void mmah8(uint32_t& d0, uint32_t& d1, uint32_t a0, uint32_t a1, uint32_t b0, uint32_t c0, uint32_t c1) {
    asm volatile("mma.sync.aligned.m16n8k8.row.col.f16.f16.f16.f16 {%0,%1}, {%2,%3}, {%4}, {%5,%6};\n"
                 : "=r"(d0), "=r"(d1) : "r"(a0), "r"(a1), "r"(b0), "r"(c0), "r"(c1));
}
template <int A = 8, int B = 32>
__device__ __forceinline__ void conv_rename(uint32_t (&acc)[32]) {
#pragma unroll
    for (int i = A; i < B; i++) { uint32_t v; asm volatile("mov.b32 %0, %1;\n" : "=r"(v) : "r"(acc[i])); acc[i] = v; }
}
__host__ __device__ constexpr uint32_t band_bits(int hw, int sh) {
    uint32_t c = 0;
    for (int s = 0; s <= 10; s++)
        for (int e = 0; e < 2; e++) {
            const int v = s - 3 + sh - 4 * e;
            if (v <= hw && v >= -hw) c |= 1u << (14 + 16 * e - s);
        }
    return c;
}
template <int HW, int SH, int J> __device__ __forceinline__ uint32_t band(uint32_t p2) {
    uint32_t d;
    asm volatile("{\n.reg .b32 t;\nmul.lo.u32 t, %1, %2;\nand.b32 %0, t, 0x40004000;\n}\n" : "=r"(d) : "r"(p2), "n"(band_bits(HW, SH) | J));
    return d;
}
template <int H0, int SH> __device__ __forceinline__ void band_pair(uint4& l, uint4& u, uint32_t p2) {
    l = make_uint4(band<H0, 8, 1>(p2), band<H0 - 1, SH + 8, 2>(p2), band<H0, 0, 1>(p2), band<H0 - 1, SH, 1>(p2));
    u = make_uint4(band<H0, 0, 2>(p2), band<H0 - 1, SH, 2>(p2), band<H0, -8, 1>(p2), band<H0 - 1, SH - 8, 1>(p2));
}
__device__ __forceinline__ void run_sums(uint32_t (&G)[3][2], const uint32_t (&c)[5], const uint4& l, const uint4& u) {
    mmah8(G[0][0], G[0][1], l.x, l.y, c[0], 0u, 0u);
    mmah8(G[1][0], G[1][1], u.z, u.w, c[3], 0u, 0u);
    mmah8(G[2][0], G[2][1], l.x, l.y, c[2], 0u, 0u);
    mmah16(G[0][0], G[0][1], u.x, u.y, u.z, u.w, c[1], c[2], G[0][0], G[0][1]);
    mmah16(G[1][0], G[1][1], l.x, l.y, l.z, l.w, c[1], c[2], G[1][0], G[1][1]);
    mmah16(G[2][0], G[2][1], u.x, u.y, u.z, u.w, c[3], c[4], G[2][0], G[2][1]);
}
__device__ __forceinline__ float h_lo(uint32_t w) { return __half2float(__ushort_as_half((unsigned short)(w & 0xffffu))); }
__device__ __forceinline__ float h_hi(uint32_t w) { return __half2float(__ushort_as_half((unsigned short)(w >> 16))); }
__device__ __forceinline__ uint64_t smem_desc(uint32_t sb, uint32_t o16, uint32_t lbo) {
    uint64_t d;
    asm("mov.b64 %0, {%1, %2};" : "=l"(d) : "r"(((sb & 0x3FFFF) >> 4) + o16 + (lbo << 12)), "r"(8));
    return d;
}
template <int I> struct IC { static constexpr int value = I; };

struct Conv {
    uint32_t u[3][5];
    uint32_t q2[3][2][4];
    uint32_t q3[2][4];
    uint32_t r[18];
};
__device__ __forceinline__ void conv_sums(Conv& c, uint32_t a0, uint32_t a1, const uint4 (&bd)[4]) {
    {
        uint32_t x;
        ldsm_x4(c.u[0][1], c.u[0][2], c.u[0][3], c.u[0][4], a1);
        ldsm_x4(c.u[0][0], c.u[1][0], c.u[2][0], x, a0);
#pragma unroll
        for (int q = 1; q < 3; q++) ldsm_x4(c.u[q][1], c.u[q][2], c.u[q][3], c.u[q][4], a1 + q * 512);
    }
    uint32_t G[3][2];
#pragma unroll
    for (int q = 0; q < 3; q++) {
        run_sums(G, c.u[q], bd[0], bd[1]);
#pragma unroll
        for (int e = 0; e < 2; e++) {
            const uint32_t s = e ? 0x7632u : 0x5410u;
            c.q2[q][e][0] = prmt(G[0][1], G[0][0], s); c.q2[q][e][1] = prmt(G[1][1], G[1][0], s);
            c.q2[q][e][2] = prmt(G[1][0], G[1][1], s ^ 0x4444u); c.q2[q][e][3] = prmt(G[2][1], G[2][0], s);
        }
    }
#pragma unroll
    for (int q = 0; q < 2; q++) {
        run_sums(G, c.u[q], bd[2], bd[3]);
        c.q3[q][0] = prmt(G[1][1], G[0][0], 0x7632u); c.q3[q][1] = prmt(G[2][1], G[1][0], 0x7632u);
        c.q3[q][2] = prmt(G[1][1], G[0][0], 0x5410u); c.q3[q][3] = prmt(G[2][1], G[1][0], 0x5410u);
    }
}
__device__ __forceinline__ void conv_edges(Conv& c, uint32_t (&acc)[32], uint32_t ka, uint32_t ks, uint32_t sel, int wq) {
#pragma unroll
    for (int i = 0; i < 32; i++) acc[i] = 0u;
    const uint4 r = lds128(ka + 256), s = lds128(ka + 272);
    const uint32_t a0 = prmt(r.x, r.y, sel), a1 = prmt(r.y, r.z, sel), a2 = prmt(r.z, r.w, sel), b1 = prmt(s.y, s.z, sel), b2 = prmt(s.z, s.w, sel);
    const uint32_t sw = sel ^ 0x4444u, a3 = prmt(r.z, r.y, sw), a4 = prmt(r.w, r.z, sw), b0 = prmt(s.x, s.y, sel), b3 = prmt(s.z, s.y, sw), b4 = prmt(s.w, s.z, sw);
#pragma unroll
    for (int q = 0; q < 3; q++) mmah8(acc[8 * q + 8], acc[8 * q + 9], a2, 0u, c.u[q][2], 0u, 0u);
#pragma unroll
    for (int q = 0; q < 2; q++) mmah8(acc[8 * q + 16], acc[8 * q + 17], b2, 0u, c.u[q][2], acc[8 * q + 16], acc[8 * q + 17]);
#pragma unroll
    for (int q = 0; q < 3; q++) mmah16(acc[8 * q + 8], acc[8 * q + 9], a1, a4, a0, a3, c.u[q][3], c.u[q][4], acc[8 * q + 8], acc[8 * q + 9]);
#pragma unroll
    for (int q = 0; q < 2; q++) mmah16(acc[8 * q + 16], acc[8 * q + 17], b1, b4, b0, b3, c.u[q][3], c.u[q][4], acc[8 * q + 16], acc[8 * q + 17]);
    {
        uint32_t t0, t1, t2, t3;
        ldsm_x4(t0, t1, t2, t3, ks);
#pragma unroll
        for (int q = 0; q < 2; q++) mmah16(acc[8 * q + 16], acc[8 * q + 17], c.q2[q][0][0], c.q2[q][0][1], c.q2[q][0][2], c.q2[q][0][3], t0, t1, acc[8 * q + 16], acc[8 * q + 17]);
#pragma unroll
        for (int q = 0; q < 2; q++) mmah16(acc[8 * q + 16], acc[8 * q + 17], c.q2[q][1][0], c.q2[q][1][1], c.q2[q][1][2], c.q2[q][1][3], t2, t3, acc[8 * q + 16], acc[8 * q + 17]);
    }
    {
        const uint32_t a = ka + wq * 64;
#pragma unroll
        for (int i = 0; i < 4; i++) { const uint4 v = lds128(a + i * 16); c.r[4 * i] = v.x; c.r[4 * i + 1] = v.y; c.r[4 * i + 2] = v.z; c.r[4 * i + 3] = v.w; }
        const uint2 v = lds64(a + 64);
        c.r[16] = v.x; c.r[17] = v.y;
    }
    if (sel == 0u) {
#pragma unroll
        for (int i = 0; i < 6; i++) sts128(ka + i * 16, c.q2[i >> 1][i & 1][0], c.q2[i >> 1][i & 1][1], c.q2[i >> 1][i & 1][2], c.q2[i >> 1][i & 1][3]);
#pragma unroll
        for (int i = 0; i < 2; i++) sts128(ka + i * 16, c.q3[i][0], c.q3[i][1], c.q3[i][2], c.q3[i][3]);
#pragma unroll
        for (int i = 1; i < 4; i++) sts64(ka + i * 16, acc[8 * i], acc[8 * i + 1]);
    }
    conv_rename(acc);
}
#define GATE 2
#define HAND 2
#define GA 6
#define GB 4
template <int TA, int TB, int IA, class FG>
__device__ __forceinline__ void conv_tail(uint32_t (&acc)[32], const uint32_t (&a)[8][4], uint32_t sb, unsigned char* gy0, int warp, size_t ycopy, FG fg) {
    const int wg = warp >> 2, wq = warp & 3, ord = TA == 0 && TB == 16 ? 3 - wg : 4;
    const uint32_t ub = sb + SM_U + wg * USLOT_B + UPAD * 16, turn = sb + SM_MISC + 376 + ord * 8, sfs = sb + SM_MISC + 256 + wg * 8;
    const uint32_t du = wg * (USLOT_B / 16) + (SM_U / 16 + UPAD + TA * 8);
    uint32_t ud[8], fs;
    auto skip = [&]() {
        const int lane = lane_v();
        const uint32_t ua = ub + ((lane >> 3) & 1) * ULO_B + (8 * wq + (lane & 7)) * 16 + (lane >> 4) * 512;
        if (IA == 0) ldsm_x4_t(ud[0], ud[1], ud[2], ud[3], ua);
        if (TB == 16) ldsm_x4_t(ud[4], ud[5], ud[6], ud[7], ua + 1024);
        const uint2 fd = lds64(sfs);
        fs = fd.x;
        const float dsk = __uint_as_float(fd.y);
#pragma unroll
        for (int i = 2 * IA; i < TB / 2; i++) ud[i] = pack_bf16(h_lo(ud[i]) * dsk, h_hi(ud[i]) * dsk);
    };
    conv_rename<2 * TA, 2 * TB>(acc);
    if (__builtin_expect(ord != 0, 0)) {
        skip();
        mbar_wait(turn);
    }
    if (TA == 0 && TB == 16) asm volatile("{\n.reg .pred p;\nelect.sync _|p, 0xffffffff;\n@p mbarrier.arrive.shared::cta.b64 _, [%0];\n}\n" ::"r"(turn + 40) : "memory");
    fg(IC<8>());
    wg_fence();
#pragma unroll
    for (int m = 7; m >= 0; m--) {
        wg_h<TA, TB - TA>(acc, a[m], smem_desc(sb, du - m, ULO_B));
        if (m == GA || m == GB || m == HAND) wg_commit();
        if (m == GB) asm volatile("wgmma.wait_group.sync.aligned 1;\n" ::: "memory");
    }
    wg_commit();
    if (TA == 0 && TB == 16) {
        asm volatile("wgmma.wait_group.sync.aligned 1;\n" ::: "memory");
        asm volatile("{\n.reg .pred p;\nelect.sync _|p, 0xffffffff;\n@p mbarrier.arrive.shared::cta.b64 _, [%0];\n}\n" ::"r"(turn + 8) : "memory");
    }
    __syncwarp();
    fg(IC<3>());
    if (!ord) skip();
    fg(IC<4>());
    const int lane = lane_v();
    const uint32_t lp = sb + SM_PL + (ord >= 3 ? ord - 3 : ord) * PL_B + lane * 8;
    unsigned char* gy = gy0 + ((4 * wq + (lane & 3)) * DM + (TA == 0 && TB == 16 ? 4 * blockIdx.x + wg : 512 + (blockIdx.x >> 1))) * 64 + (lane >> 2) * 8;
    const uint32_t st = lp + (wq * 12 - ((wq * (wq - 1)) >> 1)) * 256;
    uint32_t ld[3];
#pragma unroll
    for (int s = 1; s < 4; s++) {
        const int w = (wq - s) & 3;
        ld[s - 1] = lp + (w * 12 - ((w * (w - 1)) >> 1) + s - 1 - (wq < s ? 3 : 0)) * 256;
    }
    if (ord >= 3) bar_sync(9 + ord, 256);
    wg_wait0();
    fg(IC<6>());
#pragma unroll
    for (int j = TA; j < TB; j++)
        if ((j & 3) && j + 3 >= 4 * IA && (j + 3 < TB || j + wq < TB)) sts64(st + (j - 1 - (j >> 2)) * 256, acc[2 * j], acc[2 * j + 1]);
    bar_sync(1 + wg, 128);
    fg(IC<7>());
    uint2 v[4][3];
#pragma unroll
    for (int i = IA; i < TB / 4; i++)
#pragma unroll
        for (int s = 0; s < 3; s++) {
            if (i == 0) { v[i][s] = make_uint2(0u, 0u); if (wq > s) v[i][s] = lds64(ld[s]); }
            else v[i][s] = lds64(ld[s] + i * 768);
        }
    fg(IC<5>());
#pragma unroll
    for (int i = IA; i < TB / 4; i++) {
        const uint32_t x0 = hadd2(v[i][0].x, acc[8 * i]), x1 = hadd2(v[i][1].x, v[i][2].x), y0 = hadd2(v[i][0].y, acc[8 * i + 1]), y1 = hadd2(v[i][1].y, v[i][2].y);
        const uint32_t x = hadd2(x0, x1), y = hadd2(y0, y1);
        const uint32_t lo = pack_bf16(h_lo(x), h_hi(x)), hi = pack_bf16(h_lo(y), h_hi(y));
        const uint32_t o0 = max(hfma2_bf(lo, fs, ud[2 * i]), 1u), o1 = hfma2_bf(hi, fs, ud[2 * i + 1]);
        stg64(gy + i * 16 * DM * 64, o0, o1);
    }
    if (TA == 0 && TB == 16 && ord < 2) bar_arrive(12 + ord, 256);
}
template <int M0, int M1>
__device__ __forceinline__ void conv_frags(uint32_t (&a)[8][4], const uint32_t (&r)[18], uint32_t sel, uint32_t dep, int warp) {
    const uint32_t s = prmt_v(sel, dep, 0x3210u + (warp >> 8)), sw = s ^ 0x4444u;
#pragma unroll
    for (int m = M0; m < M1; m++) {
        a[m][0] = prmt_v(r[2 * m + 1], r[2 * m + 2], s); a[m][1] = prmt_v(r[2 * m + 2], r[2 * m + 3], s);
        a[m][2] = prmt_v(r[2 * m + 1], r[2 * m], sw); a[m][3] = prmt_v(r[2 * m + 2], r[2 * m + 1], sw);
    }
}
template <class FG>
__device__ __forceinline__ void conv_main(const Conv& c, uint32_t (&acc)[32], uint32_t sb, uint32_t sel, unsigned char* gy, int warp, size_t ycopy, FG fg) {
    const uint32_t kw = (warp >> 2) * (KW_B / 16) + SM_KW / 16;
    const uint64_t d2 = smem_desc(sb, kw + KW_T2 / 16, KW_KH), d2b = smem_desc(sb, kw + KW_T2 / 16 + 1, KW_KH), d3 = smem_desc(sb, kw + KW_T3 / 16, 16), d3b = smem_desc(sb, kw + KW_T3 / 16 + 32, 16);
    uint32_t a[8][4];
    {
        const int ord = warp < 16 ? 3 - (warp >> 2) : 4;
        if (__builtin_expect(ord >= GATE, 0)) {
            fg(IC<1>());
            mbar_wait(sb + SM_MISC + 376 + 40 + (ord - GATE) * 8);
        }
    }
    wg_fence();
    wg_h<12, 4>(acc, c.q3[0], d3b); wg_h<8, 4>(acc, c.q3[0], d3); wg_h<4, 4>(acc, c.q2[0][0], d2b);
    wg_h<12, 4>(acc, c.q3[1], d3); wg_h<8, 4>(acc, c.q2[1][0], d2b);
    wg_h<12, 4>(acc, c.q2[2][0], d2b); wg_h<4, 4>(acc, c.q2[0][1], d2); wg_h<8, 4>(acc, c.q2[1][1], d2);
    wg_h<12, 4>(acc, c.q2[2][1], d2);
    wg_commit(); __syncwarp();
    fg(IC<0>());
    wg_wait0();
    conv_frags<0, 8>(a, c.r, sel, acc[16], warp);
    fg(IC<2>());
    if (warp >= 16) {
        if (blockIdx.x & 1) conv_tail<4, 16, 2>(acc, a, sb, gy, warp, ycopy, fg);
        else conv_tail<0, 8, 0>(acc, a, sb, gy, warp, ycopy, fg);
    } else {
        conv_tail<0, 16, 0>(acc, a, sb, gy, warp, ycopy, fg);
    }
}
#define CONV_LT6 const int dd = (lane >> 3) + (lane & 4) - (lane & 3); \
        const uint4 lt6 = make_uint4(prmt_v((dd & 3) * 288, 0u, idn), prmt_v(0x3254u + (dd >> 2) * 0x2222u, 0u, idn), \
            prmt_v(UPAD * 16 + (lane & 7) * 16 + ULO_B - 32 + (lane >> 3) * 512, 0u, idn), prmt_v(UPAD * 16 + (lane & 7) * 16 + ((lane >> 3) & 1) * ULO_B - 16 + (lane & 16), 0u, idn));
#define CONV_PRE \
        CONV_LT6 \
        const uint32_t ka = kw + lt6.x, sel = lt6.y, ks = kw + lt7.x; \
        const uint32_t ca0 = sb + SM_U + wg * USLOT_B + (warp & 3) * 128 + lt6.z, ca1 = sb + SM_U + wg * USLOT_B + (warp & 3) * 128 + lt6.w; \
        uint4 bd[4]; \
        band_pair<2, 4>(bd[0], bd[1], lt7.w); band_pair<4, 0>(bd[2], bd[3], lt7.w);
#define CONV_BODY \
        Conv c; \
        uint32_t acc[32]; \
        conv_sums(c, ca0, ca1, bd); \
        conv_edges(c, acc, ka, ks, sel, warp & 3);
template <int U0, int U1>
__device__ __forceinline__ void weight_units(uint32_t sb, const CUtensorMap* tg, const CUtensorMap* tu, const CUtensorMap* td, int w) {
    if constexpr (U0 < U1) {
        if (w == 0 && elect_one()) {
            if constexpr (U0 < 12) tma_2d(sb + SM_WG + U0 * 6912, U0 < 6 ? tg : tu, 72 * (blockIdx.x >> 1), 288 * (blockIdx.x & 1) + (U0 % 6) * 48, sb + SM_MISC + 328);
            else tma_2d(sb + SM_WD + (15 - U0) * 10368, td, 288 * (blockIdx.x & 1) + 72 * (15 - U0), 72 * (blockIdx.x >> 1), sb + SM_MISC + 336);
        }
        weight_units<U0 + 1, U1>(sb, tg, tu, td, w - 1);
    }
}
#define WS x1123468899abcddeffg
#define WS_STR2(x) #x
#define WS_STR(x) WS_STR2(x)
__device__ constexpr int wsched(int i) { constexpr char t[] = WS_STR(WS); return i == 0 ? 0 : (t[i] <= '9' ? t[i] - '0' : t[i] - 'a' + 10); }
__device__ constexpr bool wsched_ok() { for (int i = 0; i < 19; i++) if (wsched(i + 1) < wsched(i) || wsched(i + 1) > wsched(i) + (i < 16 ? 3 : 1)) return false; return wsched(19) == 16 && wsched(6) <= 7 && wsched(16) <= 15; }
static_assert(wsched_ok(), "weight schedule");
#define WPOINT(i, w) do { weight_units<wsched(i), wsched(i + 1)>(sb, &tm_g, &tm_u, &tm_d, w); } while (0)

__global__ void __launch_bounds__(NTHR, 1) __cluster_dims__(2, 1, 1)
fused_kernel(const Params p, const __grid_constant__ CUtensorMap tm_g, const __grid_constant__ CUtensorMap tm_u, const __grid_constant__ CUtensorMap tm_d, const __grid_constant__ CUtensorMap tm_x,
             const __grid_constant__ CUtensorMap tm_y, const __grid_constant__ CUtensorMap tm_z) {
    extern __shared__ __align__(1024) unsigned char smem[];
    const uint32_t sb = smem_u32(smem);
    const int tid = threadIdx.x, warp = __shfl_sync(0xffffffffu, tid >> 5, 0), lane = tid & 31;
    const int b = blockIdx.x, P = b >> 1, odd = b & 1;
    const int g = lane >> 2, t = lane & 3;
    const int wg = warp >> 2, t128 = tid & 127;
    const uint32_t s_stat = sb + SM_MISC;
    const uint32_t s_key = sb + SM_MISC + 128;
    const uint32_t s_wm = sb + SM_MISC + 256;
    const uint32_t s_k16 = sb + SM_MISC + 192;
    const uint32_t s_fs = sb + SM_MISC + 256;
    const uint32_t s_cnt = sb + SM_MISC + 320;
    const uint32_t bar_w = sb + SM_MISC + 328, bar_d = bar_w + 8, bar_g = bar_w + 16, bar_h = bar_w + 40, bar_x = bar_w + 48;
    STAMP(0);

    const bool lnw = (unsigned)(warp - 10) < 9u;
    const unsigned pm = tid + (tid < 512 ? 512 * b : 65024 + 128 * P), pq = (pm & ~127u) + 4 * lane;
    uint32_t pl = ldg16(p.lar + pm), ldt = ldg16(p.ldt + (pm >> 7));
    const uint32_t pa2 = ldg16(p.aim + pm), pc = ldg16(p.cre + pm), pi = ldg16(p.cim + pm);
    const uint2 call_re = ldg64(p.cre + pq), call_im = ldg64(p.cim + pq);
    const uint32_t dskl = ldg16(p.dsk + (pm >> 7));
    const uint32_t ep = ld_poll32(p.s->hint + (b & 7) * 32 + 1 + (lane >> 5));
    if ((unsigned)(tid - 320) < 288u) {
        const bf16* xp = p.x + (unsigned)((32 * P + 2 * odd + TOKEN_OF(g)) * DM + ((tid - 320) & ~31) + 8 * t);
        const uint32_t xt = sb + SM_XT + ((tid - 320) & ~31) * 32 + lane * 16;
        asm volatile("cp.async.cg.shared.global [%0], [%1], 16;\ncp.async.cg.shared.global [%0 + 512], [%1 + 9216], 16;\n"
                     "cp.async.cg.shared.global [%0 + 9216], [%1 + 576], 16;\ncp.async.cg.shared.global [%0 + 9728], [%1 + 9792], 16;\n" ::"r"(xt), "l"(xp) : "memory");
    }
    uint32_t* const std_ = p.s->st + ((lane & 12) * 128 + odd * 256 + 4 * P + 2 * (lane & 1) + ((lane >> 1) & 1)) * 2;
    unsigned char* const ud = reinterpret_cast<unsigned char*>(p.s->uT) + (32 * (warp - UW) + 8 * (g >> 1) + (g & 1)) * 4096 + b * 32 + t * 8;
    if (warp == 0) {
        if (lane == 0) {
            mbar_init(bar_x, 1); mbar_init(bar_w, 1); mbar_init(bar_d, 1); mbar_init(bar_g, 1); mbar_init(bar_h, 3);
            #pragma unroll
            for (int i = 1; i < 9; i++) mbar_init(bar_x + 8 * i, 4);
            asm volatile("fence.mbarrier_init.release.cluster;\n" ::: "memory");
            mbar_expect(bar_x, 32768);
            mbar_expect(bar_w, 2 * 41472); mbar_expect(bar_d, 41472); mbar_expect(bar_g, 18 * 512);
        }
        __syncwarp();
        bar_arrive(0, NWRK);
    }
    asm volatile("barrier.cluster.arrive.relaxed.aligned;\n" ::: "memory");
    if (warp == 0) {
        asm volatile("barrier.cluster.wait.acquire.aligned;\n" ::: "memory");
        if (elect_one()) tma_3d_mc(sb + SM_XC + 16384 * odd, &tm_x, 8 * P, 0, 8 * odd, bar_x);
    }
    const uint32_t kw = sb + SM_KW + wg * KW_B;
    if (t128 < 2 * UPAD) sts128(sb + SM_U + wg * USLOT_B + (t128 & 1) * ULO_B + (t128 >> 1) * 16, 0u, 0u, 0u, 0u);
    sts128(kw + t128 * 16, 0u, 0u, 0u, 0u);
    if (t128 < KW_B / 16 - 128) sts128(kw + 2048 + t128 * 16, 0u, 0u, 0u, 0u);
    if (tid < 96) {
#pragma unroll
        for (int i = 0; i < 6; i++) sts128(sb + SM_ZERO + i * 1536 + tid * 16, 0u, 0u, 0u, 0u);
    }
    if (warp != 0) bar_sync(0, NWRK);
    STAMP(1);
    if (warp == 19 || warp == UW || warp == UW + 1) {
        if (warp == 19) {
            if (lane < 16) stg64(std_, 0u, 0u);
            if (lane < 9) asm volatile("prefetch.global.L2 [%0];\n" ::"l"(p.wr + lane * 64));
        } else {
#pragma unroll
            for (int k = 0; k < 4; k++) stg64(ud + k * 8192, 0u, 0u);
        }
    }
    uint32_t X[2][8];
    auto partial = [&]() {
        const uint32_t xt = sb + SM_XT + (warp - 10) * 1024 + lane * 16;
        asm volatile("cp.async.wait_all;\n" ::: "memory");
        STAMP(23);
        const uint4 a = lds128(xt), c = lds128(xt + 512), d = lds128(xt + 9216), e = lds128(xt + 9728);
        X[0][0] = a.x; X[0][1] = a.y; X[0][2] = a.z; X[0][3] = a.w; X[0][4] = d.x; X[0][5] = d.y; X[0][6] = d.z; X[0][7] = d.w;
        X[1][0] = c.x; X[1][1] = c.y; X[1][2] = c.z; X[1][3] = c.w; X[1][4] = e.x; X[1][5] = e.y; X[1][6] = e.z; X[1][7] = e.w;
        ln_partial<8>(X, sb + SM_LNP, warp - 10, g, t);
        bar_arrive(6, 320);
        if (PAUSE & 1) bar_sync(7, PCNT);
    };
    if (LNAT == 0 && lnw) {
        partial();
        pl = prmt_v(pl, X[0][0], 0x3210u + (warp >> 8)); ldt = prmt_v(ldt, X[0][0], 0x3210u + (warp >> 8));
    }
    auto finish = [&]() {
        bar_sync(6, 320);
        float mb, rc;
        ln_finish<9>(sb + SM_LNP, lane, mb, rc);
        const float rh = rbf(rc);
        const uint32_t s0 = (__float_as_uint(mb) >> 16) | (((ep & 0x7fffu) + 1u) << 16), s1 = pack_bf16(rh, rc - rh);
        if (lane < 16) { stg64(std_, s0, s1); sts64(s_stat + lane * 8, s0, s1); }
        if (lane == 16) sts32(s_cnt + 4, ep);
        bar_arrive(7, PCNT);
        STAMP(28);
    };
    auto upub = [&]() {
        if (!(PAUSE & 6)) bar_sync(7, PCNT);
        const uint32_t utag = ((ep & 3u) + 1u) * 0x10001u;
        uint32_t U[2][4];
#pragma unroll
        for (int hf = 0; hf < 2; hf++) {
            const uint2 st = lds64(s_stat + (g + 8 * hf) * 8);
            const uint4 xv = lds128(sb + SM_XT + (16 + warp - UW) * 1024 + hf * 512 + lane * 16);
            const uint32_t xs[4] = {xv.x, xv.y, xv.z, xv.w};
#pragma unroll
            for (int k = 0; k < 4; k++) {
                const uint32_t u = ln_apply(xs[k], st);
                U[hf][k] = movm((pack_f16_rz(bf_lo(u), __uint_as_float(u)) & 0xfff8fff8u) | utag);
            }
        }
#pragma unroll
        for (int k = 0; k < 4; k++) stg64(ud + k * 8192, U[0][k], U[1][k]);
    };
    STAMP(27);
    if (FINAT == 0 && warp == 19) finish();
    const uint32_t tb = table_buf(sb, warp);
    const float dt = rbf(expf(bf_lo(ldt)));
    KGen kg;
    kgen_setup(kg, pl | (pa2 << 16), dt);
    if (LNAT == 1 && lnw) {
        partial();
        kg.z8.x = __uint_as_float(prmt_v(__float_as_uint(kg.z8.x), X[0][0], 0x3210u + (warp >> 8)));
        kg.z1.x = __uint_as_float(prmt_v(__float_as_uint(kg.z1.x), X[0][0], 0x3210u + (warp >> 8)));
    }
    if (FINAT == 1 && warp == 19) finish();
    if (UAT == 0 && (warp == UW || warp == UW + 1)) upub();
    kgen_rows(kg, tb, lane);
    if (wg == 0) fence_async();
    if (LNAT == 2 && lnw) {
        partial();
        kg.z128.x = __uint_as_float(prmt_v(__float_as_uint(kg.z128.x), X[0][0], 0x3210u + (warp >> 8)));
        kg.z1.x = __uint_as_float(prmt_v(__float_as_uint(kg.z1.x), X[0][0], 0x3210u + (warp >> 8)));
    }
    if (FINAT == 2 && warp == 19) finish();
    if (UAT == 1 && (warp == UW || warp == UW + 1)) upub();
    STAMP(2);
    WPOINT(0, warp - 4);
    const int ce = c_exponent(call_re, call_im);
    if (t128 == 0) sts64(s_fs + wg * 8, (uint32_t)min(max(ce + (int)(__float_as_uint(dt) >> 23) - 116, 0), 254) * 0x800080u, dskl << 16);
    kgen_chain(kg, pc | (pi << 16), __uint_as_float(((uint32_t)(244 - ce) << 23) | (__float_as_uint(dt) & 0x7fffffu)));
    if ((PAUSE & 4) && warp < 10) bar_sync(7, PCNT);
    if (UAT == 4 && (warp == UW || warp == UW + 1)) upub();
    STAMP(3);
    WPOINT(1, warp - 6);
    kgen_cols(kg, tb, lane);
    if (LNAT == 3 && lnw) partial();
    if (FINAT == 3 && warp == 19) finish();
    if ((PAUSE & 2) && warp < 10) bar_sync(7, PCNT);
    if (UAT == 2 && (warp == UW || warp == UW + 1)) upub();
    STAMP(4);
    WPOINT(2, warp - 8);
    const uint4* usrc = wg < 4 ? reinterpret_cast<const uint4*>(p.s->st) + (warp & 1) * 512 + (lane & 1) * 128 + 16 * (warp >> 1) + (lane >> 1)
                               : reinterpret_cast<const uint4*>(p.s->uT) + P * 256 + 2 * t128;
    const int ustep = wg < 4 ? 256 : 1;
    uint4 uv0, uv1;
    kgen_mma(kg, tb, lane);
    if (UAT == 3 && (warp == UW || warp == UW + 1)) upub();
    STAMP(26);
    WPOINT(3, warp - 5);
    const uint32_t idn = 0x3210u + (warp >> 8);
    const uint4 lt7 = make_uint4(prmt_v(KW_T2 + ((lane >> 3) & 1) * KW_KH + (33 + (lane & 7)) * 16 - (lane & 16), 0u, idn), t * 288 + g * 8 + 8, (lane & 1) * 4096 + (lane >> 1) * 16,
                                 prmt_v(8u << ((lane >> 3) + (lane & 4)) >> (lane & 3), 0u, idn));
    bar_sync(1 + wg, 128);
    uv0 = ld_poll(usrc); uv1 = ld_poll(usrc + ustep);
    kgen_combine(sb, warp, lane, kw, lt7.y);
    CONV_PRE
    STAMP(5);
    WPOINT(4, warp - 7);
    if (wg < 4) {
        mbar_wait(bar_x);
        const uint32_t xa = sb + SM_XC + (warp & 1) * 16384 + (warp >> 1) * 256 + odd * 8 + lt7.z;
        uint2 xv[4] = {lds64(xa), lds64(xa + 8192), lds64(xa + 2048), lds64(xa + 10240)};
        const uint32_t tag = ((ep & 0x7fffu) + 1u) << 16;
        int it = 0;
        while (true) {
            const bool bad = (((uv0.x ^ tag) | (uv0.z ^ tag)) | ((uv1.x ^ tag) | (uv1.z ^ tag))) >> 16;
            if (!__any_sync(0xffffffffu, bad)) break;
            if (++it > SPIN_LIMIT) TRAP();
            if (bad) { uv0 = ld_poll(usrc); uv1 = ld_poll(usrc + 256); }
        }
        STAMP(6);
        DBG(wg, it);
        const uint2 st[4] = {make_uint2(uv0.x, uv0.y), make_uint2(uv0.z, uv0.w), make_uint2(uv1.x, uv1.y), make_uint2(uv1.z, uv1.w)};
#pragma unroll
        for (int i = 0; i < 4; i++) {
            xv[i].x = ln_apply(xv[i].x, st[i]);
            xv[i].y = ln_apply(xv[i].y, st[i]);
        }
        const uint32_t ub = sb + SM_U + UPAD * 16 + (warp & 1) * ULO_B + (warp >> 1) * 256 + lane * 8;
        sts64(ub, pack_f16(bf_lo(xv[0].x), bf_lo(xv[1].x)), pack_f16(bf_lo(xv[2].x), bf_lo(xv[3].x)));
        sts64(ub + USLOT_B, HI2(xv[0].x, xv[1].x), HI2(xv[2].x, xv[3].x));
        sts64(ub + 2 * USLOT_B, pack_f16(bf_lo(xv[0].y), bf_lo(xv[1].y)), pack_f16(bf_lo(xv[2].y), bf_lo(xv[3].y)));
        sts64(ub + 3 * USLOT_B, HI2(xv[0].y, xv[1].y), HI2(xv[2].y, xv[3].y));
    } else {
        const uint32_t utag = ((ep & 3u) + 1u) * 0x10001u;
        int it = 0;
        while (true) {
            const bool bad = (((uv0.x ^ utag) | (uv0.y ^ utag) | (uv0.z ^ utag) | (uv0.w ^ utag)) | ((uv1.x ^ utag) | (uv1.y ^ utag) | (uv1.z ^ utag) | (uv1.w ^ utag))) & 0x70007u;
            if (!__any_sync(0xffffffffu, bad)) break;
            if (++it > SPIN_LIMIT) TRAP();
            if (bad) { uv0 = ld_poll(usrc); uv1 = ld_poll(usrc + 1); }
        }
        STAMP(6);
        DBG(4, it);
        const uint32_t ub = sb + SM_U + UPAD * 16 + 4 * USLOT_B + (t128 >> 1) * 32 + (t128 & 1) * 8;
        sts64(ub, prmt(uv0.x, uv0.z, 0x5410u) ^ utag, prmt(uv1.x, uv1.z, 0x5410u) ^ utag);
        sts64(ub + 16, prmt(uv0.x, uv0.z, 0x7632u) ^ utag, prmt(uv1.x, uv1.z, 0x7632u) ^ utag);
        sts64(ub + ULO_B, prmt(uv0.y, uv0.w, 0x5410u) ^ utag, prmt(uv1.y, uv1.w, 0x5410u) ^ utag);
        sts64(ub + ULO_B + 16, prmt(uv0.y, uv0.w, 0x7632u) ^ utag, prmt(uv1.y, uv1.w, 0x7632u) ^ utag);
    }
    fence_async();
    WPOINT(5, warp - 3);
    if (warp < 3 && elect_one()) tma_st_3d(warp < 2 ? &tm_y : &tm_z, sb + SM_ZERO, warp < 2 ? 128 * b : 32 * (512 + P), 0, 2 * (warp < 2 ? warp : odd));
    if (warp != 0) asm volatile("barrier.cluster.wait.acquire.aligned;\n" ::: "memory");
    bar_sync(0, NWRK);
    STAMP(7);
    {
        CONV_BODY
        WPOINT(6, 19 - warp);
        bar_sync(0, NWRK);
        STAMP(8);
        size_t ycopy = 0;
        auto hook = [&](auto gi) {
                     constexpr int G = decltype(gi)::value;
                     if (G == 5) mbar_wait(bar_h);
                     if (G < 3) WPOINT(7 + G, warp - 16 - G);
                     if (G == 3) { WPOINT(10, warp - 12); WPOINT(12, warp - 8); WPOINT(14, warp - 4); }
                     if (G == 5) { WPOINT(11, warp - 13); WPOINT(13, warp - 9); WPOINT(15, warp - 5); }
                     if (G == 1 && warp < 4) {
                         if (elect_one()) {
                             if (warp == 3) {
                                 bulk_s2g(reinterpret_cast<unsigned char*>(p.s->part) + b * 9216, sb + SM_ZERO, 9216);
                                 bulk_s2g(reinterpret_cast<unsigned char*>(p.s->rows) + b * 4608, sb + SM_ZERO, 4608);
                                 bulk_s2g(reinterpret_cast<unsigned char*>(p.s->sc) + b * 128, sb + SM_ZERO, 32);
                             }
                             asm volatile("cp.async.bulk.wait_group 0;\n" ::: "memory");
                             if (warp < 3) mbar_arrive(bar_h);
                             hint_arrive(p.s->hint, warp < 3 ? 0 : 2, b & 7);
                         }
                         __syncwarp();
                     }
                 };
        conv_main(c, acc, sb, sel, reinterpret_cast<unsigned char*>(p.s->y), warp, ycopy, hook);
        STAMP(10);
    }
    {
    const int warp = warp_v(), lane = lane_v(), tid = 32 * warp + lane, g = lane >> 2, t = lane & 3;
    if (warp == 12) hint_wait(p.s->hint, 0, (lds32(s_cnt + 4) + 1u) * 48u);
    bar_sync(0, NWRK);
    STAMP(11);
    const uint32_t zr = warp >> 8;
    auto late_rows = [&](auto pub) {
        const uint32_t k = lds32(s_key + (lane & 7) * 4), ep = lds32(s_cnt + 4);
        const bool late = k & 256u, mine = late && ((k & 255u) >> 1) == (uint32_t)b;
        uint32_t todo = __ballot_sync(0xffffffffu, mine) & 0xffu;
        if (todo) {
#pragma unroll 1
            while (todo) {
                const int s = __ffs(todo) - 1, row = (__shfl_sync(0xffffffffu, k, s) >> 9) & 15;
                todo &= todo - 1;
                if ((row & 7) == g) pub(row & 8, 2 * NCTA + s);
            }
            __threadfence();
            bar_sync(0, NWRK);
            if (tid < NSEL && mine) *reinterpret_cast<volatile unsigned*>(p.s->flag + tid) = ep + 1u;
        }
        int it = 0;
        while (__any_sync(0xffffffffu, late && ld_poll32(p.s->flag + (lane & 7)) != ep + 1u)) { if (++it > SPIN_LIMIT) TRAP(); }
        __threadfence();
        const int gs = tid / 36;
        const uint4* src = reinterpret_cast<const uint4*>(p.s->rows) + __shfl_sync(0xffffffffu, late ? 2 * NCTA + (lane & 7) : (k & 255u), gs & 7) * 144 + 36 * odd + (tid - gs * 36);
        if (tid < 288) {
            uint4 v0;
            do { v0 = ld_poll(src); if (++it > SPIN_LIMIT) TRAP(); } while (!v0.x);
            sts128(sb + SM_XS + gs * XS_PITCH + (tid - gs * 36) * 16, v0.x, v0.y, v0.z, v0.w);
        }
        bar_sync(0, NWRK);
    };
    if (warp >= 18) {
        if (warp == 18) {
            uint32_t* const kp = pin(p.s->sc + 32 * b, zr);
            const uint32_t kid = pin(0x30000000u | ((lane & 15) << 9) | 2 * b, zr), ka = pin(s_k16 + (lane & 15) * 4, zr), kb = pin(s_k16 + (lane & 16) * 2, zr);
            bar_sync(8, 640);
            float mb, rc;
            ln_finish<18>(sb + SM_LNP, lane, mb, rc);
            if (lane < 16) stat_store(s_stat + lane * 8, mb, rc, 0u);
            bar_arrive(13, 608);
            bar_sync(10, 608);
            const float r = sum18(sb + SM_LNP + (32 + (lane & 15)) * 80);
            const uint32_t bits = pack_bf16(0.f, r);
            const uint32_t me = (((bits ^ ((uint32_t)((int)bits >> 31) & 0x7fffffffu)) >> 3) & 0x1fffe000u) ^ kid;
            sts32(ka, me);
            __syncwarp();
            const uint4 v = lds128(kb), w = lds128(kb + 16);
#define GT(x) ((me - (x)) >> 31)
            uint32_t rank = pin(GT(v.x) + GT(v.y) + GT(v.z), zr) + pin(GT(v.w) + GT(w.x) + GT(w.y), zr) + pin(GT(w.z) + GT(w.w), zr);
#undef GT
            rank += __shfl_xor_sync(0xffffffffu, rank, 16);
            if (lane < 16) { if (rank < 8) stg32(kp + rank, me + (rank < 2 ? rank : 256u)); }
            else sts32(ka + (s_wm - s_k16), rank);
            bar_arrive(11, 640);
        }
        const uint4* ksrc = pin(reinterpret_cast<const uint4*>(p.s->sc) + 8 * lane, zr);
        const uint4* rsrc = pin(reinterpret_cast<const uint4*>(p.s->rows) + 36 * odd + t, zr);
        if (warp == 19) {
            hint_wait(p.s->hint, 2, (lds32(s_cnt + 4) + 1u) * 16u);
            bar_sync(8, 640);
            WPOINT(16, 0);
            WPOINT(17, 0);
            bar_sync(11, 640);
        }
        bool slow = false;
        int it = 0;
        if (warp == 19) {
        uint4 q[4];
#pragma unroll
        for (int i = 0; i < 4; i++) q[i] = ld_poll(ksrc + 256 * i);
        while (true) {
            uint32_t a[4];
#pragma unroll
            for (int i = 0; i < 4; i++) a[i] = q[i].x & q[i].y & q[i].z & q[i].w;
            if (__all_sync(0xffffffffu, a[0] & a[1] & a[2] & a[3])) break;
#pragma unroll
            for (int i = 0; i < 4; i++)
                if (!a[i]) q[i] = ld_poll(ksrc + 256 * i);
            if (++it > SPIN_LIMIT) TRAP();
        }
        bar_arrive(9, 608);
        STAMP(16);
        auto merge = [](const uint4& x, const uint4& y) {
            const uint32_t a = max(x.x, y.w), c = max(x.y, y.z), d = max(x.z, y.y), e = max(x.w, y.x);
            const uint32_t a2 = max(a, d), d2 = min(a, d), c2 = max(c, e), e2 = min(c, e);
            return make_uint4(max(a2, c2), min(a2, c2), max(d2, e2), min(d2, e2));
        };
        uint4 h = merge(merge(q[0], q[1]), merge(q[2], q[3]));
        uint4 v[9];
        uint32_t key = 0;
#pragma unroll
        for (int s = 0; s < 8; s++) {
            const uint32_t m = __reduce_max_sync(0xffffffffu, h.x);
            const bool w = h.x == m;
            h.x = w ? h.y : h.x; h.y = w ? h.z : h.y; h.z = w ? h.w : h.z; h.w = w ? 0u : h.w;
            if (g == s) key = m;
        }
        rsrc += (key & 255u) * 144;
#pragma unroll
        for (int j = 0; j < 9; j++) v[j] = ld_poll(rsrc + 4 * j);
        slow = __any_sync(0xffffffffu, key & 256u);
        STAMP(18);
        if (__any_sync(0xffffffffu, h.x == 0u)) {
            uint4 r[4];
            it = 0;
            while (true) {
#pragma unroll
                for (int i = 0; i < 4; i++) r[i] = ld_poll(ksrc + 256 * i + 1);
                if (__all_sync(0xffffffffu, all_nz(r[0]) && all_nz(r[1]) && all_nz(r[2]) && all_nz(r[3]))) break;
                if (++it > SPIN_LIMIT) TRAP();
            }
            uint32_t m = 1u << 30;
#pragma unroll 1
            for (int s = 0; s < 8; s++) {
                uint32_t x = 0;
#pragma unroll
                for (int i = 0; i < 4; i++) {
                    x = max(max(max(x, q[i].x - m), max(q[i].y - m, q[i].z - m)), q[i].w - m);
                    x = max(max(max(x, r[i].x - m), max(r[i].y - m, r[i].z - m)), r[i].w - m);
                }
                m += __reduce_max_sync(0xffffffffu, x);
                if (g == s) key = m;
            }
            slow = true;
        }
        sts32(s_key + g * 4, key);
        if (!slow) {
            it = 0;
            while (true) {
                const uint32_t mn = min(min(min(min(v[0].x, v[1].x), v[2].x), min(min(v[3].x, v[4].x), v[5].x)), min(min(v[6].x, v[7].x), v[8].x));
                if (__all_sync(0xffffffffu, mn)) break;
                if (++it > SPIN_LIMIT) TRAP();
#pragma unroll
                for (int j = 0; j < 9; j++) v[j] = ld_poll(rsrc + 4 * j);
            }
#pragma unroll
            for (int j = 0; j < 9; j++) sts128(sb + SM_XS + g * XS_PITCH + t * 16 + j * 64, v[j].x, v[j].y, v[j].z, v[j].w);
        }
        }
        if (bar_or(0, NWRK, slow)) late_rows([](bool, int) {});
        STAMP(19);
        const int fl = 16 * (b & 1) + ((tid >> 2) & 15), fc = 16 * (b >> 1) + (fl >> 2) + 8 * ((tid >> 1) & 1), fsl = 2 * (fl & 3) + (tid & 1);
        const uint32_t kk = lds32(s_key + fsl * 4);
        const uint32_t* fsrc = p.s->rows + ((kk & 256u) ? 2 * NCTA + fsl : (kk & 255u)) * DM + (fc >> 1);
        uint32_t hw = 1u, uw = 1u;
        if (b < 72) { uw = ld_poll32(fsrc); hw = ld_poll32(fsrc + 288); }
        {
            const uint32_t row = 8 * (warp & 1) + (lane >> 2);
            const uint2 k = lds64(s_key + (lane & 3) * 8);
            const uint32_t id = (row << 9) | 2 * b, hit = __ballot_sync(0xffffffffu, (k.x & 0x1efeu) == id || (k.y & 0x1efeu) == id);
            if ((lane & 3) == 0 && !((hit >> lane) & 15u)) bulk_s2g(p.out + (size_t)(32 * P + 2 * odd + TOKEN_OF(row & 7) + (row & 8)) * DM, sb + SM_OUT + row * OUT_PITCH, DM * 2);
            __syncwarp();
        }
        if (b < 72) {
            it = 0;
            while (!hw || !uw) { uw = ld_poll32(fsrc); hw = ld_poll32(fsrc + 288); if (++it > SPIN_LIMIT) TRAP(); }
            const int row = (kk >> 9) & 15, ftok = 8 * (kk & 252u) + (kk & 2u) + TOKEN_OF(row & 7) + (row & 8);
            const unsigned k16 = (kk >> 13) & 0xffffu;
            const unsigned bits = (k16 & 0x8000u) ? (k16 & 0x7fffu) : (~k16 & 0xffffu);
            const float rs = __uint_as_float(pin(__float_as_uint(rbf(__fdividef(1.0f, 1.0f + __expf(-__uint_as_float(bits << 16))))), zr));
            bf16* const op = pin(p.out + (size_t)ftok * DM + fc, zr);
            const float uv = (fc & 1) ? bf_hi(uw) : bf_lo(uw), hv = (fc & 1) ? bf_hi(hw) : bf_lo(hw);
            bar_sync(14, 576);
            float v0 = 0.f, v1 = 0.f, v2 = 0.f, v3 = 0.f;
            const uint32_t a = sb + SM_EX + (tid - 576) * 4;
#pragma unroll
            for (int i = 0; i < 16; i += 4) { v0 += ldsf(a + i * 256); v1 += ldsf(a + i * 256 + 256); v2 += ldsf(a + i * 256 + 512); v3 += ldsf(a + i * 256 + 768); }
            const float y3 = rbf(rbf((v0 + v1) + (v2 + v3)) * rs);
            asm volatile("st.global.u16 [%0], %1;\n" ::"l"(op), "h"((unsigned short)pack_bf16(hv + rbf(uv + y3), 0.f)) : "memory");
        }
        asm volatile("cp.async.bulk.wait_group.read 0;\n" ::: "memory");
        if (b == 0 && tid >= 632) *reinterpret_cast<volatile unsigned*>(p.s->hint + (tid & 7) * 32 + 1) = lds32(s_cnt + 4) + 1u;
    } else {
        uint32_t H[2][4], U2[2][4], WA[9][4], WD[18];
        const int fkh = warp >= 9, fmt = warp - 9 * fkh;
        auto load_wa = [&]() {
            mbar_wait(bar_w);
            const int mi = lane >> 3, rr = lane & 7;
            const uint32_t aad = sb + SM_WG + (mi & 1) * SM_WU + (fkh * 144 + rr + 8 * (mi >> 1)) * W_PITCH + fmt * 16;
#pragma unroll
            for (int k = 0; k < 9; k++) ldsm_x4_t(WA[k][0], WA[k][1], WA[k][2], WA[k][3], aad + k * 16 * W_PITCH);
        };
        auto load_wd = [&]() {
            mbar_wait(bar_d);
            const int mi = lane >> 3, rr = lane & 7;
            const int c8 = 2 * warp + (mi & 1), bx = c8 / 9;
            const uint32_t base = sb + SM_WD + bx * 10368 + (c8 - 9 * bx) * 16 + rr * W_PITCH;
#pragma unroll
            for (int k = 0; k < 4; k++) ldsm_x4_t(WD[4 * k], WD[4 * k + 1], WD[4 * k + 2], WD[4 * k + 3], base + (k * 16 + 8 * (mi >> 1)) * W_PITCH);
            ldsm_x2_t(WD[16], WD[17], base + 64 * W_PITCH);
        };
        auto publish = [&](bool hi, int slot) {
            uint4* rowp = reinterpret_cast<uint4*>(p.s->rows) + slot * 144 + warp * 4 + t;
            stg128(rowp, nzw(hi ? U2[1][0] : U2[0][0]), nzw(hi ? U2[1][1] : U2[0][1]), nzw(hi ? U2[1][2] : U2[0][2]), nzw(hi ? U2[1][3] : U2[0][3]));
            stg128(rowp + 72, nzw(hi ? H[1][0] : H[0][0]), nzw(hi ? H[1][1] : H[0][1]), nzw(hi ? H[1][2] : H[0][2]), nzw(hi ? H[1][3] : H[0][3]));
        };
        uint4 wr = make_uint4(0u, 0u, 0u, 0u);
        {
            const unsigned char* ys = reinterpret_cast<const unsigned char*>(p.s->y) + ((size_t)P * DM + 32 * warp + 8 * (g >> 1) + (g & 1)) * 64 + odd * 32 + t * 8;
            uint2 yv[4];
#pragma unroll
            for (int k = 0; k < 4; k++) yv[k] = ld_poll64(ys + k * 128);
            if (g == 0) wr = ldg128(p.wr + 32 * warp + 8 * t);
            const uint4 x0 = lds128(sb + SM_XT + warp * 1024 + lane * 16), x1 = lds128(sb + SM_XT + warp * 1024 + 512 + lane * 16);
            if (WAAT == 0) load_wa();
            int it = 0;
            while (!__all_sync(0xffffffffu, yv[0].x && yv[1].x && yv[2].x && yv[3].x)) {
#pragma unroll
                for (int k = 0; k < 4; k++) yv[k] = ld_poll64(ys + k * 128);
                if (++it > SPIN_LIMIT) TRAP();
            }
            STAMP(12);
            const uint32_t Z[2][4] = {{x0.x, x0.y, x0.z, x0.w}, {x1.x, x1.y, x1.z, x1.w}};
#pragma unroll
            for (int k = 0; k < 4; k++) {
                H[0][k] = hadd2_bf(Z[0][k], movm(yv[k].x));
                H[1][k] = hadd2_bf(Z[1][k], movm(yv[k].y));
            }
            ln_partial<4>(H, sb + SM_LNP, warp, g, t);
        }
        bar_arrive(8, 640);
        STAMP(13);
        bar_sync(13, 608);
        STAMP(14);
#pragma unroll
        for (int hf = 0; hf < 2; hf++) {
            const uint2 st = lds64(s_stat + (g + 8 * hf) * 8);
#pragma unroll
            for (int k = 0; k < 4; k++) U2[hf][k] = ln_apply(H[hf][k], st);
        }
        {
            float cs[4] = {0.f, 0.f, 0.f, 0.f};
            mma_bf16(cs, U2[0][0], U2[1][0], U2[0][1], U2[1][1], wr.x, wr.y);
            mma_bf16(cs, U2[0][2], U2[1][2], U2[0][3], U2[1][3], wr.z, wr.w);
            if (t == 0) { stsf(sb + SM_LNP + ((32 + g) * 20 + warp) * 4, cs[0]); stsf(sb + SM_LNP + ((40 + g) * 20 + warp) * 4, cs[2]); }
            bar_arrive(10, 608);
        }
        bar_sync(11, 640);
        {
            const uint32_t rk[2] = {lds32(s_wm + g * 4), lds32(s_wm + 32 + g * 4)};
            uint32_t lo = min(rk[0], rk[1]), hi = max(rk[0], rk[1]);
#pragma unroll 1
            while (lo < 2) { publish(lo == rk[1], 2 * b + lo); lo = hi; hi = 16; }
        }
        if (WAAT == 2) load_wa();
        bar_sync(9, 608);
        if (WAAT == 1) load_wa();
#pragma unroll
        for (int hf = 0; hf < 2; hf++)
            sts128(sb + SM_OUT + (g + 8 * hf) * OUT_PITCH + warp * 64 + t * 16,
                   hadd2_bf(H[hf][0], U2[hf][0]), hadd2_bf(H[hf][1], U2[hf][1]), hadd2_bf(H[hf][2], U2[hf][2]), hadd2_bf(H[hf][3], U2[hf][3]));
        fence_async();
        WPOINT(18, warp - 17);
        if (WDAT == 0) load_wd();
        const uint32_t bad = pin(sb + SM_XS + (lane & 7) * XS_PITCH + (fkh * 144 + 8 * (lane >> 3)) * 2, zr), ex = pin(sb + SM_EX + (18 * odd + warp) * 512 + lane * 16, zr);
        uint32_t* const pp = pin(p.s->part + ((size_t)(2 * (18 * odd + warp) + (lane >> 4)) * 64 + P) * 64 + (lane & 15) * 4, zr);
        STAMP(15);
        if (bar_or(0, NWRK, false)) late_rows(publish);
        STAMP(19);
        {
            float c4[3][4];
#pragma unroll
            for (int i = 0; i < 3; i++)
#pragma unroll
                for (int j = 0; j < 4; j++) c4[i][j] = 0.f;
#pragma unroll
            for (int k = 0; k < 10; k += 2) {
                uint32_t b0, b1, b2, b3;
                ldsm_x4(b0, b1, b2, b3, bad + k * 32);
                mma_bf16(c4[k % 3], WA[k][0], WA[k][1], WA[k][2], WA[k][3], b0, b1);
                if (k < 8) mma_bf16(c4[(k + 1) % 3], WA[k + 1][0], WA[k + 1][1], WA[k + 1][2], WA[k + 1][3], b2, b3);
            }
#pragma unroll
            for (int j = 0; j < 4; j++) c4[0][j] += c4[1][j] + c4[2][j];
            asm volatile("st.async.shared::cluster.mbarrier::complete_tx::bytes.v4.b32 [%0], {%1,%2,%3,%4}, [%5];\n"
                         ::"r"(ex ^ 0x1000000u), "r"(__float_as_uint(c4[0][0])), "r"(__float_as_uint(c4[0][1])), "r"(__float_as_uint(c4[0][2])), "r"(__float_as_uint(c4[0][3])), "r"(bar_g ^ 0x1000000u) : "memory");
            sts128f(ex, c4[0]);
            if (warp >= 9) bar_arrive(6, 576);
            if (WDAT == 1) load_wd();
        }
        STAMP(20);
        if (warp < 9) {
            bar_sync(6, 576);
            mbar_wait(bar_g);
            const uint32_t ex = sb + SM_EX + tid * 16;
            const uint4 u = lds128(ex), v = lds128(ex + 4608), w = lds128(ex + 9216), x = lds128(ex + 13824);
#define S4(f) rbf((__uint_as_float(u.f) + __uint_as_float(v.f)) + (__uint_as_float(w.f) + __uint_as_float(x.f)))
            const float G0 = S4(x), G1 = S4(y), U0 = S4(z), U1 = S4(w);
#undef S4
            sts32(sb + SM_GU + tid * 4, pack_bf16(rbf(__fdividef(G0, 1.0f + __expf(-G0))) * U0, rbf(__fdividef(G1, 1.0f + __expf(-G1))) * U1));
        }
        const uint4* src = pin(reinterpret_cast<const uint4*>(p.s->part) + (size_t)b * 1024 + tid, zr);
        bar_sync(7, 576);
        STAMP(21);
        {
            uint32_t gb[9];
            ldsm_x4_t(gb[0], gb[1], gb[2], gb[3], sb + SM_GU + lane * 16);
            ldsm_x4_t(gb[4], gb[5], gb[6], gb[7], sb + SM_GU + 512 + lane * 16);
            ldsm_x1_t(gb[8], sb + SM_GU + 1024 + (lane & 7) * 16);
            float c4[4] = {0.f, 0.f, 0.f, 0.f}, d4[4] = {0.f, 0.f, 0.f, 0.f};
            mma_bf16(c4, WD[0], WD[1], WD[2], WD[3], gb[0], gb[1]);
            mma_bf16(d4, WD[4], WD[5], WD[6], WD[7], gb[2], gb[3]);
            mma_bf16(c4, WD[8], WD[9], WD[10], WD[11], gb[4], gb[5]);
            mma_bf16(d4, WD[12], WD[13], WD[14], WD[15], gb[6], gb[7]);
            mma_bf16(c4, WD[16], WD[17], 0u, 0u, gb[8], 0u);
            stg128(pp, __float_as_uint(c4[0] + d4[0]) | 1u, __float_as_uint(c4[1] + d4[1]), __float_as_uint(c4[2] + d4[2]), __float_as_uint(c4[3] + d4[3]));
        }
        STAMP(22);
        if (b < 72 && warp < 16) {
            uint4 a, c;
            int it = 0;
            while (true) {
                a = ld_poll(src); c = ld_poll(src + 512);
                if (__all_sync(0xffffffffu, a.x && c.x)) break;
                if (++it > SPIN_LIMIT) TRAP();
            }
            STAMP(24);
            const float s0 = __uint_as_float(a.x) + __uint_as_float(c.x), s1 = __uint_as_float(a.y) + __uint_as_float(c.y);
            const float s2 = __uint_as_float(a.z) + __uint_as_float(c.z), s3 = __uint_as_float(a.w) + __uint_as_float(c.w);
            const bool up = lane & 16;
            const float r0 = __shfl_xor_sync(0xffffffffu, up ? s0 : s2, 16), r1 = __shfl_xor_sync(0xffffffffu, up ? s1 : s3, 16);
            sts64f(sb + SM_EX + warp * 256 + (lane & 15) * 16 + (up ? 8 : 0), (up ? s2 : s0) + r0, (up ? s3 : s1) + r1);
            bar_arrive(14, 576);
        }
    }
    STAMP(25);
    }
}

typedef CUresult (*PFN_tmEncode)(CUtensorMap*, CUtensorMapDataType, cuuint32_t, void*, const cuuint64_t*, const cuuint64_t*, const cuuint32_t*,
                                 const cuuint32_t*, CUtensorMapInterleave, CUtensorMapSwizzle, CUtensorMapL2promotion, CUtensorMapFloatOOBfill);

extern "C" void kernel_launch(void* const* d_in, const int* in_sizes, int n_in, void* d_out, int out_size) {
    Params p;
    p.x = (const bf16*)d_in[0];
    p.lar = (const bf16*)d_in[1];
    p.aim = (const bf16*)d_in[2];
    p.cre = (const bf16*)d_in[3];
    p.cim = (const bf16*)d_in[4];
    p.ldt = (const bf16*)d_in[5];
    p.dsk = (const bf16*)d_in[6];
    p.wr = (const bf16*)d_in[8];
    p.wpf = (const bf16*)d_in[PFW];
    p.out = (bf16*)d_out;
    static PFN_tmEncode enc = nullptr;
    static void* scratch = nullptr;
    if (!enc) {
        cudaFuncSetAttribute(fused_kernel, cudaFuncAttributeMaxDynamicSharedMemorySize, SMEM_TOTAL);
        void* fn = nullptr;
        cudaDriverEntryPointQueryResult qr;
        cudaGetDriverEntryPoint("cuTensorMapEncodeTiled", &fn, cudaEnableDefault, &qr);
        enc = (PFN_tmEncode)fn;
        cudaGetSymbolAddress(&scratch, g_scratch);
    }
    p.s = (Scratch*)scratch;
    CUtensorMap tm_g, tm_u, tm_d, tm_x, tm_y, tm_z;
    const cuuint64_t dims[2] = {FF, DM}, strides[1] = {FF * 2};
    const cuuint32_t box[2] = {72, 48}, es[2] = {1, 1};
    enc(&tm_g, CU_TENSOR_MAP_DATA_TYPE_BFLOAT16, 2, d_in[9], dims, strides, box, es, CU_TENSOR_MAP_INTERLEAVE_NONE, CU_TENSOR_MAP_SWIZZLE_NONE,
        CU_TENSOR_MAP_L2_PROMOTION_NONE, CU_TENSOR_MAP_FLOAT_OOB_FILL_NONE);
    enc(&tm_u, CU_TENSOR_MAP_DATA_TYPE_BFLOAT16, 2, d_in[10], dims, strides, box, es, CU_TENSOR_MAP_INTERLEAVE_NONE, CU_TENSOR_MAP_SWIZZLE_NONE,
        CU_TENSOR_MAP_L2_PROMOTION_NONE, CU_TENSOR_MAP_FLOAT_OOB_FILL_NONE);
    const cuuint64_t ddims[2] = {DM, FF}, dstrides[1] = {DM * 2};
    const cuuint32_t dbox[2] = {72, 72};
    enc(&tm_d, CU_TENSOR_MAP_DATA_TYPE_BFLOAT16, 2, d_in[11], ddims, dstrides, dbox, es, CU_TENSOR_MAP_INTERLEAVE_NONE, CU_TENSOR_MAP_SWIZZLE_NONE,
        CU_TENSOR_MAP_L2_PROMOTION_NONE, CU_TENSOR_MAP_FLOAT_OOB_FILL_NONE);
    const cuuint64_t xdims[3] = {DM, LSEQ / 16, 16}, xstrides[2] = {16 * DM * 2, DM * 2};
    const cuuint32_t xbox[3] = {8, LSEQ / 16, 8}, es3[3] = {1, 1, 1};
    enc(&tm_x, CU_TENSOR_MAP_DATA_TYPE_BFLOAT16, 3, d_in[0], xdims, xstrides, xbox, es3, CU_TENSOR_MAP_INTERLEAVE_NONE, CU_TENSOR_MAP_SWIZZLE_NONE,
        CU_TENSOR_MAP_L2_PROMOTION_NONE, CU_TENSOR_MAP_FLOAT_OOB_FILL_NONE);
    const cuuint64_t ydims[3] = {DM * 32, 16, 4}, ystrides[2] = {DM * 64, 16 * DM * 64};
    const cuuint32_t ybox[3] = {128, 16, 2}, zbox[3] = {32, 16, 2};
    enc(&tm_y, CU_TENSOR_MAP_DATA_TYPE_BFLOAT16, 3, p.s->y, ydims, ystrides, ybox, es3, CU_TENSOR_MAP_INTERLEAVE_NONE, CU_TENSOR_MAP_SWIZZLE_NONE,
        CU_TENSOR_MAP_L2_PROMOTION_NONE, CU_TENSOR_MAP_FLOAT_OOB_FILL_NONE);
    enc(&tm_z, CU_TENSOR_MAP_DATA_TYPE_BFLOAT16, 3, p.s->y, ydims, ystrides, zbox, es3, CU_TENSOR_MAP_INTERLEAVE_NONE, CU_TENSOR_MAP_SWIZZLE_NONE,
        CU_TENSOR_MAP_L2_PROMOTION_NONE, CU_TENSOR_MAP_FLOAT_OOB_FILL_NONE);
    fused_kernel<<<NCTA, NTHR, SMEM_TOTAL>>>(p, tm_g, tm_u, tm_d, tm_x, tm_y, tm_z);
}
```

```cpp
#include <cuda_runtime.h>
#include <cuda.h>
#include <cuda_fp16.h>
#include <cuda_bf16.h>
#include <stdint.h>

#define LSEQ 2048
#define DM 576
#define NST 128
#define FF 4608
#define NSEL 8
#define NCTA 128
#define NTHR 640
#define NWRK 640

typedef __nv_bfloat16 bf16;

#define SM_WG 0
#define SM_WU 41472
#define SM_WD 82944
#define W_PITCH 144
#define SM_XC 50176
#define SM_ZERO SM_WD
#define SM_TB (SM_WD + 9216)
#define SM_PL 124416
#define PL_B 10752
#define SM_XT (SM_TB + 20 * TBW)
#define SM_U (SM_XT + 18432)
#define UPAD 8
#define ULO_B ((UPAD + 128) * 16)
#define USLOT_B (2 * ULO_B)
#define SM_KW (SM_U + 5 * USLOT_B)
#define KW_B 3600
#define KW_T2 1152
#define KW_KH 656
#define KW_T3 2464
#define SM_MISC (SM_KW + 5 * KW_B)
#define SM_LNP (SM_MISC + 576)
#define SMEM_TOTAL (SM_LNP + 4096)
#define TBP 112
#define TBW (32 * TBP)
#define SM_OUT SM_PL
#define OUT_PITCH 1216
#define SM_XS (SM_PL + 19456)
#define XS_PITCH 592
#define SM_EX (SM_PL + 24320)
#define SM_GU (SM_PL + 42752)

struct __align__(128) Scratch {
    unsigned hint[8 * 32];
    unsigned flag[32];
    uint32_t sc[NCTA * 32];
    uint32_t st[LSEQ * 2];
    uint32_t uT[64 * (LSEQ / 2)];
    uint32_t y[NCTA * DM * 8];
    uint32_t part[72 * 64 * 64];
    uint32_t rows[(2 * NCTA + NSEL) * DM];
};
__device__ Scratch g_scratch;
#define STAMP(i)
#define DBG(i, v)

__device__ __forceinline__ float rbf(float x) {
    uint32_t r;
    asm("cvt.rn.bf16x2.f32 %0, %1, %2;\n" : "=r"(r) : "f"(x), "f"(0.f));
    return __uint_as_float(r & 0xffff0000u);
}
__device__ __forceinline__ uint32_t pack_bf16(float lo, float hi) {
    uint32_t r;
    asm("cvt.rn.bf16x2.f32 %0, %1, %2;\n" : "=r"(r) : "f"(hi), "f"(lo));
    return r;
}
__device__ __forceinline__ uint32_t pack_f16(float lo, float hi) {
    uint32_t r;
    asm("cvt.rn.f16x2.f32 %0, %1, %2;\n" : "=r"(r) : "f"(hi), "f"(lo));
    return r;
}
__device__ __forceinline__ uint32_t pack_f16_rz(float lo, float hi) {
    uint32_t r;
    asm("cvt.rz.f16x2.f32 %0, %1, %2;\n" : "=r"(r) : "f"(hi), "f"(lo));
    return r;
}
__device__ __forceinline__ float bf_lo(uint32_t w) { return __uint_as_float(w << 16); }
__device__ __forceinline__ float bf_hi(uint32_t w) { return __uint_as_float(w & 0xffff0000u); }
__device__ __forceinline__ uint32_t hadd2_bf(uint32_t a, uint32_t b) {
    __nv_bfloat162 r = __hadd2_rn(*reinterpret_cast<__nv_bfloat162*>(&a), *reinterpret_cast<__nv_bfloat162*>(&b));
    return *reinterpret_cast<uint32_t*>(&r);
}
__device__ __forceinline__ uint32_t hsub2_bf(uint32_t a, uint32_t b) {
    __nv_bfloat162 r = __hsub2_rn(*reinterpret_cast<__nv_bfloat162*>(&a), *reinterpret_cast<__nv_bfloat162*>(&b));
    return *reinterpret_cast<uint32_t*>(&r);
}
__device__ __forceinline__ uint32_t hmul2_bf(uint32_t a, uint32_t b) {
    __nv_bfloat162 r = __hmul2_rn(*reinterpret_cast<__nv_bfloat162*>(&a), *reinterpret_cast<__nv_bfloat162*>(&b));
    return *reinterpret_cast<uint32_t*>(&r);
}
__device__ __forceinline__ uint32_t hfma2_bf(uint32_t a, uint32_t b, uint32_t c) { uint32_t r; asm("fma.rn.bf16x2 %0, %1, %2, %3;\n" : "=r"(r) : "r"(a), "r"(b), "r"(c)); return r; }
__device__ __forceinline__ uint32_t hmul2(uint32_t a, uint32_t b) { uint32_t r; asm("mul.rn.f16x2 %0, %1, %2;\n" : "=r"(r) : "r"(a), "r"(b)); return r; }
__device__ __forceinline__ uint32_t hadd2(uint32_t a, uint32_t b) { uint32_t r; asm("add.rn.f16x2 %0, %1, %2;\n" : "=r"(r) : "r"(a), "r"(b)); return r; }
__device__ __forceinline__ uint32_t hfma2(uint32_t a, uint32_t b, uint32_t c) { uint32_t r; asm("fma.rn.f16x2 %0, %1, %2, %3;\n" : "=r"(r) : "r"(a), "r"(b), "r"(c)); return r; }
__device__ __forceinline__ uint32_t nzw(uint32_t w) { return w ? w : 0x8000u; }
__device__ __forceinline__ uint32_t nzf(float f) { const uint32_t w = __float_as_uint(f); return w ? w : 0x80000000u; }
__device__ __forceinline__ uint32_t smem_u32(const void* p) { return (uint32_t)__cvta_generic_to_shared(p); }
__device__ __forceinline__ uint32_t lds32(uint32_t addr) {
    uint32_t v;
    asm volatile("ld.shared.u32 %0, [%1];\n" : "=r"(v) : "r"(addr) : "memory");
    return v;
}
__device__ __forceinline__ uint32_t lds16(uint32_t addr) {
    unsigned short v;
    asm volatile("ld.shared.u16 %0, [%1];\n" : "=h"(v) : "r"(addr) : "memory");
    return v;
}
__device__ __forceinline__ uint2 lds64(uint32_t addr) {
    uint2 v;
    asm volatile("ld.shared.v2.u32 {%0,%1}, [%2];\n" : "=r"(v.x), "=r"(v.y) : "r"(addr) : "memory");
    return v;
}
__device__ __forceinline__ uint4 lds128(uint32_t addr) {
    uint4 v;
    asm volatile("ld.shared.v4.u32 {%0,%1,%2,%3}, [%4];\n" : "=r"(v.x), "=r"(v.y), "=r"(v.z), "=r"(v.w) : "r"(addr) : "memory");
    return v;
}
__device__ __forceinline__ float ldsf(uint32_t addr) { return __uint_as_float(lds32(addr)); }
__device__ __forceinline__ void sts32(uint32_t addr, uint32_t v) { asm volatile("st.shared.u32 [%0], %1;\n" ::"r"(addr), "r"(v) : "memory"); }
__device__ __forceinline__ void stsf(uint32_t addr, float v) { sts32(addr, __float_as_uint(v)); }
__device__ __forceinline__ void sts64(uint32_t addr, uint32_t a, uint32_t b) { asm volatile("st.shared.v2.u32 [%0], {%1,%2};\n" ::"r"(addr), "r"(a), "r"(b) : "memory"); }
__device__ __forceinline__ void sts64f(uint32_t addr, float a, float b) { sts64(addr, __float_as_uint(a), __float_as_uint(b)); }
__device__ __forceinline__ void sts128(uint32_t addr, uint32_t a, uint32_t b, uint32_t c, uint32_t d) {
    asm volatile("st.shared.v4.u32 [%0], {%1,%2,%3,%4};\n" ::"r"(addr), "r"(a), "r"(b), "r"(c), "r"(d) : "memory");
}
__device__ __forceinline__ void sts128f(uint32_t addr, const float (&v)[4]) {
    sts128(addr, __float_as_uint(v[0]), __float_as_uint(v[1]), __float_as_uint(v[2]), __float_as_uint(v[3]));
}
__device__ __forceinline__ void ldsm_x4(uint32_t& r0, uint32_t& r1, uint32_t& r2, uint32_t& r3, uint32_t addr) {
    asm volatile("ldmatrix.sync.aligned.m8n8.x4.shared.b16 {%0,%1,%2,%3}, [%4];\n"
                 : "=r"(r0), "=r"(r1), "=r"(r2), "=r"(r3) : "r"(addr) : "memory");
}
__device__ __forceinline__ void ldsm_x4_t(uint32_t& r0, uint32_t& r1, uint32_t& r2, uint32_t& r3, uint32_t addr) {
    asm volatile("ldmatrix.sync.aligned.m8n8.x4.trans.shared.b16 {%0,%1,%2,%3}, [%4];\n"
                 : "=r"(r0), "=r"(r1), "=r"(r2), "=r"(r3) : "r"(addr) : "memory");
}
__device__ __forceinline__ void ldsm_x2_t(uint32_t& r0, uint32_t& r1, uint32_t addr) {
    asm volatile("ldmatrix.sync.aligned.m8n8.x2.trans.shared.b16 {%0,%1}, [%2];\n" : "=r"(r0), "=r"(r1) : "r"(addr) : "memory");
}
__device__ __forceinline__ void ldsm_x1_t(uint32_t& r0, uint32_t addr) {
    asm volatile("ldmatrix.sync.aligned.m8n8.x1.trans.shared.b16 {%0}, [%1];\n" : "=r"(r0) : "r"(addr) : "memory");
}
__device__ __forceinline__ uint32_t movm(uint32_t a) {
    uint32_t d;
    asm volatile("movmatrix.sync.aligned.m8n8.trans.b16 %0, %1;\n" : "=r"(d) : "r"(a));
    return d;
}
__device__ __forceinline__ void mma_f16(float (&c)[4], uint32_t a0, uint32_t a1, uint32_t a2, uint32_t a3, uint32_t b0, uint32_t b1) {
    asm volatile(
        "mma.sync.aligned.m16n8k16.row.col.f32.f16.f16.f32 {%0,%1,%2,%3}, {%4,%5,%6,%7}, {%8,%9}, {%0,%1,%2,%3};\n"
        : "+f"(c[0]), "+f"(c[1]), "+f"(c[2]), "+f"(c[3])
        : "r"(a0), "r"(a1), "r"(a2), "r"(a3), "r"(b0), "r"(b1));
}
__device__ __forceinline__ void mma_bf16(float (&c)[4], uint32_t a0, uint32_t a1, uint32_t a2, uint32_t a3, uint32_t b0, uint32_t b1) {
    asm volatile(
        "mma.sync.aligned.m16n8k16.row.col.f32.bf16.bf16.f32 {%0,%1,%2,%3}, {%4,%5,%6,%7}, {%8,%9}, {%0,%1,%2,%3};\n"
        : "+f"(c[0]), "+f"(c[1]), "+f"(c[2]), "+f"(c[3])
        : "r"(a0), "r"(a1), "r"(a2), "r"(a3), "r"(b0), "r"(b1));
}
__device__ __forceinline__ void bar_sync(int id, int n) { asm volatile("bar.sync %0, %1;\n" ::"r"(id), "r"(n) : "memory"); }
__device__ __forceinline__ void bar_arrive(int id, int n) { asm volatile("bar.arrive %0, %1;\n" ::"r"(id), "r"(n) : "memory"); }
__device__ __forceinline__ bool bar_or(int id, int n, bool v) {
    uint32_t r;
    asm volatile("{\n.reg .pred p, q;\nsetp.ne.u32 p, %3, 0;\nbar.red.or.pred q, %1, %2, p;\nselp.u32 %0, 1, 0, q;\n}\n" : "=r"(r) : "r"(id), "r"(n), "r"((uint32_t)v) : "memory");
    return r;
}
__device__ __forceinline__ uint4 ld_poll(const void* p) {
    uint4 v;
    asm volatile("ld.relaxed.gpu.global.v4.u32 {%0,%1,%2,%3}, [%4];\n" : "=r"(v.x), "=r"(v.y), "=r"(v.z), "=r"(v.w) : "l"(p) : "memory");
    return v;
}
template <class T> __device__ __forceinline__ T* pin(T* p, uint32_t z) {
    uint32_t lo, hi;
    asm volatile("mov.b64 {%0, %1}, %2;\n" : "=r"(lo), "=r"(hi) : "l"(p));
    asm volatile("xor.b32 %0, %0, %1;\n" : "+r"(lo) : "r"(z));
    asm volatile("xor.b32 %0, %0, %1;\n" : "+r"(hi) : "r"(z));
    asm volatile("mov.b64 %0, {%1, %2};\n" : "=l"(p) : "r"(lo), "r"(hi));
    return p;
}
__device__ __forceinline__ uint32_t pin(uint32_t a, uint32_t z) { asm volatile("xor.b32 %0, %0, %1;\n" : "+r"(a) : "r"(z)); return a; }
__device__ __forceinline__ uint2 ld_poll64(const void* p) {
    uint2 v;
    asm volatile("ld.relaxed.gpu.global.v2.u32 {%0,%1}, [%2];\n" : "=r"(v.x), "=r"(v.y) : "l"(p) : "memory");
    return v;
}
__device__ __forceinline__ uint32_t ld_poll32(const void* p) {
    uint32_t v;
    asm volatile("ld.relaxed.gpu.global.u32 %0, [%1];\n" : "=r"(v) : "l"(p) : "memory");
    return v;
}
__device__ __forceinline__ uint4 ldg128(const void* p) {
    uint4 v;
    asm volatile("ld.global.nc.v4.u32 {%0,%1,%2,%3}, [%4];\n" : "=r"(v.x), "=r"(v.y), "=r"(v.z), "=r"(v.w) : "l"(p));
    return v;
}
__device__ __forceinline__ uint2 ldg64(const void* p) {
    uint2 v;
    asm volatile("ld.global.nc.v2.u32 {%0,%1}, [%2];\n" : "=r"(v.x), "=r"(v.y) : "l"(p));
    return v;
}
__device__ __forceinline__ uint32_t ldg16(const void* p) {
    uint32_t v;
    asm volatile("ld.global.nc.u16 %0, [%1];\n" : "=r"(v) : "l"(p));
    return v;
}
__device__ __forceinline__ void stg128(void* p, uint32_t a, uint32_t b, uint32_t c, uint32_t d) {
    asm volatile("st.global.v4.u32 [%0], {%1,%2,%3,%4};\n" ::"l"(p), "r"(a), "r"(b), "r"(c), "r"(d) : "memory");
}
__device__ __forceinline__ void stg64(void* p, uint32_t a, uint32_t b) { asm volatile("st.global.v2.u32 [%0], {%1,%2};\n" ::"l"(p), "r"(a), "r"(b) : "memory"); }
__device__ __forceinline__ void stg32(void* p, uint32_t a) { asm volatile("st.global.u32 [%0], %1;\n" ::"l"(p), "r"(a) : "memory"); }
__device__ __forceinline__ bool all_nz(const uint4& v) { return v.x && v.y && v.z && v.w; }
#define SPIN_LIMIT (1 << 21)
#define TRAP() __trap()
__device__ __forceinline__ void hint_arrive(unsigned* g_hint, int idx, int sub) {
    asm volatile("red.relaxed.gpu.global.add.u32 [%0], 1;\n" ::"l"(&g_hint[sub * 32 + idx]) : "memory");
}
__device__ __forceinline__ void hint_wait(const unsigned* g_hint, int idx, unsigned target) {
    unsigned l;
    asm volatile("mov.u32 %0, %%laneid;" : "=r"(l));
    const unsigned* c = &g_hint[(l & 7) * 32 + idx];
    int it = 0;
    while (__any_sync(0xffffffffu, (int)(ld_poll32(c) - target) < 0)) { if (++it > SPIN_LIMIT) TRAP(); }
}
__device__ __forceinline__ void mbar_init(uint32_t bar, uint32_t cnt) { asm volatile("mbarrier.init.shared::cta.b64 [%0], %1;\n" ::"r"(bar), "r"(cnt) : "memory"); }
__device__ __forceinline__ void mbar_expect(uint32_t bar, uint32_t bytes) {
    asm volatile("mbarrier.arrive.expect_tx.shared::cta.b64 _, [%0], %1;\n" ::"r"(bar), "r"(bytes) : "memory");
}
__device__ __forceinline__ void mbar_arrive(uint32_t bar) { asm volatile("mbarrier.arrive.shared::cta.b64 _, [%0];\n" ::"r"(bar) : "memory"); }
__device__ __forceinline__ void mbar_wait_cluster(uint32_t bar) {
    asm volatile(
        "{\n.reg .pred p;\n"
        "W_%=:\n"
        "mbarrier.try_wait.parity.acquire.cluster.shared::cta.b64 p, [%0], 0;\n"
        "@!p bra W_%=;\n}\n" ::"r"(bar) : "memory");
}
__device__ __forceinline__ void mbar_wait(uint32_t bar) {
    asm volatile(
        "{\n.reg .pred p;\n"
        "W_%=:\n"
        "mbarrier.try_wait.parity.shared::cta.b64 p, [%0], 0;\n"
        "@!p bra W_%=;\n}\n" ::"r"(bar) : "memory");
}
__device__ __forceinline__ bool mbar_test(uint32_t bar) {
    uint32_t r;
    asm volatile("{\n.reg .pred p;\nmbarrier.test_wait.parity.shared::cta.b64 p, [%1], 0;\nselp.u32 %0, 1, 0, p;\n}\n" : "=r"(r) : "r"(bar) : "memory");
    return __any_sync(0xffffffffu, r);
}
__device__ __forceinline__ void bulk_g2s(uint32_t dst, const void* src, uint32_t bytes, uint32_t bar) {
    asm volatile("cp.async.bulk.shared::cluster.global.mbarrier::complete_tx::bytes [%0], [%1], %2, [%3];\n" ::"r"(dst), "l"(src), "r"(bytes), "r"(bar) : "memory");
}
__device__ __forceinline__ void bulk_s2g(void* dst, uint32_t src, uint32_t bytes) {
    asm volatile("cp.async.bulk.global.shared::cta.bulk_group [%0], [%1], %2;\ncp.async.bulk.commit_group;\n" ::"l"(dst), "r"(src), "r"(bytes) : "memory");
}
__device__ __forceinline__ void tma_2d(uint32_t dst, const CUtensorMap* tm, int c0, int c1, uint32_t bar) {
    asm volatile("cp.async.bulk.tensor.2d.shared::cluster.global.mbarrier::complete_tx::bytes [%0], [%1, {%3, %4}], [%2];\n"
                 ::"r"(dst), "l"(tm), "r"(bar), "r"(c0), "r"(c1) : "memory");
}
__device__ __forceinline__ void tma_3d(uint32_t dst, const CUtensorMap* tm, int c0, int c1, int c2, uint32_t bar) {
    asm volatile("cp.async.bulk.tensor.3d.shared::cluster.global.mbarrier::complete_tx::bytes [%0], [%1, {%3, %4, %5}], [%2];\n"
                 ::"r"(dst), "l"(tm), "r"(bar), "r"(c0), "r"(c1), "r"(c2) : "memory");
}
__device__ __forceinline__ void tma_3d_mc(uint32_t dst, const CUtensorMap* tm, int c0, int c1, int c2, uint32_t bar) {
    asm volatile("cp.async.bulk.tensor.3d.shared::cluster.global.mbarrier::complete_tx::bytes.multicast::cluster [%0], [%1, {%3, %4, %5}], [%2], %6;\n"
                 ::"r"(dst), "l"(tm), "r"(bar), "r"(c0), "r"(c1), "r"(c2), "h"((unsigned short)3) : "memory");
}
__device__ __forceinline__ void tma_st_3d(const CUtensorMap* tm, uint32_t src, int c0, int c1, int c2) {
    asm volatile("cp.async.bulk.tensor.3d.global.shared::cta.bulk_group [%0, {%2, %3, %4}], [%1];\ncp.async.bulk.commit_group;\n"
                 ::"l"(tm), "r"(src), "r"(c0), "r"(c1), "r"(c2) : "memory");
}
__device__ __forceinline__ void l2_prefetch(const void* src, uint32_t bytes) {
    asm volatile("cp.async.bulk.prefetch.L2.global [%0], %1;\n" ::"l"(src), "r"(bytes) : "memory");
}
__device__ __forceinline__ bool elect_one() {
    uint32_t r;
    asm volatile("{\n.reg .pred p;\nelect.sync _|p, 0xffffffff;\nselp.u32 %0, 1, 0, p;\n}\n" : "=r"(r));
    return r;
}
__device__ __forceinline__ void fence_async() { asm volatile("fence.proxy.async.shared::cta;\n" ::: "memory"); }

__device__ __forceinline__ float2 cmul(float2 a, float2 b) {
    return make_float2(fmaf(a.x, b.x, -a.y * b.y), fmaf(a.x, b.y, a.y * b.x));
}
__device__ __forceinline__ float2 csq(float2 a) {
    float p = a.x * a.y;
    return make_float2(fmaf(a.x, a.x, -a.y * a.y), p + p);
}
__device__ __forceinline__ float2 cexp_e(float lr2, float rh, float rl, float e) {
    float m;
    asm("ex2.approx.ftz.f32 %0, %1;\n" : "=f"(m) : "f"(lr2 * e));
    const float a = rh * e;
    const float r = fmaf(rl, e, a - rintf(a)) * 6.283185307179586f;
    return make_float2(m * __cosf(r), m * __sinf(r));
}
__device__ __forceinline__ float rcp_approx(float x) { float r; asm("rcp.approx.ftz.f32 %0, %1;\n" : "=f"(r) : "f"(x)); return r; }
__device__ __forceinline__ float sqrt_approx(float x) { float r; asm("sqrt.approx.ftz.f32 %0, %1;\n" : "=f"(r) : "f"(x)); return r; }

__device__ __forceinline__ void wg_fence() { asm volatile("wgmma.fence.sync.aligned;\n" ::: "memory"); }
__device__ __forceinline__ void wg_commit() { asm volatile("wgmma.commit_group.sync.aligned;\n" ::: "memory"); }
__device__ __forceinline__ void wg_wait0() { asm volatile("wgmma.wait_group.sync.aligned 0;\n" ::: "memory"); }
template <int T0, int NT> __device__ __forceinline__ void wg_h(uint32_t (&acc)[32], const uint32_t (&a)[4], uint64_t desc);
template <> __device__ __forceinline__ void wg_h<0, 16>(uint32_t (&acc)[32], const uint32_t (&a)[4], uint64_t desc) {
    asm volatile("wgmma.mma_async.sync.aligned.m64n128k16.f16.f16.f16 {%0,%1,%2,%3,%4,%5,%6,%7,%8,%9,%10,%11,%12,%13,%14,%15,%16,%17,%18,%19,%20,%21,%22,%23,%24,%25,%26,%27,%28,%29,%30,%31}, {%32,%33,%34,%35}, %36, 1, 1, 1, 0;\n"
                 : "+r"(acc[0]), "+r"(acc[1]), "+r"(acc[2]), "+r"(acc[3]), "+r"(acc[4]), "+r"(acc[5]), "+r"(acc[6]), "+r"(acc[7]), "+r"(acc[8]), "+r"(acc[9]), "+r"(acc[10]), "+r"(acc[11]), "+r"(acc[12]), "+r"(acc[13]), "+r"(acc[14]), "+r"(acc[15]), "+r"(acc[16]), "+r"(acc[17]), "+r"(acc[18]), "+r"(acc[19]), "+r"(acc[20]), "+r"(acc[21]), "+r"(acc[22]), "+r"(acc[23]), "+r"(acc[24]), "+r"(acc[25]), "+r"(acc[26]), "+r"(acc[27]), "+r"(acc[28]), "+r"(acc[29]), "+r"(acc[30]), "+r"(acc[31])
                 : "r"(a[0]), "r"(a[1]), "r"(a[2]), "r"(a[3]), "l"(desc));
}
template <> __device__ __forceinline__ void wg_h<4, 4>(uint32_t (&acc)[32], const uint32_t (&a)[4], uint64_t desc) {
    asm volatile("wgmma.mma_async.sync.aligned.m64n32k16.f16.f16.f16 {%0,%1,%2,%3,%4,%5,%6,%7}, {%8,%9,%10,%11}, %12, 1, 1, 1, 0;\n"
                 : "+r"(acc[8]), "+r"(acc[9]), "+r"(acc[10]), "+r"(acc[11]), "+r"(acc[12]), "+r"(acc[13]), "+r"(acc[14]), "+r"(acc[15])
                 : "r"(a[0]), "r"(a[1]), "r"(a[2]), "r"(a[3]), "l"(desc));
}
template <> __device__ __forceinline__ void wg_h<8, 4>(uint32_t (&acc)[32], const uint32_t (&a)[4], uint64_t desc) {
    asm volatile("wgmma.mma_async.sync.aligned.m64n32k16.f16.f16.f16 {%0,%1,%2,%3,%4,%5,%6,%7}, {%8,%9,%10,%11}, %12, 1, 1, 1, 0;\n"
                 : "+r"(acc[16]), "+r"(acc[17]), "+r"(acc[18]), "+r"(acc[19]), "+r"(acc[20]), "+r"(acc[21]), "+r"(acc[22]), "+r"(acc[23])
                 : "r"(a[0]), "r"(a[1]), "r"(a[2]), "r"(a[3]), "l"(desc));
}
template <> __device__ __forceinline__ void wg_h<12, 4>(uint32_t (&acc)[32], const uint32_t (&a)[4], uint64_t desc) {
    asm volatile("wgmma.mma_async.sync.aligned.m64n32k16.f16.f16.f16 {%0,%1,%2,%3,%4,%5,%6,%7}, {%8,%9,%10,%11}, %12, 1, 1, 1, 0;\n"
                 : "+r"(acc[24]), "+r"(acc[25]), "+r"(acc[26]), "+r"(acc[27]), "+r"(acc[28]), "+r"(acc[29]), "+r"(acc[30]), "+r"(acc[31])
                 : "r"(a[0]), "r"(a[1]), "r"(a[2]), "r"(a[3]), "l"(desc));
}
template <> __device__ __forceinline__ void wg_h<0, 8>(uint32_t (&acc)[32], const uint32_t (&a)[4], uint64_t desc) {
    asm volatile("wgmma.mma_async.sync.aligned.m64n64k16.f16.f16.f16 {%0,%1,%2,%3,%4,%5,%6,%7,%8,%9,%10,%11,%12,%13,%14,%15}, {%16,%17,%18,%19}, %20, 1, 1, 1, 0;\n"
                 : "+r"(acc[0]), "+r"(acc[1]), "+r"(acc[2]), "+r"(acc[3]), "+r"(acc[4]), "+r"(acc[5]), "+r"(acc[6]), "+r"(acc[7]), "+r"(acc[8]), "+r"(acc[9]), "+r"(acc[10]), "+r"(acc[11]), "+r"(acc[12]), "+r"(acc[13]), "+r"(acc[14]), "+r"(acc[15])
                 : "r"(a[0]), "r"(a[1]), "r"(a[2]), "r"(a[3]), "l"(desc));
}
template <> __device__ __forceinline__ void wg_h<4, 12>(uint32_t (&acc)[32], const uint32_t (&a)[4], uint64_t desc) {
    asm volatile("wgmma.mma_async.sync.aligned.m64n96k16.f16.f16.f16 {%0,%1,%2,%3,%4,%5,%6,%7,%8,%9,%10,%11,%12,%13,%14,%15,%16,%17,%18,%19,%20,%21,%22,%23}, {%24,%25,%26,%27}, %28, 1, 1, 1, 0;\n"
                 : "+r"(acc[8]), "+r"(acc[9]), "+r"(acc[10]), "+r"(acc[11]), "+r"(acc[12]), "+r"(acc[13]), "+r"(acc[14]), "+r"(acc[15]), "+r"(acc[16]), "+r"(acc[17]), "+r"(acc[18]), "+r"(acc[19]), "+r"(acc[20]), "+r"(acc[21]), "+r"(acc[22]), "+r"(acc[23]), "+r"(acc[24]), "+r"(acc[25]), "+r"(acc[26]), "+r"(acc[27]), "+r"(acc[28]), "+r"(acc[29]), "+r"(acc[30]), "+r"(acc[31])
                 : "r"(a[0]), "r"(a[1]), "r"(a[2]), "r"(a[3]), "l"(desc));
}

#define DSM 1
#define WMAX 9
#define YSEL 0
#define HINTW 10
#define WAS 0x0005
#define WA0 (WAS >> 12)
#define WA1 ((WAS >> 8) & 15)
#define WA2 ((WAS >> 4) & 15)
#define WA3 (WAS & 15)
#define WDAT 1
#define PAUSE 2
#define PCNT (32 + ((PAUSE & 1) ? 288 : 0) + ((PAUSE & 6) ? 320 : 64))
#define LNAT 2
#define UW 8
#define FINAT 3
#define UAT 2
#define PFW 11
#define HK 9
#define TOKEN_OF(g) (16 * ((g) & 1) + ((g) >> 2) + 2 * ((g) & 2))
#define HI2(a, b) (pack_f16_rz(__uint_as_float(a), __uint_as_float(b)) & 0xfff8fff8u)
struct Params {
    const bf16 *x, *lar, *aim, *cre, *cim, *ldt, *dsk;
    Scratch* s;
    const bf16 *wr, *wpf;
    bf16* out;
};

template <int NK>
__device__ __forceinline__ void ln_partial(const uint32_t (&H)[2][NK], uint32_t lp, int warp, int g, int t) {
    float cs[4] = {0.f, 0.f, 0.f, 0.f}, cl[4] = {0.f, 0.f, 0.f, 0.f}, ch[4] = {0.f, 0.f, 0.f, 0.f};
#pragma unroll
    for (int k = 0; k < NK; k += 2) {
        uint32_t a0, a1, a2, a3;
        asm volatile("prmt.b32 %0, %4, %4, %8;\nprmt.b32 %1, %5, %5, %8;\nprmt.b32 %2, %6, %6, %8;\nprmt.b32 %3, %7, %7, %8;\n"
                     : "=r"(a0), "=r"(a1), "=r"(a2), "=r"(a3) : "r"(H[0][k]), "r"(H[1][k]), "r"(H[0][k + 1]), "r"(H[1][k + 1]), "r"(0x3210u + (warp >> 8)));
        mma_bf16(cl, a0, a1, a2, a3, H[0][k], H[0][k + 1]);
        mma_bf16(ch, a0, a1, a2, a3, H[1][k], H[1][k + 1]);
        mma_bf16(cs, a0, a1, a2, a3, 0x3f803f80u, 0x3f803f80u);
    }
    const uint32_t a = lp + (g * 20 + warp) * 4;
    if (t == 0) {
        stsf(a, cs[0]); stsf(a + 8 * 80, cs[2]);
    }
    if (t == (g >> 1)) { stsf(a + 16 * 80, (g & 1) ? cl[1] : cl[0]); stsf(a + 24 * 80, (g & 1) ? ch[3] : ch[2]); }
}
__device__ __forceinline__ float sum18(uint32_t a) {
    const uint4 p = lds128(a), q = lds128(a + 16), r = lds128(a + 32), s = lds128(a + 48);
    const uint2 u = lds64(a + 64);
#define F(x) __uint_as_float(x)
    return (((F(p.x) + F(p.y)) + (F(p.z) + F(p.w))) + ((F(q.x) + F(q.y)) + (F(q.z) + F(q.w)))) +
           (((F(r.x) + F(r.y)) + (F(r.z) + F(r.w))) + ((F(s.x) + F(s.y)) + (F(s.z) + F(s.w))) + (F(u.x) + F(u.y)));
#undef F
}
__device__ __forceinline__ float sum9(uint32_t a) {
    const uint4 p = lds128(a), q = lds128(a + 16);
#define F(x) __uint_as_float(x)
    return (((F(p.x) + F(p.y)) + (F(p.z) + F(p.w))) + ((F(q.x) + F(q.y)) + (F(q.z) + F(q.w)))) + ldsf(a + 32);
#undef F
}
template <int N>
__device__ __forceinline__ void ln_finish(uint32_t lp, int lane, float& mb, float& rc) {
    const float v = N == 9 ? sum9(lp + lane * 80) : sum18(lp + lane * 80);
    const float o = __shfl_xor_sync(0xffffffffu, v, 16);
    const float m0 = v * (1.0f / 576.0f);
    const float mean = fmaf(fmaf(-m0, 576.0f, v), 1.0f / 576.0f, m0);
    const float var = fmaxf(fmaf(-mean, mean, o * (1.0f / 576.0f)), 0.f);
    mb = rbf(mean);
    rc = rcp_approx(rbf(sqrt_approx(rbf(rbf(var) + 1e-5f))));
}
__device__ __forceinline__ uint32_t ln_apply(uint32_t w, const uint2& st) {
    uint32_t r;
    asm("{\n.reg .b16 m, t, h, l;\n.reg .b32 mm, hh, ll, d, e;\nmov.b32 {m, t}, %2;\nmov.b32 {h, l}, %3;\nmov.b32 mm, {m, m};\nmov.b32 hh, {h, h};\nmov.b32 ll, {l, l};\n"
        "sub.rn.bf16x2 d, %1, mm;\nmul.rn.bf16x2 e, d, ll;\nfma.rn.bf16x2 %0, d, hh, e;\n}\n" : "=r"(r) : "r"(w), "r"(st.x), "r"(st.y));
    return r;
}
__device__ __forceinline__ void stat_store(uint32_t a, float mb, float rc, uint32_t extra) {
    const float rh = rbf(rc);
    sts64(a, (__float_as_uint(mb) >> 16) | (extra << 16), pack_bf16(rh, rc - rh));
}

__device__ __forceinline__ void hcmul(uint32_t re, uint32_t im, uint32_t z, uint32_t& ore, uint32_t& oim) {
    asm("{\n.reg .b16 x, y;\n.reg .b32 xx, yy, ny, a, b;\nmov.b32 {x, y}, %4;\nmov.b32 xx, {x, x};\nmov.b32 yy, {y, y};\nneg.f16x2 ny, yy;\n"
        "mul.rn.f16x2 a, %2, xx;\nfma.rn.f16x2 %0, %3, ny, a;\nmul.rn.f16x2 b, %3, xx;\nfma.rn.f16x2 %1, %2, yy, b;\n}\n" : "=&r"(ore), "=r"(oim) : "r"(re), "r"(im), "r"(z));
}
__device__ __forceinline__ void hcmul(uint32_t re, uint32_t im, uint32_t zx, uint32_t zy, uint32_t& ore, uint32_t& oim) {
    asm("{\n.reg .b32 ny, a, b;\nneg.f16x2 ny, %5;\n"
        "mul.rn.f16x2 a, %2, %4;\nfma.rn.f16x2 %0, %3, ny, a;\nmul.rn.f16x2 b, %3, %4;\nfma.rn.f16x2 %1, %2, %5, b;\n}\n" : "=&r"(ore), "=r"(oim) : "r"(re), "r"(im), "r"(zx), "r"(zy));
}

struct KGen {
    uint32_t Af[4][4];
    float2 z1, z8, z64, z128, T[9];
    uint32_t zw;
};
__device__ __forceinline__ void kgen_setup(KGen& k, uint32_t pa, float dt) {
    const float A = rbf(expf(bf_lo(pa)));
    const float lr2 = -(A * dt) * 1.4426950408889634f;
    const float li = bf_hi(pa) * dt;
    const float rh = li * 0.15915494309189535f;
    const float rl = fmaf(li, 6.4206382986e-9f, fmaf(li, 0.15915494309189535f, -rh));
    k.z1 = cexp_e(lr2, rh, rl, 1.0f);
    k.z8 = cexp_e(lr2, rh, rl, 8.0f);
    k.z64 = cexp_e(lr2, rh, rl, 64.0f);
}
__device__ __forceinline__ void kgen_rows(KGen& k, uint32_t tb, int lane) {
    const float2 z8 = k.z8, z64 = k.z64;
    const uint32_t row = tb + lane * TBP;
    k.z128 = csq(z64);
    const float2 z16 = csq(z8), z32 = csq(z16), z48 = cmul(z32, z16), z80 = cmul(z64, z16), z96 = cmul(z64, z32), z112 = cmul(z64, z48);
    uint32_t re[4], im[4], a[4], b[4];
    re[0] = pack_f16(1.0f, z16.x); im[0] = pack_f16(0.0f, z16.y);
    re[1] = pack_f16(z32.x, z48.x); im[1] = pack_f16(z32.y, z48.y);
    re[2] = pack_f16(z64.x, z80.x); im[2] = pack_f16(z64.y, z80.y);
    re[3] = pack_f16(z96.x, z112.x); im[3] = pack_f16(z96.y, z112.y);
    sts128(row, re[0], re[1], re[2], re[3]);
    sts128(row + 32, im[0], im[1], im[2], im[3]);
    const uint32_t zz = pack_f16(z8.x, z8.y);
#pragma unroll
    for (int j = 0; j < 4; j++) hcmul(re[j], im[j], zz, a[j], b[j]);
    sts128(row + 16, a[0], a[1], a[2], a[3]);
    sts128(row + 48, b[0], b[1], b[2], b[3]);
    __syncwarp();
    const int mi = lane >> 3;
    const uint32_t ad = tb + (lane & 7) * TBP + mi * 16;
#pragma unroll
    for (int ks = 0; ks < 4; ks++) ldsm_x4_t(k.Af[ks][0], k.Af[ks][1], k.Af[ks][2], k.Af[ks][3], ad + ks * 8 * TBP);
}
__device__ __forceinline__ void kgen_chain(KGen& k, uint32_t pc, float cs) {
    k.T[0] = make_float2(bf_lo(pc) * cs, -bf_hi(pc) * cs);
    const float2 y1 = make_float2(k.z1.x, -k.z1.y);
#pragma unroll
    for (int c = 1; c < 8; c++) k.T[c] = cmul(k.T[c - 1], y1);
    k.T[8] = cmul(k.T[0], make_float2(k.z8.x, -k.z8.y));
}
__device__ __forceinline__ void kgen_cols(KGen& k, uint32_t tb, int lane) {
    const uint32_t row = tb + lane * TBP;
    const float2 (&T)[9] = k.T;
    const uint32_t zv = pack_f16(k.z128.x, k.z128.y), zo = __shfl_xor_sync(0xffffffffu, zv, 1);
    k.zw = (lane & 1) ? __byte_perm(zo, zv, 0x7632) : __byte_perm(zv, zo, 0x5410);
    const float2 y256 = csq(make_float2(k.z128.x, -k.z128.y)), y512 = csq(y256), y768 = cmul(y512, y256), y1024 = csq(y512);
    const float2 c1032 = cmul(T[8], y1024);
    const uint32_t r04 = pack_f16(T[0].x, T[4].x), i04 = pack_f16(T[0].y, T[4].y), r26 = pack_f16(T[2].x, T[6].x), i26 = pack_f16(T[2].y, T[6].y);
    const uint32_t r48 = pack_f16(T[4].x, T[8].x), i48 = pack_f16(T[4].y, T[8].y);
    __syncwarp();
    sts128(row, r04, pack_f16(T[1].x, T[5].x), r26, pack_f16(T[3].x, T[7].x));
    sts128(row + 16, i04, pack_f16(T[1].y, T[5].y), i26, pack_f16(T[3].y, T[7].y));
    uint32_t a[4], b[4];
    {
        const uint32_t zz = pack_f16(y256.x, y256.y);
        hcmul(r04, i04, zz, a[0], b[0]);
        hcmul(r26, i26, zz, a[2], b[2]);
        hcmul(r48, i48, zz, a[3], b[3]);
    }
    sts128(row + 32, a[0], a[0], a[2], a[3]);
    sts128(row + 48, b[0], b[0], b[2], b[3]);
    {
        hcmul(r48, i48, pack_f16(y512.x, y512.y), a[0], b[0]);
        hcmul(r48, i48, pack_f16(y768.x, y768.y), a[1], b[1]);
        const uint32_t zz = pack_f16(c1032.x, c1032.y);
        hcmul(pack_f16(1.0f, y256.x), pack_f16(0.0f, y256.y), zz, a[2], b[2]);
        hcmul(pack_f16(y512.x, y768.x), pack_f16(y512.y, y768.y), zz, a[3], b[3]);
    }
    sts128(row + 64, a[0], a[1], a[2], a[3]);
    sts128(row + 80, b[0], b[1], b[2], b[3]);
}
__device__ __forceinline__ void kgen_mma(const KGen& k, uint32_t tb, int lane) {
    const int t = lane & 3;
    const uint32_t zw = k.zw;
    uint32_t zx[4], zy[4];
#pragma unroll
    for (int ks = 0; ks < 4; ks++) { zx[ks] = __shfl_sync(0xffffffffu, zw, 8 * ks + 2 * t); zy[ks] = __shfl_sync(0xffffffffu, zw, 8 * ks + 2 * t + 1); }
    __syncwarp();
    float acc[2][3][4];
#pragma unroll
    for (int i = 0; i < 6; i++)
#pragma unroll
        for (int j = 0; j < 4; j++) acc[i / 3][i % 3][j] = 0.f;
    {
        const int mi = lane >> 3;
        const uint32_t bd = tb + ((lane & 7) + 8 * (mi >> 1)) * TBP + (mi & 1) * 16;
#pragma unroll
        for (int kp = 0; kp < 2; kp++) {
            uint32_t b[3][4];
#pragma unroll
            for (int j = 0; j < 3; j++) ldsm_x4_t(b[j][0], b[j][1], b[j][2], b[j][3], bd + kp * 16 * TBP + j * 32);
#pragma unroll
            for (int h = 0; h < 2; h++) {
                const int ks = 2 * kp + h;
                uint32_t d[4];
                hcmul(k.Af[ks][0], k.Af[ks][2], zx[ks], zy[ks], d[0], d[2]);
                hcmul(k.Af[ks][1], k.Af[ks][3], zx[ks], zy[ks], d[1], d[3]);
#pragma unroll
                for (int j = 0; j < 3; j++) {
                    mma_f16(acc[0][j], k.Af[ks][0], k.Af[ks][1], k.Af[ks][2], k.Af[ks][3], b[j][2 * h], b[j][2 * h + 1]);
                    mma_f16(acc[1][j], d[0], d[1], d[2], d[3], b[j][2 * h], b[j][2 * h + 1]);
                }
            }
        }
    }
    __syncwarp();
#pragma unroll
    for (int h = 0; h < 2; h++) {
        sts64(tb + h * 256 + lane * 8, pack_f16(acc[h][0][0], acc[h][0][1]), pack_f16(acc[h][0][2], acc[h][0][3]));
        sts64(tb + 512 + h * 256 + lane * 8, pack_f16(acc[h][1][0], acc[h][1][1]), pack_f16(acc[h][1][2], acc[h][1][3]));
        sts32(tb + 1024 + h * 256 + lane * 4, pack_f16(acc[h][2][0], t < 2 ? acc[h][2][1] : acc[h][2][2]));
        sts32(tb + 1152 + h * 256 + lane * 4, pack_f16(t < 2 ? acc[h][2][2] : acc[h][2][1], acc[h][2][3]));
    }
}
__device__ __forceinline__ uint32_t table_buf(uint32_t sb, int warp) { return sb + SM_TB + warp * TBW; }

__device__ __forceinline__ void kgen_combine(uint32_t sb, int warp, int lane, uint32_t kw, uint32_t ao) {
    const int wq = warp & 3;
    const uint32_t a = table_buf(sb, warp & ~3) + wq * 256 + lane * 8, c = table_buf(sb, warp & ~3) + 1024 + wq * 128 + lane * 4;
    const int t = lane & 3;
    const uint32_t o0 = (t < 2 ? KW_T2 + KW_KH + 16 + t * 256 - (wq & 1) * KW_KH : KW_T3 + 16 - 1024 + t * 512 + (wq & 1) * 256) + (lane >> 2) * 16;
    const uint4 o = make_uint4(o0 + t * 36, o0 + (t ^ 1) * 36, o0 + (t ^ 2) * 36, o0 + (t ^ 3) * 36);
    const uint2 u = lds64(a), v = lds64(a + TBW), w = lds64(a + 2 * TBW), x = lds64(a + 3 * TBW);
    const uint32_t kt = hadd2(hadd2(lds32(c), lds32(c + TBW)), hadd2(lds32(c + 2 * TBW), lds32(c + 3 * TBW)));
    const uint32_t k23 = hadd2(hadd2(u.y, v.y), hadd2(w.y, x.y));
    sts64(kw + wq * 64 + ao, hadd2(hadd2(u.x, v.x), hadd2(w.x, x.x)), k23);
    const uint32_t d = kw + (wq >> 1) * 128;
    const uint32_t kh = hmul2(kt, 0x38003800u);
    sts32(d + o.x, kh); sts32(d + o.y, kh); sts32(d + o.z, kh); sts32(d + o.w, kh);
    if (wq == 3) {
        if (lane == 31) { sts32(kw + 264, k23 >> 16); sts32(kw + 288 + 264, k23 >> 16); sts32(kw + 576 + 264, k23 >> 16); }
        if (lane == 29) { sts32(kw + 864 + 280, kt >> 16); sts32(kw + 280, kt & 0xffff0000u); }
    }
}

__device__ __forceinline__ int c_exponent(const uint2& r, const uint2& i) {
    uint32_t mx = __vmaxu2(__vmaxu2(r.x & 0x7fff7fffu, r.y & 0x7fff7fffu), __vmaxu2(i.x & 0x7fff7fffu, i.y & 0x7fff7fffu));
    mx = __reduce_max_sync(0xffffffffu, max(mx & 0xffffu, mx >> 16));
    return min(max((int)(mx >> 7), 4), 240);
}

__device__ __forceinline__ int warp_v() { int l; asm volatile("mov.u32 %0, %%tid.x;" : "=r"(l)); return __shfl_sync(0xffffffffu, l >> 5, 0); }
__device__ __forceinline__ int lane_v() { int l; asm volatile("mov.u32 %0, %%laneid;" : "=r"(l)); return l; }
__device__ __forceinline__ uint32_t prmt(uint32_t a, uint32_t b, uint32_t s) { uint32_t d; asm("prmt.b32 %0, %1, %2, %3;\n" : "=r"(d) : "r"(a), "r"(b), "r"(s)); return d; }
__device__ __forceinline__ uint32_t prmt_v(uint32_t a, uint32_t b, uint32_t s) { uint32_t d; asm volatile("prmt.b32 %0, %1, %2, %3;\n" : "=r"(d) : "r"(a), "r"(b), "r"(s)); return d; }
__device__ __forceinline__ void mmah16(uint32_t& d0, uint32_t& d1, uint32_t a0, uint32_t a1, uint32_t a2, uint32_t a3, uint32_t b0, uint32_t b1, uint32_t c0, uint32_t c1) {
    asm volatile("mma.sync.aligned.m16n8k16.row.col.f16.f16.f16.f16 {%0,%1}, {%2,%3,%4,%5}, {%6,%7}, {%8,%9};\n"
                 : "=r"(d0), "=r"(d1) : "r"(a0), "r"(a1), "r"(a2), "r"(a3), "r"(b0), "r"(b1), "r"(c0), "r"(c1));
}
__device__ __forceinline__ void mmah8(uint32_t& d0, uint32_t& d1, uint32_t a0, uint32_t a1, uint32_t b0, uint32_t c0, uint32_t c1) {
    asm volatile("mma.sync.aligned.m16n8k8.row.col.f16.f16.f16.f16 {%0,%1}, {%2,%3}, {%4}, {%5,%6};\n"
                 : "=r"(d0), "=r"(d1) : "r"(a0), "r"(a1), "r"(b0), "r"(c0), "r"(c1));
}
template <int A = 8, int B = 32>
__device__ __forceinline__ void conv_rename(uint32_t (&acc)[32]) {
#pragma unroll
    for (int i = A; i < B; i++) { uint32_t v; asm volatile("mov.b32 %0, %1;\n" : "=r"(v) : "r"(acc[i])); acc[i] = v; }
}
__host__ __device__ constexpr uint32_t band_bits(int hw, int sh) {
    uint32_t c = 0;
    for (int s = 0; s <= 10; s++)
        for (int e = 0; e < 2; e++) {
            const int v = s - 3 + sh - 4 * e;
            if (v <= hw && v >= -hw) c |= 1u << (14 + 16 * e - s);
        }
    return c;
}
template <int HW, int SH, int J> __device__ __forceinline__ uint32_t band(uint32_t p2) {
    uint32_t d;
    asm volatile("{\n.reg .b32 t;\nmul.lo.u32 t, %1, %2;\nand.b32 %0, t, 0x40004000;\n}\n" : "=r"(d) : "r"(p2), "n"(band_bits(HW, SH) | J));
    return d;
}
template <int H0, int SH> __device__ __forceinline__ void band_pair(uint4& l, uint4& u, uint32_t p2) {
    l = make_uint4(band<H0, 8, 1>(p2), band<H0 - 1, SH + 8, 2>(p2), band<H0, 0, 1>(p2), band<H0 - 1, SH, 1>(p2));
    u = make_uint4(band<H0, 0, 2>(p2), band<H0 - 1, SH, 2>(p2), band<H0, -8, 1>(p2), band<H0 - 1, SH - 8, 1>(p2));
}
__device__ __forceinline__ void run_sums(uint32_t (&G)[3][2], const uint32_t (&c)[5], const uint4& l, const uint4& u) {
    mmah8(G[0][0], G[0][1], l.x, l.y, c[0], 0u, 0u);
    mmah8(G[1][0], G[1][1], u.z, u.w, c[3], 0u, 0u);
    mmah8(G[2][0], G[2][1], l.x, l.y, c[2], 0u, 0u);
    mmah16(G[0][0], G[0][1], u.x, u.y, u.z, u.w, c[1], c[2], G[0][0], G[0][1]);
    mmah16(G[1][0], G[1][1], l.x, l.y, l.z, l.w, c[1], c[2], G[1][0], G[1][1]);
    mmah16(G[2][0], G[2][1], u.x, u.y, u.z, u.w, c[3], c[4], G[2][0], G[2][1]);
}
__device__ __forceinline__ float h_lo(uint32_t w) { return __half2float(__ushort_as_half((unsigned short)(w & 0xffffu))); }
__device__ __forceinline__ float h_hi(uint32_t w) { return __half2float(__ushort_as_half((unsigned short)(w >> 16))); }
__device__ __forceinline__ uint64_t smem_desc(uint32_t sb, uint32_t o16, uint32_t lbo) {
    uint64_t d;
    asm("mov.b64 %0, {%1, %2};" : "=l"(d) : "r"(((sb & 0x3FFFF) >> 4) + o16 + (lbo << 12)), "r"(8));
    return d;
}
template <int I> struct IC { static constexpr int value = I; };

struct Conv {
    uint32_t u[3][5];
    uint32_t q2[3][2][4];
    uint32_t q3[2][4];
    uint32_t r[18];
};
__device__ __forceinline__ void conv_sums(Conv& c, uint32_t a0, uint32_t a1, const uint4 (&bd)[4]) {
    {
        uint32_t x;
        ldsm_x4(c.u[0][1], c.u[0][2], c.u[0][3], c.u[0][4], a1);
        ldsm_x4(c.u[0][0], c.u[1][0], c.u[2][0], x, a0);
#pragma unroll
        for (int q = 1; q < 3; q++) ldsm_x4(c.u[q][1], c.u[q][2], c.u[q][3], c.u[q][4], a1 + q * 512);
    }
    uint32_t G[3][2];
#pragma unroll
    for (int q = 0; q < 3; q++) {
        run_sums(G, c.u[q], bd[0], bd[1]);
#pragma unroll
        for (int e = 0; e < 2; e++) {
            const uint32_t s = e ? 0x7632u : 0x5410u;
            c.q2[q][e][0] = prmt(G[0][1], G[0][0], s); c.q2[q][e][1] = prmt(G[1][1], G[1][0], s);
            c.q2[q][e][2] = prmt(G[1][0], G[1][1], s ^ 0x4444u); c.q2[q][e][3] = prmt(G[2][1], G[2][0], s);
        }
    }
#pragma unroll
    for (int q = 0; q < 2; q++) {
        run_sums(G, c.u[q], bd[2], bd[3]);
        c.q3[q][0] = prmt(G[1][1], G[0][0], 0x7632u); c.q3[q][1] = prmt(G[2][1], G[1][0], 0x7632u);
        c.q3[q][2] = prmt(G[1][1], G[0][0], 0x5410u); c.q3[q][3] = prmt(G[2][1], G[1][0], 0x5410u);
    }
}
__device__ __forceinline__ void conv_edges(Conv& c, uint32_t (&acc)[32], uint32_t ka, uint32_t ks, uint32_t sel, int wq) {
#pragma unroll
    for (int i = 0; i < 32; i++) acc[i] = 0u;
    const uint4 r = lds128(ka + 256), s = lds128(ka + 272);
    const uint32_t a0 = prmt(r.x, r.y, sel), a1 = prmt(r.y, r.z, sel), a2 = prmt(r.z, r.w, sel), b1 = prmt(s.y, s.z, sel), b2 = prmt(s.z, s.w, sel);
    const uint32_t sw = sel ^ 0x4444u, a3 = prmt(r.z, r.y, sw), a4 = prmt(r.w, r.z, sw), b0 = prmt(s.x, s.y, sel), b3 = prmt(s.z, s.y, sw), b4 = prmt(s.w, s.z, sw);
#pragma unroll
    for (int q = 0; q < 3; q++) mmah8(acc[8 * q + 8], acc[8 * q + 9], a2, 0u, c.u[q][2], 0u, 0u);
#pragma unroll
    for (int q = 0; q < 2; q++) mmah8(acc[8 * q + 16], acc[8 * q + 17], b2, 0u, c.u[q][2], acc[8 * q + 16], acc[8 * q + 17]);
#pragma unroll
    for (int q = 0; q < 3; q++) mmah16(acc[8 * q + 8], acc[8 * q + 9], a1, a4, a0, a3, c.u[q][3], c.u[q][4], acc[8 * q + 8], acc[8 * q + 9]);
#pragma unroll
    for (int q = 0; q < 2; q++) mmah16(acc[8 * q + 16], acc[8 * q + 17], b1, b4, b0, b3, c.u[q][3], c.u[q][4], acc[8 * q + 16], acc[8 * q + 17]);
    {
        uint32_t t0, t1, t2, t3;
        ldsm_x4(t0, t1, t2, t3, ks);
#pragma unroll
        for (int q = 0; q < 2; q++) mmah16(acc[8 * q + 16], acc[8 * q + 17], c.q2[q][0][0], c.q2[q][0][1], c.q2[q][0][2], c.q2[q][0][3], t0, t1, acc[8 * q + 16], acc[8 * q + 17]);
#pragma unroll
        for (int q = 0; q < 2; q++) mmah16(acc[8 * q + 16], acc[8 * q + 17], c.q2[q][1][0], c.q2[q][1][1], c.q2[q][1][2], c.q2[q][1][3], t2, t3, acc[8 * q + 16], acc[8 * q + 17]);
    }
    {
        const uint32_t a = ka + wq * 64;
#pragma unroll
        for (int i = 0; i < 4; i++) { const uint4 v = lds128(a + i * 16); c.r[4 * i] = v.x; c.r[4 * i + 1] = v.y; c.r[4 * i + 2] = v.z; c.r[4 * i + 3] = v.w; }
        const uint2 v = lds64(a + 64);
        c.r[16] = v.x; c.r[17] = v.y;
    }
    if (sel == 0u) {
#pragma unroll
        for (int i = 0; i < 6; i++) sts128(ka + i * 16, c.q2[i >> 1][i & 1][0], c.q2[i >> 1][i & 1][1], c.q2[i >> 1][i & 1][2], c.q2[i >> 1][i & 1][3]);
#pragma unroll
        for (int i = 0; i < 2; i++) sts128(ka + i * 16, c.q3[i][0], c.q3[i][1], c.q3[i][2], c.q3[i][3]);
#pragma unroll
        for (int i = 1; i < 4; i++) sts64(ka + i * 16, acc[8 * i], acc[8 * i + 1]);
    }
    conv_rename(acc);
}
#define GATE 2
#define HAND 2
#define GA 6
#define GB 4
template <int TA, int TB, int IA, class FG>
__device__ __forceinline__ void conv_tail(uint32_t (&acc)[32], const uint32_t (&a)[8][4], uint32_t sb, unsigned char* gy0, int warp, size_t ycopy, FG fg) {
    const int wg = warp >> 2, wq = warp & 3, ord = TA == 0 && TB == 16 ? 3 - wg : 4;
    const uint32_t ub = sb + SM_U + wg * USLOT_B + UPAD * 16, turn = sb + SM_MISC + 376 + ord * 8, sfs = sb + SM_MISC + 256 + wg * 8;
    const uint32_t du = wg * (USLOT_B / 16) + (SM_U / 16 + UPAD + TA * 8);
    uint32_t ud[8], fs;
    auto skip = [&]() {
        const int lane = lane_v();
        const uint32_t ua = ub + ((lane >> 3) & 1) * ULO_B + (8 * wq + (lane & 7)) * 16 + (lane >> 4) * 512;
        if (IA == 0) ldsm_x4_t(ud[0], ud[1], ud[2], ud[3], ua);
        if (TB == 16) ldsm_x4_t(ud[4], ud[5], ud[6], ud[7], ua + 1024);
        const uint2 fd = lds64(sfs);
        fs = fd.x;
        const float dsk = __uint_as_float(fd.y);
#pragma unroll
        for (int i = 2 * IA; i < TB / 2; i++) ud[i] = pack_bf16(h_lo(ud[i]) * dsk, h_hi(ud[i]) * dsk);
    };
    conv_rename<2 * TA, 2 * TB>(acc);
    if (__builtin_expect(ord != 0, 0)) {
        skip();
        mbar_wait(turn);
    }
    if (TA == 0 && TB == 16) asm volatile("{\n.reg .pred p;\nelect.sync _|p, 0xffffffff;\n@p mbarrier.arrive.shared::cta.b64 _, [%0];\n}\n" ::"r"(turn + 40) : "memory");
    fg(IC<8>());
    wg_fence();
#pragma unroll
    for (int m = 7; m >= 0; m--) {
        wg_h<TA, TB - TA>(acc, a[m], smem_desc(sb, du - m, ULO_B));
        if (m == GA || m == GB || m == HAND) wg_commit();
        if (m == GB) asm volatile("wgmma.wait_group.sync.aligned 1;\n" ::: "memory");
    }
    wg_commit();
    if (TA == 0 && TB == 16) {
        asm volatile("wgmma.wait_group.sync.aligned 1;\n" ::: "memory");
        asm volatile("{\n.reg .pred p;\nelect.sync _|p, 0xffffffff;\n@p mbarrier.arrive.shared::cta.b64 _, [%0];\n}\n" ::"r"(turn + 8) : "memory");
    }
    __syncwarp();
    fg(IC<3>());
    if (!ord) skip();
    fg(IC<4>());
    const int lane = lane_v();
    const uint32_t lp = sb + SM_PL + (ord >= 3 ? ord - 3 : ord) * PL_B + lane * 8;
    unsigned char* gy = gy0 + ((4 * wq + (lane & 3)) * DM + (TA == 0 && TB == 16 ? 4 * blockIdx.x + wg : 512 + (blockIdx.x >> 1))) * 64 + (lane >> 2) * 8;
    const uint32_t st = lp + (wq * 12 - ((wq * (wq - 1)) >> 1)) * 256;
    uint32_t ld[3];
#pragma unroll
    for (int s = 1; s < 4; s++) {
        const int w = (wq - s) & 3;
        ld[s - 1] = lp + (w * 12 - ((w * (w - 1)) >> 1) + s - 1 - (wq < s ? 3 : 0)) * 256;
    }
    if (ord >= 3) bar_sync(9 + ord, 256);
    wg_wait0();
    fg(IC<6>());
#pragma unroll
    for (int j = TA; j < TB; j++)
        if ((j & 3) && j + 3 >= 4 * IA && (j + 3 < TB || j + wq < TB)) sts64(st + (j - 1 - (j >> 2)) * 256, acc[2 * j], acc[2 * j + 1]);
    bar_sync(1 + wg, 128);
    fg(IC<7>());
    uint2 v[4][3];
#pragma unroll
    for (int i = IA; i < TB / 4; i++)
#pragma unroll
        for (int s = 0; s < 3; s++) {
            if (i == 0) { v[i][s] = make_uint2(0u, 0u); if (wq > s) v[i][s] = lds64(ld[s]); }
            else v[i][s] = lds64(ld[s] + i * 768);
        }
    fg(IC<5>());
#pragma unroll
    for (int i = IA; i < TB / 4; i++) {
        const uint32_t x0 = hadd2(v[i][0].x, acc[8 * i]), x1 = hadd2(v[i][1].x, v[i][2].x), y0 = hadd2(v[i][0].y, acc[8 * i + 1]), y1 = hadd2(v[i][1].y, v[i][2].y);
        const uint32_t x = hadd2(x0, x1), y = hadd2(y0, y1);
        const uint32_t lo = pack_bf16(h_lo(x), h_hi(x)), hi = pack_bf16(h_lo(y), h_hi(y));
        const uint32_t o0 = max(hfma2_bf(lo, fs, ud[2 * i]), 1u), o1 = hfma2_bf(hi, fs, ud[2 * i + 1]);
        stg64(gy + i * 16 * DM * 64, o0, o1);
    }
    if (TA == 0 && TB == 16 && ord < 2) bar_arrive(12 + ord, 256);
}
template <int M0, int M1>
__device__ __forceinline__ void conv_frags(uint32_t (&a)[8][4], const uint32_t (&r)[18], uint32_t sel, uint32_t dep, int warp) {
    const uint32_t s = prmt_v(sel, dep, 0x3210u + (warp >> 8)), sw = s ^ 0x4444u;
#pragma unroll
    for (int m = M0; m < M1; m++) {
        a[m][0] = prmt_v(r[2 * m + 1], r[2 * m + 2], s); a[m][1] = prmt_v(r[2 * m + 2], r[2 * m + 3], s);
        a[m][2] = prmt_v(r[2 * m + 1], r[2 * m], sw); a[m][3] = prmt_v(r[2 * m + 2], r[2 * m + 1], sw);
    }
}
template <class FG>
__device__ __forceinline__ void conv_main(const Conv& c, uint32_t (&acc)[32], uint32_t sb, uint32_t sel, unsigned char* gy, int warp, size_t ycopy, FG fg) {
    const uint32_t kw = (warp >> 2) * (KW_B / 16) + SM_KW / 16;
    const uint64_t d2 = smem_desc(sb, kw + KW_T2 / 16, KW_KH), d2b = smem_desc(sb, kw + KW_T2 / 16 + 1, KW_KH), d3 = smem_desc(sb, kw + KW_T3 / 16, 16), d3b = smem_desc(sb, kw + KW_T3 / 16 + 32, 16);
    uint32_t a[8][4];
    {
        const int ord = warp < 16 ? 3 - (warp >> 2) : 4;
        if (__builtin_expect(ord >= GATE, 0)) {
            fg(IC<1>());
            mbar_wait(sb + SM_MISC + 376 + 40 + (ord - GATE) * 8);
        }
    }
    wg_fence();
    wg_h<12, 4>(acc, c.q3[0], d3b); wg_h<8, 4>(acc, c.q3[0], d3); wg_h<4, 4>(acc, c.q2[0][0], d2b);
    wg_h<12, 4>(acc, c.q3[1], d3); wg_h<8, 4>(acc, c.q2[1][0], d2b);
    wg_h<12, 4>(acc, c.q2[2][0], d2b); wg_h<4, 4>(acc, c.q2[0][1], d2); wg_h<8, 4>(acc, c.q2[1][1], d2);
    wg_h<12, 4>(acc, c.q2[2][1], d2);
    wg_commit(); __syncwarp();
    fg(IC<0>());
    wg_wait0();
    conv_frags<0, 8>(a, c.r, sel, acc[16], warp);
    fg(IC<2>());
    if (warp >= 16) {
        if (blockIdx.x & 1) conv_tail<4, 16, 2>(acc, a, sb, gy, warp, ycopy, fg);
        else conv_tail<0, 8, 0>(acc, a, sb, gy, warp, ycopy, fg);
    } else {
        conv_tail<0, 16, 0>(acc, a, sb, gy, warp, ycopy, fg);
    }
}
#define CONV_LT6 const int dd = (lane >> 3) + (lane & 4) - (lane & 3); \
        const uint4 lt6 = make_uint4(prmt_v((dd & 3) * 288, 0u, idn), prmt_v(0x3254u + (dd >> 2) * 0x2222u, 0u, idn), \
            prmt_v(UPAD * 16 + (lane & 7) * 16 + ULO_B - 32 + (lane >> 3) * 512, 0u, idn), prmt_v(UPAD * 16 + (lane & 7) * 16 + ((lane >> 3) & 1) * ULO_B - 16 + (lane & 16), 0u, idn));
#define CONV_PRE \
        CONV_LT6 \
        const uint32_t ka = kw + lt6.x, sel = lt6.y, ks = kw + lt7.x; \
        const uint32_t ca0 = sb + SM_U + wg * USLOT_B + (warp & 3) * 128 + lt6.z, ca1 = sb + SM_U + wg * USLOT_B + (warp & 3) * 128 + lt6.w; \
        uint4 bd[4]; \
        band_pair<2, 4>(bd[0], bd[1], lt7.w); band_pair<4, 0>(bd[2], bd[3], lt7.w);
#define CONV_BODY \
        Conv c; \
        uint32_t acc[32]; \
        conv_sums(c, ca0, ca1, bd); \
        conv_edges(c, acc, ka, ks, sel, warp & 3);
template <int U0, int U1>
__device__ __forceinline__ void weight_units(uint32_t sb, const CUtensorMap* tg, const CUtensorMap* tu, const CUtensorMap* td, int w) {
    if constexpr (U0 < U1) {
        if (w == 0 && elect_one()) {
            if constexpr (U0 < 12) tma_2d(sb + SM_WG + U0 * 6912, U0 < 6 ? tg : tu, 72 * (blockIdx.x >> 1), 288 * (blockIdx.x & 1) + (U0 % 6) * 48, sb + SM_MISC + 328);
            else tma_2d(sb + SM_WD + (15 - U0) * 10368, td, 288 * (blockIdx.x & 1) + 72 * (15 - U0), 72 * (blockIdx.x >> 1), sb + SM_MISC + 336);
        }
        weight_units<U0 + 1, U1>(sb, tg, tu, td, w - 1);
    }
}
#define WS x112347cccdeeeeeeffg
#define WS_STR2(x) #x
#define WS_STR(x) WS_STR2(x)
__device__ constexpr int wsched(int i) { constexpr char t[] = WS_STR(WS); return i == 0 ? 0 : (t[i] <= '9' ? t[i] - '0' : t[i] - 'a' + 10); }
__device__ constexpr bool wsched_ok() { for (int i = 0; i < 19; i++) if (wsched(i + 1) < wsched(i) || wsched(i + 1) > wsched(i) + (i == 6 ? 8 : i < 16 ? 3 : 1)) return false; return wsched(19) == 16 && wsched(6) <= WMAX && wsched(16) <= 15; }
static_assert((PAUSE & 2) && GATE <= 2, "resets");
static_assert(wsched_ok(), "weight schedule");
#define PS x00000
__device__ constexpr int psched(int i) { constexpr char t[] = WS_STR(PS); return i == 0 ? 0 : (t[i] <= '9' ? t[i] - '0' : t[i] - 'a' + 10); }
#define PPOINT(i) do { if (psched(i + 1) > psched(i) && warp == 1 + (i & 1) && elect_one()) \
    l2_prefetch(reinterpret_cast<const unsigned char*>(p.wpf) + b * 41472 + psched(i) * 4608, (psched(i + 1) - psched(i)) * 4608); } while (0)
#define WPOINT(i, w) do { weight_units<wsched(i), wsched(i + 1)>(sb, &tm_g, &tm_u, &tm_d, w); } while (0)

__global__ void __launch_bounds__(NTHR, 1) __cluster_dims__(2, 1, 1)
fused_kernel(const Params p, const __grid_constant__ CUtensorMap tm_g, const __grid_constant__ CUtensorMap tm_u, const __grid_constant__ CUtensorMap tm_d, const __grid_constant__ CUtensorMap tm_x,
             const __grid_constant__ CUtensorMap tm_y, const __grid_constant__ CUtensorMap tm_z) {
    extern __shared__ __align__(1024) unsigned char smem[];
    const uint32_t sb = smem_u32(smem);
    const int tid = threadIdx.x, warp = __shfl_sync(0xffffffffu, tid >> 5, 0), lane = tid & 31;
    const int b = blockIdx.x, P = b >> 1, odd = b & 1;
    const int g = lane >> 2, t = lane & 3;
    const int wg = warp >> 2, t128 = tid & 127;
    const uint32_t s_stat = sb + SM_MISC;
    const uint32_t s_key = sb + SM_MISC + 128;
    const uint32_t s_wm = sb + SM_MISC + 256;
    const uint32_t s_k16 = sb + SM_MISC + 192;
    const uint32_t s_fs = sb + SM_MISC + 256;
    const uint32_t s_cnt = sb + SM_MISC + 320;
    const uint32_t bar_w = sb + SM_MISC + 328, bar_d = bar_w + 8, bar_g = bar_w + 16, bar_r = bar_w + 32, bar_h = bar_w + 40, bar_x = bar_w + 48;
    STAMP(0);

    const bool lnw = (unsigned)(warp - 10) < 9u;
    const unsigned pm = tid + (tid < 512 ? 512 * b : 65024 + 128 * P), pq = (pm & ~127u) + 4 * lane;
    uint32_t pl = ldg16(p.lar + pm), ldt = ldg16(p.ldt + (pm >> 7));
    const uint32_t pa2 = ldg16(p.aim + pm), pc = ldg16(p.cre + pm), pi = ldg16(p.cim + pm);
    const uint2 call_re = ldg64(p.cre + pq), call_im = ldg64(p.cim + pq);
    const uint32_t dskl = ldg16(p.dsk + (pm >> 7));
    const uint32_t ep = ld_poll32(p.s->hint + (b & 7) * 32 + 1 + (lane >> 5));
    if ((unsigned)(tid - 320) < 288u) {
        const bf16* xp = p.x + (unsigned)((32 * P + 2 * odd + TOKEN_OF(g)) * DM + ((tid - 320) & ~31) + 8 * t);
        const uint32_t xt = sb + SM_XT + ((tid - 320) & ~31) * 32 + lane * 16;
        asm volatile("cp.async.cg.shared.global [%0], [%1], 16;\ncp.async.cg.shared.global [%0 + 512], [%1 + 9216], 16;\n"
                     "cp.async.cg.shared.global [%0 + 9216], [%1 + 576], 16;\ncp.async.cg.shared.global [%0 + 9728], [%1 + 9792], 16;\n" ::"r"(xt), "l"(xp) : "memory");
    }
    uint32_t* const std_ = p.s->st + ((lane & 12) * 128 + odd * 256 + 4 * P + 2 * (lane & 1) + ((lane >> 1) & 1)) * 2;
    unsigned char* const ud = reinterpret_cast<unsigned char*>(p.s->uT) + (32 * (warp - UW) + 8 * (g >> 1) + (g & 1)) * 4096 + b * 32 + t * 8;
    if (warp == 0) {
        if (lane == 0) {
            mbar_init(bar_x, 1); mbar_init(bar_w, 1); mbar_init(bar_d, 1); mbar_init(bar_g, 1); mbar_init(bar_h, 3); mbar_init(bar_r, 1);
            #pragma unroll
            for (int i = 1; i < 9; i++) mbar_init(bar_x + 8 * i, 4);
            asm volatile("fence.mbarrier_init.release.cluster;\n" ::: "memory");
            mbar_expect(bar_x, 16384); mbar_expect(bar_r, 8192);
            mbar_expect(bar_w, 2 * 41472); mbar_expect(bar_d, 41472); mbar_expect(bar_g, 18 * 512);
        }
        __syncwarp();
        bar_arrive(0, NWRK);
    }
    if (warp == 0 && elect_one()) tma_3d(sb + SM_XC + 16384, &tm_x, 8 * P, 0, 8 * odd, bar_x);
    asm volatile("barrier.cluster.arrive.relaxed.aligned;\n" ::: "memory");
    const uint32_t kw = sb + SM_KW + wg * KW_B;
    if (t128 < 2 * UPAD) sts128(sb + SM_U + wg * USLOT_B + (t128 & 1) * ULO_B + (t128 >> 1) * 16, 0u, 0u, 0u, 0u);
    sts128(kw + t128 * 16, 0u, 0u, 0u, 0u);
    if (t128 < KW_B / 16 - 128) sts128(kw + 2048 + t128 * 16, 0u, 0u, 0u, 0u);
    if (tid < 96) {
#pragma unroll
        for (int i = 0; i < 6; i++) sts128(sb + SM_ZERO + i * 1536 + tid * 16, 0u, 0u, 0u, 0u);
    }
    if (warp != 0) bar_sync(0, NWRK);
    STAMP(1);
    if (warp == 19 || warp == UW || warp == UW + 1) {
        if (warp == 19) {
            if (lane < 16) stg64(std_, 0u, 0u);
            if (lane < 9) asm volatile("prefetch.global.L2 [%0];\n" ::"l"(p.wr + lane * 64));
        } else {
#pragma unroll
            for (int k = 0; k < 4; k++) stg64(ud + k * 8192, 0u, 0u);
        }
    }
    uint32_t X[2][8];
    auto partial = [&]() {
        const uint32_t xt = sb + SM_XT + (warp - 10) * 1024 + lane * 16;
        asm volatile("cp.async.wait_all;\n" ::: "memory");
        STAMP(23);
        const uint4 a = lds128(xt), c = lds128(xt + 512), d = lds128(xt + 9216), e = lds128(xt + 9728);
        X[0][0] = a.x; X[0][1] = a.y; X[0][2] = a.z; X[0][3] = a.w; X[0][4] = d.x; X[0][5] = d.y; X[0][6] = d.z; X[0][7] = d.w;
        X[1][0] = c.x; X[1][1] = c.y; X[1][2] = c.z; X[1][3] = c.w; X[1][4] = e.x; X[1][5] = e.y; X[1][6] = e.z; X[1][7] = e.w;
        ln_partial<8>(X, sb + SM_LNP, warp - 10, g, t);
        bar_arrive(6, 320);
        if (PAUSE & 1) bar_sync(7, PCNT);
    };
    if (LNAT == 0 && lnw) {
        partial();
        pl = prmt_v(pl, X[0][0], 0x3210u + (warp >> 8)); ldt = prmt_v(ldt, X[0][0], 0x3210u + (warp >> 8));
    }
    auto finish = [&]() {
        bar_sync(6, 320);
        float mb, rc;
        ln_finish<9>(sb + SM_LNP, lane, mb, rc);
        const float rh = rbf(rc);
        const uint32_t s0 = (__float_as_uint(mb) >> 16) | (((ep & 0x7fffu) + 1u) << 16), s1 = pack_bf16(rh, rc - rh);
        if (lane < 16) { stg64(std_, s0, s1); sts64(s_stat + lane * 8, s0, s1); }
        if (lane == 16) sts32(s_cnt + 4, ep);
        bar_arrive(7, PCNT);
        STAMP(28);
    };
    auto upub = [&]() {
        if (!(PAUSE & 6)) bar_sync(7, PCNT);
        const uint32_t utag = ((ep & 3u) + 1u) * 0x10001u;
        uint32_t U[2][4];
#pragma unroll
        for (int hf = 0; hf < 2; hf++) {
            const uint2 st = lds64(s_stat + (g + 8 * hf) * 8);
            const uint4 xv = lds128(sb + SM_XT + (16 + warp - UW) * 1024 + hf * 512 + lane * 16);
            const uint32_t xs[4] = {xv.x, xv.y, xv.z, xv.w};
#pragma unroll
            for (int k = 0; k < 4; k++) {
                const uint32_t u = ln_apply(xs[k], st);
                U[hf][k] = movm((pack_f16_rz(bf_lo(u), __uint_as_float(u)) & 0xfff8fff8u) | utag);
            }
        }
#pragma unroll
        for (int k = 0; k < 4; k++) stg64(ud + k * 8192, U[0][k], U[1][k]);
    };
    if (FINAT == 0 && warp == 19) finish();
    const uint32_t tb = table_buf(sb, warp);
    const float dt = rbf(expf(bf_lo(ldt)));
    KGen kg;
    kgen_setup(kg, pl | (pa2 << 16), dt);
    if (LNAT == 1 && lnw) {
        partial();
        kg.z8.x = __uint_as_float(prmt_v(__float_as_uint(kg.z8.x), X[0][0], 0x3210u + (warp >> 8)));
        kg.z1.x = __uint_as_float(prmt_v(__float_as_uint(kg.z1.x), X[0][0], 0x3210u + (warp >> 8)));
    }
    if (FINAT == 1 && warp == 19) finish();
    if (UAT == 0 && (warp == UW || warp == UW + 1)) upub();
    kgen_rows(kg, tb, lane);
    if (wg == 0) fence_async();
    if (LNAT == 2 && lnw) {
        partial();
        kg.z128.x = __uint_as_float(prmt_v(__float_as_uint(kg.z128.x), X[0][0], 0x3210u + (warp >> 8)));
        kg.z1.x = __uint_as_float(prmt_v(__float_as_uint(kg.z1.x), X[0][0], 0x3210u + (warp >> 8)));
    }
    if (FINAT == 2 && warp == 19) finish();
    if (UAT == 1 && (warp == UW || warp == UW + 1)) upub();
    STAMP(2);
    WPOINT(0, warp - 4);
    PPOINT(0);
    const int ce = c_exponent(call_re, call_im);
    if (t128 == 0) sts64(s_fs + wg * 8, (uint32_t)min(max(ce + (int)(__float_as_uint(dt) >> 23) - 116, 0), 254) * 0x800080u, dskl << 16);
    kgen_chain(kg, pc | (pi << 16), __uint_as_float(((uint32_t)(244 - ce) << 23) | (__float_as_uint(dt) & 0x7fffffu)));
    if ((PAUSE & 4) && warp < 10) bar_sync(7, PCNT);
    if (UAT == 4 && (warp == UW || warp == UW + 1)) upub();
    STAMP(3);
    WPOINT(1, warp - 6);
    PPOINT(1);
    kgen_cols(kg, tb, lane);
    if (LNAT == 3 && lnw) partial();
    if (FINAT == 3 && warp == 19) finish();
    if ((PAUSE & 2) && warp < 10) bar_sync(7, PCNT);
    if (UAT == 2 && (warp == UW || warp == UW + 1)) upub();
    STAMP(4);
    WPOINT(2, warp - 8);
    PPOINT(2);
    const uint4* usrc = wg < 4 ? reinterpret_cast<const uint4*>(p.s->st) + odd * 512 + (lane & 1) * 128 + 16 * (warp & 7) + (lane >> 1)
                               : reinterpret_cast<const uint4*>(p.s->uT) + P * 256 + 2 * t128;
    const int ustep = wg < 4 ? 256 : 1;
    uint4 uv0, uv1;
    kgen_mma(kg, tb, lane);
    if (UAT == 3 && (warp == UW || warp == UW + 1)) upub();
    STAMP(26);
    WPOINT(3, warp - 5);
    PPOINT(3);
    const uint32_t idn = 0x3210u + (warp >> 8);
    const uint4 lt7 = make_uint4(prmt_v(KW_T2 + ((lane >> 3) & 1) * KW_KH + (33 + (lane & 7)) * 16 - (lane & 16), 0u, idn), t * 288 + g * 8 + 8, (lane & 1) * 4096 + (lane >> 1) * 16,
                                 prmt_v(8u << ((lane >> 3) + (lane & 4)) >> (lane & 3), 0u, idn));
    asm volatile("barrier.cluster.wait.acquire.aligned;\n" ::: "memory");
    bar_sync(1 + wg, 128);
    uv0 = ld_poll(usrc); uv1 = ld_poll(usrc + ustep);
    kgen_combine(sb, warp, lane, kw, lt7.y);
    CONV_PRE
    STAMP(5);
    WPOINT(4, warp - 7);
    PPOINT(4);
    if (wg < 4) {
        mbar_wait(bar_x);
        const bool far = DSM == 1 ? warp < 8 : warp >= 8;
        const uint32_t xa = sb + SM_XC + 16384 + (warp & 7) * 256 + (odd ^ far) * 8 + lt7.z;
        uint2 xv[4] = {lds64(xa), lds64(xa + 8192), lds64(xa + 2048), lds64(xa + 10240)};
        const uint32_t tag = ((ep & 0x7fffu) + 1u) << 16;
        int it = 0;
        while (true) {
            const bool bad = (((uv0.x ^ tag) | (uv0.z ^ tag)) | ((uv1.x ^ tag) | (uv1.z ^ tag))) >> 16;
            if (!__any_sync(0xffffffffu, bad)) break;
            if (++it > SPIN_LIMIT) TRAP();
            if (bad) { uv0 = ld_poll(usrc); uv1 = ld_poll(usrc + 256); }
        }
        STAMP(6);
        DBG(wg, it);
        const uint2 st[4] = {make_uint2(uv0.x, uv0.y), make_uint2(uv0.z, uv0.w), make_uint2(uv1.x, uv1.y), make_uint2(uv1.z, uv1.w)};
#pragma unroll
        for (int i = 0; i < 4; i++) {
            xv[i].x = ln_apply(xv[i].x, st[i]);
            xv[i].y = ln_apply(xv[i].y, st[i]);
        }
        const uint32_t ub = sb + SM_U + UPAD * 16 + odd * ULO_B + (warp & 7) * 256 + lane * 8;
        const uint32_t w[4][2] = {{pack_f16(bf_lo(xv[0].x), bf_lo(xv[1].x)), pack_f16(bf_lo(xv[2].x), bf_lo(xv[3].x))}, {HI2(xv[0].x, xv[1].x), HI2(xv[2].x, xv[3].x)},
                                  {pack_f16(bf_lo(xv[0].y), bf_lo(xv[1].y)), pack_f16(bf_lo(xv[2].y), bf_lo(xv[3].y))}, {HI2(xv[0].y, xv[1].y), HI2(xv[2].y, xv[3].y)}};
#pragma unroll
        for (int i = 0; i < 4; i++) {
            if (far) asm volatile("st.async.shared::cluster.mbarrier::complete_tx::bytes.v2.b32 [%0], {%1,%2}, [%3];\n" ::"r"((ub ^ 0x1000000u) + i * USLOT_B), "r"(w[i][0]), "r"(w[i][1]), "r"(bar_r ^ 0x1000000u) : "memory");
            else sts64(ub + i * USLOT_B, w[i][0], w[i][1]);
        }
    } else {
        const uint32_t utag = ((ep & 3u) + 1u) * 0x10001u;
        int it = 0;
        while (true) {
            const bool bad = (((uv0.x ^ utag) | (uv0.y ^ utag) | (uv0.z ^ utag) | (uv0.w ^ utag)) | ((uv1.x ^ utag) | (uv1.y ^ utag) | (uv1.z ^ utag) | (uv1.w ^ utag))) & 0x70007u;
            if (!__any_sync(0xffffffffu, bad)) break;
            if (++it > SPIN_LIMIT) TRAP();
            if (bad) { uv0 = ld_poll(usrc); uv1 = ld_poll(usrc + 1); }
        }
        STAMP(6);
        DBG(4, it);
        const uint32_t ub = sb + SM_U + UPAD * 16 + 4 * USLOT_B + (t128 >> 1) * 32 + (t128 & 1) * 8;
        sts64(ub, prmt(uv0.x, uv0.z, 0x5410u) ^ utag, prmt(uv1.x, uv1.z, 0x5410u) ^ utag);
        sts64(ub + 16, prmt(uv0.x, uv0.z, 0x7632u) ^ utag, prmt(uv1.x, uv1.z, 0x7632u) ^ utag);
        sts64(ub + ULO_B, prmt(uv0.y, uv0.w, 0x5410u) ^ utag, prmt(uv1.y, uv1.w, 0x5410u) ^ utag);
        sts64(ub + ULO_B + 16, prmt(uv0.y, uv0.w, 0x7632u) ^ utag, prmt(uv1.y, uv1.w, 0x7632u) ^ utag);
    }
    if (warp < 3 && elect_one()) tma_st_3d(warp < 2 ? &tm_y : &tm_z, sb + SM_ZERO, warp < 2 ? 128 * b : 32 * (512 + P), 0, 2 * (warp < 2 ? warp : odd));
    WPOINT(5, warp - 3);
    mbar_wait(bar_r);
    fence_async();
    bar_sync(0, NWRK);
    STAMP(7);
    uint32_t hv0 = 0;
    {
        if (warp >= 12) WPOINT(6, 19 - warp);
        CONV_BODY
        WPOINT(7, 19 - warp);
        bar_sync(0, NWRK);
        STAMP(8);
        size_t ycopy = 0;
        auto hook = [&](auto gi) {
                     constexpr int G = decltype(gi)::value;
                     if (G == 4 && warp == HINTW) hv0 = ld_poll32(p.s->hint + (lane_v() & 7) * 32);
                     if (G == 5) mbar_wait(bar_h);
                     if (G == 1 || G == 2) WPOINT(7 + G, warp - 16);
                     if (G == 3) { WPOINT(10, warp - 12); WPOINT(12, warp - 8); WPOINT(14, warp - 4); }
                     if (G == 5) { WPOINT(11, warp - 13); WPOINT(13, warp - 9); WPOINT(15, warp - 5); }
                     if (G == 1 && warp >= 17 && elect_one())
                         bulk_s2g(warp == 17 ? p.s->part + b * 2304 : warp == 18 ? p.s->rows + b * 1152 : p.s->sc + b * 32, sb + SM_ZERO, warp == 17 ? 9216 : warp == 18 ? 4608 : 32);
                     if (G == 4 && warp >= 17 && elect_one()) {
                         asm volatile("cp.async.bulk.wait_group 0;\n" ::: "memory");
                         hint_arrive(p.s->hint, 2, b & 7);
                     }
                     if (G == 1 && warp < 3) {
                         if (elect_one()) {
                             asm volatile("cp.async.bulk.wait_group 0;\n" ::: "memory");
                             mbar_arrive(bar_h);
                             hint_arrive(p.s->hint, 0, b & 7);
                         }
                         __syncwarp();
                         STAMP(17);
                     }
                 };
        conv_main(c, acc, sb, sel, reinterpret_cast<unsigned char*>(p.s->y), warp, ycopy, hook);
        STAMP(10);
    }
    {
    const int warp = warp_v(), lane = lane_v(), tid = 32 * warp + lane, g = lane >> 2, t = lane & 3;
    if (warp == HINTW) {
        const uint32_t target = (lds32(s_cnt + 4) + 1u) * 48u;
        if (__any_sync(0xffffffffu, (int)(hv0 - target) < 0)) hint_wait(p.s->hint, 0, target);
    }
    STAMP(27);
    bar_sync(0, NWRK);
    STAMP(11);
    const uint32_t zr = warp >> 8;
    auto late_rows = [&](auto pub) {
        const uint32_t k = lds32(s_key + (lane & 7) * 4), ep = lds32(s_cnt + 4);
        const bool late = k & 256u, mine = late && ((k & 255u) >> 1) == (uint32_t)b;
        uint32_t todo = __ballot_sync(0xffffffffu, mine) & 0xffu;
        if (todo) {
#pragma unroll 1
            while (todo) {
                const int s = __ffs(todo) - 1, row = (__shfl_sync(0xffffffffu, k, s) >> 9) & 15;
                todo &= todo - 1;
                if ((row & 7) == g) pub(row & 8, 2 * NCTA + s);
            }
            __threadfence();
            bar_sync(0, NWRK);
            if (tid < NSEL && mine) *reinterpret_cast<volatile unsigned*>(p.s->flag + tid) = ep + 1u;
        }
        int it = 0;
        while (__any_sync(0xffffffffu, late && ld_poll32(p.s->flag + (lane & 7)) != ep + 1u)) { if (++it > SPIN_LIMIT) TRAP(); }
        __threadfence();
        const int gs = tid / 36;
        const uint4* src = reinterpret_cast<const uint4*>(p.s->rows) + __shfl_sync(0xffffffffu, late ? 2 * NCTA + (lane & 7) : (k & 255u), gs & 7) * 144 + 36 * odd + (tid - gs * 36);
        if (tid < 288) {
            uint4 v0;
            do { v0 = ld_poll(src); if (++it > SPIN_LIMIT) TRAP(); } while (!v0.x);
            sts128(sb + SM_XS + gs * XS_PITCH + (tid - gs * 36) * 16, v0.x, v0.y, v0.z, v0.w);
        }
        bar_sync(0, NWRK);
    };
    if (warp >= 18) {
        if (warp == 18) {
            uint32_t* const kp = pin(p.s->sc + 32 * b, zr);
            const uint32_t kid = pin(0x30000000u | ((lane & 15) << 9) | 2 * b, zr), ka = pin(s_k16 + (lane & 15) * 4, zr), kb = pin(s_k16 + (lane & 16) * 2, zr);
            bar_sync(8, 640);
            float mb, rc;
            ln_finish<18>(sb + SM_LNP, lane, mb, rc);
            if (lane < 16) stat_store(s_stat + lane * 8, mb, rc, 0u);
            bar_arrive(13, 608);
            bar_sync(10, 608);
            const float r = sum18(sb + SM_LNP + (32 + (lane & 15)) * 80);
            const uint32_t bits = pack_bf16(0.f, r);
            const uint32_t me = (((bits ^ ((uint32_t)((int)bits >> 31) & 0x7fffffffu)) >> 3) & 0x1fffe000u) ^ kid;
            sts32(ka, me);
            __syncwarp();
            const uint4 v = lds128(kb), w = lds128(kb + 16);
#define GT(x) ((me - (x)) >> 31)
            uint32_t rank = pin(GT(v.x) + GT(v.y) + GT(v.z), zr) + pin(GT(v.w) + GT(w.x) + GT(w.y), zr) + pin(GT(w.z) + GT(w.w), zr);
#undef GT
            rank += __shfl_xor_sync(0xffffffffu, rank, 16);
            if (lane < 16) { if (rank < 8) stg32(kp + rank, me + (rank < 2 ? rank : 256u)); }
            else sts32(ka + (s_wm - s_k16), rank);
            bar_arrive(11, 640);
        }
        const uint4* ksrc = pin(reinterpret_cast<const uint4*>(p.s->sc) + 8 * lane, zr);
        const uint4* rsrc = pin(reinterpret_cast<const uint4*>(p.s->rows) + 36 * odd + t, zr);
        if (warp == 19) {
            hint_wait(p.s->hint, 2, (lds32(s_cnt + 4) + 1u) * 48u);
            bar_sync(8, 640);
            WPOINT(16, 0);
            WPOINT(17, 0);
            bar_sync(11, 640);
        }
        bool slow = false;
        int it = 0;
        if (warp == 19) {
        uint4 q[4];
#pragma unroll
        for (int i = 0; i < 4; i++) q[i] = ld_poll(ksrc + 256 * i);
        while (true) {
            uint32_t a[4];
#pragma unroll
            for (int i = 0; i < 4; i++) a[i] = q[i].x & q[i].y & q[i].z & q[i].w;
            if (__all_sync(0xffffffffu, a[0] & a[1] & a[2] & a[3])) break;
#pragma unroll
            for (int i = 0; i < 4; i++)
                if (!a[i]) q[i] = ld_poll(ksrc + 256 * i);
            if (++it > SPIN_LIMIT) TRAP();
        }
        bar_arrive(9, 608);
        STAMP(16);
        auto merge = [](const uint4& x, const uint4& y) {
            const uint32_t a = max(x.x, y.w), c = max(x.y, y.z), d = max(x.z, y.y), e = max(x.w, y.x);
            const uint32_t a2 = max(a, d), d2 = min(a, d), c2 = max(c, e), e2 = min(c, e);
            return make_uint4(max(a2, c2), min(a2, c2), max(d2, e2), min(d2, e2));
        };
        uint4 h = merge(merge(q[0], q[1]), merge(q[2], q[3]));
        uint4 v[9];
        uint32_t key = 0;
#pragma unroll
        for (int s = 0; s < 8; s++) {
            const uint32_t m = __reduce_max_sync(0xffffffffu, h.x);
            const bool w = h.x == m;
            h.x = w ? h.y : h.x; h.y = w ? h.z : h.y; h.z = w ? h.w : h.z; h.w = w ? 0u : h.w;
            if (g == s) key = m;
        }
        rsrc += (key & 255u) * 144;
#pragma unroll
        for (int j = 0; j < 9; j++) v[j] = ld_poll(rsrc + 4 * j);
        slow = __any_sync(0xffffffffu, key & 256u);
        STAMP(18);
        if (__any_sync(0xffffffffu, h.x == 0u)) {
            uint4 r[4];
            it = 0;
            while (true) {
#pragma unroll
                for (int i = 0; i < 4; i++) r[i] = ld_poll(ksrc + 256 * i + 1);
                if (__all_sync(0xffffffffu, all_nz(r[0]) && all_nz(r[1]) && all_nz(r[2]) && all_nz(r[3]))) break;
                if (++it > SPIN_LIMIT) TRAP();
            }
            uint32_t m = 1u << 30;
#pragma unroll 1
            for (int s = 0; s < 8; s++) {
                uint32_t x = 0;
#pragma unroll
                for (int i = 0; i < 4; i++) {
                    x = max(max(max(x, q[i].x - m), max(q[i].y - m, q[i].z - m)), q[i].w - m);
                    x = max(max(max(x, r[i].x - m), max(r[i].y - m, r[i].z - m)), r[i].w - m);
                }
                m += __reduce_max_sync(0xffffffffu, x);
                if (g == s) key = m;
            }
            slow = true;
        }
        sts32(s_key + g * 4, key);
        if (!slow) {
            it = 0;
            while (true) {
                const uint32_t mn = min(min(min(min(v[0].x, v[1].x), v[2].x), min(min(v[3].x, v[4].x), v[5].x)), min(min(v[6].x, v[7].x), v[8].x));
                if (__all_sync(0xffffffffu, mn)) break;
                if (++it > SPIN_LIMIT) TRAP();
#pragma unroll
                for (int j = 0; j < 9; j++) v[j] = ld_poll(rsrc + 4 * j);
            }
#pragma unroll
            for (int j = 0; j < 9; j++) sts128(sb + SM_XS + g * XS_PITCH + t * 16 + j * 64, v[j].x, v[j].y, v[j].z, v[j].w);
        }
        }
        if (bar_or(0, NWRK, slow)) late_rows([](bool, int) {});
        STAMP(19);
        const int fl = 16 * (b & 1) + ((tid >> 2) & 15), fc = 16 * (b >> 1) + (fl >> 2) + 8 * ((tid >> 1) & 1), fsl = 2 * (fl & 3) + (tid & 1);
        const uint32_t kk = lds32(s_key + fsl * 4);
        const uint32_t* fsrc = p.s->rows + ((kk & 256u) ? 2 * NCTA + fsl : (kk & 255u)) * DM + (fc >> 1);
        uint32_t hw = 1u, uw = 1u;
        if (b < 72) { uw = ld_poll32(fsrc); hw = ld_poll32(fsrc + 288); }
        {
            const uint32_t row = 8 * (warp & 1) + (lane >> 2);
            const uint2 k = lds64(s_key + (lane & 3) * 8);
            const uint32_t id = (row << 9) | 2 * b, hit = __ballot_sync(0xffffffffu, (k.x & 0x1efeu) == id || (k.y & 0x1efeu) == id);
            if ((lane & 3) == 0 && !((hit >> lane) & 15u)) bulk_s2g(p.out + (size_t)(32 * P + 2 * odd + TOKEN_OF(row & 7) + (row & 8)) * DM, sb + SM_OUT + row * OUT_PITCH, DM * 2);
            __syncwarp();
        }
        if (b < 72) {
            it = 0;
            while (!hw || !uw) { uw = ld_poll32(fsrc); hw = ld_poll32(fsrc + 288); if (++it > SPIN_LIMIT) TRAP(); }
            const int row = (kk >> 9) & 15, ftok = 8 * (kk & 252u) + (kk & 2u) + TOKEN_OF(row & 7) + (row & 8);
            const unsigned k16 = (kk >> 13) & 0xffffu;
            const unsigned bits = (k16 & 0x8000u) ? (k16 & 0x7fffu) : (~k16 & 0xffffu);
            const float rs = __uint_as_float(pin(__float_as_uint(rbf(__fdividef(1.0f, 1.0f + __expf(-__uint_as_float(bits << 16))))), zr));
            bf16* const op = pin(p.out + (size_t)ftok * DM + fc, zr);
            const float uv = (fc & 1) ? bf_hi(uw) : bf_lo(uw), hv = (fc & 1) ? bf_hi(hw) : bf_lo(hw);
            bar_sync(14, 576);
            float v0 = 0.f, v1 = 0.f, v2 = 0.f, v3 = 0.f;
            const uint32_t a = sb + SM_EX + (tid - 576) * 4;
#pragma unroll
            for (int i = 0; i < 16; i += 4) { v0 += ldsf(a + i * 256); v1 += ldsf(a + i * 256 + 256); v2 += ldsf(a + i * 256 + 512); v3 += ldsf(a + i * 256 + 768); }
            const float y3 = rbf(rbf((v0 + v1) + (v2 + v3)) * rs);
            asm volatile("st.global.u16 [%0], %1;\n" ::"l"(op), "h"((unsigned short)pack_bf16(hv + rbf(uv + y3), 0.f)) : "memory");
        }
        asm volatile("cp.async.bulk.wait_group.read 0;\n" ::: "memory");
        if (b == 0 && tid >= 632) *reinterpret_cast<volatile unsigned*>(p.s->hint + (tid & 7) * 32 + 1) = lds32(s_cnt + 4) + 1u;
    } else {
        uint32_t H[2][4], U2[2][4], WA[9][4], WD[18];
        const int fkh = warp >= 9, fmt = warp - 9 * fkh;
        auto load_wa = [&](auto k0, auto k1) {
            if (k0.value >= k1.value) return;
            if (k0.value == 0) mbar_wait(bar_w);
            const int mi = lane >> 3, rr = lane & 7;
            const uint32_t aad = sb + SM_WG + (mi & 1) * SM_WU + (fkh * 144 + rr + 8 * (mi >> 1)) * W_PITCH + fmt * 16;
#pragma unroll
            for (int k = k0.value; k < k1.value; k++) ldsm_x4_t(WA[k][0], WA[k][1], WA[k][2], WA[k][3], aad + k * 16 * W_PITCH);
        };
        auto load_wd = [&]() {
            mbar_wait(bar_d);
            const int mi = lane >> 3, rr = lane & 7;
            const int c8 = 2 * warp + (mi & 1), bx = c8 / 9;
            const uint32_t base = sb + SM_WD + bx * 10368 + (c8 - 9 * bx) * 16 + rr * W_PITCH;
#pragma unroll
            for (int k = 0; k < 4; k++) ldsm_x4_t(WD[4 * k], WD[4 * k + 1], WD[4 * k + 2], WD[4 * k + 3], base + (k * 16 + 8 * (mi >> 1)) * W_PITCH);
            ldsm_x2_t(WD[16], WD[17], base + 64 * W_PITCH);
        };
        auto publish = [&](bool hi, int slot) {
            uint4* rowp = reinterpret_cast<uint4*>(p.s->rows) + slot * 144 + warp * 4 + t;
            stg128(rowp, nzw(hi ? U2[1][0] : U2[0][0]), nzw(hi ? U2[1][1] : U2[0][1]), nzw(hi ? U2[1][2] : U2[0][2]), nzw(hi ? U2[1][3] : U2[0][3]));
            stg128(rowp + 72, nzw(hi ? H[1][0] : H[0][0]), nzw(hi ? H[1][1] : H[0][1]), nzw(hi ? H[1][2] : H[0][2]), nzw(hi ? H[1][3] : H[0][3]));
        };
        uint4 wr = make_uint4(0u, 0u, 0u, 0u);
        {
            const unsigned char* ys = reinterpret_cast<const unsigned char*>(p.s->y) + ((size_t)P * DM + 32 * warp + 8 * (g >> 1) + (g & 1)) * 64 + odd * 32 + t * 8;
            uint2 yv[4];
#pragma unroll
            for (int k = 0; k < 4; k++) yv[k] = ld_poll64(ys + k * 128);
            if (g == 0) wr = ldg128(p.wr + 32 * warp + 8 * t);
            const uint4 x0 = lds128(sb + SM_XT + warp * 1024 + lane * 16), x1 = lds128(sb + SM_XT + warp * 1024 + 512 + lane * 16);
            load_wa(IC<0>(), IC<WA0>());
            int it = 0;
            while (!__all_sync(0xffffffffu, yv[0].x && yv[1].x && yv[2].x && yv[3].x)) {
#pragma unroll
                for (int k = 0; k < 4; k++) if (!YSEL || !yv[k].x) yv[k] = ld_poll64(ys + k * 128);
                if (++it > SPIN_LIMIT) TRAP();
            }
            STAMP(12);
            const uint32_t Z[2][4] = {{x0.x, x0.y, x0.z, x0.w}, {x1.x, x1.y, x1.z, x1.w}};
#pragma unroll
            for (int k = 0; k < 4; k++) {
                H[0][k] = hadd2_bf(Z[0][k], movm(yv[k].x));
                H[1][k] = hadd2_bf(Z[1][k], movm(yv[k].y));
            }
            ln_partial<4>(H, sb + SM_LNP, warp, g, t);
        }
        bar_arrive(8, 640);
        load_wa(IC<WA0>(), IC<WA1>());
        STAMP(13);
        bar_sync(13, 608);
        STAMP(14);
#pragma unroll
        for (int hf = 0; hf < 2; hf++) {
            const uint2 st = lds64(s_stat + (g + 8 * hf) * 8);
#pragma unroll
            for (int k = 0; k < 4; k++) U2[hf][k] = ln_apply(H[hf][k], st);
        }
        {
            float cs[4] = {0.f, 0.f, 0.f, 0.f};
            mma_bf16(cs, U2[0][0], U2[1][0], U2[0][1], U2[1][1], wr.x, wr.y);
            mma_bf16(cs, U2[0][2], U2[1][2], U2[0][3], U2[1][3], wr.z, wr.w);
            if (t == 0) { stsf(sb + SM_LNP + ((32 + g) * 20 + warp) * 4, cs[0]); stsf(sb + SM_LNP + ((40 + g) * 20 + warp) * 4, cs[2]); }
            bar_arrive(10, 608);
        }
        load_wa(IC<WA1>(), IC<WA2>());
        bar_sync(11, 640);
        {
            const uint32_t rk[2] = {lds32(s_wm + g * 4), lds32(s_wm + 32 + g * 4)};
            uint32_t lo = min(rk[0], rk[1]), hi = max(rk[0], rk[1]);
#pragma unroll 1
            while (lo < 2) { publish(lo == rk[1], 2 * b + lo); lo = hi; hi = 16; }
        }
        load_wa(IC<WA2>(), IC<WA3>());
        bar_sync(9, 608);
        load_wa(IC<WA3>(), IC<9>());
#pragma unroll
        for (int hf = 0; hf < 2; hf++)
            sts128(sb + SM_OUT + (g + 8 * hf) * OUT_PITCH + warp * 64 + t * 16,
                   hadd2_bf(H[hf][0], U2[hf][0]), hadd2_bf(H[hf][1], U2[hf][1]), hadd2_bf(H[hf][2], U2[hf][2]), hadd2_bf(H[hf][3], U2[hf][3]));
        fence_async();
        WPOINT(18, warp - 17);
        if (WDAT == 0) load_wd();
        const uint32_t bad = pin(sb + SM_XS + (lane & 7) * XS_PITCH + (fkh * 144 + 8 * (lane >> 3)) * 2, zr), ex = pin(sb + SM_EX + (18 * odd + warp) * 512 + lane * 16, zr);
        uint32_t* const pp = pin(p.s->part + ((size_t)(2 * (18 * odd + warp) + (lane >> 4)) * 64 + P) * 64 + (lane & 15) * 4, zr);
        STAMP(15);
        if (bar_or(0, NWRK, false)) late_rows(publish);
        STAMP(19);
        {
            float c4[3][4];
#pragma unroll
            for (int i = 0; i < 3; i++)
#pragma unroll
                for (int j = 0; j < 4; j++) c4[i][j] = 0.f;
#pragma unroll
            for (int k = 0; k < 10; k += 2) {
                uint32_t b0, b1, b2, b3;
                ldsm_x4(b0, b1, b2, b3, bad + k * 32);
                mma_bf16(c4[k % 3], WA[k][0], WA[k][1], WA[k][2], WA[k][3], b0, b1);
                if (k < 8) mma_bf16(c4[(k + 1) % 3], WA[k + 1][0], WA[k + 1][1], WA[k + 1][2], WA[k + 1][3], b2, b3);
            }
#pragma unroll
            for (int j = 0; j < 4; j++) c4[0][j] += c4[1][j] + c4[2][j];
            asm volatile("st.async.shared::cluster.mbarrier::complete_tx::bytes.v4.b32 [%0], {%1,%2,%3,%4}, [%5];\n"
                         ::"r"(ex ^ 0x1000000u), "r"(__float_as_uint(c4[0][0])), "r"(__float_as_uint(c4[0][1])), "r"(__float_as_uint(c4[0][2])), "r"(__float_as_uint(c4[0][3])), "r"(bar_g ^ 0x1000000u) : "memory");
            sts128f(ex, c4[0]);
            if (warp >= 9) bar_arrive(6, 576);
            if (WDAT == 1) load_wd();
        }
        STAMP(20);
        if (warp < 9) {
            bar_sync(6, 576);
            mbar_wait(bar_g);
            const uint32_t ex = sb + SM_EX + tid * 16;
            const uint4 u = lds128(ex), v = lds128(ex + 4608), w = lds128(ex + 9216), x = lds128(ex + 13824);
#define S4(f) rbf((__uint_as_float(u.f) + __uint_as_float(v.f)) + (__uint_as_float(w.f) + __uint_as_float(x.f)))
            const float G0 = S4(x), G1 = S4(y), U0 = S4(z), U1 = S4(w);
#undef S4
            sts32(sb + SM_GU + tid * 4, pack_bf16(rbf(__fdividef(G0, 1.0f + __expf(-G0))) * U0, rbf(__fdividef(G1, 1.0f + __expf(-G1))) * U1));
        }
        const uint4* src = pin(reinterpret_cast<const uint4*>(p.s->part) + (size_t)b * 1024 + tid, zr);
        bar_sync(7, 576);
        STAMP(21);
        {
            uint32_t gb[9];
            ldsm_x4_t(gb[0], gb[1], gb[2], gb[3], sb + SM_GU + lane * 16);
            ldsm_x4_t(gb[4], gb[5], gb[6], gb[7], sb + SM_GU + 512 + lane * 16);
            ldsm_x1_t(gb[8], sb + SM_GU + 1024 + (lane & 7) * 16);
            float c4[4] = {0.f, 0.f, 0.f, 0.f}, d4[4] = {0.f, 0.f, 0.f, 0.f};
            mma_bf16(c4, WD[0], WD[1], WD[2], WD[3], gb[0], gb[1]);
            mma_bf16(d4, WD[4], WD[5], WD[6], WD[7], gb[2], gb[3]);
            mma_bf16(c4, WD[8], WD[9], WD[10], WD[11], gb[4], gb[5]);
            mma_bf16(d4, WD[12], WD[13], WD[14], WD[15], gb[6], gb[7]);
            mma_bf16(c4, WD[16], WD[17], 0u, 0u, gb[8], 0u);
            stg128(pp, __float_as_uint(c4[0] + d4[0]) | 1u, __float_as_uint(c4[1] + d4[1]), __float_as_uint(c4[2] + d4[2]), __float_as_uint(c4[3] + d4[3]));
        }
        STAMP(22);
        if (b < 72 && warp < 16) {
            uint4 a, c;
            int it = 0;
            while (true) {
                a = ld_poll(src); c = ld_poll(src + 512);
                if (__all_sync(0xffffffffu, a.x && c.x)) break;
                if (++it > SPIN_LIMIT) TRAP();
            }
            STAMP(24);
            const float s0 = __uint_as_float(a.x) + __uint_as_float(c.x), s1 = __uint_as_float(a.y) + __uint_as_float(c.y);
            const float s2 = __uint_as_float(a.z) + __uint_as_float(c.z), s3 = __uint_as_float(a.w) + __uint_as_float(c.w);
            const bool up = lane & 16;
            const float r0 = __shfl_xor_sync(0xffffffffu, up ? s0 : s2, 16), r1 = __shfl_xor_sync(0xffffffffu, up ? s1 : s3, 16);
            sts64f(sb + SM_EX + warp * 256 + (lane & 15) * 16 + (up ? 8 : 0), (up ? s2 : s0) + r0, (up ? s3 : s1) + r1);
            bar_arrive(14, 576);
        }
    }
    STAMP(25);
    }
}

typedef CUresult (*PFN_tmEncode)(CUtensorMap*, CUtensorMapDataType, cuuint32_t, void*, const cuuint64_t*, const cuuint64_t*, const cuuint32_t*,
                                 const cuuint32_t*, CUtensorMapInterleave, CUtensorMapSwizzle, CUtensorMapL2promotion, CUtensorMapFloatOOBfill);

extern "C" void kernel_launch(void* const* d_in, const int* in_sizes, int n_in, void* d_out, int out_size) {
    Params p;
    p.x = (const bf16*)d_in[0];
    p.lar = (const bf16*)d_in[1];
    p.aim = (const bf16*)d_in[2];
    p.cre = (const bf16*)d_in[3];
    p.cim = (const bf16*)d_in[4];
    p.ldt = (const bf16*)d_in[5];
    p.dsk = (const bf16*)d_in[6];
    p.wr = (const bf16*)d_in[8];
    p.wpf = (const bf16*)d_in[PFW];
    p.out = (bf16*)d_out;
    static PFN_tmEncode enc = nullptr;
    static void* scratch = nullptr;
    if (!enc) {
        cudaFuncSetAttribute(fused_kernel, cudaFuncAttributeMaxDynamicSharedMemorySize, SMEM_TOTAL);
        void* fn = nullptr;
        cudaDriverEntryPointQueryResult qr;
        cudaGetDriverEntryPoint("cuTensorMapEncodeTiled", &fn, cudaEnableDefault, &qr);
        enc = (PFN_tmEncode)fn;
        cudaGetSymbolAddress(&scratch, g_scratch);
    }
    p.s = (Scratch*)scratch;
    CUtensorMap tm_g, tm_u, tm_d, tm_x, tm_y, tm_z;
    const cuuint64_t dims[2] = {FF, DM}, strides[1] = {FF * 2};
    const cuuint32_t box[2] = {72, 48}, es[2] = {1, 1};
    enc(&tm_g, CU_TENSOR_MAP_DATA_TYPE_BFLOAT16, 2, d_in[9], dims, strides, box, es, CU_TENSOR_MAP_INTERLEAVE_NONE, CU_TENSOR_MAP_SWIZZLE_NONE,
        CU_TENSOR_MAP_L2_PROMOTION_NONE, CU_TENSOR_MAP_FLOAT_OOB_FILL_NONE);
    enc(&tm_u, CU_TENSOR_MAP_DATA_TYPE_BFLOAT16, 2, d_in[10], dims, strides, box, es, CU_TENSOR_MAP_INTERLEAVE_NONE, CU_TENSOR_MAP_SWIZZLE_NONE,
        CU_TENSOR_MAP_L2_PROMOTION_NONE, CU_TENSOR_MAP_FLOAT_OOB_FILL_NONE);
    const cuuint64_t ddims[2] = {DM, FF}, dstrides[1] = {DM * 2};
    const cuuint32_t dbox[2] = {72, 72};
    enc(&tm_d, CU_TENSOR_MAP_DATA_TYPE_BFLOAT16, 2, d_in[11], ddims, dstrides, dbox, es, CU_TENSOR_MAP_INTERLEAVE_NONE, CU_TENSOR_MAP_SWIZZLE_NONE,
        CU_TENSOR_MAP_L2_PROMOTION_NONE, CU_TENSOR_MAP_FLOAT_OOB_FILL_NONE);
    const cuuint64_t xdims[3] = {DM, LSEQ / 16, 16}, xstrides[2] = {16 * DM * 2, DM * 2};
    const cuuint32_t xbox[3] = {8, LSEQ / 16, 8}, es3[3] = {1, 1, 1};
    enc(&tm_x, CU_TENSOR_MAP_DATA_TYPE_BFLOAT16, 3, d_in[0], xdims, xstrides, xbox, es3, CU_TENSOR_MAP_INTERLEAVE_NONE, CU_TENSOR_MAP_SWIZZLE_NONE,
        CU_TENSOR_MAP_L2_PROMOTION_NONE, CU_TENSOR_MAP_FLOAT_OOB_FILL_NONE);
    const cuuint64_t ydims[3] = {DM * 32, 16, 4}, ystrides[2] = {DM * 64, 16 * DM * 64};
    const cuuint32_t ybox[3] = {128, 16, 2}, zbox[3] = {32, 16, 2};
    enc(&tm_y, CU_TENSOR_MAP_DATA_TYPE_BFLOAT16, 3, p.s->y, ydims, ystrides, ybox, es3, CU_TENSOR_MAP_INTERLEAVE_NONE, CU_TENSOR_MAP_SWIZZLE_NONE,
        CU_TENSOR_MAP_L2_PROMOTION_NONE, CU_TENSOR_MAP_FLOAT_OOB_FILL_NONE);
    enc(&tm_z, CU_TENSOR_MAP_DATA_TYPE_BFLOAT16, 3, p.s->y, ydims, ystrides, zbox, es3, CU_TENSOR_MAP_INTERLEAVE_NONE, CU_TENSOR_MAP_SWIZZLE_NONE,
        CU_TENSOR_MAP_L2_PROMOTION_NONE, CU_TENSOR_MAP_FLOAT_OOB_FILL_NONE);
    fused_kernel<<<NCTA, NTHR, SMEM_TOTAL>>>(p, tm_g, tm_u, tm_d, tm_x, tm_y, tm_z);
}
```

```cpp
#include <cuda_runtime.h>
#include <cuda.h>
#include <cuda_fp16.h>
#include <cuda_bf16.h>
#include <stdint.h>

#define LSEQ 2048
#define DM 576
#define NST 128
#define FF 4608
#define NSEL 8
#define NCTA 128
#define NTHR 640
#define NWRK 640

typedef __nv_bfloat16 bf16;

#define SM_WG 0
#define SM_WU 41472
#define SM_WD 82944
#define W_PITCH 144
#define SM_XC 50176
#define SM_ZERO SM_WD
#define SM_TB (SM_WD + 9216)
#define SM_PL 124416
#define PL_B 10752
#define SM_XT (SM_TB + 20 * TBW)
#define SM_U (SM_XT + 18432)
#define UPAD 8
#define ULO_B ((UPAD + 128) * 16)
#define USLOT_B (2 * ULO_B)
#define SM_KW (SM_U + 5 * USLOT_B)
#define KW_B 3600
#define KW_T2 1152
#define KW_KH 656
#define KW_T3 2464
#define SM_MISC (SM_KW + 5 * KW_B)
#define SM_LNP (SM_MISC + 576)
#define SMEM_TOTAL (SM_LNP + 4096)
#define TBP 112
#define TBW (32 * TBP)
#define SM_OUT SM_PL
#define OUT_PITCH 1216
#define SM_XS (SM_PL + 19456)
#define XS_PITCH 592
#define SM_EX (SM_PL + 24320)
#define SM_GU (SM_PL + 42752)

struct __align__(128) Scratch {
    unsigned hint[8 * 32];
    unsigned flag[32];
    uint32_t sc[NCTA * 32];
    uint32_t st[LSEQ * 2];
    uint32_t uT[64 * (LSEQ / 2)];
    uint32_t y[NCTA * DM * 8];
    uint32_t part[72 * 64 * 32];
    uint32_t rows[(2 * NCTA + NSEL) * DM];
};
__device__ Scratch g_scratch;
#define STAMP(i)
#define DBG(i, v)

__device__ __forceinline__ float rbf(float x) {
    uint32_t r;
    asm("cvt.rn.bf16x2.f32 %0, %1, %2;\n" : "=r"(r) : "f"(x), "f"(0.f));
    return __uint_as_float(r & 0xffff0000u);
}
__device__ __forceinline__ uint32_t pack_bf16(float lo, float hi) {
    uint32_t r;
    asm("cvt.rn.bf16x2.f32 %0, %1, %2;\n" : "=r"(r) : "f"(hi), "f"(lo));
    return r;
}
__device__ __forceinline__ uint32_t pack_f16(float lo, float hi) {
    uint32_t r;
    asm("cvt.rn.f16x2.f32 %0, %1, %2;\n" : "=r"(r) : "f"(hi), "f"(lo));
    return r;
}
__device__ __forceinline__ uint32_t pack_f16_rz(float lo, float hi) {
    uint32_t r;
    asm("cvt.rz.f16x2.f32 %0, %1, %2;\n" : "=r"(r) : "f"(hi), "f"(lo));
    return r;
}
__device__ __forceinline__ float bf_lo(uint32_t w) { return __uint_as_float(w << 16); }
__device__ __forceinline__ float bf_hi(uint32_t w) { return __uint_as_float(w & 0xffff0000u); }
__device__ __forceinline__ uint32_t hadd2_bf(uint32_t a, uint32_t b) {
    __nv_bfloat162 r = __hadd2_rn(*reinterpret_cast<__nv_bfloat162*>(&a), *reinterpret_cast<__nv_bfloat162*>(&b));
    return *reinterpret_cast<uint32_t*>(&r);
}
__device__ __forceinline__ uint32_t hsub2_bf(uint32_t a, uint32_t b) {
    __nv_bfloat162 r = __hsub2_rn(*reinterpret_cast<__nv_bfloat162*>(&a), *reinterpret_cast<__nv_bfloat162*>(&b));
    return *reinterpret_cast<uint32_t*>(&r);
}
__device__ __forceinline__ uint32_t hmul2_bf(uint32_t a, uint32_t b) {
    __nv_bfloat162 r = __hmul2_rn(*reinterpret_cast<__nv_bfloat162*>(&a), *reinterpret_cast<__nv_bfloat162*>(&b));
    return *reinterpret_cast<uint32_t*>(&r);
}
__device__ __forceinline__ uint32_t hfma2_bf(uint32_t a, uint32_t b, uint32_t c) { uint32_t r; asm("fma.rn.bf16x2 %0, %1, %2, %3;\n" : "=r"(r) : "r"(a), "r"(b), "r"(c)); return r; }
__device__ __forceinline__ uint32_t hmul2(uint32_t a, uint32_t b) { uint32_t r; asm("mul.rn.f16x2 %0, %1, %2;\n" : "=r"(r) : "r"(a), "r"(b)); return r; }
__device__ __forceinline__ uint32_t hadd2(uint32_t a, uint32_t b) { uint32_t r; asm("add.rn.f16x2 %0, %1, %2;\n" : "=r"(r) : "r"(a), "r"(b)); return r; }
__device__ __forceinline__ uint32_t hfma2(uint32_t a, uint32_t b, uint32_t c) { uint32_t r; asm("fma.rn.f16x2 %0, %1, %2, %3;\n" : "=r"(r) : "r"(a), "r"(b), "r"(c)); return r; }
__device__ __forceinline__ uint32_t nzw(uint32_t w) { return w ? w : 0x8000u; }
__device__ __forceinline__ uint32_t nzf(float f) { const uint32_t w = __float_as_uint(f); return w ? w : 0x80000000u; }
__device__ __forceinline__ uint32_t smem_u32(const void* p) { return (uint32_t)__cvta_generic_to_shared(p); }
__device__ __forceinline__ uint32_t lds32(uint32_t addr) {
    uint32_t v;
    asm volatile("ld.shared.u32 %0, [%1];\n" : "=r"(v) : "r"(addr) : "memory");
    return v;
}
__device__ __forceinline__ uint32_t lds16(uint32_t addr) {
    unsigned short v;
    asm volatile("ld.shared.u16 %0, [%1];\n" : "=h"(v) : "r"(addr) : "memory");
    return v;
}
__device__ __forceinline__ uint2 lds64(uint32_t addr) {
    uint2 v;
    asm volatile("ld.shared.v2.u32 {%0,%1}, [%2];\n" : "=r"(v.x), "=r"(v.y) : "r"(addr) : "memory");
    return v;
}
__device__ __forceinline__ uint4 lds128(uint32_t addr) {
    uint4 v;
    asm volatile("ld.shared.v4.u32 {%0,%1,%2,%3}, [%4];\n" : "=r"(v.x), "=r"(v.y), "=r"(v.z), "=r"(v.w) : "r"(addr) : "memory");
    return v;
}
__device__ __forceinline__ float ldsf(uint32_t addr) { return __uint_as_float(lds32(addr)); }
__device__ __forceinline__ void sts32(uint32_t addr, uint32_t v) { asm volatile("st.shared.u32 [%0], %1;\n" ::"r"(addr), "r"(v) : "memory"); }
__device__ __forceinline__ void stsf(uint32_t addr, float v) { sts32(addr, __float_as_uint(v)); }
__device__ __forceinline__ void sts64(uint32_t addr, uint32_t a, uint32_t b) { asm volatile("st.shared.v2.u32 [%0], {%1,%2};\n" ::"r"(addr), "r"(a), "r"(b) : "memory"); }
__device__ __forceinline__ void sts64f(uint32_t addr, float a, float b) { sts64(addr, __float_as_uint(a), __float_as_uint(b)); }
__device__ __forceinline__ void sts128(uint32_t addr, uint32_t a, uint32_t b, uint32_t c, uint32_t d) {
    asm volatile("st.shared.v4.u32 [%0], {%1,%2,%3,%4};\n" ::"r"(addr), "r"(a), "r"(b), "r"(c), "r"(d) : "memory");
}
__device__ __forceinline__ void sts128f(uint32_t addr, const float (&v)[4]) {
    sts128(addr, __float_as_uint(v[0]), __float_as_uint(v[1]), __float_as_uint(v[2]), __float_as_uint(v[3]));
}
__device__ __forceinline__ void ldsm_x4(uint32_t& r0, uint32_t& r1, uint32_t& r2, uint32_t& r3, uint32_t addr) {
    asm volatile("ldmatrix.sync.aligned.m8n8.x4.shared.b16 {%0,%1,%2,%3}, [%4];\n"
                 : "=r"(r0), "=r"(r1), "=r"(r2), "=r"(r3) : "r"(addr) : "memory");
}
__device__ __forceinline__ void ldsm_x4_t(uint32_t& r0, uint32_t& r1, uint32_t& r2, uint32_t& r3, uint32_t addr) {
    asm volatile("ldmatrix.sync.aligned.m8n8.x4.trans.shared.b16 {%0,%1,%2,%3}, [%4];\n"
                 : "=r"(r0), "=r"(r1), "=r"(r2), "=r"(r3) : "r"(addr) : "memory");
}
__device__ __forceinline__ void ldsm_x2_t(uint32_t& r0, uint32_t& r1, uint32_t addr) {
    asm volatile("ldmatrix.sync.aligned.m8n8.x2.trans.shared.b16 {%0,%1}, [%2];\n" : "=r"(r0), "=r"(r1) : "r"(addr) : "memory");
}
__device__ __forceinline__ void ldsm_x1_t(uint32_t& r0, uint32_t addr) {
    asm volatile("ldmatrix.sync.aligned.m8n8.x1.trans.shared.b16 {%0}, [%1];\n" : "=r"(r0) : "r"(addr) : "memory");
}
__device__ __forceinline__ uint32_t movm(uint32_t a) {
    uint32_t d;
    asm volatile("movmatrix.sync.aligned.m8n8.trans.b16 %0, %1;\n" : "=r"(d) : "r"(a));
    return d;
}
__device__ __forceinline__ void mma_f16(float (&c)[4], uint32_t a0, uint32_t a1, uint32_t a2, uint32_t a3, uint32_t b0, uint32_t b1) {
    asm volatile(
        "mma.sync.aligned.m16n8k16.row.col.f32.f16.f16.f32 {%0,%1,%2,%3}, {%4,%5,%6,%7}, {%8,%9}, {%0,%1,%2,%3};\n"
        : "+f"(c[0]), "+f"(c[1]), "+f"(c[2]), "+f"(c[3])
        : "r"(a0), "r"(a1), "r"(a2), "r"(a3), "r"(b0), "r"(b1));
}
__device__ __forceinline__ void mma_bf16(float (&c)[4], uint32_t a0, uint32_t a1, uint32_t a2, uint32_t a3, uint32_t b0, uint32_t b1) {
    asm volatile(
        "mma.sync.aligned.m16n8k16.row.col.f32.bf16.bf16.f32 {%0,%1,%2,%3}, {%4,%5,%6,%7}, {%8,%9}, {%0,%1,%2,%3};\n"
        : "+f"(c[0]), "+f"(c[1]), "+f"(c[2]), "+f"(c[3])
        : "r"(a0), "r"(a1), "r"(a2), "r"(a3), "r"(b0), "r"(b1));
}
__device__ __forceinline__ void bar_sync(int id, int n) { asm volatile("bar.sync %0, %1;\n" ::"r"(id), "r"(n) : "memory"); }
__device__ __forceinline__ void bar_arrive(int id, int n) { asm volatile("bar.arrive %0, %1;\n" ::"r"(id), "r"(n) : "memory"); }
__device__ __forceinline__ bool bar_or(int id, int n, bool v) {
    uint32_t r;
    asm volatile("{\n.reg .pred p, q;\nsetp.ne.u32 p, %3, 0;\nbar.red.or.pred q, %1, %2, p;\nselp.u32 %0, 1, 0, q;\n}\n" : "=r"(r) : "r"(id), "r"(n), "r"((uint32_t)v) : "memory");
    return r;
}
__device__ __forceinline__ uint4 ld_poll(const void* p) {
    uint4 v;
    asm volatile("ld.relaxed.gpu.global.v4.u32 {%0,%1,%2,%3}, [%4];\n" : "=r"(v.x), "=r"(v.y), "=r"(v.z), "=r"(v.w) : "l"(p) : "memory");
    return v;
}
template <class T> __device__ __forceinline__ T* pin(T* p, uint32_t z) {
    uint32_t lo, hi;
    asm volatile("mov.b64 {%0, %1}, %2;\n" : "=r"(lo), "=r"(hi) : "l"(p));
    asm volatile("xor.b32 %0, %0, %1;\n" : "+r"(lo) : "r"(z));
    asm volatile("xor.b32 %0, %0, %1;\n" : "+r"(hi) : "r"(z));
    asm volatile("mov.b64 %0, {%1, %2};\n" : "=l"(p) : "r"(lo), "r"(hi));
    return p;
}
__device__ __forceinline__ uint32_t pin(uint32_t a, uint32_t z) { asm volatile("xor.b32 %0, %0, %1;\n" : "+r"(a) : "r"(z)); return a; }
__device__ __forceinline__ uint2 ld_poll64(const void* p) {
    uint2 v;
    asm volatile("ld.relaxed.gpu.global.v2.u32 {%0,%1}, [%2];\n" : "=r"(v.x), "=r"(v.y) : "l"(p) : "memory");
    return v;
}
__device__ __forceinline__ uint32_t ld_poll32(const void* p) {
    uint32_t v;
    asm volatile("ld.relaxed.gpu.global.u32 %0, [%1];\n" : "=r"(v) : "l"(p) : "memory");
    return v;
}
__device__ __forceinline__ uint4 ldg128(const void* p) {
    uint4 v;
    asm volatile("ld.global.nc.v4.u32 {%0,%1,%2,%3}, [%4];\n" : "=r"(v.x), "=r"(v.y), "=r"(v.z), "=r"(v.w) : "l"(p));
    return v;
}
__device__ __forceinline__ uint2 ldg64(const void* p) {
    uint2 v;
    asm volatile("ld.global.nc.v2.u32 {%0,%1}, [%2];\n" : "=r"(v.x), "=r"(v.y) : "l"(p));
    return v;
}
__device__ __forceinline__ uint32_t ldg16(const void* p) {
    uint32_t v;
    asm volatile("ld.global.nc.u16 %0, [%1];\n" : "=r"(v) : "l"(p));
    return v;
}
__device__ __forceinline__ void stg128(void* p, uint32_t a, uint32_t b, uint32_t c, uint32_t d) {
    asm volatile("st.global.v4.u32 [%0], {%1,%2,%3,%4};\n" ::"l"(p), "r"(a), "r"(b), "r"(c), "r"(d) : "memory");
}
__device__ __forceinline__ void stg64(void* p, uint32_t a, uint32_t b) { asm volatile("st.global.v2.u32 [%0], {%1,%2};\n" ::"l"(p), "r"(a), "r"(b) : "memory"); }
__device__ __forceinline__ void stg32(void* p, uint32_t a) { asm volatile("st.global.u32 [%0], %1;\n" ::"l"(p), "r"(a) : "memory"); }
__device__ __forceinline__ bool all_nz(const uint4& v) { return v.x && v.y && v.z && v.w; }
#define SPIN_LIMIT (1 << 21)
#define TRAP() __trap()
__device__ __forceinline__ void hint_arrive(unsigned* g_hint, int idx, int sub) {
    asm volatile("red.relaxed.gpu.global.add.u32 [%0], 1;\n" ::"l"(&g_hint[sub * 32 + idx]) : "memory");
}
__device__ __forceinline__ void hint_wait(const unsigned* g_hint, int idx, unsigned target) {
    unsigned l;
    asm volatile("mov.u32 %0, %%laneid;" : "=r"(l));
    const unsigned* c = &g_hint[(l & 7) * 32 + idx];
    int it = 0;
    while (__any_sync(0xffffffffu, (int)(ld_poll32(c) - target) < 0)) { if (++it > SPIN_LIMIT) TRAP(); }
}
__device__ __forceinline__ void mbar_init(uint32_t bar, uint32_t cnt) { asm volatile("mbarrier.init.shared::cta.b64 [%0], %1;\n" ::"r"(bar), "r"(cnt) : "memory"); }
__device__ __forceinline__ void mbar_expect(uint32_t bar, uint32_t bytes) {
    asm volatile("mbarrier.arrive.expect_tx.shared::cta.b64 _, [%0], %1;\n" ::"r"(bar), "r"(bytes) : "memory");
}
__device__ __forceinline__ void mbar_arrive(uint32_t bar) { asm volatile("mbarrier.arrive.shared::cta.b64 _, [%0];\n" ::"r"(bar) : "memory"); }
__device__ __forceinline__ void mbar_wait_cluster(uint32_t bar) {
    asm volatile(
        "{\n.reg .pred p;\n"
        "W_%=:\n"
        "mbarrier.try_wait.parity.acquire.cluster.shared::cta.b64 p, [%0], 0;\n"
        "@!p bra W_%=;\n}\n" ::"r"(bar) : "memory");
}
__device__ __forceinline__ void mbar_wait(uint32_t bar) {
    asm volatile(
        "{\n.reg .pred p;\n"
        "W_%=:\n"
        "mbarrier.try_wait.parity.shared::cta.b64 p, [%0], 0;\n"
        "@!p bra W_%=;\n}\n" ::"r"(bar) : "memory");
}
__device__ __forceinline__ bool mbar_test(uint32_t bar) {
    uint32_t r;
    asm volatile("{\n.reg .pred p;\nmbarrier.test_wait.parity.shared::cta.b64 p, [%1], 0;\nselp.u32 %0, 1, 0, p;\n}\n" : "=r"(r) : "r"(bar) : "memory");
    return __any_sync(0xffffffffu, r);
}
__device__ __forceinline__ void bulk_g2s(uint32_t dst, const void* src, uint32_t bytes, uint32_t bar) {
    asm volatile("cp.async.bulk.shared::cluster.global.mbarrier::complete_tx::bytes [%0], [%1], %2, [%3];\n" ::"r"(dst), "l"(src), "r"(bytes), "r"(bar) : "memory");
}
__device__ __forceinline__ void bulk_s2g(void* dst, uint32_t src, uint32_t bytes) {
    asm volatile("cp.async.bulk.global.shared::cta.bulk_group [%0], [%1], %2;\ncp.async.bulk.commit_group;\n" ::"l"(dst), "r"(src), "r"(bytes) : "memory");
}
__device__ __forceinline__ void tma_2d(uint32_t dst, const CUtensorMap* tm, int c0, int c1, uint32_t bar) {
    asm volatile("cp.async.bulk.tensor.2d.shared::cluster.global.mbarrier::complete_tx::bytes [%0], [%1, {%3, %4}], [%2];\n"
                 ::"r"(dst), "l"(tm), "r"(bar), "r"(c0), "r"(c1) : "memory");
}
__device__ __forceinline__ void tma_3d(uint32_t dst, const CUtensorMap* tm, int c0, int c1, int c2, uint32_t bar) {
    asm volatile("cp.async.bulk.tensor.3d.shared::cluster.global.mbarrier::complete_tx::bytes [%0], [%1, {%3, %4, %5}], [%2];\n"
                 ::"r"(dst), "l"(tm), "r"(bar), "r"(c0), "r"(c1), "r"(c2) : "memory");
}
__device__ __forceinline__ void tma_3d_mc(uint32_t dst, const CUtensorMap* tm, int c0, int c1, int c2, uint32_t bar) {
    asm volatile("cp.async.bulk.tensor.3d.shared::cluster.global.mbarrier::complete_tx::bytes.multicast::cluster [%0], [%1, {%3, %4, %5}], [%2], %6;\n"
                 ::"r"(dst), "l"(tm), "r"(bar), "r"(c0), "r"(c1), "r"(c2), "h"((unsigned short)3) : "memory");
}
__device__ __forceinline__ void tma_st_3d(const CUtensorMap* tm, uint32_t src, int c0, int c1, int c2) {
    asm volatile("cp.async.bulk.tensor.3d.global.shared::cta.bulk_group [%0, {%2, %3, %4}], [%1];\ncp.async.bulk.commit_group;\n"
                 ::"l"(tm), "r"(src), "r"(c0), "r"(c1), "r"(c2) : "memory");
}
__device__ __forceinline__ void l2_prefetch(const void* src, uint32_t bytes) {
    asm volatile("cp.async.bulk.prefetch.L2.global [%0], %1;\n" ::"l"(src), "r"(bytes) : "memory");
}
__device__ __forceinline__ bool elect_one() {
    uint32_t r;
    asm volatile("{\n.reg .pred p;\nelect.sync _|p, 0xffffffff;\nselp.u32 %0, 1, 0, p;\n}\n" : "=r"(r));
    return r;
}
__device__ __forceinline__ void fence_async() { asm volatile("fence.proxy.async.shared::cta;\n" ::: "memory"); }

__device__ __forceinline__ float2 cmul(float2 a, float2 b) {
    return make_float2(fmaf(a.x, b.x, -a.y * b.y), fmaf(a.x, b.y, a.y * b.x));
}
__device__ __forceinline__ float2 csq(float2 a) {
    float p = a.x * a.y;
    return make_float2(fmaf(a.x, a.x, -a.y * a.y), p + p);
}
__device__ __forceinline__ float2 cexp_e(float lr2, float rh, float rl, float e) {
    float m;
    asm("ex2.approx.ftz.f32 %0, %1;\n" : "=f"(m) : "f"(lr2 * e));
    const float a = rh * e;
    const float r = fmaf(rl, e, a - rintf(a)) * 6.283185307179586f;
    return make_float2(m * __cosf(r), m * __sinf(r));
}
__device__ __forceinline__ float rcp_approx(float x) { float r; asm("rcp.approx.ftz.f32 %0, %1;\n" : "=f"(r) : "f"(x)); return r; }
__device__ __forceinline__ float sqrt_approx(float x) { float r; asm("sqrt.approx.ftz.f32 %0, %1;\n" : "=f"(r) : "f"(x)); return r; }

__device__ __forceinline__ void wg_fence() { asm volatile("wgmma.fence.sync.aligned;\n" ::: "memory"); }
__device__ __forceinline__ void wg_commit() { asm volatile("wgmma.commit_group.sync.aligned;\n" ::: "memory"); }
__device__ __forceinline__ void wg_wait0() { asm volatile("wgmma.wait_group.sync.aligned 0;\n" ::: "memory"); }
template <int T0, int NT> __device__ __forceinline__ void wg_h(uint32_t (&acc)[32], const uint32_t (&a)[4], uint64_t desc);
template <> __device__ __forceinline__ void wg_h<0, 16>(uint32_t (&acc)[32], const uint32_t (&a)[4], uint64_t desc) {
    asm volatile("wgmma.mma_async.sync.aligned.m64n128k16.f16.f16.f16 {%0,%1,%2,%3,%4,%5,%6,%7,%8,%9,%10,%11,%12,%13,%14,%15,%16,%17,%18,%19,%20,%21,%22,%23,%24,%25,%26,%27,%28,%29,%30,%31}, {%32,%33,%34,%35}, %36, 1, 1, 1, 0;\n"
                 : "+r"(acc[0]), "+r"(acc[1]), "+r"(acc[2]), "+r"(acc[3]), "+r"(acc[4]), "+r"(acc[5]), "+r"(acc[6]), "+r"(acc[7]), "+r"(acc[8]), "+r"(acc[9]), "+r"(acc[10]), "+r"(acc[11]), "+r"(acc[12]), "+r"(acc[13]), "+r"(acc[14]), "+r"(acc[15]), "+r"(acc[16]), "+r"(acc[17]), "+r"(acc[18]), "+r"(acc[19]), "+r"(acc[20]), "+r"(acc[21]), "+r"(acc[22]), "+r"(acc[23]), "+r"(acc[24]), "+r"(acc[25]), "+r"(acc[26]), "+r"(acc[27]), "+r"(acc[28]), "+r"(acc[29]), "+r"(acc[30]), "+r"(acc[31])
                 : "r"(a[0]), "r"(a[1]), "r"(a[2]), "r"(a[3]), "l"(desc));
}
template <> __device__ __forceinline__ void wg_h<4, 4>(uint32_t (&acc)[32], const uint32_t (&a)[4], uint64_t desc) {
    asm volatile("wgmma.mma_async.sync.aligned.m64n32k16.f16.f16.f16 {%0,%1,%2,%3,%4,%5,%6,%7}, {%8,%9,%10,%11}, %12, 1, 1, 1, 0;\n"
                 : "+r"(acc[8]), "+r"(acc[9]), "+r"(acc[10]), "+r"(acc[11]), "+r"(acc[12]), "+r"(acc[13]), "+r"(acc[14]), "+r"(acc[15])
                 : "r"(a[0]), "r"(a[1]), "r"(a[2]), "r"(a[3]), "l"(desc));
}
template <> __device__ __forceinline__ void wg_h<8, 4>(uint32_t (&acc)[32], const uint32_t (&a)[4], uint64_t desc) {
    asm volatile("wgmma.mma_async.sync.aligned.m64n32k16.f16.f16.f16 {%0,%1,%2,%3,%4,%5,%6,%7}, {%8,%9,%10,%11}, %12, 1, 1, 1, 0;\n"
                 : "+r"(acc[16]), "+r"(acc[17]), "+r"(acc[18]), "+r"(acc[19]), "+r"(acc[20]), "+r"(acc[21]), "+r"(acc[22]), "+r"(acc[23])
                 : "r"(a[0]), "r"(a[1]), "r"(a[2]), "r"(a[3]), "l"(desc));
}
template <> __device__ __forceinline__ void wg_h<12, 4>(uint32_t (&acc)[32], const uint32_t (&a)[4], uint64_t desc) {
    asm volatile("wgmma.mma_async.sync.aligned.m64n32k16.f16.f16.f16 {%0,%1,%2,%3,%4,%5,%6,%7}, {%8,%9,%10,%11}, %12, 1, 1, 1, 0;\n"
                 : "+r"(acc[24]), "+r"(acc[25]), "+r"(acc[26]), "+r"(acc[27]), "+r"(acc[28]), "+r"(acc[29]), "+r"(acc[30]), "+r"(acc[31])
                 : "r"(a[0]), "r"(a[1]), "r"(a[2]), "r"(a[3]), "l"(desc));
}
template <> __device__ __forceinline__ void wg_h<0, 8>(uint32_t (&acc)[32], const uint32_t (&a)[4], uint64_t desc) {
    asm volatile("wgmma.mma_async.sync.aligned.m64n64k16.f16.f16.f16 {%0,%1,%2,%3,%4,%5,%6,%7,%8,%9,%10,%11,%12,%13,%14,%15}, {%16,%17,%18,%19}, %20, 1, 1, 1, 0;\n"
                 : "+r"(acc[0]), "+r"(acc[1]), "+r"(acc[2]), "+r"(acc[3]), "+r"(acc[4]), "+r"(acc[5]), "+r"(acc[6]), "+r"(acc[7]), "+r"(acc[8]), "+r"(acc[9]), "+r"(acc[10]), "+r"(acc[11]), "+r"(acc[12]), "+r"(acc[13]), "+r"(acc[14]), "+r"(acc[15])
                 : "r"(a[0]), "r"(a[1]), "r"(a[2]), "r"(a[3]), "l"(desc));
}
template <> __device__ __forceinline__ void wg_h<4, 12>(uint32_t (&acc)[32], const uint32_t (&a)[4], uint64_t desc) {
    asm volatile("wgmma.mma_async.sync.aligned.m64n96k16.f16.f16.f16 {%0,%1,%2,%3,%4,%5,%6,%7,%8,%9,%10,%11,%12,%13,%14,%15,%16,%17,%18,%19,%20,%21,%22,%23}, {%24,%25,%26,%27}, %28, 1, 1, 1, 0;\n"
                 : "+r"(acc[8]), "+r"(acc[9]), "+r"(acc[10]), "+r"(acc[11]), "+r"(acc[12]), "+r"(acc[13]), "+r"(acc[14]), "+r"(acc[15]), "+r"(acc[16]), "+r"(acc[17]), "+r"(acc[18]), "+r"(acc[19]), "+r"(acc[20]), "+r"(acc[21]), "+r"(acc[22]), "+r"(acc[23]), "+r"(acc[24]), "+r"(acc[25]), "+r"(acc[26]), "+r"(acc[27]), "+r"(acc[28]), "+r"(acc[29]), "+r"(acc[30]), "+r"(acc[31])
                 : "r"(a[0]), "r"(a[1]), "r"(a[2]), "r"(a[3]), "l"(desc));
}

#define DSM 1
#define WMAX 9
#define PBYTES 4608
#define HINTW 10
#define WAS 0x0005
#define WA0 (WAS >> 12)
#define WA1 ((WAS >> 8) & 15)
#define WA2 ((WAS >> 4) & 15)
#define WA3 (WAS & 15)
#define WDAT 1
#define PAUSE 2
#define PCNT (32 + ((PAUSE & 1) ? 288 : 0) + ((PAUSE & 6) ? 320 : 64))
#define LNAT 2
#define UW 8
#define FINAT 3
#define UAT 2
#define PFW 11
#define HK 9
#define TOKEN_OF(g) (16 * ((g) & 1) + ((g) >> 2) + 2 * ((g) & 2))
#define HI2(a, b) (pack_f16_rz(__uint_as_float(a), __uint_as_float(b)) & 0xfff8fff8u)
struct Params {
    const bf16 *x, *lar, *aim, *cre, *cim, *ldt, *dsk;
    Scratch* s;
    const bf16 *wr, *wpf;
    bf16* out;
};

template <int NK>
__device__ __forceinline__ void ln_partial(const uint32_t (&H)[2][NK], uint32_t lp, int warp, int g, int t) {
    float cs[4] = {0.f, 0.f, 0.f, 0.f}, cl[4] = {0.f, 0.f, 0.f, 0.f}, ch[4] = {0.f, 0.f, 0.f, 0.f};
#pragma unroll
    for (int k = 0; k < NK; k += 2) {
        uint32_t a0, a1, a2, a3;
        asm volatile("prmt.b32 %0, %4, %4, %8;\nprmt.b32 %1, %5, %5, %8;\nprmt.b32 %2, %6, %6, %8;\nprmt.b32 %3, %7, %7, %8;\n"
                     : "=r"(a0), "=r"(a1), "=r"(a2), "=r"(a3) : "r"(H[0][k]), "r"(H[1][k]), "r"(H[0][k + 1]), "r"(H[1][k + 1]), "r"(0x3210u + (warp >> 8)));
        mma_bf16(cl, a0, a1, a2, a3, H[0][k], H[0][k + 1]);
        mma_bf16(ch, a0, a1, a2, a3, H[1][k], H[1][k + 1]);
        mma_bf16(cs, a0, a1, a2, a3, 0x3f803f80u, 0x3f803f80u);
    }
    const uint32_t a = lp + (g * 20 + warp) * 4;
    if (t == 0) {
        stsf(a, cs[0]); stsf(a + 8 * 80, cs[2]);
    }
    if (t == (g >> 1)) { stsf(a + 16 * 80, (g & 1) ? cl[1] : cl[0]); stsf(a + 24 * 80, (g & 1) ? ch[3] : ch[2]); }
}
__device__ __forceinline__ float sum18(uint32_t a) {
    const uint4 p = lds128(a), q = lds128(a + 16), r = lds128(a + 32), s = lds128(a + 48);
    const uint2 u = lds64(a + 64);
#define F(x) __uint_as_float(x)
    return (((F(p.x) + F(p.y)) + (F(p.z) + F(p.w))) + ((F(q.x) + F(q.y)) + (F(q.z) + F(q.w)))) +
           (((F(r.x) + F(r.y)) + (F(r.z) + F(r.w))) + ((F(s.x) + F(s.y)) + (F(s.z) + F(s.w))) + (F(u.x) + F(u.y)));
#undef F
}
__device__ __forceinline__ float sum9(uint32_t a) {
    const uint4 p = lds128(a), q = lds128(a + 16);
#define F(x) __uint_as_float(x)
    return (((F(p.x) + F(p.y)) + (F(p.z) + F(p.w))) + ((F(q.x) + F(q.y)) + (F(q.z) + F(q.w)))) + ldsf(a + 32);
#undef F
}
template <int N>
__device__ __forceinline__ void ln_finish(uint32_t lp, int lane, float& mb, float& rc) {
    const float v = N == 9 ? sum9(lp + lane * 80) : sum18(lp + lane * 80);
    const float o = __shfl_xor_sync(0xffffffffu, v, 16);
    const float m0 = v * (1.0f / 576.0f);
    const float mean = fmaf(fmaf(-m0, 576.0f, v), 1.0f / 576.0f, m0);
    const float var = fmaxf(fmaf(-mean, mean, o * (1.0f / 576.0f)), 0.f);
    mb = rbf(mean);
    rc = rcp_approx(rbf(sqrt_approx(rbf(rbf(var) + 1e-5f))));
}
__device__ __forceinline__ uint32_t ln_apply(uint32_t w, const uint2& st) {
    uint32_t r;
    asm("{\n.reg .b16 m, t, h, l;\n.reg .b32 mm, hh, ll, d, e;\nmov.b32 {m, t}, %2;\nmov.b32 {h, l}, %3;\nmov.b32 mm, {m, m};\nmov.b32 hh, {h, h};\nmov.b32 ll, {l, l};\n"
        "sub.rn.bf16x2 d, %1, mm;\nmul.rn.bf16x2 e, d, ll;\nfma.rn.bf16x2 %0, d, hh, e;\n}\n" : "=r"(r) : "r"(w), "r"(st.x), "r"(st.y));
    return r;
}
__device__ __forceinline__ void stat_store(uint32_t a, float mb, float rc, uint32_t extra) {
    const float rh = rbf(rc);
    sts64(a, (__float_as_uint(mb) >> 16) | (extra << 16), pack_bf16(rh, rc - rh));
}

__device__ __forceinline__ void hcmul(uint32_t re, uint32_t im, uint32_t z, uint32_t& ore, uint32_t& oim) {
    asm("{\n.reg .b16 x, y;\n.reg .b32 xx, yy, ny, a, b;\nmov.b32 {x, y}, %4;\nmov.b32 xx, {x, x};\nmov.b32 yy, {y, y};\nneg.f16x2 ny, yy;\n"
        "mul.rn.f16x2 a, %2, xx;\nfma.rn.f16x2 %0, %3, ny, a;\nmul.rn.f16x2 b, %3, xx;\nfma.rn.f16x2 %1, %2, yy, b;\n}\n" : "=&r"(ore), "=r"(oim) : "r"(re), "r"(im), "r"(z));
}
__device__ __forceinline__ void hcmul(uint32_t re, uint32_t im, uint32_t zx, uint32_t zy, uint32_t& ore, uint32_t& oim) {
    asm("{\n.reg .b32 ny, a, b;\nneg.f16x2 ny, %5;\n"
        "mul.rn.f16x2 a, %2, %4;\nfma.rn.f16x2 %0, %3, ny, a;\nmul.rn.f16x2 b, %3, %4;\nfma.rn.f16x2 %1, %2, %5, b;\n}\n" : "=&r"(ore), "=r"(oim) : "r"(re), "r"(im), "r"(zx), "r"(zy));
}

struct KGen {
    uint32_t Af[4][4];
    float2 z1, z8, z64, z128, T[9];
    uint32_t zw;
};
__device__ __forceinline__ void kgen_setup(KGen& k, uint32_t pa, float dt) {
    const float A = rbf(expf(bf_lo(pa)));
    const float lr2 = -(A * dt) * 1.4426950408889634f;
    const float li = bf_hi(pa) * dt;
    const float rh = li * 0.15915494309189535f;
    const float rl = fmaf(li, 6.4206382986e-9f, fmaf(li, 0.15915494309189535f, -rh));
    k.z1 = cexp_e(lr2, rh, rl, 1.0f);
    k.z8 = cexp_e(lr2, rh, rl, 8.0f);
    k.z64 = cexp_e(lr2, rh, rl, 64.0f);
}
__device__ __forceinline__ void kgen_rows(KGen& k, uint32_t tb, int lane) {
    const float2 z8 = k.z8, z64 = k.z64;
    const uint32_t row = tb + lane * TBP;
    k.z128 = csq(z64);
    const float2 z16 = csq(z8), z32 = csq(z16), z48 = cmul(z32, z16), z80 = cmul(z64, z16), z96 = cmul(z64, z32), z112 = cmul(z64, z48);
    uint32_t re[4], im[4], a[4], b[4];
    re[0] = pack_f16(1.0f, z16.x); im[0] = pack_f16(0.0f, z16.y);
    re[1] = pack_f16(z32.x, z48.x); im[1] = pack_f16(z32.y, z48.y);
    re[2] = pack_f16(z64.x, z80.x); im[2] = pack_f16(z64.y, z80.y);
    re[3] = pack_f16(z96.x, z112.x); im[3] = pack_f16(z96.y, z112.y);
    sts128(row, re[0], re[1], re[2], re[3]);
    sts128(row + 32, im[0], im[1], im[2], im[3]);
    const uint32_t zz = pack_f16(z8.x, z8.y);
#pragma unroll
    for (int j = 0; j < 4; j++) hcmul(re[j], im[j], zz, a[j], b[j]);
    sts128(row + 16, a[0], a[1], a[2], a[3]);
    sts128(row + 48, b[0], b[1], b[2], b[3]);
    __syncwarp();
    const int mi = lane >> 3;
    const uint32_t ad = tb + (lane & 7) * TBP + mi * 16;
#pragma unroll
    for (int ks = 0; ks < 4; ks++) ldsm_x4_t(k.Af[ks][0], k.Af[ks][1], k.Af[ks][2], k.Af[ks][3], ad + ks * 8 * TBP);
}
__device__ __forceinline__ void kgen_chain(KGen& k, uint32_t pc, float cs) {
    k.T[0] = make_float2(bf_lo(pc) * cs, -bf_hi(pc) * cs);
    const float2 y1 = make_float2(k.z1.x, -k.z1.y);
#pragma unroll
    for (int c = 1; c < 8; c++) k.T[c] = cmul(k.T[c - 1], y1);
    k.T[8] = cmul(k.T[0], make_float2(k.z8.x, -k.z8.y));
}
__device__ __forceinline__ void kgen_cols(KGen& k, uint32_t tb, int lane) {
    const uint32_t row = tb + lane * TBP;
    const float2 (&T)[9] = k.T;
    const uint32_t zv = pack_f16(k.z128.x, k.z128.y), zo = __shfl_xor_sync(0xffffffffu, zv, 1);
    k.zw = (lane & 1) ? __byte_perm(zo, zv, 0x7632) : __byte_perm(zv, zo, 0x5410);
    const float2 y256 = csq(make_float2(k.z128.x, -k.z128.y)), y512 = csq(y256), y768 = cmul(y512, y256), y1024 = csq(y512);
    const float2 c1032 = cmul(T[8], y1024);
    const uint32_t r04 = pack_f16(T[0].x, T[4].x), i04 = pack_f16(T[0].y, T[4].y), r26 = pack_f16(T[2].x, T[6].x), i26 = pack_f16(T[2].y, T[6].y);
    const uint32_t r48 = pack_f16(T[4].x, T[8].x), i48 = pack_f16(T[4].y, T[8].y);
    __syncwarp();
    sts128(row, r04, pack_f16(T[1].x, T[5].x), r26, pack_f16(T[3].x, T[7].x));
    sts128(row + 16, i04, pack_f16(T[1].y, T[5].y), i26, pack_f16(T[3].y, T[7].y));
    uint32_t a[4], b[4];
    {
        const uint32_t zz = pack_f16(y256.x, y256.y);
        hcmul(r04, i04, zz, a[0], b[0]);
        hcmul(r26, i26, zz, a[2], b[2]);
        hcmul(r48, i48, zz, a[3], b[3]);
    }
    sts128(row + 32, a[0], a[0], a[2], a[3]);
    sts128(row + 48, b[0], b[0], b[2], b[3]);
    {
        hcmul(r48, i48, pack_f16(y512.x, y512.y), a[0], b[0]);
        hcmul(r48, i48, pack_f16(y768.x, y768.y), a[1], b[1]);
        const uint32_t zz = pack_f16(c1032.x, c1032.y);
        hcmul(pack_f16(1.0f, y256.x), pack_f16(0.0f, y256.y), zz, a[2], b[2]);
        hcmul(pack_f16(y512.x, y768.x), pack_f16(y512.y, y768.y), zz, a[3], b[3]);
    }
    sts128(row + 64, a[0], a[1], a[2], a[3]);
    sts128(row + 80, b[0], b[1], b[2], b[3]);
}
__device__ __forceinline__ void kgen_mma(const KGen& k, uint32_t tb, int lane) {
    const int t = lane & 3;
    const uint32_t zw = k.zw;
    uint32_t zx[4], zy[4];
#pragma unroll
    for (int ks = 0; ks < 4; ks++) { zx[ks] = __shfl_sync(0xffffffffu, zw, 8 * ks + 2 * t); zy[ks] = __shfl_sync(0xffffffffu, zw, 8 * ks + 2 * t + 1); }
    __syncwarp();
    float acc[2][3][4];
#pragma unroll
    for (int i = 0; i < 6; i++)
#pragma unroll
        for (int j = 0; j < 4; j++) acc[i / 3][i % 3][j] = 0.f;
    {
        const int mi = lane >> 3;
        const uint32_t bd = tb + ((lane & 7) + 8 * (mi >> 1)) * TBP + (mi & 1) * 16;
#pragma unroll
        for (int kp = 0; kp < 2; kp++) {
            uint32_t b[3][4];
#pragma unroll
            for (int j = 0; j < 3; j++) ldsm_x4_t(b[j][0], b[j][1], b[j][2], b[j][3], bd + kp * 16 * TBP + j * 32);
#pragma unroll
            for (int h = 0; h < 2; h++) {
                const int ks = 2 * kp + h;
                uint32_t d[4];
                hcmul(k.Af[ks][0], k.Af[ks][2], zx[ks], zy[ks], d[0], d[2]);
                hcmul(k.Af[ks][1], k.Af[ks][3], zx[ks], zy[ks], d[1], d[3]);
#pragma unroll
                for (int j = 0; j < 3; j++) {
                    mma_f16(acc[0][j], k.Af[ks][0], k.Af[ks][1], k.Af[ks][2], k.Af[ks][3], b[j][2 * h], b[j][2 * h + 1]);
                    mma_f16(acc[1][j], d[0], d[1], d[2], d[3], b[j][2 * h], b[j][2 * h + 1]);
                }
            }
        }
    }
    __syncwarp();
#pragma unroll
    for (int h = 0; h < 2; h++) {
        sts64(tb + h * 256 + lane * 8, pack_f16(acc[h][0][0], acc[h][0][1]), pack_f16(acc[h][0][2], acc[h][0][3]));
        sts64(tb + 512 + h * 256 + lane * 8, pack_f16(acc[h][1][0], acc[h][1][1]), pack_f16(acc[h][1][2], acc[h][1][3]));
        sts32(tb + 1024 + h * 256 + lane * 4, pack_f16(acc[h][2][0], t < 2 ? acc[h][2][1] : acc[h][2][2]));
        sts32(tb + 1152 + h * 256 + lane * 4, pack_f16(t < 2 ? acc[h][2][2] : acc[h][2][1], acc[h][2][3]));
    }
}
__device__ __forceinline__ uint32_t table_buf(uint32_t sb, int warp) { return sb + SM_TB + warp * TBW; }

__device__ __forceinline__ void kgen_combine(uint32_t sb, int warp, int lane, uint32_t kw, uint32_t ao) {
    const int wq = warp & 3;
    const uint32_t a = table_buf(sb, warp & ~3) + wq * 256 + lane * 8, c = table_buf(sb, warp & ~3) + 1024 + wq * 128 + lane * 4;
    const int t = lane & 3;
    const uint32_t o0 = (t < 2 ? KW_T2 + KW_KH + 16 + t * 256 - (wq & 1) * KW_KH : KW_T3 + 16 - 1024 + t * 512 + (wq & 1) * 256) + (lane >> 2) * 16;
    const uint4 o = make_uint4(o0 + t * 36, o0 + (t ^ 1) * 36, o0 + (t ^ 2) * 36, o0 + (t ^ 3) * 36);
    const uint2 u = lds64(a), v = lds64(a + TBW), w = lds64(a + 2 * TBW), x = lds64(a + 3 * TBW);
    const uint32_t kt = hadd2(hadd2(lds32(c), lds32(c + TBW)), hadd2(lds32(c + 2 * TBW), lds32(c + 3 * TBW)));
    const uint32_t k23 = hadd2(hadd2(u.y, v.y), hadd2(w.y, x.y));
    sts64(kw + wq * 64 + ao, hadd2(hadd2(u.x, v.x), hadd2(w.x, x.x)), k23);
    const uint32_t d = kw + (wq >> 1) * 128;
    const uint32_t kh = hmul2(kt, 0x38003800u);
    sts32(d + o.x, kh); sts32(d + o.y, kh); sts32(d + o.z, kh); sts32(d + o.w, kh);
    if (wq == 3) {
        if (lane == 31) { sts32(kw + 264, k23 >> 16); sts32(kw + 288 + 264, k23 >> 16); sts32(kw + 576 + 264, k23 >> 16); }
        if (lane == 29) { sts32(kw + 864 + 280, kt >> 16); sts32(kw + 280, kt & 0xffff0000u); }
    }
}

__device__ __forceinline__ int c_exponent(const uint2& r, const uint2& i) {
    uint32_t mx = __vmaxu2(__vmaxu2(r.x & 0x7fff7fffu, r.y & 0x7fff7fffu), __vmaxu2(i.x & 0x7fff7fffu, i.y & 0x7fff7fffu));
    mx = __reduce_max_sync(0xffffffffu, max(mx & 0xffffu, mx >> 16));
    return min(max((int)(mx >> 7), 4), 240);
}

__device__ __forceinline__ int warp_v() { int l; asm volatile("mov.u32 %0, %%tid.x;" : "=r"(l)); return __shfl_sync(0xffffffffu, l >> 5, 0); }
__device__ __forceinline__ int lane_v() { int l; asm volatile("mov.u32 %0, %%laneid;" : "=r"(l)); return l; }
__device__ __forceinline__ uint32_t prmt(uint32_t a, uint32_t b, uint32_t s) { uint32_t d; asm("prmt.b32 %0, %1, %2, %3;\n" : "=r"(d) : "r"(a), "r"(b), "r"(s)); return d; }
__device__ __forceinline__ uint32_t prmt_v(uint32_t a, uint32_t b, uint32_t s) { uint32_t d; asm volatile("prmt.b32 %0, %1, %2, %3;\n" : "=r"(d) : "r"(a), "r"(b), "r"(s)); return d; }
__device__ __forceinline__ void mmah16(uint32_t& d0, uint32_t& d1, uint32_t a0, uint32_t a1, uint32_t a2, uint32_t a3, uint32_t b0, uint32_t b1, uint32_t c0, uint32_t c1) {
    asm volatile("mma.sync.aligned.m16n8k16.row.col.f16.f16.f16.f16 {%0,%1}, {%2,%3,%4,%5}, {%6,%7}, {%8,%9};\n"
                 : "=r"(d0), "=r"(d1) : "r"(a0), "r"(a1), "r"(a2), "r"(a3), "r"(b0), "r"(b1), "r"(c0), "r"(c1));
}
__device__ __forceinline__ void mmah8(uint32_t& d0, uint32_t& d1, uint32_t a0, uint32_t a1, uint32_t b0, uint32_t c0, uint32_t c1) {
    asm volatile("mma.sync.aligned.m16n8k8.row.col.f16.f16.f16.f16 {%0,%1}, {%2,%3}, {%4}, {%5,%6};\n"
                 : "=r"(d0), "=r"(d1) : "r"(a0), "r"(a1), "r"(b0), "r"(c0), "r"(c1));
}
template <int A = 8, int B = 32>
__device__ __forceinline__ void conv_rename(uint32_t (&acc)[32]) {
#pragma unroll
    for (int i = A; i < B; i++) { uint32_t v; asm volatile("mov.b32 %0, %1;\n" : "=r"(v) : "r"(acc[i])); acc[i] = v; }
}
__host__ __device__ constexpr uint32_t band_bits(int hw, int sh) {
    uint32_t c = 0;
    for (int s = 0; s <= 10; s++)
        for (int e = 0; e < 2; e++) {
            const int v = s - 3 + sh - 4 * e;
            if (v <= hw && v >= -hw) c |= 1u << (14 + 16 * e - s);
        }
    return c;
}
template <int HW, int SH, int J> __device__ __forceinline__ uint32_t band(uint32_t p2) {
    uint32_t d;
    asm volatile("{\n.reg .b32 t;\nmul.lo.u32 t, %1, %2;\nand.b32 %0, t, 0x40004000;\n}\n" : "=r"(d) : "r"(p2), "n"(band_bits(HW, SH) | J));
    return d;
}
template <int H0, int SH> __device__ __forceinline__ void band_pair(uint4& l, uint4& u, uint32_t p2) {
    l = make_uint4(band<H0, 8, 1>(p2), band<H0 - 1, SH + 8, 2>(p2), band<H0, 0, 1>(p2), band<H0 - 1, SH, 1>(p2));
    u = make_uint4(band<H0, 0, 2>(p2), band<H0 - 1, SH, 2>(p2), band<H0, -8, 1>(p2), band<H0 - 1, SH - 8, 1>(p2));
}
__device__ __forceinline__ void run_sums(uint32_t (&G)[3][2], const uint32_t (&c)[5], const uint4& l, const uint4& u) {
    mmah8(G[0][0], G[0][1], l.x, l.y, c[0], 0u, 0u);
    mmah8(G[1][0], G[1][1], u.z, u.w, c[3], 0u, 0u);
    mmah8(G[2][0], G[2][1], l.x, l.y, c[2], 0u, 0u);
    mmah16(G[0][0], G[0][1], u.x, u.y, u.z, u.w, c[1], c[2], G[0][0], G[0][1]);
    mmah16(G[1][0], G[1][1], l.x, l.y, l.z, l.w, c[1], c[2], G[1][0], G[1][1]);
    mmah16(G[2][0], G[2][1], u.x, u.y, u.z, u.w, c[3], c[4], G[2][0], G[2][1]);
}
__device__ __forceinline__ float h_lo(uint32_t w) { return __half2float(__ushort_as_half((unsigned short)(w & 0xffffu))); }
__device__ __forceinline__ float h_hi(uint32_t w) { return __half2float(__ushort_as_half((unsigned short)(w >> 16))); }
__device__ __forceinline__ uint64_t smem_desc(uint32_t sb, uint32_t o16, uint32_t lbo) {
    uint64_t d;
    asm("mov.b64 %0, {%1, %2};" : "=l"(d) : "r"(((sb & 0x3FFFF) >> 4) + o16 + (lbo << 12)), "r"(8));
    return d;
}
template <int I> struct IC { static constexpr int value = I; };

struct Conv {
    uint32_t u[3][5];
    uint32_t q2[3][2][4];
    uint32_t q3[2][4];
    uint32_t r[18];
};
__device__ __forceinline__ void conv_sums(Conv& c, uint32_t a0, uint32_t a1, const uint4 (&bd)[4]) {
    {
        uint32_t x;
        ldsm_x4(c.u[0][1], c.u[0][2], c.u[0][3], c.u[0][4], a1);
        ldsm_x4(c.u[0][0], c.u[1][0], c.u[2][0], x, a0);
#pragma unroll
        for (int q = 1; q < 3; q++) ldsm_x4(c.u[q][1], c.u[q][2], c.u[q][3], c.u[q][4], a1 + q * 512);
    }
    uint32_t G[3][2];
#pragma unroll
    for (int q = 0; q < 3; q++) {
        run_sums(G, c.u[q], bd[0], bd[1]);
#pragma unroll
        for (int e = 0; e < 2; e++) {
            const uint32_t s = e ? 0x7632u : 0x5410u;
            c.q2[q][e][0] = prmt(G[0][1], G[0][0], s); c.q2[q][e][1] = prmt(G[1][1], G[1][0], s);
            c.q2[q][e][2] = prmt(G[1][0], G[1][1], s ^ 0x4444u); c.q2[q][e][3] = prmt(G[2][1], G[2][0], s);
        }
    }
#pragma unroll
    for (int q = 0; q < 2; q++) {
        run_sums(G, c.u[q], bd[2], bd[3]);
        c.q3[q][0] = prmt(G[1][1], G[0][0], 0x7632u); c.q3[q][1] = prmt(G[2][1], G[1][0], 0x7632u);
        c.q3[q][2] = prmt(G[1][1], G[0][0], 0x5410u); c.q3[q][3] = prmt(G[2][1], G[1][0], 0x5410u);
    }
}
__device__ __forceinline__ void conv_edges(Conv& c, uint32_t (&acc)[32], uint32_t ka, uint32_t ks, uint32_t sel, int wq) {
#pragma unroll
    for (int i = 0; i < 32; i++) acc[i] = 0u;
    const uint4 r = lds128(ka + 256), s = lds128(ka + 272);
    const uint32_t a0 = prmt(r.x, r.y, sel), a1 = prmt(r.y, r.z, sel), a2 = prmt(r.z, r.w, sel), b1 = prmt(s.y, s.z, sel), b2 = prmt(s.z, s.w, sel);
    const uint32_t sw = sel ^ 0x4444u, a3 = prmt(r.z, r.y, sw), a4 = prmt(r.w, r.z, sw), b0 = prmt(s.x, s.y, sel), b3 = prmt(s.z, s.y, sw), b4 = prmt(s.w, s.z, sw);
#pragma unroll
    for (int q = 0; q < 3; q++) mmah8(acc[8 * q + 8], acc[8 * q + 9], a2, 0u, c.u[q][2], 0u, 0u);
#pragma unroll
    for (int q = 0; q < 2; q++) mmah8(acc[8 * q + 16], acc[8 * q + 17], b2, 0u, c.u[q][2], acc[8 * q + 16], acc[8 * q + 17]);
#pragma unroll
    for (int q = 0; q < 3; q++) mmah16(acc[8 * q + 8], acc[8 * q + 9], a1, a4, a0, a3, c.u[q][3], c.u[q][4], acc[8 * q + 8], acc[8 * q + 9]);
#pragma unroll
    for (int q = 0; q < 2; q++) mmah16(acc[8 * q + 16], acc[8 * q + 17], b1, b4, b0, b3, c.u[q][3], c.u[q][4], acc[8 * q + 16], acc[8 * q + 17]);
    {
        uint32_t t0, t1, t2, t3;
        ldsm_x4(t0, t1, t2, t3, ks);
#pragma unroll
        for (int q = 0; q < 2; q++) mmah16(acc[8 * q + 16], acc[8 * q + 17], c.q2[q][0][0], c.q2[q][0][1], c.q2[q][0][2], c.q2[q][0][3], t0, t1, acc[8 * q + 16], acc[8 * q + 17]);
#pragma unroll
        for (int q = 0; q < 2; q++) mmah16(acc[8 * q + 16], acc[8 * q + 17], c.q2[q][1][0], c.q2[q][1][1], c.q2[q][1][2], c.q2[q][1][3], t2, t3, acc[8 * q + 16], acc[8 * q + 17]);
    }
    {
        const uint32_t a = ka + wq * 64;
#pragma unroll
        for (int i = 0; i < 4; i++) { const uint4 v = lds128(a + i * 16); c.r[4 * i] = v.x; c.r[4 * i + 1] = v.y; c.r[4 * i + 2] = v.z; c.r[4 * i + 3] = v.w; }
        const uint2 v = lds64(a + 64);
        c.r[16] = v.x; c.r[17] = v.y;
    }
    if (sel == 0u) {
#pragma unroll
        for (int i = 0; i < 6; i++) sts128(ka + i * 16, c.q2[i >> 1][i & 1][0], c.q2[i >> 1][i & 1][1], c.q2[i >> 1][i & 1][2], c.q2[i >> 1][i & 1][3]);
#pragma unroll
        for (int i = 0; i < 2; i++) sts128(ka + i * 16, c.q3[i][0], c.q3[i][1], c.q3[i][2], c.q3[i][3]);
#pragma unroll
        for (int i = 1; i < 4; i++) sts64(ka + i * 16, acc[8 * i], acc[8 * i + 1]);
    }
    conv_rename(acc);
}
#define SPACE 0
#define SPN 3
#define GATE 2
#define HAND 2
#define GA 6
#define GB 4
template <int TA, int TB, int IA, class FG>
__device__ __forceinline__ void conv_tail(uint32_t (&acc)[32], const uint32_t (&a)[8][4], uint32_t sb, unsigned char* gy0, int warp, size_t ycopy, FG fg) {
    const int wg = warp >> 2, wq = warp & 3, ord = TA == 0 && TB == 16 ? 3 - wg : 4;
    const uint32_t ub = sb + SM_U + wg * USLOT_B + UPAD * 16, turn = sb + SM_MISC + 376 + ord * 8, sfs = sb + SM_MISC + 256 + wg * 8;
    const uint32_t du = wg * (USLOT_B / 16) + (SM_U / 16 + UPAD + TA * 8);
    uint32_t ud[8], fs;
    auto skip = [&]() {
        const int lane = lane_v();
        const uint32_t ua = ub + ((lane >> 3) & 1) * ULO_B + (8 * wq + (lane & 7)) * 16 + (lane >> 4) * 512;
        if (IA == 0) ldsm_x4_t(ud[0], ud[1], ud[2], ud[3], ua);
        if (TB == 16) ldsm_x4_t(ud[4], ud[5], ud[6], ud[7], ua + 1024);
        const uint2 fd = lds64(sfs);
        fs = fd.x;
        const float dsk = __uint_as_float(fd.y);
#pragma unroll
        for (int i = 2 * IA; i < TB / 2; i++) ud[i] = pack_bf16(h_lo(ud[i]) * dsk, h_hi(ud[i]) * dsk);
    };
    conv_rename<2 * TA, 2 * TB>(acc);
    if (__builtin_expect(ord != 0, 0)) {
        skip();
        mbar_wait(turn);
    }
    if (TA == 0 && TB == 16) asm volatile("{\n.reg .pred p;\nelect.sync _|p, 0xffffffff;\n@p mbarrier.arrive.shared::cta.b64 _, [%0];\n}\n" ::"r"(turn + 40) : "memory");
    fg(IC<8>());
    wg_fence();
#pragma unroll
    for (int m = 7; m >= 0; m--) {
        wg_h<TA, TB - TA>(acc, a[m], smem_desc(sb, du - m, ULO_B));
        if (m == GA || m == GB || m == HAND) wg_commit();
        if (m == GB) asm volatile("wgmma.wait_group.sync.aligned 1;\n" ::: "memory");
    }
    wg_commit();
    if (TA == 0 && TB == 16) {
        asm volatile("wgmma.wait_group.sync.aligned 1;\n" ::: "memory");
        asm volatile("{\n.reg .pred p;\nelect.sync _|p, 0xffffffff;\n@p mbarrier.arrive.shared::cta.b64 _, [%0];\n}\n" ::"r"(turn + 8) : "memory");
    }
    __syncwarp();
    fg(IC<3>());
    if (!ord) skip();
    fg(IC<4>());
    const int lane = lane_v();
    const uint32_t lp = sb + SM_PL + (ord >= 3 ? ord - 3 : ord) * PL_B + lane * 8;
    unsigned char* gy = gy0 + ((4 * wq + (lane & 3)) * DM + (TA == 0 && TB == 16 ? 4 * blockIdx.x + wg : 512 + (blockIdx.x >> 1))) * 64 + (lane >> 2) * 8;
    const uint32_t st = lp + (wq * 12 - ((wq * (wq - 1)) >> 1)) * 256;
    uint32_t ld[3];
#pragma unroll
    for (int s = 1; s < 4; s++) {
        const int w = (wq - s) & 3;
        ld[s - 1] = lp + (w * 12 - ((w * (w - 1)) >> 1) + s - 1 - (wq < s ? 3 : 0)) * 256;
    }
    if (ord >= 3) bar_sync(9 + ord, 256);
    wg_wait0();
    fg(IC<6>());
#pragma unroll
    for (int j = TA; j < TB; j++)
        if ((j & 3) && j + 3 >= 4 * IA && (j + 3 < TB || j + wq < TB)) sts64(st + (j - 1 - (j >> 2)) * 256, acc[2 * j], acc[2 * j + 1]);
    bar_sync(1 + wg, 128);
    fg(IC<7>());
    uint2 v[4][3];
#pragma unroll
    for (int i = IA; i < TB / 4; i++)
#pragma unroll
        for (int s = 0; s < 3; s++) {
            if (i == 0) { v[i][s] = make_uint2(0u, 0u); if (wq > s) v[i][s] = lds64(ld[s]); }
            else v[i][s] = lds64(ld[s] + i * 768);
        }
    fg(IC<5>());
#pragma unroll
    for (int i = IA; i < TB / 4; i++) {
        const uint32_t x0 = hadd2(v[i][0].x, acc[8 * i]), x1 = hadd2(v[i][1].x, v[i][2].x), y0 = hadd2(v[i][0].y, acc[8 * i + 1]), y1 = hadd2(v[i][1].y, v[i][2].y);
        const uint32_t x = hadd2(x0, x1), y = hadd2(y0, y1);
        const uint32_t lo = pack_bf16(h_lo(x), h_hi(x)), hi = pack_bf16(h_lo(y), h_hi(y));
        const uint32_t o0 = max(hfma2_bf(lo, fs, ud[2 * i]), 1u), o1 = hfma2_bf(hi, fs, ud[2 * i + 1]);
        stg64(gy + i * 16 * DM * 64, o0, o1);
        if (SPACE && TA == 0 && TB == 16 && i < 3 && ord < SPN) { const unsigned c0 = clock(); while (clock() - c0 < SPACE) {} }
    }
    if (TA == 0 && TB == 16 && ord < 2) bar_arrive(12 + ord, 256);
}
template <int M0, int M1>
__device__ __forceinline__ void conv_frags(uint32_t (&a)[8][4], const uint32_t (&r)[18], uint32_t sel, uint32_t dep, int warp) {
    const uint32_t s = prmt_v(sel, dep, 0x3210u + (warp >> 8)), sw = s ^ 0x4444u;
#pragma unroll
    for (int m = M0; m < M1; m++) {
        a[m][0] = prmt_v(r[2 * m + 1], r[2 * m + 2], s); a[m][1] = prmt_v(r[2 * m + 2], r[2 * m + 3], s);
        a[m][2] = prmt_v(r[2 * m + 1], r[2 * m], sw); a[m][3] = prmt_v(r[2 * m + 2], r[2 * m + 1], sw);
    }
}
template <class FG>
__device__ __forceinline__ void conv_main(const Conv& c, uint32_t (&acc)[32], uint32_t sb, uint32_t sel, unsigned char* gy, int warp, size_t ycopy, FG fg) {
    const uint32_t kw = (warp >> 2) * (KW_B / 16) + SM_KW / 16;
    const uint64_t d2 = smem_desc(sb, kw + KW_T2 / 16, KW_KH), d2b = smem_desc(sb, kw + KW_T2 / 16 + 1, KW_KH), d3 = smem_desc(sb, kw + KW_T3 / 16, 16), d3b = smem_desc(sb, kw + KW_T3 / 16 + 32, 16);
    uint32_t a[8][4];
    {
        const int ord = warp < 16 ? 3 - (warp >> 2) : 4;
        if (__builtin_expect(ord >= GATE, 0)) {
            fg(IC<1>());
            mbar_wait(sb + SM_MISC + 376 + 40 + (ord - GATE) * 8);
        }
    }
    wg_fence();
    wg_h<12, 4>(acc, c.q3[0], d3b); wg_h<8, 4>(acc, c.q3[0], d3); wg_h<4, 4>(acc, c.q2[0][0], d2b);
    wg_h<12, 4>(acc, c.q3[1], d3); wg_h<8, 4>(acc, c.q2[1][0], d2b);
    wg_h<12, 4>(acc, c.q2[2][0], d2b); wg_h<4, 4>(acc, c.q2[0][1], d2); wg_h<8, 4>(acc, c.q2[1][1], d2);
    wg_h<12, 4>(acc, c.q2[2][1], d2);
    wg_commit(); __syncwarp();
    fg(IC<0>());
    wg_wait0();
    conv_frags<0, 8>(a, c.r, sel, acc[16], warp);
    fg(IC<2>());
    if (warp >= 16) {
        if (blockIdx.x & 1) conv_tail<4, 16, 2>(acc, a, sb, gy, warp, ycopy, fg);
        else conv_tail<0, 8, 0>(acc, a, sb, gy, warp, ycopy, fg);
    } else {
        conv_tail<0, 16, 0>(acc, a, sb, gy, warp, ycopy, fg);
    }
}
#define CONV_LT6 const int dd = (lane >> 3) + (lane & 4) - (lane & 3); \
        const uint4 lt6 = make_uint4(prmt_v((dd & 3) * 288, 0u, idn), prmt_v(0x3254u + (dd >> 2) * 0x2222u, 0u, idn), \
            prmt_v(UPAD * 16 + (lane & 7) * 16 + ULO_B - 32 + (lane >> 3) * 512, 0u, idn), prmt_v(UPAD * 16 + (lane & 7) * 16 + ((lane >> 3) & 1) * ULO_B - 16 + (lane & 16), 0u, idn));
#define CONV_PRE \
        CONV_LT6 \
        const uint32_t ka = kw + lt6.x, sel = lt6.y, ks = kw + lt7.x; \
        const uint32_t ca0 = sb + SM_U + wg * USLOT_B + (warp & 3) * 128 + lt6.z, ca1 = sb + SM_U + wg * USLOT_B + (warp & 3) * 128 + lt6.w; \
        uint4 bd[4]; \
        band_pair<2, 4>(bd[0], bd[1], lt7.w); band_pair<4, 0>(bd[2], bd[3], lt7.w);
#define CONV_BODY \
        Conv c; \
        uint32_t acc[32]; \
        conv_sums(c, ca0, ca1, bd); \
        conv_edges(c, acc, ka, ks, sel, warp & 3);
template <int U0, int U1>
__device__ __forceinline__ void weight_units(uint32_t sb, const CUtensorMap* tg, const CUtensorMap* tu, const CUtensorMap* td, int w) {
    if constexpr (U0 < U1) {
        if (w == 0 && elect_one()) {
            if constexpr (U0 < 12) tma_2d(sb + SM_WG + U0 * 6912, U0 < 6 ? tg : tu, 72 * (blockIdx.x >> 1), 288 * (blockIdx.x & 1) + (U0 % 6) * 48, sb + SM_MISC + 328);
            else tma_2d(sb + SM_WD + (15 - U0) * 10368, td, 288 * (blockIdx.x & 1) + 72 * (15 - U0), 72 * (blockIdx.x >> 1), sb + SM_MISC + 336);
        }
        weight_units<U0 + 1, U1>(sb, tg, tu, td, w - 1);
    }
}
#define WS x112347cccdeeeeeeffg
#define WS_STR2(x) #x
#define WS_STR(x) WS_STR2(x)
__device__ constexpr int wsched(int i) { constexpr char t[] = WS_STR(WS); return i == 0 ? 0 : (t[i] <= '9' ? t[i] - '0' : t[i] - 'a' + 10); }
__device__ constexpr bool wsched_ok() { for (int i = 0; i < 19; i++) if (wsched(i + 1) < wsched(i) || wsched(i + 1) > wsched(i) + (i == 6 ? 8 : i < 16 ? 3 : 1)) return false; return wsched(19) == 16 && wsched(6) <= WMAX && wsched(16) <= 15; }
static_assert((PAUSE & 2) && GATE <= 2, "resets");
static_assert(wsched_ok(), "weight schedule");
#define PS x00000
__device__ constexpr int psched(int i) { constexpr char t[] = WS_STR(PS); return i == 0 ? 0 : (t[i] <= '9' ? t[i] - '0' : t[i] - 'a' + 10); }
#define PPOINT(i) do { if (psched(i + 1) > psched(i) && warp == 1 + (i & 1) && elect_one()) \
    l2_prefetch(reinterpret_cast<const unsigned char*>(p.wpf) + b * 41472 + psched(i) * 4608, (psched(i + 1) - psched(i)) * 4608); } while (0)
#define WPOINT(i, w) do { weight_units<wsched(i), wsched(i + 1)>(sb, &tm_g, &tm_u, &tm_d, w); } while (0)

__global__ void __launch_bounds__(NTHR, 1) __cluster_dims__(2, 1, 1)
fused_kernel(const Params p, const __grid_constant__ CUtensorMap tm_g, const __grid_constant__ CUtensorMap tm_u, const __grid_constant__ CUtensorMap tm_d, const __grid_constant__ CUtensorMap tm_x,
             const __grid_constant__ CUtensorMap tm_y, const __grid_constant__ CUtensorMap tm_z) {
    extern __shared__ __align__(1024) unsigned char smem[];
    const uint32_t sb = smem_u32(smem);
    const int tid = threadIdx.x, warp = __shfl_sync(0xffffffffu, tid >> 5, 0), lane = tid & 31;
    const int b = blockIdx.x, P = b >> 1, odd = b & 1;
    const int g = lane >> 2, t = lane & 3;
    const int wg = warp >> 2, t128 = tid & 127;
    const uint32_t s_stat = sb + SM_MISC;
    const uint32_t s_key = sb + SM_MISC + 128;
    const uint32_t s_wm = sb + SM_MISC + 256;
    const uint32_t s_k16 = sb + SM_MISC + 192;
    const uint32_t s_fs = sb + SM_MISC + 256;
    const uint32_t s_cnt = sb + SM_MISC + 320;
    const uint32_t bar_w = sb + SM_MISC + 328, bar_d = bar_w + 8, bar_g = bar_w + 16, bar_r = bar_w + 32, bar_h = bar_w + 40, bar_x = bar_w + 48;
    STAMP(0);

    const bool lnw = (unsigned)(warp - 10) < 9u;
    const unsigned pm = tid + (tid < 512 ? 512 * b : 65024 + 128 * P), pq = (pm & ~127u) + 4 * lane;
    uint32_t pl = ldg16(p.lar + pm), ldt = ldg16(p.ldt + (pm >> 7));
    const uint32_t pa2 = ldg16(p.aim + pm), pc = ldg16(p.cre + pm), pi = ldg16(p.cim + pm);
    const uint2 call_re = ldg64(p.cre + pq), call_im = ldg64(p.cim + pq);
    const uint32_t dskl = ldg16(p.dsk + (pm >> 7));
    const uint32_t ep = ld_poll32(p.s->hint + (b & 7) * 32 + 1 + (lane >> 5));
    if ((unsigned)(tid - 320) < 288u) {
        const bf16* xp = p.x + (unsigned)((32 * P + 2 * odd + TOKEN_OF(g)) * DM + ((tid - 320) & ~31) + 8 * t);
        const uint32_t xt = sb + SM_XT + ((tid - 320) & ~31) * 32 + lane * 16;
        asm volatile("cp.async.cg.shared.global [%0], [%1], 16;\ncp.async.cg.shared.global [%0 + 512], [%1 + 9216], 16;\n"
                     "cp.async.cg.shared.global [%0 + 9216], [%1 + 576], 16;\ncp.async.cg.shared.global [%0 + 9728], [%1 + 9792], 16;\n" ::"r"(xt), "l"(xp) : "memory");
    }
    uint32_t* const std_ = p.s->st + ((lane & 12) * 128 + odd * 256 + 4 * P + 2 * (lane & 1) + ((lane >> 1) & 1)) * 2;
    unsigned char* const ud = reinterpret_cast<unsigned char*>(p.s->uT) + (32 * (warp - UW) + 8 * (g >> 1) + (g & 1)) * 4096 + b * 32 + t * 8;
    if (warp == 0) {
        if (lane == 0) {
            mbar_init(bar_x, 1); mbar_init(bar_w, 1); mbar_init(bar_d, 1); mbar_init(bar_g, 1); mbar_init(bar_h, 3); mbar_init(bar_r, 1);
            #pragma unroll
            for (int i = 1; i < 9; i++) mbar_init(bar_x + 8 * i, 4);
            asm volatile("fence.mbarrier_init.release.cluster;\n" ::: "memory");
            mbar_expect(bar_x, 16384); mbar_expect(bar_r, 8192);
            mbar_expect(bar_w, 2 * 41472); mbar_expect(bar_d, 41472); mbar_expect(bar_g, 18 * 512);
        }
        __syncwarp();
        bar_arrive(0, NWRK);
    }
    if (warp == 0 && elect_one()) tma_3d(sb + SM_XC + 16384, &tm_x, 8 * P, 0, 8 * odd, bar_x);
    asm volatile("barrier.cluster.arrive.relaxed.aligned;\n" ::: "memory");
    const uint32_t kw = sb + SM_KW + wg * KW_B;
    if (t128 < 2 * UPAD) sts128(sb + SM_U + wg * USLOT_B + (t128 & 1) * ULO_B + (t128 >> 1) * 16, 0u, 0u, 0u, 0u);
    sts128(kw + t128 * 16, 0u, 0u, 0u, 0u);
    if (t128 < KW_B / 16 - 128) sts128(kw + 2048 + t128 * 16, 0u, 0u, 0u, 0u);
    if (tid < 96) {
#pragma unroll
        for (int i = 0; i < 6; i++) sts128(sb + SM_ZERO + i * 1536 + tid * 16, 0u, 0u, 0u, 0u);
    }
    if (warp != 0) bar_sync(0, NWRK);
    STAMP(1);
    if (warp == 19 || warp == UW || warp == UW + 1) {
        if (warp == 19) {
            if (lane < 16) stg64(std_, 0u, 0u);
            if (lane < 9) asm volatile("prefetch.global.L2 [%0];\n" ::"l"(p.wr + lane * 64));
        } else {
#pragma unroll
            for (int k = 0; k < 4; k++) stg64(ud + k * 8192, 0u, 0u);
        }
    }
    uint32_t X[2][8];
    auto partial = [&]() {
        const uint32_t xt = sb + SM_XT + (warp - 10) * 1024 + lane * 16;
        asm volatile("cp.async.wait_all;\n" ::: "memory");
        STAMP(23);
        const uint4 a = lds128(xt), c = lds128(xt + 512), d = lds128(xt + 9216), e = lds128(xt + 9728);
        X[0][0] = a.x; X[0][1] = a.y; X[0][2] = a.z; X[0][3] = a.w; X[0][4] = d.x; X[0][5] = d.y; X[0][6] = d.z; X[0][7] = d.w;
        X[1][0] = c.x; X[1][1] = c.y; X[1][2] = c.z; X[1][3] = c.w; X[1][4] = e.x; X[1][5] = e.y; X[1][6] = e.z; X[1][7] = e.w;
        ln_partial<8>(X, sb + SM_LNP, warp - 10, g, t);
        bar_arrive(6, 320);
        if (PAUSE & 1) bar_sync(7, PCNT);
    };
    if (LNAT == 0 && lnw) {
        partial();
        pl = prmt_v(pl, X[0][0], 0x3210u + (warp >> 8)); ldt = prmt_v(ldt, X[0][0], 0x3210u + (warp >> 8));
    }
    auto finish = [&]() {
        bar_sync(6, 320);
        float mb, rc;
        ln_finish<9>(sb + SM_LNP, lane, mb, rc);
        const float rh = rbf(rc);
        const uint32_t s0 = (__float_as_uint(mb) >> 16) | (((ep & 0x7fffu) + 1u) << 16), s1 = pack_bf16(rh, rc - rh);
        if (lane < 16) { stg64(std_, s0, s1); sts64(s_stat + lane * 8, s0, s1); }
        if (lane == 16) sts32(s_cnt + 4, ep);
        bar_arrive(7, PCNT);
        STAMP(28);
    };
    auto upub = [&]() {
        if (!(PAUSE & 6)) bar_sync(7, PCNT);
        const uint32_t utag = ((ep & 3u) + 1u) * 0x10001u;
        uint32_t U[2][4];
#pragma unroll
        for (int hf = 0; hf < 2; hf++) {
            const uint2 st = lds64(s_stat + (g + 8 * hf) * 8);
            const uint4 xv = lds128(sb + SM_XT + (16 + warp - UW) * 1024 + hf * 512 + lane * 16);
            const uint32_t xs[4] = {xv.x, xv.y, xv.z, xv.w};
#pragma unroll
            for (int k = 0; k < 4; k++) {
                const uint32_t u = ln_apply(xs[k], st);
                U[hf][k] = movm((pack_f16_rz(bf_lo(u), __uint_as_float(u)) & 0xfff8fff8u) | utag);
            }
        }
#pragma unroll
        for (int k = 0; k < 4; k++) stg64(ud + k * 8192, U[0][k], U[1][k]);
    };
    if (FINAT == 0 && warp == 19) finish();
    const uint32_t tb = table_buf(sb, warp);
    const float dt = rbf(expf(bf_lo(ldt)));
    KGen kg;
    kgen_setup(kg, pl | (pa2 << 16), dt);
    if (LNAT == 1 && lnw) {
        partial();
        kg.z8.x = __uint_as_float(prmt_v(__float_as_uint(kg.z8.x), X[0][0], 0x3210u + (warp >> 8)));
        kg.z1.x = __uint_as_float(prmt_v(__float_as_uint(kg.z1.x), X[0][0], 0x3210u + (warp >> 8)));
    }
    if (FINAT == 1 && warp == 19) finish();
    if (UAT == 0 && (warp == UW || warp == UW + 1)) upub();
    kgen_rows(kg, tb, lane);
    if (wg == 0) fence_async();
    if (LNAT == 2 && lnw) {
        partial();
        kg.z128.x = __uint_as_float(prmt_v(__float_as_uint(kg.z128.x), X[0][0], 0x3210u + (warp >> 8)));
        kg.z1.x = __uint_as_float(prmt_v(__float_as_uint(kg.z1.x), X[0][0], 0x3210u + (warp >> 8)));
    }
    if (FINAT == 2 && warp == 19) finish();
    if (UAT == 1 && (warp == UW || warp == UW + 1)) upub();
    STAMP(2);
    WPOINT(0, warp - 4);
    PPOINT(0);
    const int ce = c_exponent(call_re, call_im);
    if (t128 == 0) sts64(s_fs + wg * 8, (uint32_t)min(max(ce + (int)(__float_as_uint(dt) >> 23) - 116, 0), 254) * 0x800080u, dskl << 16);
    kgen_chain(kg, pc | (pi << 16), __uint_as_float(((uint32_t)(244 - ce) << 23) | (__float_as_uint(dt) & 0x7fffffu)));
    if ((PAUSE & 4) && warp < 10) bar_sync(7, PCNT);
    if (UAT == 4 && (warp == UW || warp == UW + 1)) upub();
    STAMP(3);
    WPOINT(1, warp - 6);
    PPOINT(1);
    kgen_cols(kg, tb, lane);
    if (LNAT == 3 && lnw) partial();
    if (FINAT == 3 && warp == 19) finish();
    if ((PAUSE & 2) && warp < 10) bar_sync(7, PCNT);
    if (UAT == 2 && (warp == UW || warp == UW + 1)) upub();
    STAMP(4);
    WPOINT(2, warp - 8);
    PPOINT(2);
    const uint4* usrc = wg < 4 ? reinterpret_cast<const uint4*>(p.s->st) + odd * 512 + (lane & 1) * 128 + 16 * (warp & 7) + (lane >> 1)
                               : reinterpret_cast<const uint4*>(p.s->uT) + P * 256 + 2 * t128;
    const int ustep = wg < 4 ? 256 : 1;
    uint4 uv0, uv1;
    kgen_mma(kg, tb, lane);
    if (UAT == 3 && (warp == UW || warp == UW + 1)) upub();
    STAMP(26);
    WPOINT(3, warp - 5);
    PPOINT(3);
    const uint32_t idn = 0x3210u + (warp >> 8);
    const uint4 lt7 = make_uint4(prmt_v(KW_T2 + ((lane >> 3) & 1) * KW_KH + (33 + (lane & 7)) * 16 - (lane & 16), 0u, idn), t * 288 + g * 8 + 8, (lane & 1) * 4096 + (lane >> 1) * 16,
                                 prmt_v(8u << ((lane >> 3) + (lane & 4)) >> (lane & 3), 0u, idn));
    asm volatile("barrier.cluster.wait.acquire.aligned;\n" ::: "memory");
    bar_sync(1 + wg, 128);
    uv0 = ld_poll(usrc); uv1 = ld_poll(usrc + ustep);
    kgen_combine(sb, warp, lane, kw, lt7.y);
    CONV_PRE
    STAMP(5);
    WPOINT(4, warp - 7);
    PPOINT(4);
    if (wg < 4) {
        mbar_wait(bar_x);
        const bool far = DSM == 1 ? warp < 8 : warp >= 8;
        const uint32_t xa = sb + SM_XC + 16384 + (warp & 7) * 256 + (odd ^ far) * 8 + lt7.z;
        uint2 xv[4] = {lds64(xa), lds64(xa + 8192), lds64(xa + 2048), lds64(xa + 10240)};
        const uint32_t tag = ((ep & 0x7fffu) + 1u) << 16;
        int it = 0;
        while (true) {
            const bool bad = (((uv0.x ^ tag) | (uv0.z ^ tag)) | ((uv1.x ^ tag) | (uv1.z ^ tag))) >> 16;
            if (!__any_sync(0xffffffffu, bad)) break;
            if (++it > SPIN_LIMIT) TRAP();
            if (bad) { uv0 = ld_poll(usrc); uv1 = ld_poll(usrc + 256); }
        }
        STAMP(6);
        DBG(wg, it);
        const uint2 st[4] = {make_uint2(uv0.x, uv0.y), make_uint2(uv0.z, uv0.w), make_uint2(uv1.x, uv1.y), make_uint2(uv1.z, uv1.w)};
#pragma unroll
        for (int i = 0; i < 4; i++) {
            xv[i].x = ln_apply(xv[i].x, st[i]);
            xv[i].y = ln_apply(xv[i].y, st[i]);
        }
        const uint32_t ub = sb + SM_U + UPAD * 16 + odd * ULO_B + (warp & 7) * 256 + lane * 8;
        const uint32_t w[4][2] = {{pack_f16(bf_lo(xv[0].x), bf_lo(xv[1].x)), pack_f16(bf_lo(xv[2].x), bf_lo(xv[3].x))}, {HI2(xv[0].x, xv[1].x), HI2(xv[2].x, xv[3].x)},
                                  {pack_f16(bf_lo(xv[0].y), bf_lo(xv[1].y)), pack_f16(bf_lo(xv[2].y), bf_lo(xv[3].y))}, {HI2(xv[0].y, xv[1].y), HI2(xv[2].y, xv[3].y)}};
#pragma unroll
        for (int i = 0; i < 4; i++) {
            if (far) asm volatile("st.async.shared::cluster.mbarrier::complete_tx::bytes.v2.b32 [%0], {%1,%2}, [%3];\n" ::"r"((ub ^ 0x1000000u) + i * USLOT_B), "r"(w[i][0]), "r"(w[i][1]), "r"(bar_r ^ 0x1000000u) : "memory");
            else sts64(ub + i * USLOT_B, w[i][0], w[i][1]);
        }
    } else {
        const uint32_t utag = ((ep & 3u) + 1u) * 0x10001u;
        int it = 0;
        while (true) {
            const bool bad = (((uv0.x ^ utag) | (uv0.y ^ utag) | (uv0.z ^ utag) | (uv0.w ^ utag)) | ((uv1.x ^ utag) | (uv1.y ^ utag) | (uv1.z ^ utag) | (uv1.w ^ utag))) & 0x70007u;
            if (!__any_sync(0xffffffffu, bad)) break;
            if (++it > SPIN_LIMIT) TRAP();
            if (bad) { uv0 = ld_poll(usrc); uv1 = ld_poll(usrc + 1); }
        }
        STAMP(6);
        DBG(4, it);
        const uint32_t ub = sb + SM_U + UPAD * 16 + 4 * USLOT_B + (t128 >> 1) * 32 + (t128 & 1) * 8;
        sts64(ub, prmt(uv0.x, uv0.z, 0x5410u) ^ utag, prmt(uv1.x, uv1.z, 0x5410u) ^ utag);
        sts64(ub + 16, prmt(uv0.x, uv0.z, 0x7632u) ^ utag, prmt(uv1.x, uv1.z, 0x7632u) ^ utag);
        sts64(ub + ULO_B, prmt(uv0.y, uv0.w, 0x5410u) ^ utag, prmt(uv1.y, uv1.w, 0x5410u) ^ utag);
        sts64(ub + ULO_B + 16, prmt(uv0.y, uv0.w, 0x7632u) ^ utag, prmt(uv1.y, uv1.w, 0x7632u) ^ utag);
    }
    if (warp < 3 && elect_one()) tma_st_3d(warp < 2 ? &tm_y : &tm_z, sb + SM_ZERO, warp < 2 ? 128 * b : 32 * (512 + P), 0, 2 * (warp < 2 ? warp : odd));
    WPOINT(5, warp - 3);
    mbar_wait(bar_r);
    fence_async();
    bar_sync(0, NWRK);
    STAMP(7);
    uint32_t hv0 = 0;
    {
        if (warp >= 12) WPOINT(6, 19 - warp);
        CONV_BODY
        WPOINT(7, 19 - warp);
        bar_sync(0, NWRK);
        STAMP(8);
        size_t ycopy = 0;
        auto hook = [&](auto gi) {
                     constexpr int G = decltype(gi)::value;
                     if (G == 4 && warp == HINTW) hv0 = ld_poll32(p.s->hint + (lane_v() & 7) * 32);
                     if (G == 5) mbar_wait(bar_h);
                     if (G == 1 || G == 2) WPOINT(7 + G, warp - 16);
                     if (G == 3) { WPOINT(10, warp - 12); WPOINT(12, warp - 8); WPOINT(14, warp - 4); }
                     if (G == 5) { WPOINT(11, warp - 13); WPOINT(13, warp - 9); WPOINT(15, warp - 5); }
                     if (G == 1 && warp >= 17 && elect_one())
                         bulk_s2g(warp == 17 ? p.s->part + b * (PBYTES / 4) : warp == 18 ? p.s->rows + b * 1152 : p.s->sc + b * 32, sb + SM_ZERO, warp == 17 ? PBYTES : warp == 18 ? 4608 : 32);
                     if (G == 4 && warp >= 17 && elect_one()) {
                         asm volatile("cp.async.bulk.wait_group 0;\n" ::: "memory");
                         hint_arrive(p.s->hint, 2, b & 7);
                     }
                     if (G == 1 && warp < 3) {
                         if (elect_one()) {
                             asm volatile("cp.async.bulk.wait_group 0;\n" ::: "memory");
                             mbar_arrive(bar_h);
                             hint_arrive(p.s->hint, 0, b & 7);
                         }
                         __syncwarp();
                         STAMP(17);
                     }
                 };
        conv_main(c, acc, sb, sel, reinterpret_cast<unsigned char*>(p.s->y), warp, ycopy, hook);
        STAMP(10);
    }
    {
    const int warp = warp_v(), lane = lane_v(), tid = 32 * warp + lane, g = lane >> 2, t = lane & 3;
    if (warp == HINTW) {
        const uint32_t target = (lds32(s_cnt + 4) + 1u) * 48u;
        if (__any_sync(0xffffffffu, (int)(hv0 - target) < 0)) hint_wait(p.s->hint, 0, target);
    }
    const unsigned char* ys = reinterpret_cast<const unsigned char*>(p.s->y) + ((size_t)P * DM + 32 * warp + 8 * (g >> 1) + (g & 1)) * 64 + odd * 32 + t * 8;
    STAMP(27);
    bar_sync(0, NWRK);
    STAMP(11);
    const uint32_t zr = warp >> 8;
    auto late_rows = [&](auto pub) {
        const uint32_t k = lds32(s_key + (lane & 7) * 4), ep = lds32(s_cnt + 4);
        const bool late = k & 256u, mine = late && ((k & 255u) >> 1) == (uint32_t)b;
        uint32_t todo = __ballot_sync(0xffffffffu, mine) & 0xffu;
        if (todo) {
#pragma unroll 1
            while (todo) {
                const int s = __ffs(todo) - 1, row = (__shfl_sync(0xffffffffu, k, s) >> 9) & 15;
                todo &= todo - 1;
                if ((row & 7) == g) pub(row & 8, 2 * NCTA + s);
            }
            __threadfence();
            bar_sync(0, NWRK);
            if (tid < NSEL && mine) *reinterpret_cast<volatile unsigned*>(p.s->flag + tid) = ep + 1u;
        }
        int it = 0;
        while (__any_sync(0xffffffffu, late && ld_poll32(p.s->flag + (lane & 7)) != ep + 1u)) { if (++it > SPIN_LIMIT) TRAP(); }
        __threadfence();
        const int gs = tid / 36;
        const uint4* src = reinterpret_cast<const uint4*>(p.s->rows) + __shfl_sync(0xffffffffu, late ? 2 * NCTA + (lane & 7) : (k & 255u), gs & 7) * 144 + 36 * odd + (tid - gs * 36);
        if (tid < 288) {
            uint4 v0;
            do { v0 = ld_poll(src); if (++it > SPIN_LIMIT) TRAP(); } while (!v0.x);
            sts128(sb + SM_XS + gs * XS_PITCH + (tid - gs * 36) * 16, v0.x, v0.y, v0.z, v0.w);
        }
        bar_sync(0, NWRK);
    };
    if (warp >= 18) {
        if (warp == 18) {
            uint32_t* const kp = pin(p.s->sc + 32 * b, zr);
            const uint32_t kid = pin(0x30000000u | ((lane & 15) << 9) | 2 * b, zr), ka = pin(s_k16 + (lane & 15) * 4, zr), kb = pin(s_k16 + (lane & 16) * 2, zr);
            bar_sync(8, 640);
            float mb, rc;
            ln_finish<18>(sb + SM_LNP, lane, mb, rc);
            if (lane < 16) stat_store(s_stat + lane * 8, mb, rc, 0u);
            bar_arrive(13, 608);
            bar_sync(10, 608);
            const float r = sum18(sb + SM_LNP + (32 + (lane & 15)) * 80);
            const uint32_t bits = pack_bf16(0.f, r);
            const uint32_t me = (((bits ^ ((uint32_t)((int)bits >> 31) & 0x7fffffffu)) >> 3) & 0x1fffe000u) ^ kid;
            sts32(ka, me);
            __syncwarp();
            const uint4 v = lds128(kb), w = lds128(kb + 16);
#define GT(x) ((me - (x)) >> 31)
            uint32_t rank = pin(GT(v.x) + GT(v.y) + GT(v.z), zr) + pin(GT(v.w) + GT(w.x) + GT(w.y), zr) + pin(GT(w.z) + GT(w.w), zr);
#undef GT
            rank += __shfl_xor_sync(0xffffffffu, rank, 16);
            if (lane < 16) { if (rank < 8) stg32(kp + rank, me + (rank < 2 ? rank : 256u)); }
            else sts32(ka + (s_wm - s_k16), rank);
            bar_arrive(11, 640);
        }
        const uint4* ksrc = pin(reinterpret_cast<const uint4*>(p.s->sc) + 8 * lane, zr);
        const uint4* rsrc = pin(reinterpret_cast<const uint4*>(p.s->rows) + 36 * odd + t, zr);
        if (warp == 19) {
            hint_wait(p.s->hint, 2, (lds32(s_cnt + 4) + 1u) * 48u);
            bar_sync(8, 640);
            WPOINT(16, 0);
            WPOINT(17, 0);
            bar_sync(11, 640);
        }
        bool slow = false;
        int it = 0;
        if (warp == 19) {
        uint4 q[4];
#pragma unroll
        for (int i = 0; i < 4; i++) q[i] = ld_poll(ksrc + 256 * i);
        while (true) {
            uint32_t a[4];
#pragma unroll
            for (int i = 0; i < 4; i++) a[i] = q[i].x & q[i].y & q[i].z & q[i].w;
            if (__all_sync(0xffffffffu, a[0] & a[1] & a[2] & a[3])) break;
#pragma unroll
            for (int i = 0; i < 4; i++)
                if (!a[i]) q[i] = ld_poll(ksrc + 256 * i);
            if (++it > SPIN_LIMIT) TRAP();
        }
        bar_arrive(9, 608);
        STAMP(16);
        auto merge = [](const uint4& x, const uint4& y) {
            const uint32_t a = max(x.x, y.w), c = max(x.y, y.z), d = max(x.z, y.y), e = max(x.w, y.x);
            const uint32_t a2 = max(a, d), d2 = min(a, d), c2 = max(c, e), e2 = min(c, e);
            return make_uint4(max(a2, c2), min(a2, c2), max(d2, e2), min(d2, e2));
        };
        uint4 h = merge(merge(q[0], q[1]), merge(q[2], q[3]));
        uint4 v[9];
        uint32_t key = 0;
#pragma unroll
        for (int s = 0; s < 8; s++) {
            const uint32_t m = __reduce_max_sync(0xffffffffu, h.x);
            const bool w = h.x == m;
            h.x = w ? h.y : h.x; h.y = w ? h.z : h.y; h.z = w ? h.w : h.z; h.w = w ? 0u : h.w;
            if (g == s) key = m;
        }
        rsrc += (key & 255u) * 144;
#pragma unroll
        for (int j = 0; j < 9; j++) v[j] = ld_poll(rsrc + 4 * j);
        slow = __any_sync(0xffffffffu, key & 256u);
        STAMP(18);
        if (__any_sync(0xffffffffu, h.x == 0u)) {
            uint4 r[4];
            it = 0;
            while (true) {
#pragma unroll
                for (int i = 0; i < 4; i++) r[i] = ld_poll(ksrc + 256 * i + 1);
                if (__all_sync(0xffffffffu, all_nz(r[0]) && all_nz(r[1]) && all_nz(r[2]) && all_nz(r[3]))) break;
                if (++it > SPIN_LIMIT) TRAP();
            }
            uint32_t m = 1u << 30;
#pragma unroll 1
            for (int s = 0; s < 8; s++) {
                uint32_t x = 0;
#pragma unroll
                for (int i = 0; i < 4; i++) {
                    x = max(max(max(x, q[i].x - m), max(q[i].y - m, q[i].z - m)), q[i].w - m);
                    x = max(max(max(x, r[i].x - m), max(r[i].y - m, r[i].z - m)), r[i].w - m);
                }
                m += __reduce_max_sync(0xffffffffu, x);
                if (g == s) key = m;
            }
            slow = true;
        }
        sts32(s_key + g * 4, key);
        bar_arrive(12, 608);
        if (!slow) {
            it = 0;
            while (true) {
                const uint32_t mn = min(min(min(min(v[0].x, v[1].x), v[2].x), min(min(v[3].x, v[4].x), v[5].x)), min(min(v[6].x, v[7].x), v[8].x));
                if (__all_sync(0xffffffffu, mn)) break;
                if (++it > SPIN_LIMIT) TRAP();
#pragma unroll
                for (int j = 0; j < 9; j++) v[j] = ld_poll(rsrc + 4 * j);
            }
#pragma unroll
            for (int j = 0; j < 9; j++) sts128(sb + SM_XS + g * XS_PITCH + t * 16 + j * 64, v[j].x, v[j].y, v[j].z, v[j].w);
        }
        }
        if (bar_or(0, NWRK, slow)) late_rows([](bool, int) {});
        STAMP(19);
        const int fl = 16 * (b & 1) + ((tid >> 2) & 15), fc = 16 * (b >> 1) + (fl >> 2) + 8 * ((tid >> 1) & 1), fsl = 2 * (fl & 3) + (tid & 1);
        const uint32_t kk = lds32(s_key + fsl * 4);
        const uint32_t* fsrc = p.s->rows + ((kk & 256u) ? 2 * NCTA + fsl : (kk & 255u)) * DM + (fc >> 1);
        uint32_t hw = 1u, uw = 1u;
        if (b < 72) { uw = ld_poll32(fsrc); hw = ld_poll32(fsrc + 288); }
        if (b < 72) {
            it = 0;
            while (!hw || !uw) { uw = ld_poll32(fsrc); hw = ld_poll32(fsrc + 288); if (++it > SPIN_LIMIT) TRAP(); }
            const int row = (kk >> 9) & 15, ftok = 8 * (kk & 252u) + (kk & 2u) + TOKEN_OF(row & 7) + (row & 8);
            const unsigned k16 = (kk >> 13) & 0xffffu;
            const unsigned bits = (k16 & 0x8000u) ? (k16 & 0x7fffu) : (~k16 & 0xffffu);
            const float rs = __uint_as_float(pin(__float_as_uint(rbf(__fdividef(1.0f, 1.0f + __expf(-__uint_as_float(bits << 16))))), zr));
            bf16* const op = pin(p.out + (size_t)ftok * DM + fc, zr);
            const float uv = (fc & 1) ? bf_hi(uw) : bf_lo(uw), hv = (fc & 1) ? bf_hi(hw) : bf_lo(hw);
            bar_sync(14, 576);
            float v0 = 0.f, v1 = 0.f, v2 = 0.f, v3 = 0.f;
            const uint32_t a = sb + SM_EX + (tid - 576) * 4;
#pragma unroll
            for (int i = 0; i < 16; i += 4) { v0 += ldsf(a + i * 256); v1 += ldsf(a + i * 256 + 256); v2 += ldsf(a + i * 256 + 512); v3 += ldsf(a + i * 256 + 768); }
            const float y3 = rbf(rbf(((v0 + v1) + (v2 + v3)) * 512.0f) * rs);
            asm volatile("st.global.u16 [%0], %1;\n" ::"l"(op), "h"((unsigned short)pack_bf16(hv + rbf(uv + y3), 0.f)) : "memory");
        }
        if (b == 0 && tid >= 632) *reinterpret_cast<volatile unsigned*>(p.s->hint + (tid & 7) * 32 + 1) = lds32(s_cnt + 4) + 1u;
    } else {
        uint32_t H[2][4], U2[2][4], WA[9][4], WD[18];
        const int fkh = warp >= 9, fmt = warp - 9 * fkh;
        auto load_wa = [&](auto k0, auto k1) {
            if (k0.value >= k1.value) return;
            if (k0.value == 0) mbar_wait(bar_w);
            const int mi = lane >> 3, rr = lane & 7;
            const uint32_t aad = sb + SM_WG + (mi & 1) * SM_WU + (fkh * 144 + rr + 8 * (mi >> 1)) * W_PITCH + fmt * 16;
#pragma unroll
            for (int k = k0.value; k < k1.value; k++) ldsm_x4_t(WA[k][0], WA[k][1], WA[k][2], WA[k][3], aad + k * 16 * W_PITCH);
        };
        auto load_wd = [&]() {
            mbar_wait(bar_d);
            const int mi = lane >> 3, rr = lane & 7;
            const int c8 = 2 * warp + (mi & 1), bx = c8 / 9;
            const uint32_t base = sb + SM_WD + bx * 10368 + (c8 - 9 * bx) * 16 + rr * W_PITCH;
#pragma unroll
            for (int k = 0; k < 4; k++) ldsm_x4_t(WD[4 * k], WD[4 * k + 1], WD[4 * k + 2], WD[4 * k + 3], base + (k * 16 + 8 * (mi >> 1)) * W_PITCH);
            ldsm_x2_t(WD[16], WD[17], base + 64 * W_PITCH);
        };
        auto publish = [&](bool hi, int slot) {
            uint4* rowp = reinterpret_cast<uint4*>(p.s->rows) + slot * 144 + warp * 4 + t;
            stg128(rowp, nzw(hi ? U2[1][0] : U2[0][0]), nzw(hi ? U2[1][1] : U2[0][1]), nzw(hi ? U2[1][2] : U2[0][2]), nzw(hi ? U2[1][3] : U2[0][3]));
            stg128(rowp + 72, nzw(hi ? H[1][0] : H[0][0]), nzw(hi ? H[1][1] : H[0][1]), nzw(hi ? H[1][2] : H[0][2]), nzw(hi ? H[1][3] : H[0][3]));
        };
        uint4 wr = make_uint4(0u, 0u, 0u, 0u);
        {
            uint2 yv[4];
#pragma unroll
            for (int k = 0; k < 4; k++) yv[k] = ld_poll64(ys + k * 128);
            if (g == 0) wr = ldg128(p.wr + 32 * warp + 8 * t);
            const uint4 x0 = lds128(sb + SM_XT + warp * 1024 + lane * 16), x1 = lds128(sb + SM_XT + warp * 1024 + 512 + lane * 16);
            load_wa(IC<0>(), IC<WA0>());
            int it = 0;
            while (!__all_sync(0xffffffffu, yv[0].x && yv[1].x && yv[2].x && yv[3].x)) {
#pragma unroll
                for (int k = 0; k < 4; k++) yv[k] = ld_poll64(ys + k * 128);
                if (++it > SPIN_LIMIT) TRAP();
            }
            STAMP(12);
            const uint32_t Z[2][4] = {{x0.x, x0.y, x0.z, x0.w}, {x1.x, x1.y, x1.z, x1.w}};
#pragma unroll
            for (int k = 0; k < 4; k++) {
                H[0][k] = hadd2_bf(Z[0][k], movm(yv[k].x));
                H[1][k] = hadd2_bf(Z[1][k], movm(yv[k].y));
            }
            ln_partial<4>(H, sb + SM_LNP, warp, g, t);
        }
        bar_arrive(8, 640);
        load_wa(IC<WA0>(), IC<WA1>());
        STAMP(13);
        bar_sync(13, 608);
        STAMP(14);
#pragma unroll
        for (int hf = 0; hf < 2; hf++) {
            const uint2 st = lds64(s_stat + (g + 8 * hf) * 8);
#pragma unroll
            for (int k = 0; k < 4; k++) U2[hf][k] = ln_apply(H[hf][k], st);
        }
        {
            float cs[4] = {0.f, 0.f, 0.f, 0.f};
            mma_bf16(cs, U2[0][0], U2[1][0], U2[0][1], U2[1][1], wr.x, wr.y);
            mma_bf16(cs, U2[0][2], U2[1][2], U2[0][3], U2[1][3], wr.z, wr.w);
            if (t == 0) { stsf(sb + SM_LNP + ((32 + g) * 20 + warp) * 4, cs[0]); stsf(sb + SM_LNP + ((40 + g) * 20 + warp) * 4, cs[2]); }
            bar_arrive(10, 608);
        }
        load_wa(IC<WA1>(), IC<WA2>());
        bar_sync(11, 640);
        {
            const uint32_t rk[2] = {lds32(s_wm + g * 4), lds32(s_wm + 32 + g * 4)};
            uint32_t lo = min(rk[0], rk[1]), hi = max(rk[0], rk[1]);
#pragma unroll 1
            while (lo < 2) { publish(lo == rk[1], 2 * b + lo); lo = hi; hi = 16; }
        }
        load_wa(IC<WA2>(), IC<WA3>());
        bar_sync(9, 608);
        load_wa(IC<WA3>(), IC<9>());
#pragma unroll
        for (int hf = 0; hf < 2; hf++)
            sts128(sb + SM_OUT + (g + 8 * hf) * OUT_PITCH + warp * 64 + t * 16,
                   hadd2_bf(H[hf][0], U2[hf][0]), hadd2_bf(H[hf][1], U2[hf][1]), hadd2_bf(H[hf][2], U2[hf][2]), hadd2_bf(H[hf][3], U2[hf][3]));
        fence_async();
        WPOINT(18, warp - 17);
        if (WDAT == 0) load_wd();
        const uint32_t bad = pin(sb + SM_XS + (lane & 7) * XS_PITCH + (fkh * 144 + 8 * (lane >> 3)) * 2, zr), ex = pin(sb + SM_EX + (18 * odd + warp) * 512 + lane * 16, zr);
        uint32_t* const pp = pin(p.s->part + ((size_t)(2 * (18 * odd + warp) + (lane >> 4)) * 64 + P) * 32 + (lane & 15) * 2, zr);
        bar_sync(12, 608);
        if (warp < 16 && !__any_sync(0xffffffffu, (lds32(s_key + (lane & 7) * 4) & 0x1efeu) == (uint32_t)((warp << 9) | 2 * b)) && elect_one())
            bulk_s2g(p.out + (size_t)(32 * P + 2 * odd + TOKEN_OF(warp & 7) + (warp & 8)) * DM, sb + SM_OUT + warp * OUT_PITCH, DM * 2);
        STAMP(15);
        if (bar_or(0, NWRK, false)) late_rows(publish);
        STAMP(19);
        {
            float c4[3][4];
#pragma unroll
            for (int i = 0; i < 3; i++)
#pragma unroll
                for (int j = 0; j < 4; j++) c4[i][j] = 0.f;
#pragma unroll
            for (int k = 0; k < 10; k += 2) {
                uint32_t b0, b1, b2, b3;
                ldsm_x4(b0, b1, b2, b3, bad + k * 32);
                mma_bf16(c4[k % 3], WA[k][0], WA[k][1], WA[k][2], WA[k][3], b0, b1);
                if (k < 8) mma_bf16(c4[(k + 1) % 3], WA[k + 1][0], WA[k + 1][1], WA[k + 1][2], WA[k + 1][3], b2, b3);
            }
#pragma unroll
            for (int j = 0; j < 4; j++) c4[0][j] += c4[1][j] + c4[2][j];
            asm volatile("st.async.shared::cluster.mbarrier::complete_tx::bytes.v4.b32 [%0], {%1,%2,%3,%4}, [%5];\n"
                         ::"r"(ex ^ 0x1000000u), "r"(__float_as_uint(c4[0][0])), "r"(__float_as_uint(c4[0][1])), "r"(__float_as_uint(c4[0][2])), "r"(__float_as_uint(c4[0][3])), "r"(bar_g ^ 0x1000000u) : "memory");
            sts128f(ex, c4[0]);
            if (warp >= 9) bar_arrive(6, 576);
            if (WDAT == 1) load_wd();
        }
        STAMP(20);
        if (warp < 9) {
            bar_sync(6, 576);
            mbar_wait(bar_g);
            const uint32_t ex = sb + SM_EX + tid * 16;
            const uint4 u = lds128(ex), v = lds128(ex + 4608), w = lds128(ex + 9216), x = lds128(ex + 13824);
#define S4(f) rbf((__uint_as_float(u.f) + __uint_as_float(v.f)) + (__uint_as_float(w.f) + __uint_as_float(x.f)))
            const float G0 = S4(x), G1 = S4(y), U0 = S4(z), U1 = S4(w);
#undef S4
            sts32(sb + SM_GU + tid * 4, pack_bf16(rbf(__fdividef(G0, 1.0f + __expf(-G0))) * U0, rbf(__fdividef(G1, 1.0f + __expf(-G1))) * U1));
        }
        const uint2* src = pin(reinterpret_cast<const uint2*>(p.s->part) + (size_t)b * 1024 + tid, zr);
        bar_sync(7, 576);
        STAMP(21);
        {
            uint32_t gb[9];
            ldsm_x4_t(gb[0], gb[1], gb[2], gb[3], sb + SM_GU + lane * 16);
            ldsm_x4_t(gb[4], gb[5], gb[6], gb[7], sb + SM_GU + 512 + lane * 16);
            ldsm_x1_t(gb[8], sb + SM_GU + 1024 + (lane & 7) * 16);
            float c4[4] = {0.f, 0.f, 0.f, 0.f}, d4[4] = {0.f, 0.f, 0.f, 0.f};
            mma_bf16(c4, WD[0], WD[1], WD[2], WD[3], gb[0], gb[1]);
            mma_bf16(d4, WD[4], WD[5], WD[6], WD[7], gb[2], gb[3]);
            mma_bf16(c4, WD[8], WD[9], WD[10], WD[11], gb[4], gb[5]);
            mma_bf16(d4, WD[12], WD[13], WD[14], WD[15], gb[6], gb[7]);
            mma_bf16(c4, WD[16], WD[17], 0u, 0u, gb[8], 0u);
            const float v0 = c4[0] + d4[0], v1 = c4[1] + d4[1], v2 = c4[2] + d4[2], v3 = c4[3] + d4[3];
            const uint32_t e = min(max(__float_as_uint(fmaxf(fmaxf(fabsf(v0), fabsf(v1)), fmaxf(fabsf(v2), fabsf(v3)))) >> 23, 16u), 244u);
            const float sc = __uint_as_float((245u - e) << 23);
            stg64(pp, pack_f16(v0 * sc, v1 * sc) | ((e * 0x8002000u) & 0x60006000u), pack_f16(v2 * sc, v3 * sc) | ((e * 0x800200u) & 0x60006000u));
        }
        asm volatile("cp.async.bulk.wait_group.read 0;\n" ::: "memory");
        STAMP(22);
        if (b < 72 && warp < 16) {
            uint2 a, c;
            int it = 0;
            a = ld_poll64(src); c = ld_poll64(src + 512);
            while (!__all_sync(0xffffffffu, a.y && c.y)) {
                a = ld_poll64(src); c = ld_poll64(src + 512);
                if (++it > SPIN_LIMIT) TRAP();
            }
            STAMP(24);
            const float ea = __uint_as_float((((a.y & 0x60006000u) | ((a.x >> 4) & 0x06000600u)) * 0x4001u) & 0x7f800000u);
            const float ec = __uint_as_float((((c.y & 0x60006000u) | ((c.x >> 4) & 0x06000600u)) * 0x4001u) & 0x7f800000u);
            a.x &= 0x9fff9fffu; a.y &= 0x9fff9fffu; c.x &= 0x9fff9fffu; c.y &= 0x9fff9fffu;
            const float s0 = fmaf(h_lo(a.x), ea, h_lo(c.x) * ec), s1 = fmaf(h_hi(a.x), ea, h_hi(c.x) * ec), s2 = fmaf(h_lo(a.y), ea, h_lo(c.y) * ec), s3 = fmaf(h_hi(a.y), ea, h_hi(c.y) * ec);
            const bool up = lane & 16;
            const float r0 = __shfl_xor_sync(0xffffffffu, up ? s0 : s2, 16), r1 = __shfl_xor_sync(0xffffffffu, up ? s1 : s3, 16);
            sts64f(sb + SM_EX + warp * 256 + (lane & 15) * 16 + (up ? 8 : 0), (up ? s2 : s0) + r0, (up ? s3 : s1) + r1);
            bar_arrive(14, 576);
        }
    }
    STAMP(25);
    }
}

typedef CUresult (*PFN_tmEncode)(CUtensorMap*, CUtensorMapDataType, cuuint32_t, void*, const cuuint64_t*, const cuuint64_t*, const cuuint32_t*,
                                 const cuuint32_t*, CUtensorMapInterleave, CUtensorMapSwizzle, CUtensorMapL2promotion, CUtensorMapFloatOOBfill);

extern "C" void kernel_launch(void* const* d_in, const int* in_sizes, int n_in, void* d_out, int out_size) {
    Params p;
    p.x = (const bf16*)d_in[0];
    p.lar = (const bf16*)d_in[1];
    p.aim = (const bf16*)d_in[2];
    p.cre = (const bf16*)d_in[3];
    p.cim = (const bf16*)d_in[4];
    p.ldt = (const bf16*)d_in[5];
    p.dsk = (const bf16*)d_in[6];
    p.wr = (const bf16*)d_in[8];
    p.wpf = (const bf16*)d_in[PFW];
    p.out = (bf16*)d_out;
    static PFN_tmEncode enc = nullptr;
    static void* scratch = nullptr;
    if (!enc) {
        cudaFuncSetAttribute(fused_kernel, cudaFuncAttributeMaxDynamicSharedMemorySize, SMEM_TOTAL);
        void* fn = nullptr;
        cudaDriverEntryPointQueryResult qr;
        cudaGetDriverEntryPoint("cuTensorMapEncodeTiled", &fn, cudaEnableDefault, &qr);
        enc = (PFN_tmEncode)fn;
        cudaGetSymbolAddress(&scratch, g_scratch);
    }
    p.s = (Scratch*)scratch;
    CUtensorMap tm_g, tm_u, tm_d, tm_x, tm_y, tm_z;
    const cuuint64_t dims[2] = {FF, DM}, strides[1] = {FF * 2};
    const cuuint32_t box[2] = {72, 48}, es[2] = {1, 1};
    enc(&tm_g, CU_TENSOR_MAP_DATA_TYPE_BFLOAT16, 2, d_in[9], dims, strides, box, es, CU_TENSOR_MAP_INTERLEAVE_NONE, CU_TENSOR_MAP_SWIZZLE_NONE,
        CU_TENSOR_MAP_L2_PROMOTION_NONE, CU_TENSOR_MAP_FLOAT_OOB_FILL_NONE);
    enc(&tm_u, CU_TENSOR_MAP_DATA_TYPE_BFLOAT16, 2, d_in[10], dims, strides, box, es, CU_TENSOR_MAP_INTERLEAVE_NONE, CU_TENSOR_MAP_SWIZZLE_NONE,
        CU_TENSOR_MAP_L2_PROMOTION_NONE, CU_TENSOR_MAP_FLOAT_OOB_FILL_NONE);
    const cuuint64_t ddims[2] = {DM, FF}, dstrides[1] = {DM * 2};
    const cuuint32_t dbox[2] = {72, 72};
    enc(&tm_d, CU_TENSOR_MAP_DATA_TYPE_BFLOAT16, 2, d_in[11], ddims, dstrides, dbox, es, CU_TENSOR_MAP_INTERLEAVE_NONE, CU_TENSOR_MAP_SWIZZLE_NONE,
        CU_TENSOR_MAP_L2_PROMOTION_NONE, CU_TENSOR_MAP_FLOAT_OOB_FILL_NONE);
    const cuuint64_t xdims[3] = {DM, LSEQ / 16, 16}, xstrides[2] = {16 * DM * 2, DM * 2};
    const cuuint32_t xbox[3] = {8, LSEQ / 16, 8}, es3[3] = {1, 1, 1};
    enc(&tm_x, CU_TENSOR_MAP_DATA_TYPE_BFLOAT16, 3, d_in[0], xdims, xstrides, xbox, es3, CU_TENSOR_MAP_INTERLEAVE_NONE, CU_TENSOR_MAP_SWIZZLE_NONE,
        CU_TENSOR_MAP_L2_PROMOTION_NONE, CU_TENSOR_MAP_FLOAT_OOB_FILL_NONE);
    const cuuint64_t ydims[3] = {DM * 32, 16, 4}, ystrides[2] = {DM * 64, 16 * DM * 64};
    const cuuint32_t ybox[3] = {128, 16, 2}, zbox[3] = {32, 16, 2};
    enc(&tm_y, CU_TENSOR_MAP_DATA_TYPE_BFLOAT16, 3, p.s->y, ydims, ystrides, ybox, es3, CU_TENSOR_MAP_INTERLEAVE_NONE, CU_TENSOR_MAP_SWIZZLE_NONE,
        CU_TENSOR_MAP_L2_PROMOTION_NONE, CU_TENSOR_MAP_FLOAT_OOB_FILL_NONE);
    enc(&tm_z, CU_TENSOR_MAP_DATA_TYPE_BFLOAT16, 3, p.s->y, ydims, ystrides, zbox, es3, CU_TENSOR_MAP_INTERLEAVE_NONE, CU_TENSOR_MAP_SWIZZLE_NONE,
        CU_TENSOR_MAP_L2_PROMOTION_NONE, CU_TENSOR_MAP_FLOAT_OOB_FILL_NONE);
    fused_kernel<<<NCTA, NTHR, SMEM_TOTAL>>>(p, tm_g, tm_u, tm_d, tm_x, tm_y, tm_z);
}
```

```cpp
#include <cuda_runtime.h>
#include <cuda.h>
#include <cuda_fp16.h>
#include <cuda_bf16.h>
#include <stdint.h>

#define LSEQ 2048
#define DM 576
#define NST 128
#define FF 4608
#define NSEL 8
#define NCTA 128
#define NTHR 640
#define NWRK 640

typedef __nv_bfloat16 bf16;

#define SM_WG 0
#define SM_WU 41472
#define SM_WD 82944
#define W_PITCH 144
#define SM_XC 50176
#define SM_ZERO SM_WD
#define SM_TB (SM_WD + 9216)
#define SM_PL 124416
#define PL_B 10752
#define SM_XT (SM_TB + 20 * TBW)
#define SM_U (SM_XT + 18432)
#define UPAD 8
#define ULO_B ((UPAD + 128) * 16)
#define USLOT_B (2 * ULO_B)
#define SM_KW (SM_U + 5 * USLOT_B)
#define KW_B 3600
#define KW_T2 1152
#define KW_KH 656
#define KW_T3 2464
#define SM_MISC (SM_KW + 5 * KW_B)
#define SM_LNP (SM_MISC + 576)
#define SMEM_TOTAL (SM_LNP + 4096)
#define TBP 112
#define TBW (32 * TBP)
#define SM_OUT SM_PL
#define OUT_PITCH 1216
#define SM_XS (SM_PL + 19456)
#define XS_PITCH 592
#define SM_EX (SM_PL + 24320)
#define SM_GU (SM_PL + 42752)

struct __align__(128) Scratch {
    unsigned hint[8 * 32];
    unsigned flag[32];
    uint32_t sc[NCTA * 32];
    uint32_t st[LSEQ * 2];
    uint32_t uT[64 * (LSEQ / 2)];
    uint32_t y[NCTA * DM * 8];
    uint32_t part[72 * 64 * 32];
    uint32_t rows[(2 * NCTA + NSEL) * DM];
};
__device__ Scratch g_scratch;
#define STAMP(i)
#define DBG(i, v)

__device__ __forceinline__ float rbf(float x) {
    uint32_t r;
    asm("cvt.rn.bf16x2.f32 %0, %1, %2;\n" : "=r"(r) : "f"(x), "f"(0.f));
    return __uint_as_float(r & 0xffff0000u);
}
__device__ __forceinline__ uint32_t pack_bf16(float lo, float hi) {
    uint32_t r;
    asm("cvt.rn.bf16x2.f32 %0, %1, %2;\n" : "=r"(r) : "f"(hi), "f"(lo));
    return r;
}
__device__ __forceinline__ uint32_t pack_f16(float lo, float hi) {
    uint32_t r;
    asm("cvt.rn.f16x2.f32 %0, %1, %2;\n" : "=r"(r) : "f"(hi), "f"(lo));
    return r;
}
__device__ __forceinline__ uint32_t pack_f16_rz(float lo, float hi) {
    uint32_t r;
    asm("cvt.rz.f16x2.f32 %0, %1, %2;\n" : "=r"(r) : "f"(hi), "f"(lo));
    return r;
}
__device__ __forceinline__ float bf_lo(uint32_t w) { return __uint_as_float(w << 16); }
__device__ __forceinline__ float bf_hi(uint32_t w) { return __uint_as_float(w & 0xffff0000u); }
__device__ __forceinline__ uint32_t hadd2_bf(uint32_t a, uint32_t b) {
    __nv_bfloat162 r = __hadd2_rn(*reinterpret_cast<__nv_bfloat162*>(&a), *reinterpret_cast<__nv_bfloat162*>(&b));
    return *reinterpret_cast<uint32_t*>(&r);
}
__device__ __forceinline__ uint32_t hsub2_bf(uint32_t a, uint32_t b) {
    __nv_bfloat162 r = __hsub2_rn(*reinterpret_cast<__nv_bfloat162*>(&a), *reinterpret_cast<__nv_bfloat162*>(&b));
    return *reinterpret_cast<uint32_t*>(&r);
}
__device__ __forceinline__ uint32_t hmul2_bf(uint32_t a, uint32_t b) {
    __nv_bfloat162 r = __hmul2_rn(*reinterpret_cast<__nv_bfloat162*>(&a), *reinterpret_cast<__nv_bfloat162*>(&b));
    return *reinterpret_cast<uint32_t*>(&r);
}
__device__ __forceinline__ uint32_t hfma2_bf(uint32_t a, uint32_t b, uint32_t c) { uint32_t r; asm("fma.rn.bf16x2 %0, %1, %2, %3;\n" : "=r"(r) : "r"(a), "r"(b), "r"(c)); return r; }
__device__ __forceinline__ uint32_t hmul2(uint32_t a, uint32_t b) { uint32_t r; asm("mul.rn.f16x2 %0, %1, %2;\n" : "=r"(r) : "r"(a), "r"(b)); return r; }
__device__ __forceinline__ uint32_t hadd2(uint32_t a, uint32_t b) { uint32_t r; asm("add.rn.f16x2 %0, %1, %2;\n" : "=r"(r) : "r"(a), "r"(b)); return r; }
__device__ __forceinline__ uint32_t hfma2(uint32_t a, uint32_t b, uint32_t c) { uint32_t r; asm("fma.rn.f16x2 %0, %1, %2, %3;\n" : "=r"(r) : "r"(a), "r"(b), "r"(c)); return r; }
__device__ __forceinline__ uint32_t nzw(uint32_t w) { return w ? w : 0x8000u; }
__device__ __forceinline__ uint32_t nzf(float f) { const uint32_t w = __float_as_uint(f); return w ? w : 0x80000000u; }
__device__ __forceinline__ uint32_t smem_u32(const void* p) { return (uint32_t)__cvta_generic_to_shared(p); }
__device__ __forceinline__ uint32_t lds32(uint32_t addr) {
    uint32_t v;
    asm volatile("ld.shared.u32 %0, [%1];\n" : "=r"(v) : "r"(addr) : "memory");
    return v;
}
__device__ __forceinline__ uint32_t lds16(uint32_t addr) {
    unsigned short v;
    asm volatile("ld.shared.u16 %0, [%1];\n" : "=h"(v) : "r"(addr) : "memory");
    return v;
}
__device__ __forceinline__ uint2 lds64(uint32_t addr) {
    uint2 v;
    asm volatile("ld.shared.v2.u32 {%0,%1}, [%2];\n" : "=r"(v.x), "=r"(v.y) : "r"(addr) : "memory");
    return v;
}
__device__ __forceinline__ uint4 lds128(uint32_t addr) {
    uint4 v;
    asm volatile("ld.shared.v4.u32 {%0,%1,%2,%3}, [%4];\n" : "=r"(v.x), "=r"(v.y), "=r"(v.z), "=r"(v.w) : "r"(addr) : "memory");
    return v;
}
__device__ __forceinline__ float ldsf(uint32_t addr) { return __uint_as_float(lds32(addr)); }
__device__ __forceinline__ void sts32(uint32_t addr, uint32_t v) { asm volatile("st.shared.u32 [%0], %1;\n" ::"r"(addr), "r"(v) : "memory"); }
__device__ __forceinline__ void stsf(uint32_t addr, float v) { sts32(addr, __float_as_uint(v)); }
__device__ __forceinline__ void sts64(uint32_t addr, uint32_t a, uint32_t b) { asm volatile("st.shared.v2.u32 [%0], {%1,%2};\n" ::"r"(addr), "r"(a), "r"(b) : "memory"); }
__device__ __forceinline__ void sts64f(uint32_t addr, float a, float b) { sts64(addr, __float_as_uint(a), __float_as_uint(b)); }
__device__ __forceinline__ void sts128(uint32_t addr, uint32_t a, uint32_t b, uint32_t c, uint32_t d) {
    asm volatile("st.shared.v4.u32 [%0], {%1,%2,%3,%4};\n" ::"r"(addr), "r"(a), "r"(b), "r"(c), "r"(d) : "memory");
}
__device__ __forceinline__ void sts128f(uint32_t addr, const float (&v)[4]) {
    sts128(addr, __float_as_uint(v[0]), __float_as_uint(v[1]), __float_as_uint(v[2]), __float_as_uint(v[3]));
}
__device__ __forceinline__ void ldsm_x4(uint32_t& r0, uint32_t& r1, uint32_t& r2, uint32_t& r3, uint32_t addr) {
    asm volatile("ldmatrix.sync.aligned.m8n8.x4.shared.b16 {%0,%1,%2,%3}, [%4];\n"
                 : "=r"(r0), "=r"(r1), "=r"(r2), "=r"(r3) : "r"(addr) : "memory");
}
__device__ __forceinline__ void ldsm_x4_t(uint32_t& r0, uint32_t& r1, uint32_t& r2, uint32_t& r3, uint32_t addr) {
    asm volatile("ldmatrix.sync.aligned.m8n8.x4.trans.shared.b16 {%0,%1,%2,%3}, [%4];\n"
                 : "=r"(r0), "=r"(r1), "=r"(r2), "=r"(r3) : "r"(addr) : "memory");
}
__device__ __forceinline__ void ldsm_x2_t(uint32_t& r0, uint32_t& r1, uint32_t addr) {
    asm volatile("ldmatrix.sync.aligned.m8n8.x2.trans.shared.b16 {%0,%1}, [%2];\n" : "=r"(r0), "=r"(r1) : "r"(addr) : "memory");
}
__device__ __forceinline__ void ldsm_x1_t(uint32_t& r0, uint32_t addr) {
    asm volatile("ldmatrix.sync.aligned.m8n8.x1.trans.shared.b16 {%0}, [%1];\n" : "=r"(r0) : "r"(addr) : "memory");
}
__device__ __forceinline__ uint32_t movm(uint32_t a) {
    uint32_t d;
    asm volatile("movmatrix.sync.aligned.m8n8.trans.b16 %0, %1;\n" : "=r"(d) : "r"(a));
    return d;
}
__device__ __forceinline__ void mma_f16(float (&c)[4], uint32_t a0, uint32_t a1, uint32_t a2, uint32_t a3, uint32_t b0, uint32_t b1) {
    asm volatile(
        "mma.sync.aligned.m16n8k16.row.col.f32.f16.f16.f32 {%0,%1,%2,%3}, {%4,%5,%6,%7}, {%8,%9}, {%0,%1,%2,%3};\n"
        : "+f"(c[0]), "+f"(c[1]), "+f"(c[2]), "+f"(c[3])
        : "r"(a0), "r"(a1), "r"(a2), "r"(a3), "r"(b0), "r"(b1));
}
__device__ __forceinline__ void mma_bf16(float (&c)[4], uint32_t a0, uint32_t a1, uint32_t a2, uint32_t a3, uint32_t b0, uint32_t b1) {
    asm volatile(
        "mma.sync.aligned.m16n8k16.row.col.f32.bf16.bf16.f32 {%0,%1,%2,%3}, {%4,%5,%6,%7}, {%8,%9}, {%0,%1,%2,%3};\n"
        : "+f"(c[0]), "+f"(c[1]), "+f"(c[2]), "+f"(c[3])
        : "r"(a0), "r"(a1), "r"(a2), "r"(a3), "r"(b0), "r"(b1));
}
__device__ __forceinline__ void bar_sync(int id, int n) { asm volatile("bar.sync %0, %1;\n" ::"r"(id), "r"(n) : "memory"); }
__device__ __forceinline__ void bar_arrive(int id, int n) { asm volatile("bar.arrive %0, %1;\n" ::"r"(id), "r"(n) : "memory"); }
__device__ __forceinline__ bool bar_or(int id, int n, bool v) {
    uint32_t r;
    asm volatile("{\n.reg .pred p, q;\nsetp.ne.u32 p, %3, 0;\nbar.red.or.pred q, %1, %2, p;\nselp.u32 %0, 1, 0, q;\n}\n" : "=r"(r) : "r"(id), "r"(n), "r"((uint32_t)v) : "memory");
    return r;
}
__device__ __forceinline__ uint4 ld_poll(const void* p) {
    uint4 v;
    asm volatile("ld.relaxed.gpu.global.v4.u32 {%0,%1,%2,%3}, [%4];\n" : "=r"(v.x), "=r"(v.y), "=r"(v.z), "=r"(v.w) : "l"(p) : "memory");
    return v;
}
template <class T> __device__ __forceinline__ T* pin(T* p, uint32_t z) {
    uint32_t lo, hi;
    asm volatile("mov.b64 {%0, %1}, %2;\n" : "=r"(lo), "=r"(hi) : "l"(p));
    asm volatile("xor.b32 %0, %0, %1;\n" : "+r"(lo) : "r"(z));
    asm volatile("xor.b32 %0, %0, %1;\n" : "+r"(hi) : "r"(z));
    asm volatile("mov.b64 %0, {%1, %2};\n" : "=l"(p) : "r"(lo), "r"(hi));
    return p;
}
__device__ __forceinline__ uint32_t pin(uint32_t a, uint32_t z) { asm volatile("xor.b32 %0, %0, %1;\n" : "+r"(a) : "r"(z)); return a; }
__device__ __forceinline__ uint2 ld_poll64(const void* p) {
    uint2 v;
    asm volatile("ld.relaxed.gpu.global.v2.u32 {%0,%1}, [%2];\n" : "=r"(v.x), "=r"(v.y) : "l"(p) : "memory");
    return v;
}
__device__ __forceinline__ uint32_t ld_poll32(const void* p) {
    uint32_t v;
    asm volatile("ld.relaxed.gpu.global.u32 %0, [%1];\n" : "=r"(v) : "l"(p) : "memory");
    return v;
}
__device__ __forceinline__ uint4 ldg128(const void* p) {
    uint4 v;
    asm volatile("ld.global.nc.v4.u32 {%0,%1,%2,%3}, [%4];\n" : "=r"(v.x), "=r"(v.y), "=r"(v.z), "=r"(v.w) : "l"(p));
    return v;
}
__device__ __forceinline__ uint2 ldg64(const void* p) {
    uint2 v;
    asm volatile("ld.global.nc.v2.u32 {%0,%1}, [%2];\n" : "=r"(v.x), "=r"(v.y) : "l"(p));
    return v;
}
__device__ __forceinline__ uint32_t ldg16(const void* p) {
    uint32_t v;
    asm volatile("ld.global.nc.u16 %0, [%1];\n" : "=r"(v) : "l"(p));
    return v;
}
__device__ __forceinline__ void stg128(void* p, uint32_t a, uint32_t b, uint32_t c, uint32_t d) {
    asm volatile("st.global.v4.u32 [%0], {%1,%2,%3,%4};\n" ::"l"(p), "r"(a), "r"(b), "r"(c), "r"(d) : "memory");
}
__device__ __forceinline__ void stg64(void* p, uint32_t a, uint32_t b) { asm volatile("st.global.v2.u32 [%0], {%1,%2};\n" ::"l"(p), "r"(a), "r"(b) : "memory"); }
__device__ __forceinline__ void stg32(void* p, uint32_t a) { asm volatile("st.global.u32 [%0], %1;\n" ::"l"(p), "r"(a) : "memory"); }
__device__ __forceinline__ bool all_nz(const uint4& v) { return v.x && v.y && v.z && v.w; }
#define SPIN_LIMIT (1 << 21)
#define TRAP() __trap()
__device__ __forceinline__ void hint_arrive(unsigned* g_hint, int idx, int sub) {
    asm volatile("red.relaxed.gpu.global.add.u32 [%0], 1;\n" ::"l"(&g_hint[sub * 32 + idx]) : "memory");
}
__device__ __forceinline__ void hint_wait(const unsigned* g_hint, int idx, unsigned target) {
    unsigned l;
    asm volatile("mov.u32 %0, %%laneid;" : "=r"(l));
    const unsigned* c = &g_hint[(l & 7) * 32 + idx];
    int it = 0;
    while (__any_sync(0xffffffffu, (int)(ld_poll32(c) - target) < 0)) { if (++it > SPIN_LIMIT) TRAP(); }
}
__device__ __forceinline__ void mbar_init(uint32_t bar, uint32_t cnt) { asm volatile("mbarrier.init.shared::cta.b64 [%0], %1;\n" ::"r"(bar), "r"(cnt) : "memory"); }
__device__ __forceinline__ void mbar_expect(uint32_t bar, uint32_t bytes) {
    asm volatile("mbarrier.arrive.expect_tx.shared::cta.b64 _, [%0], %1;\n" ::"r"(bar), "r"(bytes) : "memory");
}
__device__ __forceinline__ void mbar_arrive(uint32_t bar) { asm volatile("mbarrier.arrive.shared::cta.b64 _, [%0];\n" ::"r"(bar) : "memory"); }
__device__ __forceinline__ void mbar_wait_cluster(uint32_t bar) {
    asm volatile(
        "{\n.reg .pred p;\n"
        "W_%=:\n"
        "mbarrier.try_wait.parity.acquire.cluster.shared::cta.b64 p, [%0], 0;\n"
        "@!p bra W_%=;\n}\n" ::"r"(bar) : "memory");
}
__device__ __forceinline__ void mbar_wait(uint32_t bar) {
    asm volatile(
        "{\n.reg .pred p;\n"
        "W_%=:\n"
        "mbarrier.try_wait.parity.shared::cta.b64 p, [%0], 0;\n"
        "@!p bra W_%=;\n}\n" ::"r"(bar) : "memory");
}
__device__ __forceinline__ bool mbar_test(uint32_t bar) {
    uint32_t r;
    asm volatile("{\n.reg .pred p;\nmbarrier.test_wait.parity.shared::cta.b64 p, [%1], 0;\nselp.u32 %0, 1, 0, p;\n}\n" : "=r"(r) : "r"(bar) : "memory");
    return __any_sync(0xffffffffu, r);
}
__device__ __forceinline__ void bulk_g2s(uint32_t dst, const void* src, uint32_t bytes, uint32_t bar) {
    asm volatile("cp.async.bulk.shared::cluster.global.mbarrier::complete_tx::bytes [%0], [%1], %2, [%3];\n" ::"r"(dst), "l"(src), "r"(bytes), "r"(bar) : "memory");
}
__device__ __forceinline__ void bulk_s2g(void* dst, uint32_t src, uint32_t bytes) {
    asm volatile("cp.async.bulk.global.shared::cta.bulk_group [%0], [%1], %2;\ncp.async.bulk.commit_group;\n" ::"l"(dst), "r"(src), "r"(bytes) : "memory");
}
__device__ __forceinline__ void tma_2d(uint32_t dst, const CUtensorMap* tm, int c0, int c1, uint32_t bar) {
    asm volatile("cp.async.bulk.tensor.2d.shared::cluster.global.mbarrier::complete_tx::bytes [%0], [%1, {%3, %4}], [%2];\n"
                 ::"r"(dst), "l"(tm), "r"(bar), "r"(c0), "r"(c1) : "memory");
}
__device__ __forceinline__ void tma_3d(uint32_t dst, const CUtensorMap* tm, int c0, int c1, int c2, uint32_t bar) {
    asm volatile("cp.async.bulk.tensor.3d.shared::cluster.global.mbarrier::complete_tx::bytes [%0], [%1, {%3, %4, %5}], [%2];\n"
                 ::"r"(dst), "l"(tm), "r"(bar), "r"(c0), "r"(c1), "r"(c2) : "memory");
}
__device__ __forceinline__ void tma_3d_mc(uint32_t dst, const CUtensorMap* tm, int c0, int c1, int c2, uint32_t bar) {
    asm volatile("cp.async.bulk.tensor.3d.shared::cluster.global.mbarrier::complete_tx::bytes.multicast::cluster [%0], [%1, {%3, %4, %5}], [%2], %6;\n"
                 ::"r"(dst), "l"(tm), "r"(bar), "r"(c0), "r"(c1), "r"(c2), "h"((unsigned short)3) : "memory");
}
__device__ __forceinline__ void tma_st_3d(const CUtensorMap* tm, uint32_t src, int c0, int c1, int c2) {
    asm volatile("cp.async.bulk.tensor.3d.global.shared::cta.bulk_group [%0, {%2, %3, %4}], [%1];\ncp.async.bulk.commit_group;\n"
                 ::"l"(tm), "r"(src), "r"(c0), "r"(c1), "r"(c2) : "memory");
}
__device__ __forceinline__ void l2_prefetch(const void* src, uint32_t bytes) {
    asm volatile("cp.async.bulk.prefetch.L2.global [%0], %1;\n" ::"l"(src), "r"(bytes) : "memory");
}
__device__ __forceinline__ bool elect_one() {
    uint32_t r;
    asm volatile("{\n.reg .pred p;\nelect.sync _|p, 0xffffffff;\nselp.u32 %0, 1, 0, p;\n}\n" : "=r"(r));
    return r;
}
__device__ __forceinline__ void fence_async() { asm volatile("fence.proxy.async.shared::cta;\n" ::: "memory"); }

__device__ __forceinline__ float2 cmul(float2 a, float2 b) {
    return make_float2(fmaf(a.x, b.x, -a.y * b.y), fmaf(a.x, b.y, a.y * b.x));
}
__device__ __forceinline__ float2 csq(float2 a) {
    float p = a.x * a.y;
    return make_float2(fmaf(a.x, a.x, -a.y * a.y), p + p);
}
__device__ __forceinline__ float2 cexp_e(float lr2, float rh, float rl, float e) {
    float m;
    asm("ex2.approx.ftz.f32 %0, %1;\n" : "=f"(m) : "f"(lr2 * e));
    const float a = rh * e;
    const float r = fmaf(rl, e, a - rintf(a)) * 6.283185307179586f;
    return make_float2(m * __cosf(r), m * __sinf(r));
}
__device__ __forceinline__ float rcp_approx(float x) { float r; asm("rcp.approx.ftz.f32 %0, %1;\n" : "=f"(r) : "f"(x)); return r; }
__device__ __forceinline__ float sqrt_approx(float x) { float r; asm("sqrt.approx.ftz.f32 %0, %1;\n" : "=f"(r) : "f"(x)); return r; }

__device__ __forceinline__ void wg_fence() { asm volatile("wgmma.fence.sync.aligned;\n" ::: "memory"); }
__device__ __forceinline__ void wg_commit() { asm volatile("wgmma.commit_group.sync.aligned;\n" ::: "memory"); }
__device__ __forceinline__ void wg_wait0() { asm volatile("wgmma.wait_group.sync.aligned 0;\n" ::: "memory"); }
template <int T0, int NT> __device__ __forceinline__ void wg_h(uint32_t (&acc)[32], const uint32_t (&a)[4], uint64_t desc);
template <> __device__ __forceinline__ void wg_h<0, 16>(uint32_t (&acc)[32], const uint32_t (&a)[4], uint64_t desc) {
    asm volatile("wgmma.mma_async.sync.aligned.m64n128k16.f16.f16.f16 {%0,%1,%2,%3,%4,%5,%6,%7,%8,%9,%10,%11,%12,%13,%14,%15,%16,%17,%18,%19,%20,%21,%22,%23,%24,%25,%26,%27,%28,%29,%30,%31}, {%32,%33,%34,%35}, %36, 1, 1, 1, 0;\n"
                 : "+r"(acc[0]), "+r"(acc[1]), "+r"(acc[2]), "+r"(acc[3]), "+r"(acc[4]), "+r"(acc[5]), "+r"(acc[6]), "+r"(acc[7]), "+r"(acc[8]), "+r"(acc[9]), "+r"(acc[10]), "+r"(acc[11]), "+r"(acc[12]), "+r"(acc[13]), "+r"(acc[14]), "+r"(acc[15]), "+r"(acc[16]), "+r"(acc[17]), "+r"(acc[18]), "+r"(acc[19]), "+r"(acc[20]), "+r"(acc[21]), "+r"(acc[22]), "+r"(acc[23]), "+r"(acc[24]), "+r"(acc[25]), "+r"(acc[26]), "+r"(acc[27]), "+r"(acc[28]), "+r"(acc[29]), "+r"(acc[30]), "+r"(acc[31])
                 : "r"(a[0]), "r"(a[1]), "r"(a[2]), "r"(a[3]), "l"(desc));
}
template <> __device__ __forceinline__ void wg_h<4, 4>(uint32_t (&acc)[32], const uint32_t (&a)[4], uint64_t desc) {
    asm volatile("wgmma.mma_async.sync.aligned.m64n32k16.f16.f16.f16 {%0,%1,%2,%3,%4,%5,%6,%7}, {%8,%9,%10,%11}, %12, 1, 1, 1, 0;\n"
                 : "+r"(acc[8]), "+r"(acc[9]), "+r"(acc[10]), "+r"(acc[11]), "+r"(acc[12]), "+r"(acc[13]), "+r"(acc[14]), "+r"(acc[15])
                 : "r"(a[0]), "r"(a[1]), "r"(a[2]), "r"(a[3]), "l"(desc));
}
template <> __device__ __forceinline__ void wg_h<8, 4>(uint32_t (&acc)[32], const uint32_t (&a)[4], uint64_t desc) {
    asm volatile("wgmma.mma_async.sync.aligned.m64n32k16.f16.f16.f16 {%0,%1,%2,%3,%4,%5,%6,%7}, {%8,%9,%10,%11}, %12, 1, 1, 1, 0;\n"
                 : "+r"(acc[16]), "+r"(acc[17]), "+r"(acc[18]), "+r"(acc[19]), "+r"(acc[20]), "+r"(acc[21]), "+r"(acc[22]), "+r"(acc[23])
                 : "r"(a[0]), "r"(a[1]), "r"(a[2]), "r"(a[3]), "l"(desc));
}
template <> __device__ __forceinline__ void wg_h<12, 4>(uint32_t (&acc)[32], const uint32_t (&a)[4], uint64_t desc) {
    asm volatile("wgmma.mma_async.sync.aligned.m64n32k16.f16.f16.f16 {%0,%1,%2,%3,%4,%5,%6,%7}, {%8,%9,%10,%11}, %12, 1, 1, 1, 0;\n"
                 : "+r"(acc[24]), "+r"(acc[25]), "+r"(acc[26]), "+r"(acc[27]), "+r"(acc[28]), "+r"(acc[29]), "+r"(acc[30]), "+r"(acc[31])
                 : "r"(a[0]), "r"(a[1]), "r"(a[2]), "r"(a[3]), "l"(desc));
}
template <> __device__ __forceinline__ void wg_h<0, 8>(uint32_t (&acc)[32], const uint32_t (&a)[4], uint64_t desc) {
    asm volatile("wgmma.mma_async.sync.aligned.m64n64k16.f16.f16.f16 {%0,%1,%2,%3,%4,%5,%6,%7,%8,%9,%10,%11,%12,%13,%14,%15}, {%16,%17,%18,%19}, %20, 1, 1, 1, 0;\n"
                 : "+r"(acc[0]), "+r"(acc[1]), "+r"(acc[2]), "+r"(acc[3]), "+r"(acc[4]), "+r"(acc[5]), "+r"(acc[6]), "+r"(acc[7]), "+r"(acc[8]), "+r"(acc[9]), "+r"(acc[10]), "+r"(acc[11]), "+r"(acc[12]), "+r"(acc[13]), "+r"(acc[14]), "+r"(acc[15])
                 : "r"(a[0]), "r"(a[1]), "r"(a[2]), "r"(a[3]), "l"(desc));
}
template <> __device__ __forceinline__ void wg_h<4, 12>(uint32_t (&acc)[32], const uint32_t (&a)[4], uint64_t desc) {
    asm volatile("wgmma.mma_async.sync.aligned.m64n96k16.f16.f16.f16 {%0,%1,%2,%3,%4,%5,%6,%7,%8,%9,%10,%11,%12,%13,%14,%15,%16,%17,%18,%19,%20,%21,%22,%23}, {%24,%25,%26,%27}, %28, 1, 1, 1, 0;\n"
                 : "+r"(acc[8]), "+r"(acc[9]), "+r"(acc[10]), "+r"(acc[11]), "+r"(acc[12]), "+r"(acc[13]), "+r"(acc[14]), "+r"(acc[15]), "+r"(acc[16]), "+r"(acc[17]), "+r"(acc[18]), "+r"(acc[19]), "+r"(acc[20]), "+r"(acc[21]), "+r"(acc[22]), "+r"(acc[23]), "+r"(acc[24]), "+r"(acc[25]), "+r"(acc[26]), "+r"(acc[27]), "+r"(acc[28]), "+r"(acc[29]), "+r"(acc[30]), "+r"(acc[31])
                 : "r"(a[0]), "r"(a[1]), "r"(a[2]), "r"(a[3]), "l"(desc));
}

#define DSM 1
#define PBYTES 4608
#define HINTW 10
#define WAS 0x0005
#define WA0 (WAS >> 12)
#define WA1 ((WAS >> 8) & 15)
#define WA2 ((WAS >> 4) & 15)
#define WA3 (WAS & 15)
#define WDAT 1
#define PAUSE 2
#define PCNT (32 + ((PAUSE & 1) ? 288 : 0) + ((PAUSE & 6) ? 320 : 64))
#define LNAT 2
#define UW 8
#define FINAT 3
#define UAT 2
#define PFW 11
#define HK 9
#define TOKEN_OF(g) (16 * ((g) & 1) + ((g) >> 2) + 2 * ((g) & 2))
#define HI2(a, b) (pack_f16_rz(__uint_as_float(a), __uint_as_float(b)) & 0xfff8fff8u)
struct Params {
    const bf16 *x, *lar, *aim, *cre, *cim, *ldt, *dsk;
    Scratch* s;
    const bf16 *wr, *wpf;
    bf16* out;
};

template <int NK>
__device__ __forceinline__ void ln_partial(const uint32_t (&H)[2][NK], uint32_t lp, int warp, int g, int t) {
    float cs[4] = {0.f, 0.f, 0.f, 0.f}, cl[4] = {0.f, 0.f, 0.f, 0.f}, ch[4] = {0.f, 0.f, 0.f, 0.f};
#pragma unroll
    for (int k = 0; k < NK; k += 2) {
        uint32_t a0, a1, a2, a3;
        asm volatile("prmt.b32 %0, %4, %4, %8;\nprmt.b32 %1, %5, %5, %8;\nprmt.b32 %2, %6, %6, %8;\nprmt.b32 %3, %7, %7, %8;\n"
                     : "=r"(a0), "=r"(a1), "=r"(a2), "=r"(a3) : "r"(H[0][k]), "r"(H[1][k]), "r"(H[0][k + 1]), "r"(H[1][k + 1]), "r"(0x3210u + (warp >> 8)));
        mma_bf16(cl, a0, a1, a2, a3, H[0][k], H[0][k + 1]);
        mma_bf16(ch, a0, a1, a2, a3, H[1][k], H[1][k + 1]);
        mma_bf16(cs, a0, a1, a2, a3, 0x3f803f80u, 0x3f803f80u);
    }
    const uint32_t a = lp + (g * 20 + warp) * 4;
    if (t == 0) {
        stsf(a, cs[0]); stsf(a + 8 * 80, cs[2]);
    }
    if (t == (g >> 1)) { stsf(a + 16 * 80, (g & 1) ? cl[1] : cl[0]); stsf(a + 24 * 80, (g & 1) ? ch[3] : ch[2]); }
}
__device__ __forceinline__ float sum18(uint32_t a) {
    const uint4 p = lds128(a), q = lds128(a + 16), r = lds128(a + 32), s = lds128(a + 48);
    const uint2 u = lds64(a + 64);
#define F(x) __uint_as_float(x)
    return (((F(p.x) + F(p.y)) + (F(p.z) + F(p.w))) + ((F(q.x) + F(q.y)) + (F(q.z) + F(q.w)))) +
           (((F(r.x) + F(r.y)) + (F(r.z) + F(r.w))) + ((F(s.x) + F(s.y)) + (F(s.z) + F(s.w))) + (F(u.x) + F(u.y)));
#undef F
}
__device__ __forceinline__ float sum9(uint32_t a) {
    const uint4 p = lds128(a), q = lds128(a + 16);
#define F(x) __uint_as_float(x)
    return (((F(p.x) + F(p.y)) + (F(p.z) + F(p.w))) + ((F(q.x) + F(q.y)) + (F(q.z) + F(q.w)))) + ldsf(a + 32);
#undef F
}
template <int N>
__device__ __forceinline__ void ln_finish(uint32_t lp, int lane, float& mb, float& rc) {
    const float v = N == 9 ? sum9(lp + lane * 80) : sum18(lp + lane * 80);
    const float o = __shfl_xor_sync(0xffffffffu, v, 16);
    const float m0 = v * (1.0f / 576.0f);
    const float mean = fmaf(fmaf(-m0, 576.0f, v), 1.0f / 576.0f, m0);
    const float var = fmaxf(fmaf(-mean, mean, o * (1.0f / 576.0f)), 0.f);
    mb = rbf(mean);
    rc = rcp_approx(rbf(sqrt_approx(rbf(rbf(var) + 1e-5f))));
}
__device__ __forceinline__ uint32_t ln_apply(uint32_t w, const uint2& st) {
    uint32_t r;
    asm("{\n.reg .b16 m, t, h, l;\n.reg .b32 mm, hh, ll, d, e;\nmov.b32 {m, t}, %2;\nmov.b32 {h, l}, %3;\nmov.b32 mm, {m, m};\nmov.b32 hh, {h, h};\nmov.b32 ll, {l, l};\n"
        "sub.rn.bf16x2 d, %1, mm;\nmul.rn.bf16x2 e, d, ll;\nfma.rn.bf16x2 %0, d, hh, e;\n}\n" : "=r"(r) : "r"(w), "r"(st.x), "r"(st.y));
    return r;
}
__device__ __forceinline__ void stat_store(uint32_t a, float mb, float rc, uint32_t extra) {
    const float rh = rbf(rc);
    sts64(a, (__float_as_uint(mb) >> 16) | (extra << 16), pack_bf16(rh, rc - rh));
}

__device__ __forceinline__ void hcmul(uint32_t re, uint32_t im, uint32_t z, uint32_t& ore, uint32_t& oim) {
    asm("{\n.reg .b16 x, y;\n.reg .b32 xx, yy, ny, a, b;\nmov.b32 {x, y}, %4;\nmov.b32 xx, {x, x};\nmov.b32 yy, {y, y};\nneg.f16x2 ny, yy;\n"
        "mul.rn.f16x2 a, %2, xx;\nfma.rn.f16x2 %0, %3, ny, a;\nmul.rn.f16x2 b, %3, xx;\nfma.rn.f16x2 %1, %2, yy, b;\n}\n" : "=&r"(ore), "=r"(oim) : "r"(re), "r"(im), "r"(z));
}
__device__ __forceinline__ void hcmul(uint32_t re, uint32_t im, uint32_t zx, uint32_t zy, uint32_t& ore, uint32_t& oim) {
    asm("{\n.reg .b32 ny, a, b;\nneg.f16x2 ny, %5;\n"
        "mul.rn.f16x2 a, %2, %4;\nfma.rn.f16x2 %0, %3, ny, a;\nmul.rn.f16x2 b, %3, %4;\nfma.rn.f16x2 %1, %2, %5, b;\n}\n" : "=&r"(ore), "=r"(oim) : "r"(re), "r"(im), "r"(zx), "r"(zy));
}

struct KGen {
    uint32_t Af[4][4];
    float2 z1, z8, z64, z128, T[9];
    uint32_t zw;
};
__device__ __forceinline__ void kgen_setup(KGen& k, uint32_t pa, float dt) {
    const float A = rbf(expf(bf_lo(pa)));
    const float lr2 = -(A * dt) * 1.4426950408889634f;
    const float li = bf_hi(pa) * dt;
    const float rh = li * 0.15915494309189535f;
    const float rl = fmaf(li, 6.4206382986e-9f, fmaf(li, 0.15915494309189535f, -rh));
    k.z1 = cexp_e(lr2, rh, rl, 1.0f);
    k.z8 = cexp_e(lr2, rh, rl, 8.0f);
    k.z64 = cexp_e(lr2, rh, rl, 64.0f);
}
__device__ __forceinline__ void kgen_rows(KGen& k, uint32_t tb, int lane) {
    const float2 z8 = k.z8, z64 = k.z64;
    const uint32_t row = tb + lane * TBP;
    k.z128 = csq(z64);
    const float2 z16 = csq(z8), z32 = csq(z16), z48 = cmul(z32, z16), z80 = cmul(z64, z16), z96 = cmul(z64, z32), z112 = cmul(z64, z48);
    uint32_t re[4], im[4], a[4], b[4];
    re[0] = pack_f16(1.0f, z16.x); im[0] = pack_f16(0.0f, z16.y);
    re[1] = pack_f16(z32.x, z48.x); im[1] = pack_f16(z32.y, z48.y);
    re[2] = pack_f16(z64.x, z80.x); im[2] = pack_f16(z64.y, z80.y);
    re[3] = pack_f16(z96.x, z112.x); im[3] = pack_f16(z96.y, z112.y);
    sts128(row, re[0], re[1], re[2], re[3]);
    sts128(row + 32, im[0], im[1], im[2], im[3]);
    const uint32_t zz = pack_f16(z8.x, z8.y);
#pragma unroll
    for (int j = 0; j < 4; j++) hcmul(re[j], im[j], zz, a[j], b[j]);
    sts128(row + 16, a[0], a[1], a[2], a[3]);
    sts128(row + 48, b[0], b[1], b[2], b[3]);
    __syncwarp();
    const int mi = lane >> 3;
    const uint32_t ad = tb + (lane & 7) * TBP + mi * 16;
#pragma unroll
    for (int ks = 0; ks < 4; ks++) ldsm_x4_t(k.Af[ks][0], k.Af[ks][1], k.Af[ks][2], k.Af[ks][3], ad + ks * 8 * TBP);
}
__device__ __forceinline__ void kgen_chain(KGen& k, uint32_t pc, float cs) {
    k.T[0] = make_float2(bf_lo(pc) * cs, -bf_hi(pc) * cs);
    const float2 y1 = make_float2(k.z1.x, -k.z1.y);
#pragma unroll
    for (int c = 1; c < 8; c++) k.T[c] = cmul(k.T[c - 1], y1);
    k.T[8] = cmul(k.T[0], make_float2(k.z8.x, -k.z8.y));
}
__device__ __forceinline__ void kgen_cols(KGen& k, uint32_t tb, int lane) {
    const uint32_t row = tb + lane * TBP;
    const float2 (&T)[9] = k.T;
    const uint32_t zv = pack_f16(k.z128.x, k.z128.y), zo = __shfl_xor_sync(0xffffffffu, zv, 1);
    k.zw = (lane & 1) ? __byte_perm(zo, zv, 0x7632) : __byte_perm(zv, zo, 0x5410);
    const float2 y256 = csq(make_float2(k.z128.x, -k.z128.y)), y512 = csq(y256), y768 = cmul(y512, y256), y1024 = csq(y512);
    const float2 c1032 = cmul(T[8], y1024);
    const uint32_t r04 = pack_f16(T[0].x, T[4].x), i04 = pack_f16(T[0].y, T[4].y), r26 = pack_f16(T[2].x, T[6].x), i26 = pack_f16(T[2].y, T[6].y);
    const uint32_t r48 = pack_f16(T[4].x, T[8].x), i48 = pack_f16(T[4].y, T[8].y);
    __syncwarp();
    sts128(row, r04, pack_f16(T[1].x, T[5].x), r26, pack_f16(T[3].x, T[7].x));
    sts128(row + 16, i04, pack_f16(T[1].y, T[5].y), i26, pack_f16(T[3].y, T[7].y));
    uint32_t a[4], b[4];
    {
        const uint32_t zz = pack_f16(y256.x, y256.y);
        hcmul(r04, i04, zz, a[0], b[0]);
        hcmul(r26, i26, zz, a[2], b[2]);
        hcmul(r48, i48, zz, a[3], b[3]);
    }
    sts128(row + 32, a[0], a[0], a[2], a[3]);
    sts128(row + 48, b[0], b[0], b[2], b[3]);
    {
        hcmul(r48, i48, pack_f16(y512.x, y512.y), a[0], b[0]);
        hcmul(r48, i48, pack_f16(y768.x, y768.y), a[1], b[1]);
        const uint32_t zz = pack_f16(c1032.x, c1032.y);
        hcmul(pack_f16(1.0f, y256.x), pack_f16(0.0f, y256.y), zz, a[2], b[2]);
        hcmul(pack_f16(y512.x, y768.x), pack_f16(y512.y, y768.y), zz, a[3], b[3]);
    }
    sts128(row + 64, a[0], a[1], a[2], a[3]);
    sts128(row + 80, b[0], b[1], b[2], b[3]);
}
__device__ __forceinline__ void kgen_mma(const KGen& k, uint32_t tb, int lane) {
    const int t = lane & 3;
    const uint32_t zw = k.zw;
    uint32_t zx[4], zy[4];
#pragma unroll
    for (int ks = 0; ks < 4; ks++) { zx[ks] = __shfl_sync(0xffffffffu, zw, 8 * ks + 2 * t); zy[ks] = __shfl_sync(0xffffffffu, zw, 8 * ks + 2 * t + 1); }
    __syncwarp();
    float acc[2][3][4];
#pragma unroll
    for (int i = 0; i < 6; i++)
#pragma unroll
        for (int j = 0; j < 4; j++) acc[i / 3][i % 3][j] = 0.f;
    {
        const int mi = lane >> 3;
        const uint32_t bd = tb + ((lane & 7) + 8 * (mi >> 1)) * TBP + (mi & 1) * 16;
#pragma unroll
        for (int kp = 0; kp < 2; kp++) {
            uint32_t b[3][4];
#pragma unroll
            for (int j = 0; j < 3; j++) ldsm_x4_t(b[j][0], b[j][1], b[j][2], b[j][3], bd + kp * 16 * TBP + j * 32);
#pragma unroll
            for (int h = 0; h < 2; h++) {
                const int ks = 2 * kp + h;
                uint32_t d[4];
                hcmul(k.Af[ks][0], k.Af[ks][2], zx[ks], zy[ks], d[0], d[2]);
                hcmul(k.Af[ks][1], k.Af[ks][3], zx[ks], zy[ks], d[1], d[3]);
#pragma unroll
                for (int j = 0; j < 3; j++) {
                    mma_f16(acc[0][j], k.Af[ks][0], k.Af[ks][1], k.Af[ks][2], k.Af[ks][3], b[j][2 * h], b[j][2 * h + 1]);
                    mma_f16(acc[1][j], d[0], d[1], d[2], d[3], b[j][2 * h], b[j][2 * h + 1]);
                }
            }
        }
    }
    __syncwarp();
#pragma unroll
    for (int h = 0; h < 2; h++) {
        sts64(tb + h * 256 + lane * 8, pack_f16(acc[h][0][0], acc[h][0][1]), pack_f16(acc[h][0][2], acc[h][0][3]));
        sts64(tb + 512 + h * 256 + lane * 8, pack_f16(acc[h][1][0], acc[h][1][1]), pack_f16(acc[h][1][2], acc[h][1][3]));
        sts32(tb + 1024 + h * 256 + lane * 4, pack_f16(acc[h][2][0], t < 2 ? acc[h][2][1] : acc[h][2][2]));
        sts32(tb + 1152 + h * 256 + lane * 4, pack_f16(t < 2 ? acc[h][2][2] : acc[h][2][1], acc[h][2][3]));
    }
}
__device__ __forceinline__ uint32_t table_buf(uint32_t sb, int warp) { return sb + SM_TB + warp * TBW; }

__device__ __forceinline__ void kgen_combine(uint32_t sb, int warp, int lane, uint32_t kw, uint32_t ao) {
    const int wq = warp & 3;
    const uint32_t a = table_buf(sb, warp & ~3) + wq * 256 + lane * 8, c = table_buf(sb, warp & ~3) + 1024 + wq * 128 + lane * 4;
    const int t = lane & 3;
    const uint32_t o0 = (t < 2 ? KW_T2 + KW_KH + 16 + t * 256 - (wq & 1) * KW_KH : KW_T3 + 16 - 1024 + t * 512 + (wq & 1) * 256) + (lane >> 2) * 16;
    const uint4 o = make_uint4(o0 + t * 36, o0 + (t ^ 1) * 36, o0 + (t ^ 2) * 36, o0 + (t ^ 3) * 36);
    const uint2 u = lds64(a), v = lds64(a + TBW), w = lds64(a + 2 * TBW), x = lds64(a + 3 * TBW);
    const uint32_t kt = hadd2(hadd2(lds32(c), lds32(c + TBW)), hadd2(lds32(c + 2 * TBW), lds32(c + 3 * TBW)));
    const uint32_t k23 = hadd2(hadd2(u.y, v.y), hadd2(w.y, x.y));
    sts64(kw + wq * 64 + ao, hadd2(hadd2(u.x, v.x), hadd2(w.x, x.x)), k23);
    const uint32_t d = kw + (wq >> 1) * 128;
    const uint32_t kh = hmul2(kt, 0x38003800u);
    sts32(d + o.x, kh); sts32(d + o.y, kh); sts32(d + o.z, kh); sts32(d + o.w, kh);
    if (wq == 3) {
        if (lane == 31) { sts32(kw + 264, k23 >> 16); sts32(kw + 288 + 264, k23 >> 16); sts32(kw + 576 + 264, k23 >> 16); }
        if (lane == 29) { sts32(kw + 864 + 280, kt >> 16); sts32(kw + 280, kt & 0xffff0000u); }
    }
}

__device__ __forceinline__ int c_exponent(const uint2& r, const uint2& i) {
    uint32_t mx = __vmaxu2(__vmaxu2(r.x & 0x7fff7fffu, r.y & 0x7fff7fffu), __vmaxu2(i.x & 0x7fff7fffu, i.y & 0x7fff7fffu));
    mx = __reduce_max_sync(0xffffffffu, max(mx & 0xffffu, mx >> 16));
    return min(max((int)(mx >> 7), 4), 240);
}

__device__ __forceinline__ int warp_v() { int l; asm volatile("mov.u32 %0, %%tid.x;" : "=r"(l)); return __shfl_sync(0xffffffffu, l >> 5, 0); }
__device__ __forceinline__ int lane_v() { int l; asm volatile("mov.u32 %0, %%laneid;" : "=r"(l)); return l; }
__device__ __forceinline__ uint32_t prmt(uint32_t a, uint32_t b, uint32_t s) { uint32_t d; asm("prmt.b32 %0, %1, %2, %3;\n" : "=r"(d) : "r"(a), "r"(b), "r"(s)); return d; }
__device__ __forceinline__ uint32_t prmt_v(uint32_t a, uint32_t b, uint32_t s) { uint32_t d; asm volatile("prmt.b32 %0, %1, %2, %3;\n" : "=r"(d) : "r"(a), "r"(b), "r"(s)); return d; }
__device__ __forceinline__ void mmah16(uint32_t& d0, uint32_t& d1, uint32_t a0, uint32_t a1, uint32_t a2, uint32_t a3, uint32_t b0, uint32_t b1, uint32_t c0, uint32_t c1) {
    asm volatile("mma.sync.aligned.m16n8k16.row.col.f16.f16.f16.f16 {%0,%1}, {%2,%3,%4,%5}, {%6,%7}, {%8,%9};\n"
                 : "=r"(d0), "=r"(d1) : "r"(a0), "r"(a1), "r"(a2), "r"(a3), "r"(b0), "r"(b1), "r"(c0), "r"(c1));
}
__device__ __forceinline__ void mmah8(uint32_t& d0, uint32_t& d1, uint32_t a0, uint32_t a1, uint32_t b0, uint32_t c0, uint32_t c1) {
    asm volatile("mma.sync.aligned.m16n8k8.row.col.f16.f16.f16.f16 {%0,%1}, {%2,%3}, {%4}, {%5,%6};\n"
                 : "=r"(d0), "=r"(d1) : "r"(a0), "r"(a1), "r"(b0), "r"(c0), "r"(c1));
}
template <int A = 8, int B = 32>
__device__ __forceinline__ void conv_rename(uint32_t (&acc)[32]) {
#pragma unroll
    for (int i = A; i < B; i++) { uint32_t v; asm volatile("mov.b32 %0, %1;\n" : "=r"(v) : "r"(acc[i])); acc[i] = v; }
}
__host__ __device__ constexpr uint32_t band_bits(int hw, int sh) {
    uint32_t c = 0;
    for (int s = 0; s <= 10; s++)
        for (int e = 0; e < 2; e++) {
            const int v = s - 3 + sh - 4 * e;
            if (v <= hw && v >= -hw) c |= 1u << (14 + 16 * e - s);
        }
    return c;
}
template <int HW, int SH, int J> __device__ __forceinline__ uint32_t band(uint32_t p2) {
    uint32_t d;
    asm volatile("{\n.reg .b32 t;\nmul.lo.u32 t, %1, %2;\nand.b32 %0, t, 0x40004000;\n}\n" : "=r"(d) : "r"(p2), "n"(band_bits(HW, SH) | J));
    return d;
}
template <int H0, int SH> __device__ __forceinline__ void band_pair(uint4& l, uint4& u, uint32_t p2) {
    l = make_uint4(band<H0, 8, 1>(p2), band<H0 - 1, SH + 8, 2>(p2), band<H0, 0, 1>(p2), band<H0 - 1, SH, 1>(p2));
    u = make_uint4(band<H0, 0, 2>(p2), band<H0 - 1, SH, 2>(p2), band<H0, -8, 1>(p2), band<H0 - 1, SH - 8, 1>(p2));
}
__device__ __forceinline__ void run_sums(uint32_t (&G)[3][2], const uint32_t (&c)[5], const uint4& l, const uint4& u) {
    mmah8(G[0][0], G[0][1], l.x, l.y, c[0], 0u, 0u);
    mmah8(G[1][0], G[1][1], u.z, u.w, c[3], 0u, 0u);
    mmah8(G[2][0], G[2][1], l.x, l.y, c[2], 0u, 0u);
    mmah16(G[0][0], G[0][1], u.x, u.y, u.z, u.w, c[1], c[2], G[0][0], G[0][1]);
    mmah16(G[1][0], G[1][1], l.x, l.y, l.z, l.w, c[1], c[2], G[1][0], G[1][1]);
    mmah16(G[2][0], G[2][1], u.x, u.y, u.z, u.w, c[3], c[4], G[2][0], G[2][1]);
}
__device__ __forceinline__ float h_lo(uint32_t w) { return __half2float(__ushort_as_half((unsigned short)(w & 0xffffu))); }
__device__ __forceinline__ float h_hi(uint32_t w) { return __half2float(__ushort_as_half((unsigned short)(w >> 16))); }
__device__ __forceinline__ uint64_t smem_desc(uint32_t sb, uint32_t o16, uint32_t lbo) {
    uint64_t d;
    asm("mov.b64 %0, {%1, %2};" : "=l"(d) : "r"(((sb & 0x3FFFF) >> 4) + o16 + (lbo << 12)), "r"(8));
    return d;
}
template <int I> struct IC { static constexpr int value = I; };

struct Conv {
    uint32_t u[3][5];
    uint32_t q2[3][2][4];
    uint32_t q3[2][4];
    uint32_t r[18];
};
struct ConvPre {
    uint32_t a[5], b[5];
    uint32_t t[4];
};
__device__ __forceinline__ void conv_pre(ConvPre& e, uint32_t ka, uint32_t ks, uint32_t sel) {
    const uint4 r = lds128(ka + 256), s = lds128(ka + 272);
    ldsm_x4(e.t[0], e.t[1], e.t[2], e.t[3], ks);
    const uint32_t sw = sel ^ 0x4444u;
    e.a[0] = prmt(r.y, r.z, sel); e.a[1] = prmt(r.w, r.z, sw); e.a[2] = prmt(r.x, r.y, sel); e.a[3] = prmt(r.z, r.y, sw); e.a[4] = prmt(r.z, r.w, sel);
    e.b[0] = prmt(s.y, s.z, sel); e.b[1] = prmt(s.w, s.z, sw); e.b[2] = prmt(s.x, s.y, sel); e.b[3] = prmt(s.z, s.y, sw); e.b[4] = prmt(s.z, s.w, sel);
}
__device__ __forceinline__ void conv_sums(Conv& c, uint32_t (&acc)[32], const ConvPre& e, uint32_t a0, uint32_t a1, const uint4 (&bd)[4], uint32_t ka, uint32_t sel, int wq, uint32_t zr) {
    {
        uint32_t x;
        ldsm_x4(c.u[0][1], c.u[0][2], c.u[0][3], c.u[0][4], a1);
        ldsm_x4(c.u[0][0], c.u[1][0], c.u[2][0], x, a0);
#pragma unroll
        for (int q = 1; q < 3; q++) ldsm_x4(c.u[q][1], c.u[q][2], c.u[q][3], c.u[q][4], a1 + q * 512);
    }
#pragma unroll
    for (int i = 0; i < 32; i++) acc[i] = 0u;
    uint32_t G[3][2];
#pragma unroll
    for (int q = 0; q < 3; q++) {
        mmah8(acc[8 * q + 8], acc[8 * q + 9], e.a[4], 0u, c.u[q][2], acc[8 * q + 8], acc[8 * q + 9]);
        mmah16(acc[8 * q + 8], acc[8 * q + 9], e.a[0], e.a[1], e.a[2], e.a[3], c.u[q][3], c.u[q][4], acc[8 * q + 8], acc[8 * q + 9]);
        if (q < 2) {
            mmah8(acc[8 * q + 16], acc[8 * q + 17], e.b[4], 0u, c.u[q][2], 0u, 0u);
            mmah16(acc[8 * q + 16], acc[8 * q + 17], e.b[0], e.b[1], e.b[2], e.b[3], c.u[q][3], c.u[q][4], acc[8 * q + 16], acc[8 * q + 17]);
            run_sums(G, c.u[q], bd[2], bd[3]);
            c.q3[q][0] = prmt(G[1][1], G[0][0], 0x7632u); c.q3[q][1] = prmt(G[2][1], G[1][0], 0x7632u);
            c.q3[q][2] = prmt(G[1][1], G[0][0], 0x5410u); c.q3[q][3] = prmt(G[2][1], G[1][0], 0x5410u);
        }
    }
    {
        const uint32_t a = (ka + wq * 64) ^ (((acc[8] | acc[16] | acc[24]) | (c.q3[0][0] | c.q3[0][1]) | (c.q3[1][0] | c.q3[1][1])) & zr);
#pragma unroll
        for (int i = 0; i < 4; i++) { const uint4 v = lds128(a + i * 16); c.r[4 * i] = v.x; c.r[4 * i + 1] = v.y; c.r[4 * i + 2] = v.z; c.r[4 * i + 3] = v.w; }
        const uint2 v = lds64(a + 64);
        c.r[16] = v.x; c.r[17] = v.y;
    }
#pragma unroll
    for (int q = 0; q < 3; q++) {
        run_sums(G, c.u[q], bd[0], bd[1]);
#pragma unroll
        for (int h = 0; h < 2; h++) {
            const uint32_t s = h ? 0x7632u : 0x5410u;
            c.q2[q][h][0] = prmt(G[0][1], G[0][0], s); c.q2[q][h][1] = prmt(G[1][1], G[1][0], s);
            c.q2[q][h][2] = prmt(G[1][0], G[1][1], s ^ 0x4444u); c.q2[q][h][3] = prmt(G[2][1], G[2][0], s);
            if (q < 2) mmah16(acc[8 * q + 16], acc[8 * q + 17], c.q2[q][h][0], c.q2[q][h][1], c.q2[q][h][2], c.q2[q][h][3], e.t[2 * h], e.t[2 * h + 1], acc[8 * q + 16], acc[8 * q + 17]);
        }
    }
    if (sel == 0u) {
#pragma unroll
        for (int i = 0; i < 6; i++) sts128(ka + i * 16, c.q2[i >> 1][i & 1][0], c.q2[i >> 1][i & 1][1], c.q2[i >> 1][i & 1][2], c.q2[i >> 1][i & 1][3]);
#pragma unroll
        for (int i = 0; i < 2; i++) sts128(ka + i * 16, c.q3[i][0], c.q3[i][1], c.q3[i][2], c.q3[i][3]);
#pragma unroll
        for (int i = 1; i < 4; i++) sts64(ka + i * 16, acc[8 * i], acc[8 * i + 1]);
    }
    conv_rename(acc);
}
#define SPACE 120
#define SPN 3
#define GATE 2
#define HAND 2
#define GA 6
#define GB 4
template <int TA, int TB, int IA, class FG>
__device__ __forceinline__ void conv_tail(uint32_t (&acc)[32], const uint32_t (&a)[8][4], uint32_t sb, unsigned char* gy0, int warp, size_t ycopy, FG fg) {
    const int wg = warp >> 2, wq = warp & 3, ord = TA == 0 && TB == 16 ? 3 - wg : 4;
    const uint32_t ub = sb + SM_U + wg * USLOT_B + UPAD * 16, turn = sb + SM_MISC + 376 + ord * 8, sfs = sb + SM_MISC + 256 + wg * 8;
    const uint32_t du = wg * (USLOT_B / 16) + (SM_U / 16 + UPAD + TA * 8);
    uint32_t ud[8], fs;
    auto skip = [&]() {
        const int lane = lane_v();
        const uint32_t ua = ub + ((lane >> 3) & 1) * ULO_B + (8 * wq + (lane & 7)) * 16 + (lane >> 4) * 512;
        if (IA == 0) ldsm_x4_t(ud[0], ud[1], ud[2], ud[3], ua);
        if (TB == 16) ldsm_x4_t(ud[4], ud[5], ud[6], ud[7], ua + 1024);
        const uint2 fd = lds64(sfs);
        fs = fd.x;
        const float dsk = __uint_as_float(fd.y);
#pragma unroll
        for (int i = 2 * IA; i < TB / 2; i++) ud[i] = pack_bf16(h_lo(ud[i]) * dsk, h_hi(ud[i]) * dsk);
    };
    conv_rename<2 * TA, 2 * TB>(acc);
    if (__builtin_expect(ord != 0, 0)) {
        skip();
        mbar_wait(turn);
    }
    if (TA == 0 && TB == 16) asm volatile("{\n.reg .pred p;\nelect.sync _|p, 0xffffffff;\n@p mbarrier.arrive.shared::cta.b64 _, [%0];\n}\n" ::"r"(turn + 40) : "memory");
    fg(IC<8>());
    wg_fence();
#pragma unroll
    for (int m = 7; m >= 0; m--) {
        wg_h<TA, TB - TA>(acc, a[m], smem_desc(sb, du - m, ULO_B));
        if (m == GA || m == GB || m == HAND) wg_commit();
        if (m == GB) asm volatile("wgmma.wait_group.sync.aligned 1;\n" ::: "memory");
    }
    wg_commit();
    if (TA == 0 && TB == 16) {
        asm volatile("wgmma.wait_group.sync.aligned 1;\n" ::: "memory");
        asm volatile("{\n.reg .pred p;\nelect.sync _|p, 0xffffffff;\n@p mbarrier.arrive.shared::cta.b64 _, [%0];\n}\n" ::"r"(turn + 8) : "memory");
    }
    __syncwarp();
    fg(IC<3>());
    if (!ord) skip();
    fg(IC<4>());
    const int lane = lane_v();
    const uint32_t lp = sb + SM_PL + (ord >= 3 ? ord - 3 : ord) * PL_B + lane * 8;
    unsigned char* gy = gy0 + ((4 * wq + (lane & 3)) * DM + (TA == 0 && TB == 16 ? 4 * blockIdx.x + wg : 512 + (blockIdx.x >> 1))) * 64 + (lane >> 2) * 8;
    const uint32_t st = lp + (wq * 12 - ((wq * (wq - 1)) >> 1)) * 256;
    uint32_t ld[3];
#pragma unroll
    for (int s = 1; s < 4; s++) {
        const int w = (wq - s) & 3;
        ld[s - 1] = lp + (w * 12 - ((w * (w - 1)) >> 1) + s - 1 - (wq < s ? 3 : 0)) * 256;
    }
    if (ord >= 3) bar_sync(9 + ord, 256);
    wg_wait0();
    fg(IC<6>());
#pragma unroll
    for (int j = TA; j < TB; j++)
        if ((j & 3) && j + 3 >= 4 * IA && (j + 3 < TB || j + wq < TB)) sts64(st + (j - 1 - (j >> 2)) * 256, acc[2 * j], acc[2 * j + 1]);
    bar_sync(1 + wg, 128);
    fg(IC<7>());
    uint2 v[4][3];
#pragma unroll
    for (int i = IA; i < TB / 4; i++)
#pragma unroll
        for (int s = 0; s < 3; s++) {
            if (i == 0) { v[i][s] = make_uint2(0u, 0u); if (wq > s) v[i][s] = lds64(ld[s]); }
            else v[i][s] = lds64(ld[s] + i * 768);
        }
    fg(IC<5>());
#pragma unroll
    for (int i = IA; i < TB / 4; i++) {
        const uint32_t x0 = hadd2(v[i][0].x, acc[8 * i]), x1 = hadd2(v[i][1].x, v[i][2].x), y0 = hadd2(v[i][0].y, acc[8 * i + 1]), y1 = hadd2(v[i][1].y, v[i][2].y);
        const uint32_t x = hadd2(x0, x1), y = hadd2(y0, y1);
        const uint32_t lo = pack_bf16(h_lo(x), h_hi(x)), hi = pack_bf16(h_lo(y), h_hi(y));
        const uint32_t o0 = max(hfma2_bf(lo, fs, ud[2 * i]), 1u), o1 = hfma2_bf(hi, fs, ud[2 * i + 1]);
        stg64(gy + i * 16 * DM * 64, o0, o1);
        if (SPACE && TA == 0 && TB == 16 && i < 3 && ord < SPN) { const unsigned c0 = clock(); while (clock() - c0 < SPACE) {} }
    }
    if (TA == 0 && TB == 16 && ord < 2) bar_arrive(12 + ord, 256);
}
template <int M0, int M1>
__device__ __forceinline__ void conv_frags(uint32_t (&a)[8][4], const uint32_t (&r)[18], uint32_t sel, uint32_t dep, int warp) {
    const uint32_t s = prmt_v(sel, dep, 0x3210u + (warp >> 8)), sw = s ^ 0x4444u;
#pragma unroll
    for (int m = M0; m < M1; m++) {
        a[m][0] = prmt_v(r[2 * m + 1], r[2 * m + 2], s); a[m][1] = prmt_v(r[2 * m + 2], r[2 * m + 3], s);
        a[m][2] = prmt_v(r[2 * m + 1], r[2 * m], sw); a[m][3] = prmt_v(r[2 * m + 2], r[2 * m + 1], sw);
    }
}
template <class FG>
__device__ __forceinline__ void conv_main(const Conv& c, uint32_t (&acc)[32], uint32_t sb, uint32_t sel, unsigned char* gy, int warp, size_t ycopy, FG fg) {
    const uint32_t kw = (warp >> 2) * (KW_B / 16) + SM_KW / 16;
    const uint64_t d2 = smem_desc(sb, kw + KW_T2 / 16, KW_KH), d2b = smem_desc(sb, kw + KW_T2 / 16 + 1, KW_KH), d3 = smem_desc(sb, kw + KW_T3 / 16, 16), d3b = smem_desc(sb, kw + KW_T3 / 16 + 32, 16);
    uint32_t a[8][4];
    {
        const int ord = warp < 16 ? 3 - (warp >> 2) : 4;
        if (__builtin_expect(ord >= GATE, 0)) {
            fg(IC<1>());
            mbar_wait(sb + SM_MISC + 376 + 40 + (ord - GATE) * 8);
        }
    }
    wg_fence();
    wg_h<12, 4>(acc, c.q3[0], d3b); wg_h<8, 4>(acc, c.q3[0], d3); wg_h<4, 4>(acc, c.q2[0][0], d2b);
    wg_h<12, 4>(acc, c.q3[1], d3); wg_h<8, 4>(acc, c.q2[1][0], d2b);
    wg_h<12, 4>(acc, c.q2[2][0], d2b); wg_h<4, 4>(acc, c.q2[0][1], d2); wg_h<8, 4>(acc, c.q2[1][1], d2);
    wg_h<12, 4>(acc, c.q2[2][1], d2);
    wg_commit(); __syncwarp();
    fg(IC<0>());
    wg_wait0();
    conv_frags<0, 8>(a, c.r, sel, acc[16], warp);
    fg(IC<2>());
    if (warp >= 16) {
        if (blockIdx.x & 1) conv_tail<4, 16, 2>(acc, a, sb, gy, warp, ycopy, fg);
        else conv_tail<0, 8, 0>(acc, a, sb, gy, warp, ycopy, fg);
    } else {
        conv_tail<0, 16, 0>(acc, a, sb, gy, warp, ycopy, fg);
    }
}
#define CONV_LT6 const int dd = (lane >> 3) + (lane & 4) - (lane & 3); \
        const uint4 lt6 = make_uint4(prmt_v((dd & 3) * 288, 0u, idn), prmt_v(0x3254u + (dd >> 2) * 0x2222u, 0u, idn), \
            prmt_v(UPAD * 16 + (lane & 7) * 16 + ULO_B - 32 + (lane >> 3) * 512, 0u, idn), prmt_v(UPAD * 16 + (lane & 7) * 16 + ((lane >> 3) & 1) * ULO_B - 16 + (lane & 16), 0u, idn));
#define CONV_PRE \
        CONV_LT6 \
        const uint32_t ka = kw + lt6.x, sel = lt6.y, ks = kw + lt7.x; \
        const uint32_t ca0 = sb + SM_U + wg * USLOT_B + (warp & 3) * 128 + lt6.z, ca1 = sb + SM_U + wg * USLOT_B + (warp & 3) * 128 + lt6.w; \
        uint4 bd[4]; \
        band_pair<2, 4>(bd[0], bd[1], lt7.w); band_pair<4, 0>(bd[2], bd[3], lt7.w);
#define CONV_PRE2 ConvPre ce_; conv_pre(ce_, ka, ks, sel);
#define CONV_BODY \
        Conv c; \
        uint32_t acc[32]; \
        conv_sums(c, acc, ce_, ca0, ca1, bd, ka, sel, warp & 3, warp >> 8);
template <int U0, int U1>
__device__ __forceinline__ void weight_units(uint32_t sb, const CUtensorMap* tg, const CUtensorMap* tu, const CUtensorMap* td, int w) {
    if constexpr (U0 < U1) {
        if (w == 0 && elect_one()) {
            if constexpr (U0 < 6) tma_2d(sb + SM_WG + U0 * 6912, tg, 72 * (blockIdx.x >> 1), 288 * (blockIdx.x & 1) + U0 * 48, sb + SM_MISC + 328);
            else if constexpr (U0 < 8) tma_2d(sb + SM_WU + (U0 - 6) * 20736, tu, 72 * (blockIdx.x >> 1), 288 * (blockIdx.x & 1) + (U0 - 6) * 144, sb + SM_MISC + 328);
            else tma_2d(sb + SM_WD + (11 - U0) * 10368, td, 288 * (blockIdx.x & 1) + 72 * (11 - U0), 72 * (blockIdx.x >> 1), sb + SM_MISC + 336);
        }
        weight_units<U0 + 1, U1>(sb, tg, tu, td, w - 1);
    }
}
#define WS x1123478889aaaaaabbc
#define WS_STR2(x) #x
#define WS_STR(x) WS_STR2(x)
__device__ constexpr int wsched(int i) { constexpr char t[] = WS_STR(WS); return i == 0 ? 0 : (t[i] <= '9' ? t[i] - '0' : t[i] - 'a' + 10); }
__device__ constexpr bool wsched_ok() { for (int i = 0; i < 19; i++) if (wsched(i + 1) < wsched(i) || wsched(i + 1) > wsched(i) + (i == 6 ? 8 : i < 16 ? 3 : 1)) return false; return wsched(19) == 12 && wsched(6) <= 7 && wsched(16) <= 11; }
static_assert((PAUSE & 2) && GATE <= 2, "resets");
static_assert(wsched_ok(), "weight schedule");
#define PS x00000
__device__ constexpr int psched(int i) { constexpr char t[] = WS_STR(PS); return i == 0 ? 0 : (t[i] <= '9' ? t[i] - '0' : t[i] - 'a' + 10); }
#define PPOINT(i) do { if (psched(i + 1) > psched(i) && warp == 1 + (i & 1) && elect_one()) \
    l2_prefetch(reinterpret_cast<const unsigned char*>(p.wpf) + b * 41472 + psched(i) * 4608, (psched(i + 1) - psched(i)) * 4608); } while (0)
#define WPOINT(i, w) do { weight_units<wsched(i), wsched(i + 1)>(sb, &tm_g, &tm_u, &tm_d, w); } while (0)

__global__ void __launch_bounds__(NTHR, 1) __cluster_dims__(2, 1, 1)
fused_kernel(const Params p, const __grid_constant__ CUtensorMap tm_g, const __grid_constant__ CUtensorMap tm_u, const __grid_constant__ CUtensorMap tm_d, const __grid_constant__ CUtensorMap tm_x,
             const __grid_constant__ CUtensorMap tm_y, const __grid_constant__ CUtensorMap tm_z) {
    extern __shared__ __align__(1024) unsigned char smem[];
    const uint32_t sb = smem_u32(smem);
    const int tid = threadIdx.x, warp = __shfl_sync(0xffffffffu, tid >> 5, 0), lane = tid & 31;
    const int b = blockIdx.x, P = b >> 1, odd = b & 1;
    const int g = lane >> 2, t = lane & 3;
    const int wg = warp >> 2, t128 = tid & 127;
    const uint32_t s_stat = sb + SM_MISC;
    const uint32_t s_key = sb + SM_MISC + 128;
    const uint32_t s_wm = sb + SM_MISC + 256;
    const uint32_t s_k16 = sb + SM_MISC + 192;
    const uint32_t s_fs = sb + SM_MISC + 256;
    const uint32_t s_cnt = sb + SM_MISC + 320;
    const uint32_t bar_w = sb + SM_MISC + 328, bar_d = bar_w + 8, bar_g = bar_w + 16, bar_r = bar_w + 32, bar_h = bar_w + 40, bar_x = bar_w + 48;
    STAMP(0);

    const bool lnw = (unsigned)(warp - 10) < 9u;
    const unsigned pm = tid + (tid < 512 ? 512 * b : 65024 + 128 * P), pq = (pm & ~127u) + 4 * lane;
    uint32_t pl = ldg16(p.lar + pm), ldt = ldg16(p.ldt + (pm >> 7));
    const uint32_t pa2 = ldg16(p.aim + pm), pc = ldg16(p.cre + pm), pi = ldg16(p.cim + pm);
    const uint2 call_re = ldg64(p.cre + pq), call_im = ldg64(p.cim + pq);
    const uint32_t dskl = ldg16(p.dsk + (pm >> 7));
    const uint32_t ep = ld_poll32(p.s->hint + (b & 7) * 32 + 1 + (lane >> 5));
    if ((unsigned)(tid - 320) < 288u) {
        const bf16* xp = p.x + (unsigned)((32 * P + 2 * odd + TOKEN_OF(g)) * DM + ((tid - 320) & ~31) + 8 * t);
        const uint32_t xt = sb + SM_XT + ((tid - 320) & ~31) * 32 + lane * 16;
        asm volatile("cp.async.cg.shared.global [%0], [%1], 16;\ncp.async.cg.shared.global [%0 + 512], [%1 + 9216], 16;\n"
                     "cp.async.cg.shared.global [%0 + 9216], [%1 + 576], 16;\ncp.async.cg.shared.global [%0 + 9728], [%1 + 9792], 16;\n" ::"r"(xt), "l"(xp) : "memory");
    }
    uint32_t* const std_ = p.s->st + ((lane & 12) * 128 + odd * 256 + 4 * P + 2 * (lane & 1) + ((lane >> 1) & 1)) * 2;
    unsigned char* const ud = reinterpret_cast<unsigned char*>(p.s->uT) + (32 * (warp - UW) + 8 * (g >> 1) + (g & 1)) * 4096 + b * 32 + t * 8;
    if (warp == 0) {
        if (lane == 0) {
            mbar_init(bar_x, 1); mbar_init(bar_w, 1); mbar_init(bar_d, 1); mbar_init(bar_g, 1); mbar_init(bar_h, 3); mbar_init(bar_r, 1);
            #pragma unroll
            for (int i = 1; i < 9; i++) mbar_init(bar_x + 8 * i, 4);
            asm volatile("fence.mbarrier_init.release.cluster;\n" ::: "memory");
            mbar_expect(bar_x, 16384); mbar_expect(bar_r, 8192);
            mbar_expect(bar_w, 2 * 41472); mbar_expect(bar_d, 41472); mbar_expect(bar_g, 18 * 512);
        }
        __syncwarp();
        bar_arrive(0, NWRK);
    }
    if (warp == 0 && elect_one()) tma_3d(sb + SM_XC + 16384, &tm_x, 8 * P, 0, 8 * odd, bar_x);
    asm volatile("barrier.cluster.arrive.relaxed.aligned;\n" ::: "memory");
    const uint32_t kw = sb + SM_KW + wg * KW_B;
    if (t128 < 2 * UPAD) sts128(sb + SM_U + wg * USLOT_B + (t128 & 1) * ULO_B + (t128 >> 1) * 16, 0u, 0u, 0u, 0u);
    sts128(kw + t128 * 16, 0u, 0u, 0u, 0u);
    if (t128 < KW_B / 16 - 128) sts128(kw + 2048 + t128 * 16, 0u, 0u, 0u, 0u);
    if (tid < 96) {
#pragma unroll
        for (int i = 0; i < 6; i++) sts128(sb + SM_ZERO + i * 1536 + tid * 16, 0u, 0u, 0u, 0u);
    }
    if (warp != 0) bar_sync(0, NWRK);
    STAMP(1);
    if (warp == 19 || warp == UW || warp == UW + 1) {
        if (warp == 19) {
            if (lane < 16) stg64(std_, 0u, 0u);
            if (lane < 9) asm volatile("prefetch.global.L2 [%0];\n" ::"l"(p.wr + lane * 64));
        } else {
#pragma unroll
            for (int k = 0; k < 4; k++) stg64(ud + k * 8192, 0u, 0u);
        }
    }
    uint32_t X[2][8];
    auto partial = [&]() {
        const uint32_t xt = sb + SM_XT + (warp - 10) * 1024 + lane * 16;
        asm volatile("cp.async.wait_all;\n" ::: "memory");
        STAMP(23);
        const uint4 a = lds128(xt), c = lds128(xt + 512), d = lds128(xt + 9216), e = lds128(xt + 9728);
        X[0][0] = a.x; X[0][1] = a.y; X[0][2] = a.z; X[0][3] = a.w; X[0][4] = d.x; X[0][5] = d.y; X[0][6] = d.z; X[0][7] = d.w;
        X[1][0] = c.x; X[1][1] = c.y; X[1][2] = c.z; X[1][3] = c.w; X[1][4] = e.x; X[1][5] = e.y; X[1][6] = e.z; X[1][7] = e.w;
        ln_partial<8>(X, sb + SM_LNP, warp - 10, g, t);
        bar_arrive(6, 320);
        if (PAUSE & 1) bar_sync(7, PCNT);
    };
    if (LNAT == 0 && lnw) {
        partial();
        pl = prmt_v(pl, X[0][0], 0x3210u + (warp >> 8)); ldt = prmt_v(ldt, X[0][0], 0x3210u + (warp >> 8));
    }
    auto finish = [&]() {
        bar_sync(6, 320);
        float mb, rc;
        ln_finish<9>(sb + SM_LNP, lane, mb, rc);
        const float rh = rbf(rc);
        const uint32_t s0 = (__float_as_uint(mb) >> 16) | (((ep & 0x7fffu) + 1u) << 16), s1 = pack_bf16(rh, rc - rh);
        if (lane < 16) { stg64(std_, s0, s1); sts64(s_stat + lane * 8, s0, s1); }
        if (lane == 16) sts32(s_cnt + 4, ep);
        bar_arrive(7, PCNT);
        STAMP(28);
    };
    auto upub = [&]() {
        if (!(PAUSE & 6)) bar_sync(7, PCNT);
        const uint32_t utag = ((ep & 3u) + 1u) * 0x10001u;
        uint32_t U[2][4];
#pragma unroll
        for (int hf = 0; hf < 2; hf++) {
            const uint2 st = lds64(s_stat + (g + 8 * hf) * 8);
            const uint4 xv = lds128(sb + SM_XT + (16 + warp - UW) * 1024 + hf * 512 + lane * 16);
            const uint32_t xs[4] = {xv.x, xv.y, xv.z, xv.w};
#pragma unroll
            for (int k = 0; k < 4; k++) {
                const uint32_t u = ln_apply(xs[k], st);
                U[hf][k] = movm((pack_f16_rz(bf_lo(u), __uint_as_float(u)) & 0xfff8fff8u) | utag);
            }
        }
#pragma unroll
        for (int k = 0; k < 4; k++) stg64(ud + k * 8192, U[0][k], U[1][k]);
    };
    if (FINAT == 0 && warp == 19) finish();
    const uint32_t tb = table_buf(sb, warp);
    const float dt = rbf(expf(bf_lo(ldt)));
    KGen kg;
    kgen_setup(kg, pl | (pa2 << 16), dt);
    if (LNAT == 1 && lnw) {
        partial();
        kg.z8.x = __uint_as_float(prmt_v(__float_as_uint(kg.z8.x), X[0][0], 0x3210u + (warp >> 8)));
        kg.z1.x = __uint_as_float(prmt_v(__float_as_uint(kg.z1.x), X[0][0], 0x3210u + (warp >> 8)));
    }
    if (FINAT == 1 && warp == 19) finish();
    if (UAT == 0 && (warp == UW || warp == UW + 1)) upub();
    kgen_rows(kg, tb, lane);
    if (wg == 0) fence_async();
    if (LNAT == 2 && lnw) {
        partial();
        kg.z128.x = __uint_as_float(prmt_v(__float_as_uint(kg.z128.x), X[0][0], 0x3210u + (warp >> 8)));
        kg.z1.x = __uint_as_float(prmt_v(__float_as_uint(kg.z1.x), X[0][0], 0x3210u + (warp >> 8)));
    }
    if (FINAT == 2 && warp == 19) finish();
    if (UAT == 1 && (warp == UW || warp == UW + 1)) upub();
    STAMP(2);
    WPOINT(0, warp - 4);
    PPOINT(0);
    const int ce = c_exponent(call_re, call_im);
    if (t128 == 0) sts64(s_fs + wg * 8, (uint32_t)min(max(ce + (int)(__float_as_uint(dt) >> 23) - 116, 0), 254) * 0x800080u, dskl << 16);
    kgen_chain(kg, pc | (pi << 16), __uint_as_float(((uint32_t)(244 - ce) << 23) | (__float_as_uint(dt) & 0x7fffffu)));
    if ((PAUSE & 4) && warp < 10) bar_sync(7, PCNT);
    if (UAT == 4 && (warp == UW || warp == UW + 1)) upub();
    STAMP(3);
    WPOINT(1, warp - 6);
    PPOINT(1);
    kgen_cols(kg, tb, lane);
    if (LNAT == 3 && lnw) partial();
    if (FINAT == 3 && warp == 19) finish();
    if ((PAUSE & 2) && warp < 10) bar_sync(7, PCNT);
    if (UAT == 2 && (warp == UW || warp == UW + 1)) upub();
    STAMP(4);
    WPOINT(2, warp - 8);
    PPOINT(2);
    const uint4* usrc = wg < 4 ? reinterpret_cast<const uint4*>(p.s->st) + odd * 512 + (lane & 1) * 128 + 16 * (warp & 7) + (lane >> 1)
                               : reinterpret_cast<const uint4*>(p.s->uT) + P * 256 + 2 * t128;
    const int ustep = wg < 4 ? 256 : 1;
    uint4 uv0, uv1;
    kgen_mma(kg, tb, lane);
    if (UAT == 3 && (warp == UW || warp == UW + 1)) upub();
    STAMP(26);
    WPOINT(3, warp - 5);
    PPOINT(3);
    const uint32_t idn = 0x3210u + (warp >> 8);
    const uint4 lt7 = make_uint4(prmt_v(KW_T2 + ((lane >> 3) & 1) * KW_KH + (33 + (lane & 7)) * 16 - (lane & 16), 0u, idn), t * 288 + g * 8 + 8, (lane & 1) * 4096 + (lane >> 1) * 16,
                                 prmt_v(8u << ((lane >> 3) + (lane & 4)) >> (lane & 3), 0u, idn));
    asm volatile("barrier.cluster.wait.acquire.aligned;\n" ::: "memory");
    bar_sync(1 + wg, 128);
    uv0 = ld_poll(usrc); uv1 = ld_poll(usrc + ustep);
    kgen_combine(sb, warp, lane, kw, lt7.y);
    CONV_PRE
    STAMP(5);
    WPOINT(4, warp - 7);
    PPOINT(4);
    if (wg < 4) {
        mbar_wait(bar_x);
        const bool far = DSM == 1 ? warp < 8 : warp >= 8;
        const uint32_t xa = sb + SM_XC + 16384 + (warp & 7) * 256 + (odd ^ far) * 8 + lt7.z;
        uint2 xv[4] = {lds64(xa), lds64(xa + 8192), lds64(xa + 2048), lds64(xa + 10240)};
        const uint32_t tag = ((ep & 0x7fffu) + 1u) << 16;
        int it = 0;
        while (true) {
            const bool bad = (((uv0.x ^ tag) | (uv0.z ^ tag)) | ((uv1.x ^ tag) | (uv1.z ^ tag))) >> 16;
            if (!__any_sync(0xffffffffu, bad)) break;
            if (++it > SPIN_LIMIT) TRAP();
            if (bad) { uv0 = ld_poll(usrc); uv1 = ld_poll(usrc + 256); }
        }
        STAMP(6);
        DBG(wg, it);
        const uint2 st[4] = {make_uint2(uv0.x, uv0.y), make_uint2(uv0.z, uv0.w), make_uint2(uv1.x, uv1.y), make_uint2(uv1.z, uv1.w)};
#pragma unroll
        for (int i = 0; i < 4; i++) {
            xv[i].x = ln_apply(xv[i].x, st[i]);
            xv[i].y = ln_apply(xv[i].y, st[i]);
        }
        const uint32_t ub = sb + SM_U + UPAD * 16 + odd * ULO_B + (warp & 7) * 256 + lane * 8;
        const uint32_t w[4][2] = {{pack_f16(bf_lo(xv[0].x), bf_lo(xv[1].x)), pack_f16(bf_lo(xv[2].x), bf_lo(xv[3].x))}, {HI2(xv[0].x, xv[1].x), HI2(xv[2].x, xv[3].x)},
                                  {pack_f16(bf_lo(xv[0].y), bf_lo(xv[1].y)), pack_f16(bf_lo(xv[2].y), bf_lo(xv[3].y))}, {HI2(xv[0].y, xv[1].y), HI2(xv[2].y, xv[3].y)}};
#pragma unroll
        for (int i = 0; i < 4; i++) {
            if (far) asm volatile("st.async.shared::cluster.mbarrier::complete_tx::bytes.v2.b32 [%0], {%1,%2}, [%3];\n" ::"r"((ub ^ 0x1000000u) + i * USLOT_B), "r"(w[i][0]), "r"(w[i][1]), "r"(bar_r ^ 0x1000000u) : "memory");
            else sts64(ub + i * USLOT_B, w[i][0], w[i][1]);
        }
    } else {
        const uint32_t utag = ((ep & 3u) + 1u) * 0x10001u;
        int it = 0;
        while (true) {
            const bool bad = (((uv0.x ^ utag) | (uv0.y ^ utag) | (uv0.z ^ utag) | (uv0.w ^ utag)) | ((uv1.x ^ utag) | (uv1.y ^ utag) | (uv1.z ^ utag) | (uv1.w ^ utag))) & 0x70007u;
            if (!__any_sync(0xffffffffu, bad)) break;
            if (++it > SPIN_LIMIT) TRAP();
            if (bad) { uv0 = ld_poll(usrc); uv1 = ld_poll(usrc + 1); }
        }
        STAMP(6);
        DBG(4, it);
        const uint32_t ub = sb + SM_U + UPAD * 16 + 4 * USLOT_B + (t128 >> 1) * 32 + (t128 & 1) * 8;
        sts64(ub, prmt(uv0.x, uv0.z, 0x5410u) ^ utag, prmt(uv1.x, uv1.z, 0x5410u) ^ utag);
        sts64(ub + 16, prmt(uv0.x, uv0.z, 0x7632u) ^ utag, prmt(uv1.x, uv1.z, 0x7632u) ^ utag);
        sts64(ub + ULO_B, prmt(uv0.y, uv0.w, 0x5410u) ^ utag, prmt(uv1.y, uv1.w, 0x5410u) ^ utag);
        sts64(ub + ULO_B + 16, prmt(uv0.y, uv0.w, 0x7632u) ^ utag, prmt(uv1.y, uv1.w, 0x7632u) ^ utag);
    }
    if (warp < 3 && elect_one()) tma_st_3d(warp < 2 ? &tm_y : &tm_z, sb + SM_ZERO, warp < 2 ? 128 * b : 32 * (512 + P), 0, 2 * (warp < 2 ? warp : odd));
    WPOINT(5, warp - 3);
    bar_sync(1 + wg, 128);
    CONV_PRE2
    mbar_wait(bar_r);
    fence_async();
    bar_sync(0, NWRK);
    STAMP(7);
    uint32_t hv0 = 0;
    {
        WPOINT(6, 19 - warp);
        CONV_BODY
        WPOINT(7, 19 - warp);
        bar_sync(0, NWRK);
        STAMP(8);
        size_t ycopy = 0;
        auto hook = [&](auto gi) {
                     constexpr int G = decltype(gi)::value;
                     if (G == 4 && warp == HINTW) hv0 = ld_poll32(p.s->hint + (lane_v() & 7) * 32);
                     if (G == 5) mbar_wait(bar_h);
                     if (G == 1 || G == 2) WPOINT(7 + G, warp - 16);
                     if (G == 3) { WPOINT(10, warp - 12); WPOINT(12, warp - 8); WPOINT(14, warp - 4); }
                     if (G == 5) { WPOINT(11, warp - 13); WPOINT(13, warp - 9); WPOINT(15, warp - 5); }
                     if (G == 1 && warp >= 17 && elect_one())
                         bulk_s2g(warp == 17 ? p.s->part + b * (PBYTES / 4) : warp == 18 ? p.s->rows + b * 1152 : p.s->sc + b * 32, sb + SM_ZERO, warp == 17 ? PBYTES : warp == 18 ? 4608 : 32);
                     if (G == 4 && warp >= 17 && elect_one()) {
                         asm volatile("cp.async.bulk.wait_group 0;\n" ::: "memory");
                         hint_arrive(p.s->hint, 2, b & 7);
                     }
                     if (G == 1 && warp < 3) {
                         if (elect_one()) {
                             asm volatile("cp.async.bulk.wait_group 0;\n" ::: "memory");
                             mbar_arrive(bar_h);
                             hint_arrive(p.s->hint, 0, b & 7);
                         }
                         __syncwarp();
                         STAMP(17);
                     }
                 };
        conv_main(c, acc, sb, sel, reinterpret_cast<unsigned char*>(p.s->y), warp, ycopy, hook);
        STAMP(10);
    }
    {
    const int warp = warp_v(), lane = lane_v(), tid = 32 * warp + lane, g = lane >> 2, t = lane & 3;
    if (warp == HINTW) {
        const uint32_t target = (lds32(s_cnt + 4) + 1u) * 48u;
        if (__any_sync(0xffffffffu, (int)(hv0 - target) < 0)) hint_wait(p.s->hint, 0, target);
    }
    const unsigned char* ys = reinterpret_cast<const unsigned char*>(p.s->y) + ((size_t)P * DM + 32 * warp + 8 * (g >> 1) + (g & 1)) * 64 + odd * 32 + t * 8;
    STAMP(27);
    bar_sync(0, NWRK);
    STAMP(11);
    const uint32_t zr = warp >> 8;
    auto late_rows = [&](auto pub) {
        const uint32_t k = lds32(s_key + (lane & 7) * 4), ep = lds32(s_cnt + 4);
        const bool late = k & 256u, mine = late && ((k & 255u) >> 1) == (uint32_t)b;
        uint32_t todo = __ballot_sync(0xffffffffu, mine) & 0xffu;
        if (todo) {
#pragma unroll 1
            while (todo) {
                const int s = __ffs(todo) - 1, row = (__shfl_sync(0xffffffffu, k, s) >> 9) & 15;
                todo &= todo - 1;
                if ((row & 7) == g) pub(row & 8, 2 * NCTA + s);
            }
            __threadfence();
            bar_sync(0, NWRK);
            if (tid < NSEL && mine) *reinterpret_cast<volatile unsigned*>(p.s->flag + tid) = ep + 1u;
        }
        int it = 0;
        while (__any_sync(0xffffffffu, late && ld_poll32(p.s->flag + (lane & 7)) != ep + 1u)) { if (++it > SPIN_LIMIT) TRAP(); }
        __threadfence();
        const int gs = tid / 36;
        const uint4* src = reinterpret_cast<const uint4*>(p.s->rows) + __shfl_sync(0xffffffffu, late ? 2 * NCTA + (lane & 7) : (k & 255u), gs & 7) * 144 + 36 * odd + (tid - gs * 36);
        if (tid < 288) {
            uint4 v0;
            do { v0 = ld_poll(src); if (++it > SPIN_LIMIT) TRAP(); } while (!v0.x);
            sts128(sb + SM_XS + gs * XS_PITCH + (tid - gs * 36) * 16, v0.x, v0.y, v0.z, v0.w);
        }
        bar_sync(0, NWRK);
    };
    if (warp >= 18) {
        if (warp == 18) {
            uint32_t* const kp = pin(p.s->sc + 32 * b, zr);
            const uint32_t kid = pin(0x30000000u | ((lane & 15) << 9) | 2 * b, zr), ka = pin(s_k16 + (lane & 15) * 4, zr), kb = pin(s_k16 + (lane & 16) * 2, zr);
            bar_sync(8, 640);
            float mb, rc;
            ln_finish<18>(sb + SM_LNP, lane, mb, rc);
            if (lane < 16) stat_store(s_stat + lane * 8, mb, rc, 0u);
            bar_arrive(13, 608);
            bar_sync(10, 608);
            const float r = sum18(sb + SM_LNP + (32 + (lane & 15)) * 80);
            const uint32_t bits = pack_bf16(0.f, r);
            const uint32_t me = (((bits ^ ((uint32_t)((int)bits >> 31) & 0x7fffffffu)) >> 3) & 0x1fffe000u) ^ kid;
            sts32(ka, me);
            __syncwarp();
            const uint4 v = lds128(kb), w = lds128(kb + 16);
#define GT(x) ((me - (x)) >> 31)
            uint32_t rank = pin(GT(v.x) + GT(v.y) + GT(v.z), zr) + pin(GT(v.w) + GT(w.x) + GT(w.y), zr) + pin(GT(w.z) + GT(w.w), zr);
#undef GT
            rank += __shfl_xor_sync(0xffffffffu, rank, 16);
            if (lane < 16) { if (rank < 8) stg32(kp + rank, me + (rank < 2 ? rank : 256u)); }
            else sts32(ka + (s_wm - s_k16), rank);
            bar_arrive(11, 640);
        }
        const uint4* ksrc = pin(reinterpret_cast<const uint4*>(p.s->sc) + 8 * lane, zr);
        const uint4* rsrc = pin(reinterpret_cast<const uint4*>(p.s->rows) + 36 * odd + t, zr);
        if (warp == 19) {
            hint_wait(p.s->hint, 2, (lds32(s_cnt + 4) + 1u) * 48u);
            bar_sync(8, 640);
            WPOINT(16, 0);
            WPOINT(17, 0);
            bar_sync(11, 640);
        }
        bool slow = false;
        int it = 0;
        if (warp == 19) {
        uint4 q[4];
#pragma unroll
        for (int i = 0; i < 4; i++) q[i] = ld_poll(ksrc + 256 * i);
        while (true) {
            uint32_t a[4];
#pragma unroll
            for (int i = 0; i < 4; i++) a[i] = q[i].x & q[i].y & q[i].z & q[i].w;
            if (__all_sync(0xffffffffu, a[0] & a[1] & a[2] & a[3])) break;
#pragma unroll
            for (int i = 0; i < 4; i++)
                if (!a[i]) q[i] = ld_poll(ksrc + 256 * i);
            if (++it > SPIN_LIMIT) TRAP();
        }
        bar_arrive(9, 608);
        STAMP(16);
        auto merge = [](const uint4& x, const uint4& y) {
            const uint32_t a = max(x.x, y.w), c = max(x.y, y.z), d = max(x.z, y.y), e = max(x.w, y.x);
            const uint32_t a2 = max(a, d), d2 = min(a, d), c2 = max(c, e), e2 = min(c, e);
            return make_uint4(max(a2, c2), min(a2, c2), max(d2, e2), min(d2, e2));
        };
        uint4 h = merge(merge(q[0], q[1]), merge(q[2], q[3]));
        uint4 v[9];
        uint32_t key = 0;
#pragma unroll
        for (int s = 0; s < 8; s++) {
            const uint32_t m = __reduce_max_sync(0xffffffffu, h.x);
            const bool w = h.x == m;
            h.x = w ? h.y : h.x; h.y = w ? h.z : h.y; h.z = w ? h.w : h.z; h.w = w ? 0u : h.w;
            if (g == s) key = m;
        }
        rsrc += (key & 255u) * 144;
#pragma unroll
        for (int j = 0; j < 9; j++) v[j] = ld_poll(rsrc + 4 * j);
        slow = __any_sync(0xffffffffu, key & 256u);
        STAMP(18);
        if (__any_sync(0xffffffffu, h.x == 0u)) {
            uint4 r[4];
            it = 0;
            while (true) {
#pragma unroll
                for (int i = 0; i < 4; i++) r[i] = ld_poll(ksrc + 256 * i + 1);
                if (__all_sync(0xffffffffu, all_nz(r[0]) && all_nz(r[1]) && all_nz(r[2]) && all_nz(r[3]))) break;
                if (++it > SPIN_LIMIT) TRAP();
            }
            uint32_t m = 1u << 30;
#pragma unroll 1
            for (int s = 0; s < 8; s++) {
                uint32_t x = 0;
#pragma unroll
                for (int i = 0; i < 4; i++) {
                    x = max(max(max(x, q[i].x - m), max(q[i].y - m, q[i].z - m)), q[i].w - m);
                    x = max(max(max(x, r[i].x - m), max(r[i].y - m, r[i].z - m)), r[i].w - m);
                }
                m += __reduce_max_sync(0xffffffffu, x);
                if (g == s) key = m;
            }
            slow = true;
        }
        sts32(s_key + g * 4, key);
        bar_arrive(12, 608);
        if (!slow) {
            it = 0;
            while (true) {
                const uint32_t mn = min(min(min(min(v[0].x, v[1].x), v[2].x), min(min(v[3].x, v[4].x), v[5].x)), min(min(v[6].x, v[7].x), v[8].x));
                if (__all_sync(0xffffffffu, mn)) break;
                if (++it > SPIN_LIMIT) TRAP();
#pragma unroll
                for (int j = 0; j < 9; j++) v[j] = ld_poll(rsrc + 4 * j);
            }
#pragma unroll
            for (int j = 0; j < 9; j++) sts128(sb + SM_XS + g * XS_PITCH + t * 16 + j * 64, v[j].x, v[j].y, v[j].z, v[j].w);
        }
        }
        if (bar_or(0, NWRK, slow)) late_rows([](bool, int) {});
        STAMP(19);
        const int fl = 16 * (b & 1) + ((tid >> 2) & 15), fc = 16 * (b >> 1) + (fl >> 2) + 8 * ((tid >> 1) & 1), fsl = 2 * (fl & 3) + (tid & 1);
        const uint32_t kk = lds32(s_key + fsl * 4);
        const uint32_t* fsrc = p.s->rows + ((kk & 256u) ? 2 * NCTA + fsl : (kk & 255u)) * DM + (fc >> 1);
        uint32_t hw = 1u, uw = 1u;
        if (b < 72) { uw = ld_poll32(fsrc); hw = ld_poll32(fsrc + 288); }
        if (b < 72) {
            it = 0;
            while (!hw || !uw) { uw = ld_poll32(fsrc); hw = ld_poll32(fsrc + 288); if (++it > SPIN_LIMIT) TRAP(); }
            const int row = (kk >> 9) & 15, ftok = 8 * (kk & 252u) + (kk & 2u) + TOKEN_OF(row & 7) + (row & 8);
            const unsigned k16 = (kk >> 13) & 0xffffu;
            const unsigned bits = (k16 & 0x8000u) ? (k16 & 0x7fffu) : (~k16 & 0xffffu);
            const float rs = __uint_as_float(pin(__float_as_uint(rbf(__fdividef(1.0f, 1.0f + __expf(-__uint_as_float(bits << 16))))), zr));
            bf16* const op = pin(p.out + (size_t)ftok * DM + fc, zr);
            const float uv = (fc & 1) ? bf_hi(uw) : bf_lo(uw), hv = (fc & 1) ? bf_hi(hw) : bf_lo(hw);
            bar_sync(14, 576);
            float v0 = 0.f, v1 = 0.f, v2 = 0.f, v3 = 0.f;
            const uint32_t a = sb + SM_EX + (tid - 576) * 4;
#pragma unroll
            for (int i = 0; i < 16; i += 4) { v0 += ldsf(a + i * 256); v1 += ldsf(a + i * 256 + 256); v2 += ldsf(a + i * 256 + 512); v3 += ldsf(a + i * 256 + 768); }
            const float y3 = rbf(rbf(((v0 + v1) + (v2 + v3)) * 512.0f) * rs);
            asm volatile("st.global.u16 [%0], %1;\n" ::"l"(op), "h"((unsigned short)pack_bf16(hv + rbf(uv + y3), 0.f)) : "memory");
        }
        if (b == 0 && tid >= 632) *reinterpret_cast<volatile unsigned*>(p.s->hint + (tid & 7) * 32 + 1) = lds32(s_cnt + 4) + 1u;
    } else {
        uint32_t H[2][4], U2[2][4], WA[9][4], WD[18];
        const int fkh = warp >= 9, fmt = warp - 9 * fkh;
        auto load_wa = [&](auto k0, auto k1) {
            if (k0.value >= k1.value) return;
            if (k0.value == 0) mbar_wait(bar_w);
            const int mi = lane >> 3, rr = lane & 7;
            const uint32_t aad = sb + SM_WG + (mi & 1) * SM_WU + (fkh * 144 + rr + 8 * (mi >> 1)) * W_PITCH + fmt * 16;
#pragma unroll
            for (int k = k0.value; k < k1.value; k++) ldsm_x4_t(WA[k][0], WA[k][1], WA[k][2], WA[k][3], aad + k * 16 * W_PITCH);
        };
        auto load_wd = [&]() {
            mbar_wait(bar_d);
            const int mi = lane >> 3, rr = lane & 7;
            const int c8 = 2 * warp + (mi & 1), bx = c8 / 9;
            const uint32_t base = sb + SM_WD + bx * 10368 + (c8 - 9 * bx) * 16 + rr * W_PITCH;
#pragma unroll
            for (int k = 0; k < 4; k++) ldsm_x4_t(WD[4 * k], WD[4 * k + 1], WD[4 * k + 2], WD[4 * k + 3], base + (k * 16 + 8 * (mi >> 1)) * W_PITCH);
            ldsm_x2_t(WD[16], WD[17], base + 64 * W_PITCH);
        };
        auto publish = [&](bool hi, int slot) {
            uint4* rowp = reinterpret_cast<uint4*>(p.s->rows) + slot * 144 + warp * 4 + t;
            stg128(rowp, nzw(hi ? U2[1][0] : U2[0][0]), nzw(hi ? U2[1][1] : U2[0][1]), nzw(hi ? U2[1][2] : U2[0][2]), nzw(hi ? U2[1][3] : U2[0][3]));
            stg128(rowp + 72, nzw(hi ? H[1][0] : H[0][0]), nzw(hi ? H[1][1] : H[0][1]), nzw(hi ? H[1][2] : H[0][2]), nzw(hi ? H[1][3] : H[0][3]));
        };
        uint4 wr = make_uint4(0u, 0u, 0u, 0u);
        {
            uint2 yv[4];
#pragma unroll
            for (int k = 0; k < 4; k++) yv[k] = ld_poll64(ys + k * 128);
            if (g == 0) wr = ldg128(p.wr + 32 * warp + 8 * t);
            const uint4 x0 = lds128(sb + SM_XT + warp * 1024 + lane * 16), x1 = lds128(sb + SM_XT + warp * 1024 + 512 + lane * 16);
            load_wa(IC<0>(), IC<WA0>());
            int it = 0;
            while (!__all_sync(0xffffffffu, yv[0].x && yv[1].x && yv[2].x && yv[3].x)) {
#pragma unroll
                for (int k = 0; k < 4; k++) yv[k] = ld_poll64(ys + k * 128);
                if (++it > SPIN_LIMIT) TRAP();
            }
            STAMP(12);
            const uint32_t Z[2][4] = {{x0.x, x0.y, x0.z, x0.w}, {x1.x, x1.y, x1.z, x1.w}};
#pragma unroll
            for (int k = 0; k < 4; k++) {
                H[0][k] = hadd2_bf(Z[0][k], movm(yv[k].x));
                H[1][k] = hadd2_bf(Z[1][k], movm(yv[k].y));
            }
            ln_partial<4>(H, sb + SM_LNP, warp, g, t);
        }
        bar_arrive(8, 640);
        load_wa(IC<WA0>(), IC<WA1>());
        STAMP(13);
        bar_sync(13, 608);
        STAMP(14);
#pragma unroll
        for (int hf = 0; hf < 2; hf++) {
            const uint2 st = lds64(s_stat + (g + 8 * hf) * 8);
#pragma unroll
            for (int k = 0; k < 4; k++) U2[hf][k] = ln_apply(H[hf][k], st);
        }
        {
            float cs[4] = {0.f, 0.f, 0.f, 0.f};
            mma_bf16(cs, U2[0][0], U2[1][0], U2[0][1], U2[1][1], wr.x, wr.y);
            mma_bf16(cs, U2[0][2], U2[1][2], U2[0][3], U2[1][3], wr.z, wr.w);
            if (t == 0) { stsf(sb + SM_LNP + ((32 + g) * 20 + warp) * 4, cs[0]); stsf(sb + SM_LNP + ((40 + g) * 20 + warp) * 4, cs[2]); }
            bar_arrive(10, 608);
        }
        load_wa(IC<WA1>(), IC<WA2>());
        bar_sync(11, 640);
        {
            const uint32_t rk[2] = {lds32(s_wm + g * 4), lds32(s_wm + 32 + g * 4)};
            uint32_t lo = min(rk[0], rk[1]), hi = max(rk[0], rk[1]);
#pragma unroll 1
            while (lo < 2) { publish(lo == rk[1], 2 * b + lo); lo = hi; hi = 16; }
        }
        load_wa(IC<WA2>(), IC<WA3>());
        bar_sync(9, 608);
        load_wa(IC<WA3>(), IC<9>());
#pragma unroll
        for (int hf = 0; hf < 2; hf++)
            sts128(sb + SM_OUT + (g + 8 * hf) * OUT_PITCH + warp * 64 + t * 16,
                   hadd2_bf(H[hf][0], U2[hf][0]), hadd2_bf(H[hf][1], U2[hf][1]), hadd2_bf(H[hf][2], U2[hf][2]), hadd2_bf(H[hf][3], U2[hf][3]));
        fence_async();
        WPOINT(18, warp - 17);
        if (WDAT == 0) load_wd();
        const uint32_t bad = pin(sb + SM_XS + (lane & 7) * XS_PITCH + (fkh * 144 + 8 * (lane >> 3)) * 2, zr), ex = pin(sb + SM_EX + (18 * odd + warp) * 512 + lane * 16, zr);
        uint32_t* const pp = pin(p.s->part + ((size_t)(2 * (18 * odd + warp) + (lane >> 4)) * 64 + P) * 32 + (lane & 15) * 2, zr);
        bar_sync(12, 608);
        if (warp < 16 && !__any_sync(0xffffffffu, (lds32(s_key + (lane & 7) * 4) & 0x1efeu) == (uint32_t)((warp << 9) | 2 * b)) && elect_one())
            bulk_s2g(p.out + (size_t)(32 * P + 2 * odd + TOKEN_OF(warp & 7) + (warp & 8)) * DM, sb + SM_OUT + warp * OUT_PITCH, DM * 2);
        STAMP(15);
        if (bar_or(0, NWRK, false)) late_rows(publish);
        STAMP(19);
        {
            float c4[3][4];
#pragma unroll
            for (int i = 0; i < 3; i++)
#pragma unroll
                for (int j = 0; j < 4; j++) c4[i][j] = 0.f;
#pragma unroll
            for (int k = 0; k < 10; k += 2) {
                uint32_t b0, b1, b2, b3;
                ldsm_x4(b0, b1, b2, b3, bad + k * 32);
                mma_bf16(c4[k % 3], WA[k][0], WA[k][1], WA[k][2], WA[k][3], b0, b1);
                if (k < 8) mma_bf16(c4[(k + 1) % 3], WA[k + 1][0], WA[k + 1][1], WA[k + 1][2], WA[k + 1][3], b2, b3);
            }
#pragma unroll
            for (int j = 0; j < 4; j++) c4[0][j] += c4[1][j] + c4[2][j];
            asm volatile("st.async.shared::cluster.mbarrier::complete_tx::bytes.v4.b32 [%0], {%1,%2,%3,%4}, [%5];\n"
                         ::"r"(ex ^ 0x1000000u), "r"(__float_as_uint(c4[0][0])), "r"(__float_as_uint(c4[0][1])), "r"(__float_as_uint(c4[0][2])), "r"(__float_as_uint(c4[0][3])), "r"(bar_g ^ 0x1000000u) : "memory");
            sts128f(ex, c4[0]);
            if (warp >= 9) bar_arrive(6, 576);
            if (WDAT == 1) load_wd();
        }
        STAMP(20);
        if (warp < 9) {
            bar_sync(6, 576);
            mbar_wait(bar_g);
            const uint32_t ex = sb + SM_EX + tid * 16;
            const uint4 u = lds128(ex), v = lds128(ex + 4608), w = lds128(ex + 9216), x = lds128(ex + 13824);
#define S4(f) rbf((__uint_as_float(u.f) + __uint_as_float(v.f)) + (__uint_as_float(w.f) + __uint_as_float(x.f)))
            const float G0 = S4(x), G1 = S4(y), U0 = S4(z), U1 = S4(w);
#undef S4
            sts32(sb + SM_GU + tid * 4, pack_bf16(rbf(__fdividef(G0, 1.0f + __expf(-G0))) * U0, rbf(__fdividef(G1, 1.0f + __expf(-G1))) * U1));
        }
        const uint2* src = pin(reinterpret_cast<const uint2*>(p.s->part) + (size_t)b * 1024 + tid, zr);
        bar_sync(7, 576);
        STAMP(21);
        {
            uint32_t gb[9];
            ldsm_x4_t(gb[0], gb[1], gb[2], gb[3], sb + SM_GU + lane * 16);
            ldsm_x4_t(gb[4], gb[5], gb[6], gb[7], sb + SM_GU + 512 + lane * 16);
            ldsm_x1_t(gb[8], sb + SM_GU + 1024 + (lane & 7) * 16);
            float c4[4] = {0.f, 0.f, 0.f, 0.f}, d4[4] = {0.f, 0.f, 0.f, 0.f};
            mma_bf16(c4, WD[0], WD[1], WD[2], WD[3], gb[0], gb[1]);
            mma_bf16(d4, WD[4], WD[5], WD[6], WD[7], gb[2], gb[3]);
            mma_bf16(c4, WD[8], WD[9], WD[10], WD[11], gb[4], gb[5]);
            mma_bf16(d4, WD[12], WD[13], WD[14], WD[15], gb[6], gb[7]);
            mma_bf16(c4, WD[16], WD[17], 0u, 0u, gb[8], 0u);
            const float v0 = c4[0] + d4[0], v1 = c4[1] + d4[1], v2 = c4[2] + d4[2], v3 = c4[3] + d4[3];
            const uint32_t e = min(max(__float_as_uint(fmaxf(fmaxf(fabsf(v0), fabsf(v1)), fmaxf(fabsf(v2), fabsf(v3)))) >> 23, 16u), 244u);
            const float sc = __uint_as_float((245u - e) << 23);
            stg64(pp, pack_f16(v0 * sc, v1 * sc) | ((e * 0x8002000u) & 0x60006000u), pack_f16(v2 * sc, v3 * sc) | ((e * 0x800200u) & 0x60006000u));
        }
        asm volatile("cp.async.bulk.wait_group.read 0;\n" ::: "memory");
        STAMP(22);
        if (b < 72 && warp < 16) {
            uint2 a, c;
            int it = 0;
            a = ld_poll64(src); c = ld_poll64(src + 512);
            while (!__all_sync(0xffffffffu, a.y && c.y)) {
                a = ld_poll64(src); c = ld_poll64(src + 512);
                if (++it > SPIN_LIMIT) TRAP();
            }
            STAMP(24);
            const float ea = __uint_as_float((((a.y & 0x60006000u) | ((a.x >> 4) & 0x06000600u)) * 0x4001u) & 0x7f800000u);
            const float ec = __uint_as_float((((c.y & 0x60006000u) | ((c.x >> 4) & 0x06000600u)) * 0x4001u) & 0x7f800000u);
            a.x &= 0x9fff9fffu; a.y &= 0x9fff9fffu; c.x &= 0x9fff9fffu; c.y &= 0x9fff9fffu;
            const float s0 = fmaf(h_lo(a.x), ea, h_lo(c.x) * ec), s1 = fmaf(h_hi(a.x), ea, h_hi(c.x) * ec), s2 = fmaf(h_lo(a.y), ea, h_lo(c.y) * ec), s3 = fmaf(h_hi(a.y), ea, h_hi(c.y) * ec);
            const bool up = lane & 16;
            const float r0 = __shfl_xor_sync(0xffffffffu, up ? s0 : s2, 16), r1 = __shfl_xor_sync(0xffffffffu, up ? s1 : s3, 16);
            sts64f(sb + SM_EX + warp * 256 + (lane & 15) * 16 + (up ? 8 : 0), (up ? s2 : s0) + r0, (up ? s3 : s1) + r1);
            bar_arrive(14, 576);
        }
    }
    STAMP(25);
    }
}

typedef CUresult (*PFN_tmEncode)(CUtensorMap*, CUtensorMapDataType, cuuint32_t, void*, const cuuint64_t*, const cuuint64_t*, const cuuint32_t*,
                                 const cuuint32_t*, CUtensorMapInterleave, CUtensorMapSwizzle, CUtensorMapL2promotion, CUtensorMapFloatOOBfill);

extern "C" void kernel_launch(void* const* d_in, const int* in_sizes, int n_in, void* d_out, int out_size) {
    Params p;
    p.x = (const bf16*)d_in[0];
    p.lar = (const bf16*)d_in[1];
    p.aim = (const bf16*)d_in[2];
    p.cre = (const bf16*)d_in[3];
    p.cim = (const bf16*)d_in[4];
    p.ldt = (const bf16*)d_in[5];
    p.dsk = (const bf16*)d_in[6];
    p.wr = (const bf16*)d_in[8];
    p.wpf = (const bf16*)d_in[PFW];
    p.out = (bf16*)d_out;
    static PFN_tmEncode enc = nullptr;
    static void* scratch = nullptr;
    if (!enc) {
        cudaFuncSetAttribute(fused_kernel, cudaFuncAttributeMaxDynamicSharedMemorySize, SMEM_TOTAL);
        void* fn = nullptr;
        cudaDriverEntryPointQueryResult qr;
        cudaGetDriverEntryPoint("cuTensorMapEncodeTiled", &fn, cudaEnableDefault, &qr);
        enc = (PFN_tmEncode)fn;
        cudaGetSymbolAddress(&scratch, g_scratch);
    }
    p.s = (Scratch*)scratch;
    CUtensorMap tm_g, tm_u, tm_d, tm_x, tm_y, tm_z;
    const cuuint64_t dims[2] = {FF, DM}, strides[1] = {FF * 2};
    const cuuint32_t box[2] = {72, 48}, es[2] = {1, 1};
    enc(&tm_g, CU_TENSOR_MAP_DATA_TYPE_BFLOAT16, 2, d_in[9], dims, strides, box, es, CU_TENSOR_MAP_INTERLEAVE_NONE, CU_TENSOR_MAP_SWIZZLE_NONE,
        CU_TENSOR_MAP_L2_PROMOTION_NONE, CU_TENSOR_MAP_FLOAT_OOB_FILL_NONE);
    const cuuint32_t ubox[2] = {72, 144}, es3[3] = {1, 1, 1};
    enc(&tm_u, CU_TENSOR_MAP_DATA_TYPE_BFLOAT16, 2, d_in[10], dims, strides, ubox, es, CU_TENSOR_MAP_INTERLEAVE_NONE, CU_TENSOR_MAP_SWIZZLE_NONE,
        CU_TENSOR_MAP_L2_PROMOTION_NONE, CU_TENSOR_MAP_FLOAT_OOB_FILL_NONE);
    const cuuint64_t ddims[2] = {DM, FF}, dstrides[1] = {DM * 2};
    const cuuint32_t dbox[2] = {72, 72};
    enc(&tm_d, CU_TENSOR_MAP_DATA_TYPE_BFLOAT16, 2, d_in[11], ddims, dstrides, dbox, es, CU_TENSOR_MAP_INTERLEAVE_NONE, CU_TENSOR_MAP_SWIZZLE_NONE,
        CU_TENSOR_MAP_L2_PROMOTION_NONE, CU_TENSOR_MAP_FLOAT_OOB_FILL_NONE);
    const cuuint64_t xdims[3] = {DM, LSEQ / 16, 16}, xstrides[2] = {16 * DM * 2, DM * 2};
    const cuuint32_t xbox[3] = {8, LSEQ / 16, 8};
    enc(&tm_x, CU_TENSOR_MAP_DATA_TYPE_BFLOAT16, 3, d_in[0], xdims, xstrides, xbox, es3, CU_TENSOR_MAP_INTERLEAVE_NONE, CU_TENSOR_MAP_SWIZZLE_NONE,
        CU_TENSOR_MAP_L2_PROMOTION_NONE, CU_TENSOR_MAP_FLOAT_OOB_FILL_NONE);
    const cuuint64_t ydims[3] = {DM * 32, 16, 4}, ystrides[2] = {DM * 64, 16 * DM * 64};
    const cuuint32_t ybox[3] = {128, 16, 2}, zbox[3] = {32, 16, 2};
    enc(&tm_y, CU_TENSOR_MAP_DATA_TYPE_BFLOAT16, 3, p.s->y, ydims, ystrides, ybox, es3, CU_TENSOR_MAP_INTERLEAVE_NONE, CU_TENSOR_MAP_SWIZZLE_NONE,
        CU_TENSOR_MAP_L2_PROMOTION_NONE, CU_TENSOR_MAP_FLOAT_OOB_FILL_NONE);
    enc(&tm_z, CU_TENSOR_MAP_DATA_TYPE_BFLOAT16, 3, p.s->y, ydims, ystrides, zbox, es3, CU_TENSOR_MAP_INTERLEAVE_NONE, CU_TENSOR_MAP_SWIZZLE_NONE,
        CU_TENSOR_MAP_L2_PROMOTION_NONE, CU_TENSOR_MAP_FLOAT_OOB_FILL_NONE);
    fused_kernel<<<NCTA, NTHR, SMEM_TOTAL>>>(p, tm_g, tm_u, tm_d, tm_x, tm_y, tm_z);
}
```

```cpp
#include <cuda_runtime.h>
#include <cuda.h>
#include <cuda_fp16.h>
#include <cuda_bf16.h>
#include <stdint.h>

#define LSEQ 2048
#define DM 576
#define NST 128
#define FF 4608
#define NSEL 8
#define NCTA 128
#define NTHR 640
#define NWRK 640

typedef __nv_bfloat16 bf16;

#define SM_WD 0
#define SM_WG 46080
#define SM_WU 87552
#define W_PITCH 144
#define SM_ZERO 36864
#define SM_XC 18432
#define SM_TB 96000
#define SM_PL 129024
#define PL_B 10752
#define SM_XT (SM_TB + 20 * TBW)
#define SM_U (SM_XT + 18432)
#define UPAD 8
#define ULO_B ((UPAD + 128) * 16)
#define USLOT_B (2 * ULO_B)
#define SM_KW (SM_U + 5 * USLOT_B)
#define KW_B 3600
#define KW_T2 1152
#define KW_KH 656
#define KW_T3 2464
#define SM_MISC (SM_KW + 5 * KW_B)
#define SM_LNP (SM_MISC + 576)
#define SMEM_TOTAL (SM_LNP + 3840)
#define TBP 112
#define TBW (32 * TBP)
#define SM_OUT SM_PL
#define OUT_PITCH 1216
#define SM_XS (SM_PL + 19456)
#define XS_PITCH 592
#define SM_EX (SM_PL + 24320)
#define SM_GU (SM_PL + 33536)

struct __align__(128) Scratch {
    unsigned hint[8 * 32];
    unsigned flag[32];
    uint32_t sc[NCTA * 32];
    uint32_t st[LSEQ * 2];
    uint32_t uT[64 * (LSEQ / 2)];
    uint32_t y[NCTA * DM * 8];
    uint32_t part[72 * 64 * 32];
    uint32_t rows[(2 * NCTA + NSEL) * DM];
};
__device__ Scratch g_scratch;
#define STAMP(i)
#define DBG(i, v)

__device__ __forceinline__ float rbf(float x) {
    uint32_t r;
    asm("cvt.rn.bf16x2.f32 %0, %1, %2;\n" : "=r"(r) : "f"(x), "f"(0.f));
    return __uint_as_float(r & 0xffff0000u);
}
__device__ __forceinline__ uint32_t pack_bf16(float lo, float hi) {
    uint32_t r;
    asm("cvt.rn.bf16x2.f32 %0, %1, %2;\n" : "=r"(r) : "f"(hi), "f"(lo));
    return r;
}
__device__ __forceinline__ uint32_t pack_f16(float lo, float hi) {
    uint32_t r;
    asm("cvt.rn.f16x2.f32 %0, %1, %2;\n" : "=r"(r) : "f"(hi), "f"(lo));
    return r;
}
__device__ __forceinline__ uint32_t pack_f16_rz(float lo, float hi) {
    uint32_t r;
    asm("cvt.rz.f16x2.f32 %0, %1, %2;\n" : "=r"(r) : "f"(hi), "f"(lo));
    return r;
}
__device__ __forceinline__ float bf_lo(uint32_t w) { return __uint_as_float(w << 16); }
__device__ __forceinline__ float bf_hi(uint32_t w) { return __uint_as_float(w & 0xffff0000u); }
__device__ __forceinline__ uint32_t hadd2_bf(uint32_t a, uint32_t b) {
    __nv_bfloat162 r = __hadd2_rn(*reinterpret_cast<__nv_bfloat162*>(&a), *reinterpret_cast<__nv_bfloat162*>(&b));
    return *reinterpret_cast<uint32_t*>(&r);
}
__device__ __forceinline__ uint32_t hsub2_bf(uint32_t a, uint32_t b) {
    __nv_bfloat162 r = __hsub2_rn(*reinterpret_cast<__nv_bfloat162*>(&a), *reinterpret_cast<__nv_bfloat162*>(&b));
    return *reinterpret_cast<uint32_t*>(&r);
}
__device__ __forceinline__ uint32_t hmul2_bf(uint32_t a, uint32_t b) {
    __nv_bfloat162 r = __hmul2_rn(*reinterpret_cast<__nv_bfloat162*>(&a), *reinterpret_cast<__nv_bfloat162*>(&b));
    return *reinterpret_cast<uint32_t*>(&r);
}
__device__ __forceinline__ uint32_t hfma2_bf(uint32_t a, uint32_t b, uint32_t c) { uint32_t r; asm("fma.rn.bf16x2 %0, %1, %2, %3;\n" : "=r"(r) : "r"(a), "r"(b), "r"(c)); return r; }
__device__ __forceinline__ uint32_t hmul2(uint32_t a, uint32_t b) { uint32_t r; asm("mul.rn.f16x2 %0, %1, %2;\n" : "=r"(r) : "r"(a), "r"(b)); return r; }
__device__ __forceinline__ uint32_t hadd2(uint32_t a, uint32_t b) { uint32_t r; asm("add.rn.f16x2 %0, %1, %2;\n" : "=r"(r) : "r"(a), "r"(b)); return r; }
__device__ __forceinline__ uint32_t hfma2(uint32_t a, uint32_t b, uint32_t c) { uint32_t r; asm("fma.rn.f16x2 %0, %1, %2, %3;\n" : "=r"(r) : "r"(a), "r"(b), "r"(c)); return r; }
__device__ __forceinline__ uint32_t nzw(uint32_t w) { return w ? w : 0x8000u; }
__device__ __forceinline__ uint32_t nzf(float f) { const uint32_t w = __float_as_uint(f); return w ? w : 0x80000000u; }
__device__ __forceinline__ uint32_t smem_u32(const void* p) { return (uint32_t)__cvta_generic_to_shared(p); }
__device__ __forceinline__ uint32_t lds32(uint32_t addr) {
    uint32_t v;
    asm volatile("ld.shared.u32 %0, [%1];\n" : "=r"(v) : "r"(addr) : "memory");
    return v;
}
__device__ __forceinline__ uint32_t lds16(uint32_t addr) {
    unsigned short v;
    asm volatile("ld.shared.u16 %0, [%1];\n" : "=h"(v) : "r"(addr) : "memory");
    return v;
}
__device__ __forceinline__ uint2 lds64(uint32_t addr) {
    uint2 v;
    asm volatile("ld.shared.v2.u32 {%0,%1}, [%2];\n" : "=r"(v.x), "=r"(v.y) : "r"(addr) : "memory");
    return v;
}
__device__ __forceinline__ uint4 lds128(uint32_t addr) {
    uint4 v;
    asm volatile("ld.shared.v4.u32 {%0,%1,%2,%3}, [%4];\n" : "=r"(v.x), "=r"(v.y), "=r"(v.z), "=r"(v.w) : "r"(addr) : "memory");
    return v;
}
__device__ __forceinline__ float ldsf(uint32_t addr) { return __uint_as_float(lds32(addr)); }
__device__ __forceinline__ void sts32(uint32_t addr, uint32_t v) { asm volatile("st.shared.u32 [%0], %1;\n" ::"r"(addr), "r"(v) : "memory"); }
__device__ __forceinline__ void stsf(uint32_t addr, float v) { sts32(addr, __float_as_uint(v)); }
__device__ __forceinline__ void sts64(uint32_t addr, uint32_t a, uint32_t b) { asm volatile("st.shared.v2.u32 [%0], {%1,%2};\n" ::"r"(addr), "r"(a), "r"(b) : "memory"); }
__device__ __forceinline__ void sts64f(uint32_t addr, float a, float b) { sts64(addr, __float_as_uint(a), __float_as_uint(b)); }
__device__ __forceinline__ void sts128(uint32_t addr, uint32_t a, uint32_t b, uint32_t c, uint32_t d) {
    asm volatile("st.shared.v4.u32 [%0], {%1,%2,%3,%4};\n" ::"r"(addr), "r"(a), "r"(b), "r"(c), "r"(d) : "memory");
}
__device__ __forceinline__ void sts128f(uint32_t addr, const float (&v)[4]) {
    sts128(addr, __float_as_uint(v[0]), __float_as_uint(v[1]), __float_as_uint(v[2]), __float_as_uint(v[3]));
}
__device__ __forceinline__ void ldsm_x4(uint32_t& r0, uint32_t& r1, uint32_t& r2, uint32_t& r3, uint32_t addr) {
    asm volatile("ldmatrix.sync.aligned.m8n8.x4.shared.b16 {%0,%1,%2,%3}, [%4];\n"
                 : "=r"(r0), "=r"(r1), "=r"(r2), "=r"(r3) : "r"(addr) : "memory");
}
__device__ __forceinline__ void ldsm_x4_t(uint32_t& r0, uint32_t& r1, uint32_t& r2, uint32_t& r3, uint32_t addr) {
    asm volatile("ldmatrix.sync.aligned.m8n8.x4.trans.shared.b16 {%0,%1,%2,%3}, [%4];\n"
                 : "=r"(r0), "=r"(r1), "=r"(r2), "=r"(r3) : "r"(addr) : "memory");
}
__device__ __forceinline__ void ldsm_x2_t(uint32_t& r0, uint32_t& r1, uint32_t addr) {
    asm volatile("ldmatrix.sync.aligned.m8n8.x2.trans.shared.b16 {%0,%1}, [%2];\n" : "=r"(r0), "=r"(r1) : "r"(addr) : "memory");
}
__device__ __forceinline__ void ldsm_x1_t(uint32_t& r0, uint32_t addr) {
    asm volatile("ldmatrix.sync.aligned.m8n8.x1.trans.shared.b16 {%0}, [%1];\n" : "=r"(r0) : "r"(addr) : "memory");
}
__device__ __forceinline__ uint32_t movm(uint32_t a) {
    uint32_t d;
    asm volatile("movmatrix.sync.aligned.m8n8.trans.b16 %0, %1;\n" : "=r"(d) : "r"(a));
    return d;
}
__device__ __forceinline__ void mma_f16(float (&c)[4], uint32_t a0, uint32_t a1, uint32_t a2, uint32_t a3, uint32_t b0, uint32_t b1) {
    asm volatile(
        "mma.sync.aligned.m16n8k16.row.col.f32.f16.f16.f32 {%0,%1,%2,%3}, {%4,%5,%6,%7}, {%8,%9}, {%0,%1,%2,%3};\n"
        : "+f"(c[0]), "+f"(c[1]), "+f"(c[2]), "+f"(c[3])
        : "r"(a0), "r"(a1), "r"(a2), "r"(a3), "r"(b0), "r"(b1));
}
__device__ __forceinline__ void mma_bf16(float (&c)[4], uint32_t a0, uint32_t a1, uint32_t a2, uint32_t a3, uint32_t b0, uint32_t b1) {
    asm volatile(
        "mma.sync.aligned.m16n8k16.row.col.f32.bf16.bf16.f32 {%0,%1,%2,%3}, {%4,%5,%6,%7}, {%8,%9}, {%0,%1,%2,%3};\n"
        : "+f"(c[0]), "+f"(c[1]), "+f"(c[2]), "+f"(c[3])
        : "r"(a0), "r"(a1), "r"(a2), "r"(a3), "r"(b0), "r"(b1));
}
__device__ __forceinline__ void mma_bf16_k8(float (&c)[4], uint32_t a0, uint32_t a1, uint32_t b0) {
    asm volatile("mma.sync.aligned.m16n8k8.row.col.f32.bf16.bf16.f32 {%0,%1,%2,%3}, {%4,%5}, {%6}, {%0,%1,%2,%3};\n"
        : "+f"(c[0]), "+f"(c[1]), "+f"(c[2]), "+f"(c[3]) : "r"(a0), "r"(a1), "r"(b0));
}
__device__ __forceinline__ void bar_sync(int id, int n) { asm volatile("bar.sync %0, %1;\n" ::"r"(id), "r"(n) : "memory"); }
__device__ __forceinline__ void bar_arrive(int id, int n) { asm volatile("bar.arrive %0, %1;\n" ::"r"(id), "r"(n) : "memory"); }
__device__ __forceinline__ bool bar_or(int id, int n, bool v) {
    uint32_t r;
    asm volatile("{\n.reg .pred p, q;\nsetp.ne.u32 p, %3, 0;\nbar.red.or.pred q, %1, %2, p;\nselp.u32 %0, 1, 0, q;\n}\n" : "=r"(r) : "r"(id), "r"(n), "r"((uint32_t)v) : "memory");
    return r;
}
__device__ __forceinline__ uint4 ld_poll(const void* p) {
    uint4 v;
    asm volatile("ld.relaxed.gpu.global.v4.u32 {%0,%1,%2,%3}, [%4];\n" : "=r"(v.x), "=r"(v.y), "=r"(v.z), "=r"(v.w) : "l"(p) : "memory");
    return v;
}
template <class T> __device__ __forceinline__ T* pin(T* p, uint32_t z) {
    uint32_t lo, hi;
    asm volatile("mov.b64 {%0, %1}, %2;\n" : "=r"(lo), "=r"(hi) : "l"(p));
    asm volatile("xor.b32 %0, %0, %1;\n" : "+r"(lo) : "r"(z));
    asm volatile("xor.b32 %0, %0, %1;\n" : "+r"(hi) : "r"(z));
    asm volatile("mov.b64 %0, {%1, %2};\n" : "=l"(p) : "r"(lo), "r"(hi));
    return p;
}
__device__ __forceinline__ uint32_t pin(uint32_t a, uint32_t z) { asm volatile("xor.b32 %0, %0, %1;\n" : "+r"(a) : "r"(z)); return a; }
__device__ __forceinline__ uint2 ld_poll64(const void* p) {
    uint2 v;
    asm volatile("ld.relaxed.gpu.global.v2.u32 {%0,%1}, [%2];\n" : "=r"(v.x), "=r"(v.y) : "l"(p) : "memory");
    return v;
}
__device__ __forceinline__ uint32_t ld_poll32(const void* p) {
    uint32_t v;
    asm volatile("ld.relaxed.gpu.global.u32 %0, [%1];\n" : "=r"(v) : "l"(p) : "memory");
    return v;
}
__device__ __forceinline__ uint4 ldg128(const void* p) {
    uint4 v;
    asm volatile("ld.global.nc.v4.u32 {%0,%1,%2,%3}, [%4];\n" : "=r"(v.x), "=r"(v.y), "=r"(v.z), "=r"(v.w) : "l"(p));
    return v;
}
__device__ __forceinline__ uint2 ldg64(const void* p) {
    uint2 v;
    asm volatile("ld.global.nc.v2.u32 {%0,%1}, [%2];\n" : "=r"(v.x), "=r"(v.y) : "l"(p));
    return v;
}
__device__ __forceinline__ uint32_t ldg16(const void* p) {
    uint32_t v;
    asm volatile("ld.global.nc.u16 %0, [%1];\n" : "=r"(v) : "l"(p));
    return v;
}
__device__ __forceinline__ void stg128(void* p, uint32_t a, uint32_t b, uint32_t c, uint32_t d) {
    asm volatile("st.global.v4.u32 [%0], {%1,%2,%3,%4};\n" ::"l"(p), "r"(a), "r"(b), "r"(c), "r"(d) : "memory");
}
__device__ __forceinline__ void stg64(void* p, uint32_t a, uint32_t b) { asm volatile("st.global.v2.u32 [%0], {%1,%2};\n" ::"l"(p), "r"(a), "r"(b) : "memory"); }
__device__ __forceinline__ void stg32(void* p, uint32_t a) { asm volatile("st.global.u32 [%0], %1;\n" ::"l"(p), "r"(a) : "memory"); }
__device__ __forceinline__ bool all_nz(const uint4& v) { return v.x && v.y && v.z && v.w; }
#define SPIN_LIMIT (1 << 21)
#define TRAP() __trap()
__device__ __forceinline__ void hint_arrive(unsigned* g_hint, int idx, int sub) {
    asm volatile("red.relaxed.gpu.global.add.u32 [%0], 1;\n" ::"l"(&g_hint[sub * 32 + idx]) : "memory");
}
__device__ __forceinline__ void hint_wait(const unsigned* g_hint, int idx, unsigned target) {
    unsigned l;
    asm volatile("mov.u32 %0, %%laneid;" : "=r"(l));
    const unsigned* c = &g_hint[(l & 7) * 32 + idx];
    int it = 0;
    while (__any_sync(0xffffffffu, (int)(ld_poll32(c) - target) < 0)) { if (++it > SPIN_LIMIT) TRAP(); }
}
__device__ __forceinline__ void mbar_init(uint32_t bar, uint32_t cnt) { asm volatile("mbarrier.init.shared::cta.b64 [%0], %1;\n" ::"r"(bar), "r"(cnt) : "memory"); }
__device__ __forceinline__ void mbar_expect(uint32_t bar, uint32_t bytes) {
    asm volatile("mbarrier.arrive.expect_tx.shared::cta.b64 _, [%0], %1;\n" ::"r"(bar), "r"(bytes) : "memory");
}
__device__ __forceinline__ void mbar_arrive(uint32_t bar) { asm volatile("mbarrier.arrive.shared::cta.b64 _, [%0];\n" ::"r"(bar) : "memory"); }
__device__ __forceinline__ void mbar_wait_cluster(uint32_t bar) {
    asm volatile(
        "{\n.reg .pred p;\n"
        "W_%=:\n"
        "mbarrier.try_wait.parity.acquire.cluster.shared::cta.b64 p, [%0], 0;\n"
        "@!p bra W_%=;\n}\n" ::"r"(bar) : "memory");
}
__device__ __forceinline__ void mbar_wait(uint32_t bar) {
    asm volatile(
        "{\n.reg .pred p;\n"
        "W_%=:\n"
        "mbarrier.try_wait.parity.shared::cta.b64 p, [%0], 0;\n"
        "@!p bra W_%=;\n}\n" ::"r"(bar) : "memory");
}
__device__ __forceinline__ void mbar_wait_parity(uint32_t bar, uint32_t par) {
    asm volatile(
        "{\n.reg .pred p;\n"
        "W_%=:\n"
        "mbarrier.try_wait.parity.shared::cta.b64 p, [%0], %1;\n"
        "@!p bra W_%=;\n}\n" ::"r"(bar), "r"(par) : "memory");
}
__device__ __forceinline__ bool mbar_test(uint32_t bar) {
    uint32_t r;
    asm volatile("{\n.reg .pred p;\nmbarrier.test_wait.parity.shared::cta.b64 p, [%1], 0;\nselp.u32 %0, 1, 0, p;\n}\n" : "=r"(r) : "r"(bar) : "memory");
    return __any_sync(0xffffffffu, r);
}
__device__ __forceinline__ void bulk_g2s(uint32_t dst, const void* src, uint32_t bytes, uint32_t bar) {
    asm volatile("cp.async.bulk.shared::cluster.global.mbarrier::complete_tx::bytes [%0], [%1], %2, [%3];\n" ::"r"(dst), "l"(src), "r"(bytes), "r"(bar) : "memory");
}
__device__ __forceinline__ void bulk_s2g(void* dst, uint32_t src, uint32_t bytes) {
    asm volatile("cp.async.bulk.global.shared::cta.bulk_group [%0], [%1], %2;\ncp.async.bulk.commit_group;\n" ::"l"(dst), "r"(src), "r"(bytes) : "memory");
}
__device__ __forceinline__ void tma_2d(uint32_t dst, const CUtensorMap* tm, int c0, int c1, uint32_t bar) {
    asm volatile("cp.async.bulk.tensor.2d.shared::cluster.global.mbarrier::complete_tx::bytes [%0], [%1, {%3, %4}], [%2];\n"
                 ::"r"(dst), "l"(tm), "r"(bar), "r"(c0), "r"(c1) : "memory");
}
__device__ __forceinline__ void tma_3d(uint32_t dst, const CUtensorMap* tm, int c0, int c1, int c2, uint32_t bar) {
    asm volatile("cp.async.bulk.tensor.3d.shared::cluster.global.mbarrier::complete_tx::bytes [%0], [%1, {%3, %4, %5}], [%2];\n"
                 ::"r"(dst), "l"(tm), "r"(bar), "r"(c0), "r"(c1), "r"(c2) : "memory");
}
__device__ __forceinline__ void tma_3d_mc(uint32_t dst, const CUtensorMap* tm, int c0, int c1, int c2, uint32_t bar) {
    asm volatile("cp.async.bulk.tensor.3d.shared::cluster.global.mbarrier::complete_tx::bytes.multicast::cluster [%0], [%1, {%3, %4, %5}], [%2], %6;\n"
                 ::"r"(dst), "l"(tm), "r"(bar), "r"(c0), "r"(c1), "r"(c2), "h"((unsigned short)3) : "memory");
}
__device__ __forceinline__ void tma_st_3d(const CUtensorMap* tm, uint32_t src, int c0, int c1, int c2) {
    asm volatile("cp.async.bulk.tensor.3d.global.shared::cta.bulk_group [%0, {%2, %3, %4}], [%1];\ncp.async.bulk.commit_group;\n"
                 ::"l"(tm), "r"(src), "r"(c0), "r"(c1), "r"(c2) : "memory");
}
__device__ __forceinline__ void l2_prefetch(const void* src, uint32_t bytes) {
    asm volatile("cp.async.bulk.prefetch.L2.global [%0], %1;\n" ::"l"(src), "r"(bytes) : "memory");
}
__device__ __forceinline__ bool elect_one() {
    uint32_t r;
    asm volatile("{\n.reg .pred p;\nelect.sync _|p, 0xffffffff;\nselp.u32 %0, 1, 0, p;\n}\n" : "=r"(r));
    return r;
}
__device__ __forceinline__ void fence_async() { asm volatile("fence.proxy.async.shared::cta;\n" ::: "memory"); }

__device__ __forceinline__ float2 cmul(float2 a, float2 b) {
    return make_float2(fmaf(a.x, b.x, -a.y * b.y), fmaf(a.x, b.y, a.y * b.x));
}
__device__ __forceinline__ float2 csq(float2 a) {
    float p = a.x * a.y;
    return make_float2(fmaf(a.x, a.x, -a.y * a.y), p + p);
}
__device__ __forceinline__ float2 cexp_e(float lr2, float rh, float rl, float e) {
    float m;
    asm("ex2.approx.ftz.f32 %0, %1;\n" : "=f"(m) : "f"(lr2 * e));
    const float a = rh * e;
    const float r = fmaf(rl, e, a - rintf(a)) * 6.283185307179586f;
    return make_float2(m * __cosf(r), m * __sinf(r));
}
__device__ __forceinline__ float rcp_approx(float x) { float r; asm("rcp.approx.ftz.f32 %0, %1;\n" : "=f"(r) : "f"(x)); return r; }
__device__ __forceinline__ float ex2_approx(float x) { float r; asm("ex2.approx.ftz.f32 %0, %1;\n" : "=f"(r) : "f"(x)); return r; }
__device__ __forceinline__ float sqrt_approx(float x) { float r; asm("sqrt.approx.ftz.f32 %0, %1;\n" : "=f"(r) : "f"(x)); return r; }

__device__ __forceinline__ void wg_fence() { asm volatile("wgmma.fence.sync.aligned;\n" ::: "memory"); }
__device__ __forceinline__ void wg_commit() { asm volatile("wgmma.commit_group.sync.aligned;\n" ::: "memory"); }
__device__ __forceinline__ void wg_wait0() { asm volatile("wgmma.wait_group.sync.aligned 0;\n" ::: "memory"); }
template <int T0, int NT> __device__ __forceinline__ void wg_h(uint32_t (&acc)[32], const uint32_t (&a)[4], uint64_t desc);
template <> __device__ __forceinline__ void wg_h<0, 16>(uint32_t (&acc)[32], const uint32_t (&a)[4], uint64_t desc) {
    asm volatile("wgmma.mma_async.sync.aligned.m64n128k16.f16.f16.f16 {%0,%1,%2,%3,%4,%5,%6,%7,%8,%9,%10,%11,%12,%13,%14,%15,%16,%17,%18,%19,%20,%21,%22,%23,%24,%25,%26,%27,%28,%29,%30,%31}, {%32,%33,%34,%35}, %36, 1, 1, 1, 0;\n"
                 : "+r"(acc[0]), "+r"(acc[1]), "+r"(acc[2]), "+r"(acc[3]), "+r"(acc[4]), "+r"(acc[5]), "+r"(acc[6]), "+r"(acc[7]), "+r"(acc[8]), "+r"(acc[9]), "+r"(acc[10]), "+r"(acc[11]), "+r"(acc[12]), "+r"(acc[13]), "+r"(acc[14]), "+r"(acc[15]), "+r"(acc[16]), "+r"(acc[17]), "+r"(acc[18]), "+r"(acc[19]), "+r"(acc[20]), "+r"(acc[21]), "+r"(acc[22]), "+r"(acc[23]), "+r"(acc[24]), "+r"(acc[25]), "+r"(acc[26]), "+r"(acc[27]), "+r"(acc[28]), "+r"(acc[29]), "+r"(acc[30]), "+r"(acc[31])
                 : "r"(a[0]), "r"(a[1]), "r"(a[2]), "r"(a[3]), "l"(desc));
}
template <> __device__ __forceinline__ void wg_h<4, 4>(uint32_t (&acc)[32], const uint32_t (&a)[4], uint64_t desc) {
    asm volatile("wgmma.mma_async.sync.aligned.m64n32k16.f16.f16.f16 {%0,%1,%2,%3,%4,%5,%6,%7}, {%8,%9,%10,%11}, %12, 1, 1, 1, 0;\n"
                 : "+r"(acc[8]), "+r"(acc[9]), "+r"(acc[10]), "+r"(acc[11]), "+r"(acc[12]), "+r"(acc[13]), "+r"(acc[14]), "+r"(acc[15])
                 : "r"(a[0]), "r"(a[1]), "r"(a[2]), "r"(a[3]), "l"(desc));
}
template <> __device__ __forceinline__ void wg_h<8, 4>(uint32_t (&acc)[32], const uint32_t (&a)[4], uint64_t desc) {
    asm volatile("wgmma.mma_async.sync.aligned.m64n32k16.f16.f16.f16 {%0,%1,%2,%3,%4,%5,%6,%7}, {%8,%9,%10,%11}, %12, 1, 1, 1, 0;\n"
                 : "+r"(acc[16]), "+r"(acc[17]), "+r"(acc[18]), "+r"(acc[19]), "+r"(acc[20]), "+r"(acc[21]), "+r"(acc[22]), "+r"(acc[23])
                 : "r"(a[0]), "r"(a[1]), "r"(a[2]), "r"(a[3]), "l"(desc));
}
template <> __device__ __forceinline__ void wg_h<12, 4>(uint32_t (&acc)[32], const uint32_t (&a)[4], uint64_t desc) {
    asm volatile("wgmma.mma_async.sync.aligned.m64n32k16.f16.f16.f16 {%0,%1,%2,%3,%4,%5,%6,%7}, {%8,%9,%10,%11}, %12, 1, 1, 1, 0;\n"
                 : "+r"(acc[24]), "+r"(acc[25]), "+r"(acc[26]), "+r"(acc[27]), "+r"(acc[28]), "+r"(acc[29]), "+r"(acc[30]), "+r"(acc[31])
                 : "r"(a[0]), "r"(a[1]), "r"(a[2]), "r"(a[3]), "l"(desc));
}
template <> __device__ __forceinline__ void wg_h<0, 8>(uint32_t (&acc)[32], const uint32_t (&a)[4], uint64_t desc) {
    asm volatile("wgmma.mma_async.sync.aligned.m64n64k16.f16.f16.f16 {%0,%1,%2,%3,%4,%5,%6,%7,%8,%9,%10,%11,%12,%13,%14,%15}, {%16,%17,%18,%19}, %20, 1, 1, 1, 0;\n"
                 : "+r"(acc[0]), "+r"(acc[1]), "+r"(acc[2]), "+r"(acc[3]), "+r"(acc[4]), "+r"(acc[5]), "+r"(acc[6]), "+r"(acc[7]), "+r"(acc[8]), "+r"(acc[9]), "+r"(acc[10]), "+r"(acc[11]), "+r"(acc[12]), "+r"(acc[13]), "+r"(acc[14]), "+r"(acc[15])
                 : "r"(a[0]), "r"(a[1]), "r"(a[2]), "r"(a[3]), "l"(desc));
}
template <> __device__ __forceinline__ void wg_h<4, 12>(uint32_t (&acc)[32], const uint32_t (&a)[4], uint64_t desc) {
    asm volatile("wgmma.mma_async.sync.aligned.m64n96k16.f16.f16.f16 {%0,%1,%2,%3,%4,%5,%6,%7,%8,%9,%10,%11,%12,%13,%14,%15,%16,%17,%18,%19,%20,%21,%22,%23}, {%24,%25,%26,%27}, %28, 1, 1, 1, 0;\n"
                 : "+r"(acc[8]), "+r"(acc[9]), "+r"(acc[10]), "+r"(acc[11]), "+r"(acc[12]), "+r"(acc[13]), "+r"(acc[14]), "+r"(acc[15]), "+r"(acc[16]), "+r"(acc[17]), "+r"(acc[18]), "+r"(acc[19]), "+r"(acc[20]), "+r"(acc[21]), "+r"(acc[22]), "+r"(acc[23]), "+r"(acc[24]), "+r"(acc[25]), "+r"(acc[26]), "+r"(acc[27]), "+r"(acc[28]), "+r"(acc[29]), "+r"(acc[30]), "+r"(acc[31])
                 : "r"(a[0]), "r"(a[1]), "r"(a[2]), "r"(a[3]), "l"(desc));
}

#define PBYTES 4608
#define HINTW 10
#define WAS 0x0005
#define WA0 (WAS >> 12)
#define WA1 ((WAS >> 8) & 15)
#define WA2 ((WAS >> 4) & 15)
#define WA3 (WAS & 15)
#define WDAT 1
#define PAUSE 2
#define PCNT (32 + ((PAUSE & 1) ? 288 : 0) + ((PAUSE & 6) ? 320 : 64))
#define LNAT 2
#define UW 8
#define FINAT 3
#define UAT 2
#define HK 9
#define TOKEN_OF(g) (16 * ((g) & 1) + ((g) >> 2) + 2 * ((g) & 2))
#define HI2(a, b) (pack_f16_rz(__uint_as_float(a), __uint_as_float(b)) & 0xfff8fff8u)
struct Params {
    const bf16 *x, *lar, *aim, *cre, *cim, *ldt, *dsk;
    Scratch* s;
    const bf16* wr;
    bf16* out;
};

template <int NK>
__device__ __forceinline__ void ln_partial(const uint32_t (&H)[2][NK], const uint32_t (&bw)[NK], uint32_t lp, int warp, int g, int t) {
    float cs[4] = {0.f, 0.f, 0.f, 0.f}, cl[4] = {0.f, 0.f, 0.f, 0.f}, ch[4] = {0.f, 0.f, 0.f, 0.f};
#pragma unroll
    for (int k = 0; k < NK; k += 2) {
        uint32_t a0, a1, a2, a3;
        asm volatile("prmt.b32 %0, %4, %4, %8;\nprmt.b32 %1, %5, %5, %8;\nprmt.b32 %2, %6, %6, %8;\nprmt.b32 %3, %7, %7, %8;\n"
                     : "=r"(a0), "=r"(a1), "=r"(a2), "=r"(a3) : "r"(H[0][k]), "r"(H[1][k]), "r"(H[0][k + 1]), "r"(H[1][k + 1]), "r"(0x3210u + (warp >> 8)));
        mma_bf16(cl, a0, a1, a2, a3, H[0][k], H[0][k + 1]);
        mma_bf16(ch, a0, a1, a2, a3, H[1][k], H[1][k + 1]);
        mma_bf16(cs, a0, a1, a2, a3, bw[k], bw[k + 1]);
    }
    const uint32_t a = lp + (g * 20 + warp) * 4;
    if (t == 0) {
        stsf(a, cs[1]); stsf(a + 8 * 80, cs[3]);
    }
    if (t == (g >> 1)) { stsf(a + 16 * 80, (g & 1) ? cl[1] : cl[0]); stsf(a + 24 * 80, (g & 1) ? ch[3] : ch[2]); }
}
__device__ __forceinline__ float sum18(uint32_t a) {
    const uint4 p = lds128(a), q = lds128(a + 16), r = lds128(a + 32), s = lds128(a + 48);
    const uint2 u = lds64(a + 64);
#define F(x) __uint_as_float(x)
    return (((F(p.x) + F(p.y)) + (F(p.z) + F(p.w))) + ((F(q.x) + F(q.y)) + (F(q.z) + F(q.w)))) +
           (((F(r.x) + F(r.y)) + (F(r.z) + F(r.w))) + ((F(s.x) + F(s.y)) + (F(s.z) + F(s.w))) + (F(u.x) + F(u.y)));
#undef F
}
__device__ __forceinline__ float sum9(uint32_t a) {
    const uint4 p = lds128(a), q = lds128(a + 16);
#define F(x) __uint_as_float(x)
    return (((F(p.x) + F(p.y)) + (F(p.z) + F(p.w))) + ((F(q.x) + F(q.y)) + (F(q.z) + F(q.w)))) + ldsf(a + 32);
#undef F
}
template <int N>
__device__ __forceinline__ void ln_finish(uint32_t lp, int lane, float& mb, float& rc) {
    const float v = N == 9 ? sum9(lp + lane * 80) : sum18(lp + lane * 80);
    const float o = __shfl_xor_sync(0xffffffffu, v, 16);
    const float m0 = v * (1.0f / 576.0f);
    const float mean = fmaf(fmaf(-m0, 576.0f, v), 1.0f / 576.0f, m0);
    const float var = fmaxf(fmaf(-mean, mean, o * (1.0f / 576.0f)), 0.f);
    mb = rbf(mean);
    rc = rcp_approx(rbf(sqrt_approx(rbf(rbf(var) + 1e-5f))));
}
__device__ __forceinline__ uint32_t ln_apply(uint32_t w, const uint2& st) {
    uint32_t r;
    asm("{\n.reg .b16 m, t, h, l;\n.reg .b32 mm, hh, ll, d, e;\nmov.b32 {m, t}, %2;\nmov.b32 {h, l}, %3;\nmov.b32 mm, {m, m};\nmov.b32 hh, {h, h};\nmov.b32 ll, {l, l};\n"
        "sub.rn.bf16x2 d, %1, mm;\nmul.rn.bf16x2 e, d, ll;\nfma.rn.bf16x2 %0, d, hh, e;\n}\n" : "=r"(r) : "r"(w), "r"(st.x), "r"(st.y));
    return r;
}
__device__ __forceinline__ void stat_store(uint32_t a, float mb, float rc, uint32_t extra) {
    const float rh = rbf(rc);
    sts64(a, (__float_as_uint(mb) >> 16) | (extra << 16), pack_bf16(rh, rc - rh));
}

__device__ __forceinline__ void hcmul(uint32_t re, uint32_t im, uint32_t z, uint32_t& ore, uint32_t& oim) {
    asm("{\n.reg .b16 x, y;\n.reg .b32 xx, yy, ny, a, b;\nmov.b32 {x, y}, %4;\nmov.b32 xx, {x, x};\nmov.b32 yy, {y, y};\nneg.f16x2 ny, yy;\n"
        "mul.rn.f16x2 a, %2, xx;\nfma.rn.f16x2 %0, %3, ny, a;\nmul.rn.f16x2 b, %3, xx;\nfma.rn.f16x2 %1, %2, yy, b;\n}\n" : "=&r"(ore), "=r"(oim) : "r"(re), "r"(im), "r"(z));
}
__device__ __forceinline__ void hcmul(uint32_t re, uint32_t im, uint32_t zx, uint32_t zy, uint32_t& ore, uint32_t& oim) {
    asm("{\n.reg .b32 ny, a, b;\nneg.f16x2 ny, %5;\n"
        "mul.rn.f16x2 a, %2, %4;\nfma.rn.f16x2 %0, %3, ny, a;\nmul.rn.f16x2 b, %3, %4;\nfma.rn.f16x2 %1, %2, %5, b;\n}\n" : "=&r"(ore), "=r"(oim) : "r"(re), "r"(im), "r"(zx), "r"(zy));
}

struct KGen {
    uint32_t Af[4][4];
    float2 z1, z8, z64, z128, T[9];
    uint32_t zw;
};
__device__ __forceinline__ void kgen_setup(KGen& k, uint32_t pa, float dt) {
    const float A = rbf(expf(bf_lo(pa)));
    const float lr2 = -(A * dt) * 1.4426950408889634f;
    const float li = bf_hi(pa) * dt;
    const float rh = li * 0.15915494309189535f;
    const float rl = fmaf(li, 6.4206382986e-9f, fmaf(li, 0.15915494309189535f, -rh));
    k.z1 = cexp_e(lr2, rh, rl, 1.0f);
    k.z8 = cexp_e(lr2, rh, rl, 8.0f);
    k.z64 = cexp_e(lr2, rh, rl, 64.0f);
}
__device__ __forceinline__ void kgen_rows(KGen& k, uint32_t tb, int lane) {
    const float2 z8 = k.z8, z64 = k.z64;
    const uint32_t row = tb + lane * TBP;
    k.z128 = csq(z64);
    const float2 z16 = csq(z8), z32 = csq(z16), z48 = cmul(z32, z16), z80 = cmul(z64, z16), z96 = cmul(z64, z32), z112 = cmul(z64, z48);
    uint32_t re[4], im[4], a[4], b[4];
    re[0] = pack_f16(1.0f, z16.x); im[0] = pack_f16(0.0f, z16.y);
    re[1] = pack_f16(z32.x, z48.x); im[1] = pack_f16(z32.y, z48.y);
    re[2] = pack_f16(z64.x, z80.x); im[2] = pack_f16(z64.y, z80.y);
    re[3] = pack_f16(z96.x, z112.x); im[3] = pack_f16(z96.y, z112.y);
    sts128(row, re[0], re[1], re[2], re[3]);
    sts128(row + 32, im[0], im[1], im[2], im[3]);
    const uint32_t zz = pack_f16(z8.x, z8.y);
#pragma unroll
    for (int j = 0; j < 4; j++) hcmul(re[j], im[j], zz, a[j], b[j]);
    sts128(row + 16, a[0], a[1], a[2], a[3]);
    sts128(row + 48, b[0], b[1], b[2], b[3]);
    __syncwarp();
    const int mi = lane >> 3;
    const uint32_t ad = tb + (lane & 7) * TBP + mi * 16;
#pragma unroll
    for (int ks = 0; ks < 4; ks++) ldsm_x4_t(k.Af[ks][0], k.Af[ks][1], k.Af[ks][2], k.Af[ks][3], ad + ks * 8 * TBP);
}
__device__ __forceinline__ void kgen_chain(KGen& k, uint32_t pc, float cs) {
    k.T[0] = make_float2(bf_lo(pc) * cs, -bf_hi(pc) * cs);
    const float2 y1 = make_float2(k.z1.x, -k.z1.y);
#pragma unroll
    for (int c = 1; c < 8; c++) k.T[c] = cmul(k.T[c - 1], y1);
    k.T[8] = cmul(k.T[0], make_float2(k.z8.x, -k.z8.y));
}
__device__ __forceinline__ void kgen_cols(KGen& k, uint32_t tb, int lane) {
    const uint32_t row = tb + lane * TBP;
    const float2 (&T)[9] = k.T;
    const uint32_t zv = pack_f16(k.z128.x, k.z128.y), zo = __shfl_xor_sync(0xffffffffu, zv, 1);
    k.zw = (lane & 1) ? __byte_perm(zo, zv, 0x7632) : __byte_perm(zv, zo, 0x5410);
    const float2 y256 = csq(make_float2(k.z128.x, -k.z128.y)), y512 = csq(y256), y768 = cmul(y512, y256), y1024 = csq(y512);
    const float2 c1032 = cmul(T[8], y1024);
    const uint32_t r04 = pack_f16(T[0].x, T[4].x), i04 = pack_f16(T[0].y, T[4].y), r26 = pack_f16(T[2].x, T[6].x), i26 = pack_f16(T[2].y, T[6].y);
    const uint32_t r48 = pack_f16(T[4].x, T[8].x), i48 = pack_f16(T[4].y, T[8].y);
    __syncwarp();
    sts128(row, r04, pack_f16(T[1].x, T[5].x), r26, pack_f16(T[3].x, T[7].x));
    sts128(row + 16, i04, pack_f16(T[1].y, T[5].y), i26, pack_f16(T[3].y, T[7].y));
    uint32_t a[4], b[4];
    {
        const uint32_t zz = pack_f16(y256.x, y256.y);
        hcmul(r04, i04, zz, a[0], b[0]);
        hcmul(r26, i26, zz, a[2], b[2]);
        hcmul(r48, i48, zz, a[3], b[3]);
    }
    sts128(row + 32, a[0], a[0], a[2], a[3]);
    sts128(row + 48, b[0], b[0], b[2], b[3]);
    {
        hcmul(r48, i48, pack_f16(y512.x, y512.y), a[0], b[0]);
        hcmul(r48, i48, pack_f16(y768.x, y768.y), a[1], b[1]);
        const uint32_t zz = pack_f16(c1032.x, c1032.y);
        hcmul(pack_f16(1.0f, y256.x), pack_f16(0.0f, y256.y), zz, a[2], b[2]);
        hcmul(pack_f16(y512.x, y768.x), pack_f16(y512.y, y768.y), zz, a[3], b[3]);
    }
    sts128(row + 64, a[0], a[1], a[2], a[3]);
    sts128(row + 80, b[0], b[1], b[2], b[3]);
}
__device__ __forceinline__ void kgen_mma(const KGen& k, uint32_t tb, int lane) {
    const int t = lane & 3;
    const uint32_t zw = k.zw;
    uint32_t zx[4], zy[4];
#pragma unroll
    for (int ks = 0; ks < 4; ks++) { zx[ks] = __shfl_sync(0xffffffffu, zw, 8 * ks + 2 * t); zy[ks] = __shfl_sync(0xffffffffu, zw, 8 * ks + 2 * t + 1); }
    __syncwarp();
    float acc[2][3][4];
#pragma unroll
    for (int i = 0; i < 6; i++)
#pragma unroll
        for (int j = 0; j < 4; j++) acc[i / 3][i % 3][j] = 0.f;
    {
        const int mi = lane >> 3;
        const uint32_t bd = tb + ((lane & 7) + 8 * (mi >> 1)) * TBP + (mi & 1) * 16;
#pragma unroll
        for (int kp = 0; kp < 2; kp++) {
            uint32_t b[3][4];
#pragma unroll
            for (int j = 0; j < 3; j++) ldsm_x4_t(b[j][0], b[j][1], b[j][2], b[j][3], bd + kp * 16 * TBP + j * 32);
#pragma unroll
            for (int h = 0; h < 2; h++) {
                const int ks = 2 * kp + h;
                uint32_t d[4];
                hcmul(k.Af[ks][0], k.Af[ks][2], zx[ks], zy[ks], d[0], d[2]);
                hcmul(k.Af[ks][1], k.Af[ks][3], zx[ks], zy[ks], d[1], d[3]);
#pragma unroll
                for (int j = 0; j < 3; j++) {
                    mma_f16(acc[0][j], k.Af[ks][0], k.Af[ks][1], k.Af[ks][2], k.Af[ks][3], b[j][2 * h], b[j][2 * h + 1]);
                    mma_f16(acc[1][j], d[0], d[1], d[2], d[3], b[j][2 * h], b[j][2 * h + 1]);
                }
            }
        }
    }
    __syncwarp();
#pragma unroll
    for (int h = 0; h < 2; h++) {
        sts64(tb + h * 256 + lane * 8, pack_f16(acc[h][0][0], acc[h][0][1]), pack_f16(acc[h][0][2], acc[h][0][3]));
        sts64(tb + 512 + h * 256 + lane * 8, pack_f16(acc[h][1][0], acc[h][1][1]), pack_f16(acc[h][1][2], acc[h][1][3]));
        sts32(tb + 1024 + h * 256 + lane * 4, pack_f16(acc[h][2][0], t < 2 ? acc[h][2][1] : acc[h][2][2]));
        sts32(tb + 1152 + h * 256 + lane * 4, pack_f16(t < 2 ? acc[h][2][2] : acc[h][2][1], acc[h][2][3]));
    }
}
__device__ __forceinline__ uint32_t table_buf(uint32_t sb, int warp) { return sb + SM_TB + warp * TBW; }

__device__ __forceinline__ void kgen_combine(uint32_t sb, int warp, int lane, uint32_t kw, uint32_t ao) {
    const int wq = warp & 3;
    const uint32_t a = table_buf(sb, warp & ~3) + wq * 256 + lane * 8, c = table_buf(sb, warp & ~3) + 1024 + wq * 128 + lane * 4;
    const int t = lane & 3;
    const uint32_t o0 = (t < 2 ? KW_T2 + KW_KH + 16 + t * 256 - (wq & 1) * KW_KH : KW_T3 + 16 - 1024 + t * 512 + (wq & 1) * 256) + (lane >> 2) * 16;
    const uint4 o = make_uint4(o0 + t * 36, o0 + (t ^ 1) * 36, o0 + (t ^ 2) * 36, o0 + (t ^ 3) * 36);
    const uint2 u = lds64(a), v = lds64(a + TBW), w = lds64(a + 2 * TBW), x = lds64(a + 3 * TBW);
    const uint32_t kt = hadd2(hadd2(lds32(c), lds32(c + TBW)), hadd2(lds32(c + 2 * TBW), lds32(c + 3 * TBW)));
    const uint32_t k23 = hadd2(hadd2(u.y, v.y), hadd2(w.y, x.y));
    sts64(kw + wq * 64 + ao, hadd2(hadd2(u.x, v.x), hadd2(w.x, x.x)), k23);
    const uint32_t d = kw + (wq >> 1) * 128;
    const uint32_t kh = hmul2(kt, 0x38003800u);
    sts32(d + o.x, kh); sts32(d + o.y, kh); sts32(d + o.z, kh); sts32(d + o.w, kh);
    if (wq == 3) {
        if (lane == 31) { sts32(kw + 264, k23 >> 16); sts32(kw + 288 + 264, k23 >> 16); sts32(kw + 576 + 264, k23 >> 16); }
        if (lane == 29) { sts32(kw + 864 + 280, kt >> 16); sts32(kw + 280, kt & 0xffff0000u); }
    }
}

__device__ __forceinline__ int c_exponent(const uint2& r, const uint2& i) {
    uint32_t mx = __vmaxu2(__vmaxu2(r.x & 0x7fff7fffu, r.y & 0x7fff7fffu), __vmaxu2(i.x & 0x7fff7fffu, i.y & 0x7fff7fffu));
    mx = __reduce_max_sync(0xffffffffu, max(mx & 0xffffu, mx >> 16));
    return min(max((int)(mx >> 7), 4), 240);
}

__device__ __forceinline__ int warp_v() { int l; asm volatile("mov.u32 %0, %%tid.x;" : "=r"(l)); return __shfl_sync(0xffffffffu, l >> 5, 0); }
__device__ __forceinline__ int lane_v() { int l; asm volatile("mov.u32 %0, %%laneid;" : "=r"(l)); return l; }
__device__ __forceinline__ uint32_t prmt(uint32_t a, uint32_t b, uint32_t s) { uint32_t d; asm("prmt.b32 %0, %1, %2, %3;\n" : "=r"(d) : "r"(a), "r"(b), "r"(s)); return d; }
__device__ __forceinline__ uint32_t prmt_v(uint32_t a, uint32_t b, uint32_t s) { uint32_t d; asm volatile("prmt.b32 %0, %1, %2, %3;\n" : "=r"(d) : "r"(a), "r"(b), "r"(s)); return d; }
__device__ __forceinline__ void mmah16(uint32_t& d0, uint32_t& d1, uint32_t a0, uint32_t a1, uint32_t a2, uint32_t a3, uint32_t b0, uint32_t b1, uint32_t c0, uint32_t c1) {
    asm volatile("mma.sync.aligned.m16n8k16.row.col.f16.f16.f16.f16 {%0,%1}, {%2,%3,%4,%5}, {%6,%7}, {%8,%9};\n"
                 : "=r"(d0), "=r"(d1) : "r"(a0), "r"(a1), "r"(a2), "r"(a3), "r"(b0), "r"(b1), "r"(c0), "r"(c1));
}
__device__ __forceinline__ void mmah8(uint32_t& d0, uint32_t& d1, uint32_t a0, uint32_t a1, uint32_t b0, uint32_t c0, uint32_t c1) {
    asm volatile("mma.sync.aligned.m16n8k8.row.col.f16.f16.f16.f16 {%0,%1}, {%2,%3}, {%4}, {%5,%6};\n"
                 : "=r"(d0), "=r"(d1) : "r"(a0), "r"(a1), "r"(b0), "r"(c0), "r"(c1));
}
template <int A = 8, int B = 32>
__device__ __forceinline__ void conv_rename(uint32_t (&acc)[32]) {
#pragma unroll
    for (int i = A; i < B; i++) { uint32_t v; asm volatile("mov.b32 %0, %1;\n" : "=r"(v) : "r"(acc[i])); acc[i] = v; }
}
__host__ __device__ constexpr uint32_t band_bits(int hw, int sh) {
    uint32_t c = 0;
    for (int s = 0; s <= 10; s++)
        for (int e = 0; e < 2; e++) {
            const int v = s - 3 + sh - 4 * e;
            if (v <= hw && v >= -hw) c |= 1u << (14 + 16 * e - s);
        }
    return c;
}
template <int HW, int SH, int J> __device__ __forceinline__ uint32_t band(uint32_t p2) {
    uint32_t d;
    asm volatile("{\n.reg .b32 t;\nmul.lo.u32 t, %1, %2;\nand.b32 %0, t, 0x40004000;\n}\n" : "=r"(d) : "r"(p2), "n"(band_bits(HW, SH) | J));
    return d;
}
template <int H0, int SH> __device__ __forceinline__ void band_pair(uint4& l, uint4& u, uint32_t p2) {
    l = make_uint4(band<H0, 8, 1>(p2), band<H0 - 1, SH + 8, 2>(p2), band<H0, 0, 1>(p2), band<H0 - 1, SH, 1>(p2));
    u = make_uint4(band<H0, 0, 2>(p2), band<H0 - 1, SH, 2>(p2), band<H0, -8, 1>(p2), band<H0 - 1, SH - 8, 1>(p2));
}
__device__ __forceinline__ void run_sums(uint32_t (&G)[3][2], const uint32_t (&c)[5], const uint4& l, const uint4& u) {
    mmah8(G[0][0], G[0][1], l.x, l.y, c[0], 0u, 0u);
    mmah8(G[1][0], G[1][1], u.z, u.w, c[3], 0u, 0u);
    mmah8(G[2][0], G[2][1], l.x, l.y, c[2], 0u, 0u);
    mmah16(G[0][0], G[0][1], u.x, u.y, u.z, u.w, c[1], c[2], G[0][0], G[0][1]);
    mmah16(G[1][0], G[1][1], l.x, l.y, l.z, l.w, c[1], c[2], G[1][0], G[1][1]);
    mmah16(G[2][0], G[2][1], u.x, u.y, u.z, u.w, c[3], c[4], G[2][0], G[2][1]);
}
__device__ __forceinline__ float h_lo(uint32_t w) { return __half2float(__ushort_as_half((unsigned short)(w & 0xffffu))); }
__device__ __forceinline__ float h_hi(uint32_t w) { return __half2float(__ushort_as_half((unsigned short)(w >> 16))); }
__device__ __forceinline__ uint64_t smem_desc(uint32_t sb, uint32_t o16, uint32_t lbo) {
    uint64_t d;
    asm("mov.b64 %0, {%1, %2};" : "=l"(d) : "r"(((sb & 0x3FFFF) >> 4) + o16 + (lbo << 12)), "r"(8));
    return d;
}
template <int I> struct IC { static constexpr int value = I; };

struct Conv {
    uint32_t u[3][5];
    uint32_t q2[3][2][4];
    uint32_t q3[2][4];
    uint32_t r[18];
};
struct ConvPre {
    uint32_t a[5], b[5];
    uint32_t t[4];
};
__device__ __forceinline__ void conv_pre(ConvPre& e, uint32_t ka, uint32_t ks, uint32_t sel) {
    const uint4 r = lds128(ka + 256), s = lds128(ka + 272);
    ldsm_x4(e.t[0], e.t[1], e.t[2], e.t[3], ks);
    const uint32_t sw = sel ^ 0x4444u;
    e.a[0] = prmt(r.y, r.z, sel); e.a[1] = prmt(r.w, r.z, sw); e.a[2] = prmt(r.x, r.y, sel); e.a[3] = prmt(r.z, r.y, sw); e.a[4] = prmt(r.z, r.w, sel);
    e.b[0] = prmt(s.y, s.z, sel); e.b[1] = prmt(s.w, s.z, sw); e.b[2] = prmt(s.x, s.y, sel); e.b[3] = prmt(s.z, s.y, sw); e.b[4] = prmt(s.z, s.w, sel);
}
__device__ __forceinline__ void conv_sums(Conv& c, uint32_t (&acc)[32], const ConvPre& e, uint32_t a0, uint32_t a1, const uint4 (&bd)[4], uint32_t ka, uint32_t sel, int wq, uint32_t zr) {
    {
        uint32_t x;
        ldsm_x4(c.u[0][1], c.u[0][2], c.u[0][3], c.u[0][4], a1);
        ldsm_x4(c.u[0][0], c.u[1][0], c.u[2][0], x, a0);
#pragma unroll
        for (int q = 1; q < 3; q++) ldsm_x4(c.u[q][1], c.u[q][2], c.u[q][3], c.u[q][4], a1 + q * 512);
    }
#pragma unroll
    for (int i = 0; i < 32; i++) acc[i] = 0u;
    uint32_t G[3][2];
#pragma unroll
    for (int q = 0; q < 3; q++) {
        mmah8(acc[8 * q + 8], acc[8 * q + 9], e.a[4], 0u, c.u[q][2], acc[8 * q + 8], acc[8 * q + 9]);
        mmah16(acc[8 * q + 8], acc[8 * q + 9], e.a[0], e.a[1], e.a[2], e.a[3], c.u[q][3], c.u[q][4], acc[8 * q + 8], acc[8 * q + 9]);
        if (q < 2) {
            mmah8(acc[8 * q + 16], acc[8 * q + 17], e.b[4], 0u, c.u[q][2], 0u, 0u);
            mmah16(acc[8 * q + 16], acc[8 * q + 17], e.b[0], e.b[1], e.b[2], e.b[3], c.u[q][3], c.u[q][4], acc[8 * q + 16], acc[8 * q + 17]);
            run_sums(G, c.u[q], bd[2], bd[3]);
            c.q3[q][0] = prmt(G[1][1], G[0][0], 0x7632u); c.q3[q][1] = prmt(G[2][1], G[1][0], 0x7632u);
            c.q3[q][2] = prmt(G[1][1], G[0][0], 0x5410u); c.q3[q][3] = prmt(G[2][1], G[1][0], 0x5410u);
        }
    }
    {
        const uint32_t a = (ka + wq * 64) ^ (((acc[8] | acc[16] | acc[24]) | (c.q3[0][0] | c.q3[0][1]) | (c.q3[1][0] | c.q3[1][1])) & zr);
#pragma unroll
        for (int i = 0; i < 4; i++) { const uint4 v = lds128(a + i * 16); c.r[4 * i] = v.x; c.r[4 * i + 1] = v.y; c.r[4 * i + 2] = v.z; c.r[4 * i + 3] = v.w; }
        const uint2 v = lds64(a + 64);
        c.r[16] = v.x; c.r[17] = v.y;
    }
#pragma unroll
    for (int q = 0; q < 3; q++) {
        run_sums(G, c.u[q], bd[0], bd[1]);
#pragma unroll
        for (int h = 0; h < 2; h++) {
            const uint32_t s = h ? 0x7632u : 0x5410u;
            c.q2[q][h][0] = prmt(G[0][1], G[0][0], s); c.q2[q][h][1] = prmt(G[1][1], G[1][0], s);
            c.q2[q][h][2] = prmt(G[1][0], G[1][1], s ^ 0x4444u); c.q2[q][h][3] = prmt(G[2][1], G[2][0], s);
            if (q < 2) mmah16(acc[8 * q + 16], acc[8 * q + 17], c.q2[q][h][0], c.q2[q][h][1], c.q2[q][h][2], c.q2[q][h][3], e.t[2 * h], e.t[2 * h + 1], acc[8 * q + 16], acc[8 * q + 17]);
        }
    }
    if (sel == 0u) {
#pragma unroll
        for (int i = 0; i < 6; i++) sts128(ka + i * 16, c.q2[i >> 1][i & 1][0], c.q2[i >> 1][i & 1][1], c.q2[i >> 1][i & 1][2], c.q2[i >> 1][i & 1][3]);
#pragma unroll
        for (int i = 0; i < 2; i++) sts128(ka + i * 16, c.q3[i][0], c.q3[i][1], c.q3[i][2], c.q3[i][3]);
#pragma unroll
        for (int i = 1; i < 4; i++) sts64(ka + i * 16, acc[8 * i], acc[8 * i + 1]);
    }
    conv_rename(acc);
}
#define SPACE 120
#define SPN 3
#define GATE 2
#define HAND 2
#define GA 6
#define GB 4
template <int TA, int TB, int IA, class FG>
__device__ __forceinline__ void conv_tail(uint32_t (&acc)[32], const uint32_t (&a)[8][4], uint32_t sb, unsigned char* gy0, int warp, size_t ycopy, FG fg) {
    const int wg = warp >> 2, wq = warp & 3, ord = TA == 0 && TB == 16 ? 3 - wg : 4;
    const uint32_t ub = sb + SM_U + wg * USLOT_B + UPAD * 16, turn = sb + SM_MISC + 376 + ord * 8, sfs = sb + SM_MISC + 256 + wg * 8;
    const uint32_t du = wg * (USLOT_B / 16) + (SM_U / 16 + UPAD + TA * 8);
    uint32_t ud[8], fs;
    auto skip = [&]() {
        const int lane = lane_v();
        const uint32_t ua = ub + ((lane >> 3) & 1) * ULO_B + (8 * wq + (lane & 7)) * 16 + (lane >> 4) * 512;
        if (IA == 0) ldsm_x4_t(ud[0], ud[1], ud[2], ud[3], ua);
        if (TB == 16) ldsm_x4_t(ud[4], ud[5], ud[6], ud[7], ua + 1024);
        const uint2 fd = lds64(sfs);
        fs = fd.x;
        const float dsk = __uint_as_float(fd.y);
#pragma unroll
        for (int i = 2 * IA; i < TB / 2; i++) ud[i] = pack_bf16(h_lo(ud[i]) * dsk, h_hi(ud[i]) * dsk);
    };
    conv_rename<2 * TA, 2 * TB>(acc);
    if (__builtin_expect(ord != 0, 0)) {
        skip();
        mbar_wait(turn);
    }
    if (TA == 0 && TB == 16) asm volatile("{\n.reg .pred p;\nelect.sync _|p, 0xffffffff;\n@p mbarrier.arrive.shared::cta.b64 _, [%0];\n}\n" ::"r"(turn + 40) : "memory");
    fg(IC<8>());
    wg_fence();
#pragma unroll
    for (int m = 7; m >= 0; m--) {
        wg_h<TA, TB - TA>(acc, a[m], smem_desc(sb, du - m, ULO_B));
        if (m == GA || m == GB || m == HAND) wg_commit();
        if (m == GB) asm volatile("wgmma.wait_group.sync.aligned 1;\n" ::: "memory");
    }
    wg_commit();
    if (TA == 0 && TB == 16) {
        asm volatile("wgmma.wait_group.sync.aligned 1;\n" ::: "memory");
        asm volatile("{\n.reg .pred p;\nelect.sync _|p, 0xffffffff;\n@p mbarrier.arrive.shared::cta.b64 _, [%0];\n}\n" ::"r"(turn + 8) : "memory");
    }
    __syncwarp();
    fg(IC<3>());
    if (!ord) skip();
    fg(IC<4>());
    const int lane = lane_v();
    const uint32_t lp = sb + SM_PL + (ord >= 3 ? ord - 3 : ord) * PL_B + lane * 8;
    unsigned char* gy = gy0 + ((4 * wq + (lane & 3)) * DM + (TA == 0 && TB == 16 ? 4 * blockIdx.x + wg : 512 + (blockIdx.x >> 1))) * 64 + (lane >> 2) * 8;
    const uint32_t st = lp + (wq * 12 - ((wq * (wq - 1)) >> 1)) * 256;
    uint32_t ld[3];
#pragma unroll
    for (int s = 1; s < 4; s++) {
        const int w = (wq - s) & 3;
        ld[s - 1] = lp + (w * 12 - ((w * (w - 1)) >> 1) + s - 1 - (wq < s ? 3 : 0)) * 256;
    }
    if (ord >= 3) bar_sync(9 + ord, 256);
    wg_wait0();
    fg(IC<6>());
#pragma unroll
    for (int j = TA; j < TB; j++)
        if ((j & 3) && j + 3 >= 4 * IA && (j + 3 < TB || j + wq < TB)) sts64(st + (j - 1 - (j >> 2)) * 256, acc[2 * j], acc[2 * j + 1]);
    bar_sync(1 + wg, 128);
    fg(IC<7>());
    uint2 v[4][3];
#pragma unroll
    for (int i = IA; i < TB / 4; i++)
#pragma unroll
        for (int s = 0; s < 3; s++) {
            if (i == 0) { v[i][s] = make_uint2(0u, 0u); if (wq > s) v[i][s] = lds64(ld[s]); }
            else v[i][s] = lds64(ld[s] + i * 768);
        }
    fg(IC<5>());
#pragma unroll
    for (int i = IA; i < TB / 4; i++) {
        const uint32_t x0 = hadd2(v[i][0].x, acc[8 * i]), x1 = hadd2(v[i][1].x, v[i][2].x), y0 = hadd2(v[i][0].y, acc[8 * i + 1]), y1 = hadd2(v[i][1].y, v[i][2].y);
        const uint32_t x = hadd2(x0, x1), y = hadd2(y0, y1);
        const uint32_t lo = pack_bf16(h_lo(x), h_hi(x)), hi = pack_bf16(h_lo(y), h_hi(y));
        const uint32_t o0 = max(hfma2_bf(lo, fs, ud[2 * i]), 1u), o1 = hfma2_bf(hi, fs, ud[2 * i + 1]);
        stg64(gy + i * 16 * DM * 64, o0, o1);
        if (SPACE && TA == 0 && TB == 16 && i < 3 && ord < SPN) { const unsigned c0 = clock(); while (clock() - c0 < SPACE) {} }
    }
    if (TA == 0 && TB == 16 && ord < 2) bar_arrive(12 + ord, 256);
}
template <int M0, int M1>
__device__ __forceinline__ void conv_frags(uint32_t (&a)[8][4], const uint32_t (&r)[18], uint32_t sel, uint32_t dep, int warp) {
    const uint32_t s = prmt_v(sel, dep, 0x3210u + (warp >> 8)), sw = s ^ 0x4444u;
#pragma unroll
    for (int m = M0; m < M1; m++) {
        a[m][0] = prmt_v(r[2 * m + 1], r[2 * m + 2], s); a[m][1] = prmt_v(r[2 * m + 2], r[2 * m + 3], s);
        a[m][2] = prmt_v(r[2 * m + 1], r[2 * m], sw); a[m][3] = prmt_v(r[2 * m + 2], r[2 * m + 1], sw);
    }
}
template <class FG>
__device__ __forceinline__ void conv_main(const Conv& c, uint32_t (&acc)[32], uint32_t sb, uint32_t sel, unsigned char* gy, int warp, size_t ycopy, FG fg) {
    const uint32_t kw = (warp >> 2) * (KW_B / 16) + SM_KW / 16;
    const uint64_t d2 = smem_desc(sb, kw + KW_T2 / 16, KW_KH), d2b = smem_desc(sb, kw + KW_T2 / 16 + 1, KW_KH), d3 = smem_desc(sb, kw + KW_T3 / 16, 16), d3b = smem_desc(sb, kw + KW_T3 / 16 + 32, 16);
    uint32_t a[8][4];
    {
        const int ord = warp < 16 ? 3 - (warp >> 2) : 4;
        if (__builtin_expect(ord >= GATE, 0)) {
            fg(IC<1>());
            mbar_wait(sb + SM_MISC + 376 + 40 + (ord - GATE) * 8);
        }
    }
    wg_fence();
    wg_h<12, 4>(acc, c.q3[0], d3b); wg_h<8, 4>(acc, c.q3[0], d3); wg_h<4, 4>(acc, c.q2[0][0], d2b);
    wg_h<12, 4>(acc, c.q3[1], d3); wg_h<8, 4>(acc, c.q2[1][0], d2b);
    wg_h<12, 4>(acc, c.q2[2][0], d2b); wg_h<4, 4>(acc, c.q2[0][1], d2); wg_h<8, 4>(acc, c.q2[1][1], d2);
    wg_h<12, 4>(acc, c.q2[2][1], d2);
    wg_commit(); __syncwarp();
    fg(IC<0>());
    wg_wait0();
    conv_frags<0, 8>(a, c.r, sel, acc[16], warp);
    fg(IC<2>());
    if (warp >= 16) {
        if (blockIdx.x & 1) conv_tail<4, 16, 2>(acc, a, sb, gy, warp, ycopy, fg);
        else conv_tail<0, 8, 0>(acc, a, sb, gy, warp, ycopy, fg);
    } else {
        conv_tail<0, 16, 0>(acc, a, sb, gy, warp, ycopy, fg);
    }
}
#define CONV_LT6 const int dd = (lane >> 3) + (lane & 4) - (lane & 3); \
        const uint4 lt6 = make_uint4(prmt_v((dd & 3) * 288, 0u, idn), prmt_v(0x3254u + (dd >> 2) * 0x2222u, 0u, idn), \
            prmt_v(UPAD * 16 + (lane & 7) * 16 + ULO_B - 32 + (lane >> 3) * 512, 0u, idn), prmt_v(UPAD * 16 + (lane & 7) * 16 + ((lane >> 3) & 1) * ULO_B - 16 + (lane & 16), 0u, idn));
#define CONV_PRE \
        CONV_LT6 \
        const uint32_t ka = kw + lt6.x, sel = lt6.y, ks = kw + lt7.x; \
        const uint32_t ca0 = sb + SM_U + wg * USLOT_B + (warp & 3) * 128 + lt6.z, ca1 = sb + SM_U + wg * USLOT_B + (warp & 3) * 128 + lt6.w; \
        uint4 bd[4]; \
        band_pair<2, 4>(bd[0], bd[1], lt7.w); band_pair<4, 0>(bd[2], bd[3], lt7.w);
#define CONV_PRE2 ConvPre ce_; conv_pre(ce_, ka, ks, sel);
#define CONV_BODY \
        Conv c; \
        uint32_t acc[32]; \
        conv_sums(c, acc, ce_, ca0, ca1, bd, ka, sel, warp & 3, warp >> 8);
#define WS 0__1_2_3_46_57___a_b______ce_d_
#define WS_STR2(x) #x
#define WS_STR(x) WS_STR2(x)
__device__ constexpr char wunit(int pt, int k) {
    constexpr char t[] = WS_STR(WS);
    int i = 0;
    for (; pt > 0 && t[i]; i++) pt -= t[i] == '_';
    for (; k > 0 && t[i] && t[i] != '_'; i++) k--;
    return t[i] == '_' ? 0 : t[i];
}
__device__ constexpr bool wsched_ok() {
    int seen = 0;
    for (int p = 0; p < 21; p++)
        for (int k = 0; wunit(p, k); k++) {
            const char c = wunit(p, k);
            const int bit = 1 << (c >= 'a' ? c - 'a' + 8 : c - '0');
            if ((seen & bit) || k >= (p < 16 ? 4 : 2) || (p < 5 && c >= '6' && c <= '7') || (p < 6 && c >= 'c') || (p < 16 && c == 'e')) return false;
            seen |= bit;
        }
    return seen == 0x1fff;
}
static_assert((PAUSE & 2) && GATE <= 2, "resets");
static_assert(wsched_ok(), "weight schedule");
template <int PT, int K>
__device__ __forceinline__ void weight_units(uint32_t sb, const CUtensorMap* tg, const CUtensorMap* tu, const CUtensorMap* td, int w) {
    constexpr char U = wunit(PT, K);
    if constexpr (U != 0) {
        if (w == K && elect_one()) {
            if constexpr (U == 'e') { if (!(blockIdx.x & 1)) tma_2d(sb + SM_WD + 4 * 9216, td, 256, 72 * (blockIdx.x >> 1), sb + SM_MISC + 352); }
            else if constexpr (U >= 'a') tma_2d(sb + SM_WD + (U - 'a') * 9216, td, 320 * (blockIdx.x & 1) + 64 * (U - 'a'), 72 * (blockIdx.x >> 1), sb + SM_MISC + 336);
            else if constexpr (U < '6') tma_2d(sb + SM_WG + (U - '0') * 6912, tg, 72 * (blockIdx.x >> 1), 288 * (blockIdx.x & 1) + (U - '0') * 48, sb + SM_MISC + 328);
            else tma_2d(sb + SM_WU + (U - '6') * 20736, tu, 72 * (blockIdx.x >> 1), 288 * (blockIdx.x & 1) + (U - '6') * 144, sb + SM_MISC + 328);
        }
        weight_units<PT, K + 1>(sb, tg, tu, td, w);
    }
}
#define WPOINT(i, w) do { weight_units<i, 0>(sb, &tm_g, &tm_u, &tm_d, w); } while (0)

__global__ void __launch_bounds__(NTHR, 1) __cluster_dims__(2, 1, 1)
fused_kernel(const Params p, const __grid_constant__ CUtensorMap tm_g, const __grid_constant__ CUtensorMap tm_u, const __grid_constant__ CUtensorMap tm_d, const __grid_constant__ CUtensorMap tm_x,
             const __grid_constant__ CUtensorMap tm_y, const __grid_constant__ CUtensorMap tm_z) {
    extern __shared__ __align__(1024) unsigned char smem[];
    const uint32_t sb = smem_u32(smem);
    const int tid = threadIdx.x, warp = __shfl_sync(0xffffffffu, tid >> 5, 0), lane = tid & 31;
    const int b = blockIdx.x, P = b >> 1, odd = b & 1;
    const int g = lane >> 2, t = lane & 3;
    const int wg = warp >> 2, t128 = tid & 127;
    const uint32_t s_stat = sb + SM_MISC;
    const uint32_t s_key = sb + SM_MISC + 128;
    const uint32_t s_wm = sb + SM_MISC + 256;
    const uint32_t s_k16 = sb + SM_MISC + 192;
    const uint32_t s_fs = sb + SM_MISC + 256;
    const uint32_t s_cnt = sb + SM_MISC + 320;
    const uint32_t bar_w = sb + SM_MISC + 328, bar_d = bar_w + 8, bar_g = bar_w + 16, bar_r = bar_w + 32, bar_h = bar_w + 40, bar_x = bar_w + 48;
    STAMP(0);

    const bool lnw = (unsigned)(warp - 10) < 9u;
    const unsigned pm = tid + (tid < 512 ? 512 * b : 65024 + 128 * P), pq = (pm & ~127u) + 4 * lane;
    uint32_t pl = ldg16(p.lar + pm), ldt = ldg16(p.ldt + (pm >> 7));
    const uint32_t pa2 = ldg16(p.aim + pm), pc = ldg16(p.cre + pm), pi = ldg16(p.cim + pm);
    const uint2 call_re = ldg64(p.cre + pq), call_im = ldg64(p.cim + pq);
    const uint32_t dskl = ldg16(p.dsk + (pm >> 7));
    const uint32_t ep = ld_poll32(p.s->hint + (b & 7) * 32 + 1 + (lane >> 5));
    if ((unsigned)(tid - 320) < 288u) {
        const bf16* xp = p.x + (unsigned)((32 * P + 2 * odd + TOKEN_OF(g)) * DM + ((tid - 320) & ~31) + 8 * t);
        const uint32_t xt = sb + SM_XT + ((tid - 320) & ~31) * 32 + lane * 16;
        asm volatile("cp.async.cg.shared.global [%0], [%1], 16;\ncp.async.cg.shared.global [%0 + 512], [%1 + 9216], 16;\n"
                     "cp.async.cg.shared.global [%0 + 9216], [%1 + 576], 16;\ncp.async.cg.shared.global [%0 + 9728], [%1 + 9792], 16;\n" ::"r"(xt), "l"(xp) : "memory");
    }
    uint32_t* const std_ = p.s->st + ((lane & 12) * 128 + odd * 256 + 4 * P + 2 * (lane & 1) + ((lane >> 1) & 1)) * 2;
    unsigned char* const ud = reinterpret_cast<unsigned char*>(p.s->uT) + (32 * (warp - UW) + 8 * (g >> 1) + (g & 1)) * 4096 + b * 32 + t * 8;
    if (warp == 0) {
        if (lane == 0) {
            mbar_init(bar_x, 1); mbar_init(bar_w, 1); mbar_init(bar_d, 1); mbar_init(bar_d + 16, 1); mbar_init(bar_g, 1); mbar_init(bar_h, 3); mbar_init(bar_r, 1);
            #pragma unroll
            for (int i = 1; i < 9; i++) mbar_init(bar_x + 8 * i, 4);
            asm volatile("fence.mbarrier_init.release.cluster;\n" ::: "memory");
            mbar_expect(bar_x, 16384); mbar_expect(bar_r, 8192);
            mbar_expect(bar_w, 2 * 41472); mbar_expect(bar_d, 36864); mbar_expect(bar_d + 16, 9216); mbar_expect(bar_g, 9 * 512);
        }
        __syncwarp();
        bar_arrive(0, NWRK);
    }
    if (warp == 0 && elect_one()) tma_3d(sb + SM_XC, &tm_x, 8 * P, 0, 8 * odd, bar_x);
    asm volatile("barrier.cluster.arrive.relaxed.aligned;\n" ::: "memory");
    const uint32_t kw = sb + SM_KW + wg * KW_B;
    if (t128 < 2 * UPAD) sts128(sb + SM_U + wg * USLOT_B + (t128 & 1) * ULO_B + (t128 >> 1) * 16, 0u, 0u, 0u, 0u);
    sts128(kw + t128 * 16, 0u, 0u, 0u, 0u);
    if (t128 < KW_B / 16 - 128) sts128(kw + 2048 + t128 * 16, 0u, 0u, 0u, 0u);
    if (tid < 96) {
#pragma unroll
        for (int i = 0; i < 6; i++) sts128(sb + SM_ZERO + i * 1536 + tid * 16, 0u, 0u, 0u, 0u);
    }
    if (warp != 0) bar_sync(0, NWRK);
    STAMP(1);
    if (warp == 19 || warp == UW || warp == UW + 1) {
        if (warp == 19) {
            if (lane < 16) stg64(std_, 0u, 0u);
            if (lane < 9) asm volatile("prefetch.global.L2 [%0];\n" ::"l"(p.wr + lane * 64));
        } else {
#pragma unroll
            for (int k = 0; k < 4; k++) stg64(ud + k * 8192, 0u, 0u);
        }
    }
    uint32_t X[2][8];
    auto partial = [&]() {
        const uint32_t xt = sb + SM_XT + (warp - 10) * 1024 + lane * 16;
        asm volatile("cp.async.wait_all;\n" ::: "memory");
        STAMP(23);
        const uint4 a = lds128(xt), c = lds128(xt + 512), d = lds128(xt + 9216), e = lds128(xt + 9728);
        X[0][0] = a.x; X[0][1] = a.y; X[0][2] = a.z; X[0][3] = a.w; X[0][4] = d.x; X[0][5] = d.y; X[0][6] = d.z; X[0][7] = d.w;
        X[1][0] = c.x; X[1][1] = c.y; X[1][2] = c.z; X[1][3] = c.w; X[1][4] = e.x; X[1][5] = e.y; X[1][6] = e.z; X[1][7] = e.w;
        const uint32_t one[8] = {0x3f803f80u, 0x3f803f80u, 0x3f803f80u, 0x3f803f80u, 0x3f803f80u, 0x3f803f80u, 0x3f803f80u, 0x3f803f80u};
        ln_partial<8>(X, one, sb + SM_LNP, warp - 10, g, t);
        bar_arrive(6, 320);
        if (PAUSE & 1) bar_sync(7, PCNT);
    };
    if (LNAT == 0 && lnw) {
        partial();
        pl = prmt_v(pl, X[0][0], 0x3210u + (warp >> 8)); ldt = prmt_v(ldt, X[0][0], 0x3210u + (warp >> 8));
    }
    auto finish = [&]() {
        bar_sync(6, 320);
        float mb, rc;
        ln_finish<9>(sb + SM_LNP, lane, mb, rc);
        const float rh = rbf(rc);
        const uint32_t s0 = (__float_as_uint(mb) >> 16) | (((ep & 0x7fffu) + 1u) << 16), s1 = pack_bf16(rh, rc - rh);
        if (lane < 16) { stg64(std_, s0, s1); sts64(s_stat + lane * 8, s0, s1); }
        if (lane == 16) sts32(s_cnt + 4, ep);
        bar_arrive(7, PCNT);
        STAMP(28);
    };
    auto upub = [&]() {
        if (!(PAUSE & 6)) bar_sync(7, PCNT);
        const uint32_t utag = ((ep & 3u) + 1u) * 0x10001u;
        uint32_t U[2][4];
#pragma unroll
        for (int hf = 0; hf < 2; hf++) {
            const uint2 st = lds64(s_stat + (g + 8 * hf) * 8);
            const uint4 xv = lds128(sb + SM_XT + (16 + warp - UW) * 1024 + hf * 512 + lane * 16);
            const uint32_t xs[4] = {xv.x, xv.y, xv.z, xv.w};
#pragma unroll
            for (int k = 0; k < 4; k++) {
                const uint32_t u = ln_apply(xs[k], st);
                U[hf][k] = movm((pack_f16_rz(bf_lo(u), __uint_as_float(u)) & 0xfff8fff8u) | utag);
            }
        }
#pragma unroll
        for (int k = 0; k < 4; k++) stg64(ud + k * 8192, U[0][k], U[1][k]);
    };
    if (FINAT == 0 && warp == 19) finish();
    const uint32_t tb = table_buf(sb, warp);
    const float dt = rbf(expf(bf_lo(ldt)));
    KGen kg;
    kgen_setup(kg, pl | (pa2 << 16), dt);
    if (LNAT == 1 && lnw) {
        partial();
        kg.z8.x = __uint_as_float(prmt_v(__float_as_uint(kg.z8.x), X[0][0], 0x3210u + (warp >> 8)));
        kg.z1.x = __uint_as_float(prmt_v(__float_as_uint(kg.z1.x), X[0][0], 0x3210u + (warp >> 8)));
    }
    if (FINAT == 1 && warp == 19) finish();
    if (UAT == 0 && (warp == UW || warp == UW + 1)) upub();
    kgen_rows(kg, tb, lane);
    if (wg == 0) fence_async();
    if (LNAT == 2 && lnw) {
        partial();
        kg.z128.x = __uint_as_float(prmt_v(__float_as_uint(kg.z128.x), X[0][0], 0x3210u + (warp >> 8)));
        kg.z1.x = __uint_as_float(prmt_v(__float_as_uint(kg.z1.x), X[0][0], 0x3210u + (warp >> 8)));
    }
    if (FINAT == 2 && warp == 19) finish();
    if (UAT == 1 && (warp == UW || warp == UW + 1)) upub();
    STAMP(2);
    WPOINT(0, warp - 4);
    const int ce = c_exponent(call_re, call_im);
    if (t128 == 0) sts64(s_fs + wg * 8, (uint32_t)min(max(ce + (int)(__float_as_uint(dt) >> 23) - 116, 0), 254) * 0x800080u, dskl << 16);
    kgen_chain(kg, pc | (pi << 16), __uint_as_float(((uint32_t)(244 - ce) << 23) | (__float_as_uint(dt) & 0x7fffffu)));
    if ((PAUSE & 4) && warp < 10) bar_sync(7, PCNT);
    if (UAT == 4 && (warp == UW || warp == UW + 1)) upub();
    STAMP(3);
    WPOINT(1, warp - 6);
    kgen_cols(kg, tb, lane);
    if (LNAT == 3 && lnw) partial();
    if (FINAT == 3 && warp == 19) finish();
    if ((PAUSE & 2) && warp < 10) bar_sync(7, PCNT);
    if (UAT == 2 && (warp == UW || warp == UW + 1)) upub();
    STAMP(4);
    WPOINT(2, warp - 8);
    const uint4* usrc = wg < 4 ? reinterpret_cast<const uint4*>(p.s->st) + odd * 512 + (lane & 1) * 128 + 16 * (warp & 7) + (lane >> 1)
                               : reinterpret_cast<const uint4*>(p.s->uT) + P * 256 + 2 * t128;
    const int ustep = wg < 4 ? 256 : 1;
    uint4 uv0, uv1;
    kgen_mma(kg, tb, lane);
    if (UAT == 3 && (warp == UW || warp == UW + 1)) upub();
    STAMP(26);
    WPOINT(3, warp - 5);
    const uint32_t idn = 0x3210u + (warp >> 8);
    const uint4 lt7 = make_uint4(prmt_v(KW_T2 + ((lane >> 3) & 1) * KW_KH + (33 + (lane & 7)) * 16 - (lane & 16), 0u, idn), t * 288 + g * 8 + 8, (lane & 1) * 4096 + (lane >> 1) * 16,
                                 prmt_v(8u << ((lane >> 3) + (lane & 4)) >> (lane & 3), 0u, idn));
    asm volatile("barrier.cluster.wait.acquire.aligned;\n" ::: "memory");
    bar_sync(1 + wg, 128);
    uv0 = ld_poll(usrc); uv1 = ld_poll(usrc + ustep);
    kgen_combine(sb, warp, lane, kw, lt7.y);
    if (warp < 3 || warp > 6) bar_arrive(14, NWRK);
    CONV_PRE
    STAMP(5);
    WPOINT(4, warp - 7);
    if (wg < 4) {
        mbar_wait(bar_x);
        const bool far = warp < 8;
        const uint32_t xa = sb + SM_XC + (warp & 7) * 256 + (odd ^ far) * 8 + lt7.z;
        uint2 xv[4] = {lds64(xa), lds64(xa + 8192), lds64(xa + 2048), lds64(xa + 10240)};
        const uint32_t tag = ((ep & 0x7fffu) + 1u) << 16;
        int it = 0;
        while (true) {
            const bool bad = (((uv0.x ^ tag) | (uv0.z ^ tag)) | ((uv1.x ^ tag) | (uv1.z ^ tag))) >> 16;
            if (!__any_sync(0xffffffffu, bad)) break;
            if (++it > SPIN_LIMIT) TRAP();
            if (bad) { uv0 = ld_poll(usrc); uv1 = ld_poll(usrc + 256); }
        }
        STAMP(6);
        DBG(wg, it);
        const uint2 st[4] = {make_uint2(uv0.x, uv0.y), make_uint2(uv0.z, uv0.w), make_uint2(uv1.x, uv1.y), make_uint2(uv1.z, uv1.w)};
#pragma unroll
        for (int i = 0; i < 4; i++) {
            xv[i].x = ln_apply(xv[i].x, st[i]);
            xv[i].y = ln_apply(xv[i].y, st[i]);
        }
        const uint32_t ub = sb + SM_U + UPAD * 16 + odd * ULO_B + (warp & 7) * 256 + lane * 8;
        const uint32_t w[4][2] = {{pack_f16(bf_lo(xv[0].x), bf_lo(xv[1].x)), pack_f16(bf_lo(xv[2].x), bf_lo(xv[3].x))}, {HI2(xv[0].x, xv[1].x), HI2(xv[2].x, xv[3].x)},
                                  {pack_f16(bf_lo(xv[0].y), bf_lo(xv[1].y)), pack_f16(bf_lo(xv[2].y), bf_lo(xv[3].y))}, {HI2(xv[0].y, xv[1].y), HI2(xv[2].y, xv[3].y)}};
#pragma unroll
        for (int i = 0; i < 4; i++) {
            if (far) asm volatile("st.async.shared::cluster.mbarrier::complete_tx::bytes.v2.b32 [%0], {%1,%2}, [%3];\n" ::"r"((ub ^ 0x1000000u) + i * USLOT_B), "r"(w[i][0]), "r"(w[i][1]), "r"(bar_r ^ 0x1000000u) : "memory");
            else sts64(ub + i * USLOT_B, w[i][0], w[i][1]);
        }
    } else {
        const uint32_t utag = ((ep & 3u) + 1u) * 0x10001u;
        int it = 0;
        while (true) {
            const bool bad = (((uv0.x ^ utag) | (uv0.y ^ utag) | (uv0.z ^ utag) | (uv0.w ^ utag)) | ((uv1.x ^ utag) | (uv1.y ^ utag) | (uv1.z ^ utag) | (uv1.w ^ utag))) & 0x70007u;
            if (!__any_sync(0xffffffffu, bad)) break;
            if (++it > SPIN_LIMIT) TRAP();
            if (bad) { uv0 = ld_poll(usrc); uv1 = ld_poll(usrc + 1); }
        }
        STAMP(6);
        DBG(4, it);
        const uint32_t ub = sb + SM_U + UPAD * 16 + 4 * USLOT_B + (t128 >> 1) * 32 + (t128 & 1) * 8;
        sts64(ub, prmt(uv0.x, uv0.z, 0x5410u) ^ utag, prmt(uv1.x, uv1.z, 0x5410u) ^ utag);
        sts64(ub + 16, prmt(uv0.x, uv0.z, 0x7632u) ^ utag, prmt(uv1.x, uv1.z, 0x7632u) ^ utag);
        sts64(ub + ULO_B, prmt(uv0.y, uv0.w, 0x5410u) ^ utag, prmt(uv1.y, uv1.w, 0x5410u) ^ utag);
        sts64(ub + ULO_B + 16, prmt(uv0.y, uv0.w, 0x7632u) ^ utag, prmt(uv1.y, uv1.w, 0x7632u) ^ utag);
    }
    if (warp < 3 && elect_one()) tma_st_3d(warp < 2 ? &tm_y : &tm_z, sb + SM_ZERO, warp < 2 ? 128 * b : 32 * (512 + P), 0, 2 * (warp < 2 ? warp : odd));
    if (warp >= 3 && warp <= 6) {
        bar_sync(14, NWRK);
        WPOINT(5, warp - 3);
    }
    bar_sync(1 + wg, 128);
    CONV_PRE2
    mbar_wait(bar_r);
    fence_async();
    bar_sync(0, NWRK);
    STAMP(7);
    uint32_t hv0 = 0;
    {
        WPOINT(6, 19 - warp);
        CONV_BODY
        WPOINT(7, 19 - warp);
        bar_sync(0, NWRK);
        STAMP(8);
        size_t ycopy = 0;
        auto hook = [&](auto gi) {
                     constexpr int G = decltype(gi)::value;
                     if (G == 4 && warp == HINTW) hv0 = ld_poll32(p.s->hint + (lane_v() & 7) * 32);
                     if (G == 5) mbar_wait(bar_h);
                     if (G == 1 || G == 2) WPOINT(7 + G, warp - 16);
                     if (G == 3) { WPOINT(10, warp - 12); WPOINT(12, warp - 8); WPOINT(14, warp - 4); }
                     if (G == 5) { WPOINT(11, warp - 13); WPOINT(13, warp - 9); WPOINT(15, warp - 5); }
                     if (G == 1 && warp >= 17 && elect_one())
                         bulk_s2g(warp == 17 ? p.s->part + b * (PBYTES / 4) : warp == 18 ? p.s->rows + b * 1152 : p.s->sc + b * 32, sb + SM_ZERO, warp == 17 ? PBYTES : warp == 18 ? 4608 : 32);
                     if (G == 4 && warp >= 17 && elect_one()) {
                         asm volatile("cp.async.bulk.wait_group 0;\n" ::: "memory");
                         hint_arrive(p.s->hint, 2, b & 7);
                     }
                     if (G == 1 && warp < 3) {
                         if (elect_one()) {
                             asm volatile("cp.async.bulk.wait_group 0;\n" ::: "memory");
                             mbar_arrive(bar_h);
                             hint_arrive(p.s->hint, 0, b & 7);
                         }
                         __syncwarp();
                         STAMP(17);
                     }
                 };
        conv_main(c, acc, sb, sel, reinterpret_cast<unsigned char*>(p.s->y), warp, ycopy, hook);
        STAMP(10);
    }
    {
    const int warp = warp_v(), lane = lane_v(), tid = 32 * warp + lane, g = lane >> 2, t = lane & 3;
    if (warp == HINTW) {
        const uint32_t target = (lds32(s_cnt + 4) + 1u) * 48u;
        if (__any_sync(0xffffffffu, (int)(hv0 - target) < 0)) hint_wait(p.s->hint, 0, target);
    }
    const unsigned char* ys = reinterpret_cast<const unsigned char*>(p.s->y) + ((size_t)P * DM + 32 * warp + 8 * (g >> 1) + (g & 1)) * 64 + odd * 32 + t * 8;
    STAMP(27);
    bar_sync(0, NWRK);
    STAMP(11);
    const uint32_t zr = warp >> 8;
    auto late_rows = [&](auto pub) {
        const uint32_t k = lds32(s_key + (lane & 7) * 4), ep = lds32(s_cnt + 4);
        const bool late = k & 256u, mine = late && ((k & 255u) >> 1) == (uint32_t)b;
        uint32_t todo = __ballot_sync(0xffffffffu, mine) & 0xffu;
        if (todo) {
#pragma unroll 1
            while (todo) {
                const int s = __ffs(todo) - 1, row = (__shfl_sync(0xffffffffu, k, s) >> 9) & 15;
                todo &= todo - 1;
                if ((row & 7) == g) pub(row & 8, 2 * NCTA + s);
            }
            __threadfence();
            bar_sync(0, NWRK);
            if (tid < NSEL && mine) *reinterpret_cast<volatile unsigned*>(p.s->flag + tid) = ep + 1u;
        }
        int it = 0;
        while (__any_sync(0xffffffffu, late && ld_poll32(p.s->flag + (lane & 7)) != ep + 1u)) { if (++it > SPIN_LIMIT) TRAP(); }
        __threadfence();
        const int gs = tid / 36;
        const uint4* src = reinterpret_cast<const uint4*>(p.s->rows) + __shfl_sync(0xffffffffu, late ? 2 * NCTA + (lane & 7) : (k & 255u), gs & 7) * 144 + 36 * odd + (tid - gs * 36);
        if (tid < 288) {
            uint4 v0;
            do { v0 = ld_poll(src); if (++it > SPIN_LIMIT) TRAP(); } while (!v0.x);
            sts128(sb + SM_XS + gs * XS_PITCH + (tid - gs * 36) * 16, v0.x, v0.y, v0.z, v0.w);
        }
        bar_sync(0, NWRK);
    };
    if (warp >= 18) {
        if (warp == 18) {
            uint32_t* const kp = pin(p.s->sc + 32 * b, zr);
            const uint32_t kid = pin(0x30000000u | ((lane & 15) << 9) | 2 * b, zr), ka = pin(s_k16 + (lane & 15) * 4, zr), kb = pin(s_k16 + (lane & 16) * 2, zr);
            bar_sync(8, 640);
            float mb, rc;
            ln_finish<18>(sb + SM_LNP, lane, mb, rc);
            if (lane < 16) stat_store(s_stat + lane * 8, mb, rc, 0u);
            bar_arrive(13, 608);
            bar_sync(10, 608);
            const float r = sum18(sb + SM_LNP + (32 + (lane & 15)) * 80);
            const uint32_t bits = pack_bf16(0.f, r);
            const uint32_t me = (((bits ^ ((uint32_t)((int)bits >> 31) & 0x7fffffffu)) >> 3) & 0x1fffe000u) ^ kid;
            sts32(ka, me);
            __syncwarp();
            const uint4 v = lds128(kb), w = lds128(kb + 16);
#define GT(x) ((me - (x)) >> 31)
            uint32_t rank = pin(GT(v.x) + GT(v.y) + GT(v.z), zr) + pin(GT(v.w) + GT(w.x) + GT(w.y), zr) + pin(GT(w.z) + GT(w.w), zr);
#undef GT
            rank += __shfl_xor_sync(0xffffffffu, rank, 16);
            if (lane < 16) { if (rank < 8) stg32(kp + rank, me + (rank < 2 ? rank : 256u)); }
            else sts32(ka + (s_wm - s_k16), rank);
            bar_arrive(11, 640);
            weight_units<19, 0>(sb, &tm_g, &tm_u, &tm_d, 0); weight_units<19, 1>(sb, &tm_g, &tm_u, &tm_d, 1);
        }
        const uint4* ksrc = pin(reinterpret_cast<const uint4*>(p.s->sc) + 8 * lane, zr);
        const uint4* rsrc = pin(reinterpret_cast<const uint4*>(p.s->rows) + 36 * odd + t, zr);
        if (warp == 19) {
            weight_units<20, 0>(sb, &tm_g, &tm_u, &tm_d, 0); weight_units<20, 1>(sb, &tm_g, &tm_u, &tm_d, 1);
            hint_wait(p.s->hint, 2, (lds32(s_cnt + 4) + 1u) * 48u);
            bar_sync(8, 640);
            weight_units<16, 0>(sb, &tm_g, &tm_u, &tm_d, 0); weight_units<16, 1>(sb, &tm_g, &tm_u, &tm_d, 1);
            bar_sync(11, 640);
        }
        bool slow = false;
        int it = 0;
        if (warp == 19) {
        uint4 q[4];
#pragma unroll
        for (int i = 0; i < 4; i++) q[i] = ld_poll(ksrc + 256 * i);
        while (true) {
            uint32_t a[4];
#pragma unroll
            for (int i = 0; i < 4; i++) a[i] = q[i].x & q[i].y & q[i].z & q[i].w;
            if (__all_sync(0xffffffffu, a[0] & a[1] & a[2] & a[3])) break;
#pragma unroll
            for (int i = 0; i < 4; i++)
                if (!a[i]) q[i] = ld_poll(ksrc + 256 * i);
            if (++it > SPIN_LIMIT) TRAP();
        }
        bar_arrive(9, 608);
        STAMP(16);
        auto merge = [](const uint4& x, const uint4& y) {
            const uint32_t a = max(x.x, y.w), c = max(x.y, y.z), d = max(x.z, y.y), e = max(x.w, y.x);
            const uint32_t a2 = max(a, d), d2 = min(a, d), c2 = max(c, e), e2 = min(c, e);
            return make_uint4(max(a2, c2), min(a2, c2), max(d2, e2), min(d2, e2));
        };
        uint4 h = merge(merge(q[0], q[1]), merge(q[2], q[3]));
        uint4 v[9];
        uint32_t key = 0;
#pragma unroll
        for (int s = 0; s < 8; s++) {
            const uint32_t m = __reduce_max_sync(0xffffffffu, h.x);
            const bool w = h.x == m;
            h.x = w ? h.y : h.x; h.y = w ? h.z : h.y; h.z = w ? h.w : h.z; h.w = w ? 0u : h.w;
            if (g == s) key = m;
        }
        rsrc += (key & 255u) * 144;
#pragma unroll
        for (int j = 0; j < 9; j++) v[j] = ld_poll(rsrc + 4 * j);
        slow = __any_sync(0xffffffffu, key & 256u);
        STAMP(18);
        if (__any_sync(0xffffffffu, h.x == 0u)) {
            uint4 r[4];
            it = 0;
            while (true) {
#pragma unroll
                for (int i = 0; i < 4; i++) r[i] = ld_poll(ksrc + 256 * i + 1);
                if (__all_sync(0xffffffffu, all_nz(r[0]) && all_nz(r[1]) && all_nz(r[2]) && all_nz(r[3]))) break;
                if (++it > SPIN_LIMIT) TRAP();
            }
            uint32_t m = 1u << 30;
#pragma unroll 1
            for (int s = 0; s < 8; s++) {
                uint32_t x = 0;
#pragma unroll
                for (int i = 0; i < 4; i++) {
                    x = max(max(max(x, q[i].x - m), max(q[i].y - m, q[i].z - m)), q[i].w - m);
                    x = max(max(max(x, r[i].x - m), max(r[i].y - m, r[i].z - m)), r[i].w - m);
                }
                m += __reduce_max_sync(0xffffffffu, x);
                if (g == s) key = m;
            }
            slow = true;
        }
        sts32(s_key + g * 4, key);
        bar_arrive(12, 608);
        if (!slow) {
            it = 0;
            while (true) {
                const uint32_t mn = min(min(min(min(v[0].x, v[1].x), v[2].x), min(min(v[3].x, v[4].x), v[5].x)), min(min(v[6].x, v[7].x), v[8].x));
                if (__all_sync(0xffffffffu, mn)) break;
                if (++it > SPIN_LIMIT) TRAP();
#pragma unroll
                for (int j = 0; j < 9; j++) v[j] = ld_poll(rsrc + 4 * j);
            }
#pragma unroll
            for (int j = 0; j < 9; j++) sts128(sb + SM_XS + g * XS_PITCH + t * 16 + j * 64, v[j].x, v[j].y, v[j].z, v[j].w);
        }
        }
        if (bar_or(0, NWRK, slow)) late_rows([](bool, int) {});
        STAMP(19);
        const int fl = 16 * (b & 1) + ((tid >> 2) & 15), fc = 16 * (b >> 1) + (fl >> 2) + 8 * ((tid >> 1) & 1), fsl = 2 * (fl & 3) + (tid & 1);
        const uint32_t kk = lds32(s_key + fsl * 4);
        const uint32_t* fsrc = p.s->rows + ((kk & 256u) ? 2 * NCTA + fsl : (kk & 255u)) * DM + (fc >> 1);
        uint32_t hw = 1u, uw = 1u;
        if (b < 72) { uw = ld_poll32(fsrc); hw = ld_poll32(fsrc + 288); }
        if (b < 72) {
            it = 0;
            while (!hw || !uw) { uw = ld_poll32(fsrc); hw = ld_poll32(fsrc + 288); if (++it > SPIN_LIMIT) TRAP(); }
            const int row = (kk >> 9) & 15, ftok = 8 * (kk & 252u) + (kk & 2u) + TOKEN_OF(row & 7) + (row & 8);
            const unsigned k16 = (kk >> 13) & 0xffffu;
            const unsigned bits = (k16 & 0x8000u) ? (k16 & 0x7fffu) : (~k16 & 0xffffu);
            const float rs = __uint_as_float(pin(__float_as_uint(rbf(__fdividef(1.0f, 1.0f + __expf(-__uint_as_float(bits << 16))))), zr));
            bf16* const op = pin(p.out + (size_t)ftok * DM + fc, zr);
            const float uv = (fc & 1) ? bf_hi(uw) : bf_lo(uw), hv = (fc & 1) ? bf_hi(hw) : bf_lo(hw);
            bar_sync(14, 576);
            float v0 = 0.f, v1 = 0.f, v2 = 0.f, v3 = 0.f;
            const uint32_t a = sb + SM_EX + (tid - 576) * 4;
#pragma unroll
            for (int i = 0; i < 16; i += 4) { v0 += ldsf(a + i * 256); v1 += ldsf(a + i * 256 + 256); v2 += ldsf(a + i * 256 + 512); v3 += ldsf(a + i * 256 + 768); }
            const float y3 = rbf(rbf(((v0 + v1) + (v2 + v3)) * 512.0f) * rs);
            asm volatile("st.global.u16 [%0], %1;\n" ::"l"(op), "h"((unsigned short)pack_bf16(hv + rbf(uv + y3), 0.f)) : "memory");
        }
        if (b == 0 && tid >= 632) *reinterpret_cast<volatile unsigned*>(p.s->hint + (tid & 7) * 32 + 1) = lds32(s_cnt + 4) + 1u;
    } else {
        uint32_t H[2][4], U2[2][4], WA[9][4], WD[18], WE[18];
        const int fkh = warp >= 9, fmt = warp - 9 * fkh;
        auto load_wa = [&](auto k0, auto k1) {
            if (k0.value >= k1.value) return;
            if (k0.value == 0) mbar_wait(bar_w);
            const int mi = lane >> 3, rr = lane & 7;
            const uint32_t aad = sb + SM_WG + (mi & 1) * (SM_WU - SM_WG) + (fkh * 144 + rr + 8 * (mi >> 1)) * W_PITCH + fmt * 16;
#pragma unroll
            for (int k = k0.value; k < k1.value; k++) ldsm_x4_t(WA[k][0], WA[k][1], WA[k][2], WA[k][3], aad + k * 16 * W_PITCH);
        };
        auto load_wd = [&](uint32_t (&WD)[18], int tile) {
            mbar_wait(bar_d + (tile & 16));
            const int mi = lane >> 3, rr = lane & 7;
            const uint32_t base = sb + SM_WD + (tile >> 2) * 9216 + rr * 128 + (((2 * tile + (mi & 1)) & 7) ^ rr) * 16;
#pragma unroll
            for (int k = 0; k < 4; k++) ldsm_x4_t(WD[4 * k], WD[4 * k + 1], WD[4 * k + 2], WD[4 * k + 3], base + (k * 16 + 8 * (mi >> 1)) * 128);
            ldsm_x2_t(WD[16], WD[17], base + 64 * 128);
        };
        auto publish = [&](bool hi, int slot) {
            uint4* rowp = reinterpret_cast<uint4*>(p.s->rows) + slot * 144 + warp * 4 + t;
            stg128(rowp, nzw(hi ? U2[1][0] : U2[0][0]), nzw(hi ? U2[1][1] : U2[0][1]), nzw(hi ? U2[1][2] : U2[0][2]), nzw(hi ? U2[1][3] : U2[0][3]));
            stg128(rowp + 72, nzw(hi ? H[1][0] : H[0][0]), nzw(hi ? H[1][1] : H[0][1]), nzw(hi ? H[1][2] : H[0][2]), nzw(hi ? H[1][3] : H[0][3]));
        };
        uint4 wr = make_uint4(0x3f803f80u, 0x3f803f80u, 0x3f803f80u, 0x3f803f80u);
        {
            uint2 yv[4];
#pragma unroll
            for (int k = 0; k < 4; k++) yv[k] = ld_poll64(ys + k * 128);
            if (g == 0) wr = ldg128(p.wr + 32 * warp + 8 * t);
            const uint4 x0 = lds128(sb + SM_XT + warp * 1024 + lane * 16), x1 = lds128(sb + SM_XT + warp * 1024 + 512 + lane * 16);
            load_wa(IC<0>(), IC<WA0>());
            int it = 0;
            while (!__all_sync(0xffffffffu, yv[0].x && yv[1].x && yv[2].x && yv[3].x)) {
#pragma unroll
                for (int k = 0; k < 4; k++) yv[k] = ld_poll64(ys + k * 128);
                if (++it > SPIN_LIMIT) TRAP();
            }
            STAMP(12);
            const uint32_t Z[2][4] = {{x0.x, x0.y, x0.z, x0.w}, {x1.x, x1.y, x1.z, x1.w}};
#pragma unroll
            for (int k = 0; k < 4; k++) {
                H[0][k] = hadd2_bf(Z[0][k], movm(yv[k].x));
                H[1][k] = hadd2_bf(Z[1][k], movm(yv[k].y));
            }
            const uint32_t bw[4] = {wr.x, wr.y, wr.z, wr.w};
            ln_partial<4>(H, bw, sb + SM_LNP, warp, g, t);
        }
        bar_arrive(8, 640);
        load_wa(IC<WA0>(), IC<WA1>());
        STAMP(13);
        bar_sync(13, 608);
        STAMP(14);
#pragma unroll
        for (int hf = 0; hf < 2; hf++) {
            const uint2 st = lds64(s_stat + (g + 8 * hf) * 8);
#pragma unroll
            for (int k = 0; k < 4; k++) U2[hf][k] = ln_apply(H[hf][k], st);
        }
        {
            float cs[4] = {0.f, 0.f, 0.f, 0.f};
            mma_bf16(cs, U2[0][0], U2[1][0], U2[0][1], U2[1][1], wr.x, wr.y);
            mma_bf16(cs, U2[0][2], U2[1][2], U2[0][3], U2[1][3], wr.z, wr.w);
            if (t == 0) { stsf(sb + SM_LNP + ((32 + g) * 20 + warp) * 4, cs[0]); stsf(sb + SM_LNP + ((40 + g) * 20 + warp) * 4, cs[2]); }
            bar_arrive(10, 608);
        }
        load_wa(IC<WA1>(), IC<WA2>());
        bar_sync(11, 640);
        {
            const uint32_t rk[2] = {lds32(s_wm + g * 4), lds32(s_wm + 32 + g * 4)};
            uint32_t lo = min(rk[0], rk[1]), hi = max(rk[0], rk[1]);
#pragma unroll 1
            while (lo < 2) { publish(lo == rk[1], 2 * b + lo); lo = hi; hi = 16; }
        }
        load_wa(IC<WA2>(), IC<WA3>());
        bar_sync(9, 608);
        load_wa(IC<WA3>(), IC<9>());
#pragma unroll
        for (int hf = 0; hf < 2; hf++)
            sts128(sb + SM_OUT + (g + 8 * hf) * OUT_PITCH + warp * 64 + t * 16,
                   hadd2_bf(H[hf][0], U2[hf][0]), hadd2_bf(H[hf][1], U2[hf][1]), hadd2_bf(H[hf][2], U2[hf][2]), hadd2_bf(H[hf][3], U2[hf][3]));
        fence_async();
        WPOINT(17, warp - 16);
        if ((WDAT == 0 || (WDAT == 2 && fkh)) && (warp < 16 || !odd)) load_wd(WD, warp);
        const uint32_t bad = pin(sb + SM_XS + (lane & 7) * XS_PITCH + (fkh * 144 + 8 * (lane >> 3)) * 2, zr), ex = pin(sb + SM_EX + warp * 512 + lane * 16, zr);
        uint32_t* pp = pin(p.s->part + ((size_t)(2 * (20 * odd + warp) + (lane >> 4)) * 64 + P) * 32 + (lane & 15) * 2, zr);
        bar_sync(12, 608);
        if (warp < 16 && !__any_sync(0xffffffffu, (lds32(s_key + (lane & 7) * 4) & 0x1efeu) == (uint32_t)((warp << 9) | 2 * b)) && elect_one())
            bulk_s2g(p.out + (size_t)(32 * P + 2 * odd + TOKEN_OF(warp & 7) + (warp & 8)) * DM, sb + SM_OUT + warp * OUT_PITCH, DM * 2);
        WPOINT(18, warp - 16);
        STAMP(15);
        if (bar_or(0, NWRK, false)) late_rows(publish);
        STAMP(19);
        float gp[4];
        {
            float c4[3][4];
#pragma unroll
            for (int i = 0; i < 3; i++)
#pragma unroll
                for (int j = 0; j < 4; j++) c4[i][j] = 0.f;
#pragma unroll
            for (int k = 0; k < 10; k += 2) {
                uint32_t b0, b1, b2, b3;
                ldsm_x4(b0, b1, b2, b3, bad + k * 32);
                mma_bf16(c4[k % 3], WA[k][0], WA[k][1], WA[k][2], WA[k][3], b0, b1);
                if (k < 8) mma_bf16(c4[(k + 1) % 3], WA[k + 1][0], WA[k + 1][1], WA[k + 1][2], WA[k + 1][3], b2, b3);
            }
#pragma unroll
            for (int j = 0; j < 4; j++) gp[j] = c4[0][j] + (c4[1][j] + c4[2][j]);
            if (warp >= 9) {
                sts128f(ex, gp);
                bar_arrive(6, 576);
            } else {
                bar_sync(6, 576);
                const uint4 o = lds128(ex + 4608);
                gp[0] += __uint_as_float(o.x); gp[1] += __uint_as_float(o.y); gp[2] += __uint_as_float(o.z); gp[3] += __uint_as_float(o.w);
                asm volatile("st.async.shared::cluster.mbarrier::complete_tx::bytes.v4.b32 [%0], {%1,%2,%3,%4}, [%5];\n"
                             ::"r"(ex ^ 0x1000000u), "r"(__float_as_uint(gp[0])), "r"(__float_as_uint(gp[1])), "r"(__float_as_uint(gp[2])), "r"(__float_as_uint(gp[3])), "r"(bar_g ^ 0x1000000u) : "memory");
                if (WDAT == 2) load_wd(WD, warp);
            }
            if (WDAT == 1 && (warp < 16 || !odd)) load_wd(WD, warp);
            if (warp >= 16 && !odd) load_wd(WE, warp + 2);
        }
        STAMP(20);
        if (warp < 9) {
            mbar_wait(bar_g);
            const uint4 u = lds128(ex);
            const uint32_t G = pack_bf16(gp[0] + __uint_as_float(u.x), gp[1] + __uint_as_float(u.y)), U = pack_bf16(gp[2] + __uint_as_float(u.z), gp[3] + __uint_as_float(u.w));
            const float G0 = bf_lo(G), G1 = bf_hi(G);
            sts32(sb + SM_GU + tid * 4, hmul2_bf(pack_bf16(G0 * rcp_approx(1.0f + ex2_approx(G0 * -1.4426950408889634f)), G1 * rcp_approx(1.0f + ex2_approx(G1 * -1.4426950408889634f))), U));
        }
        bar_sync(7, 576);
        STAMP(21);
        if (warp < 16 || !odd) {
            uint32_t gb[9];
            ldsm_x4_t(gb[0], gb[1], gb[2], gb[3], sb + SM_GU + lane * 16);
            ldsm_x4_t(gb[4], gb[5], gb[6], gb[7], sb + SM_GU + 512 + lane * 16);
            ldsm_x1_t(gb[8], sb + SM_GU + 1024 + (lane & 7) * 16);
            auto down = [&](const uint32_t (&W)[18], uint32_t* dst) {
                float c4[4] = {0.f, 0.f, 0.f, 0.f}, d4[4] = {0.f, 0.f, 0.f, 0.f}, e4[4] = {0.f, 0.f, 0.f, 0.f};
                mma_bf16(c4, W[0], W[1], W[2], W[3], gb[0], gb[1]);
                mma_bf16(d4, W[4], W[5], W[6], W[7], gb[2], gb[3]);
                mma_bf16(e4, W[8], W[9], W[10], W[11], gb[4], gb[5]);
                mma_bf16_k8(c4, W[16], W[17], gb[8]);
                mma_bf16(d4, W[12], W[13], W[14], W[15], gb[6], gb[7]);
                const float v0 = (c4[0] + e4[0]) + d4[0], v1 = (c4[1] + e4[1]) + d4[1], v2 = (c4[2] + e4[2]) + d4[2], v3 = (c4[3] + e4[3]) + d4[3];
                const uint32_t e = max(max(__float_as_uint(fmaxf(fabsf(v0), fabsf(v1))), __float_as_uint(fmaxf(fabsf(v2), fabsf(v3)))), 16u << 23) >> 23;
                const float sc = __uint_as_float((245u - e) << 23);
                stg64(dst, pack_f16(v0 * sc, v1 * sc) | ((e * 0x8002000u) & 0x60006000u), pack_f16(v2 * sc, v3 * sc) | ((e * 0x800200u) & 0x60006000u));
            };
            if (warp >= 16) { down(WE, pp + 4 * 64 * 32); down(WD, pp); }
            else down(WD, pp);
        }
        asm volatile("cp.async.bulk.wait_group.read 0;\n" ::: "memory");
        STAMP(22);
        if (b < 72 && warp < 16) {
            const uint2* src = reinterpret_cast<const uint2*>(p.s->part) + (unsigned)(b * 1024 + tid);
            uint2 a, c;
            int it = 0;
            a = ld_poll64(src); c = ld_poll64(src + 512);
            while (!__all_sync(0xffffffffu, a.y && c.y)) {
                a = ld_poll64(src); c = ld_poll64(src + 512);
                if (++it > SPIN_LIMIT) TRAP();
            }
            STAMP(24);
            const float ea = __uint_as_float((((a.y & 0x60006000u) | ((a.x >> 4) & 0x06000600u)) * 0x4001u) & 0x7f800000u);
            const float ec = __uint_as_float((((c.y & 0x60006000u) | ((c.x >> 4) & 0x06000600u)) * 0x4001u) & 0x7f800000u);
            a.x &= 0x9fff9fffu; a.y &= 0x9fff9fffu; c.x &= 0x9fff9fffu; c.y &= 0x9fff9fffu;
            const float s0 = fmaf(h_lo(a.x), ea, h_lo(c.x) * ec), s1 = fmaf(h_hi(a.x), ea, h_hi(c.x) * ec), s2 = fmaf(h_lo(a.y), ea, h_lo(c.y) * ec), s3 = fmaf(h_hi(a.y), ea, h_hi(c.y) * ec);
            const bool up = lane & 16;
            const float r0 = __shfl_xor_sync(0xffffffffu, up ? s0 : s2, 16), r1 = __shfl_xor_sync(0xffffffffu, up ? s1 : s3, 16);
            sts64f(sb + SM_EX + warp * 256 + (lane & 15) * 16 + (up ? 8 : 0), (up ? s2 : s0) + r0, (up ? s3 : s1) + r1);
            bar_arrive(14, 576);
        }
    }
    STAMP(25);
    }
}

typedef CUresult (*PFN_tmEncode)(CUtensorMap*, CUtensorMapDataType, cuuint32_t, void*, const cuuint64_t*, const cuuint64_t*, const cuuint32_t*,
                                 const cuuint32_t*, CUtensorMapInterleave, CUtensorMapSwizzle, CUtensorMapL2promotion, CUtensorMapFloatOOBfill);

extern "C" void kernel_launch(void* const* d_in, const int* in_sizes, int n_in, void* d_out, int out_size) {
    Params p;
    p.x = (const bf16*)d_in[0];
    p.lar = (const bf16*)d_in[1];
    p.aim = (const bf16*)d_in[2];
    p.cre = (const bf16*)d_in[3];
    p.cim = (const bf16*)d_in[4];
    p.ldt = (const bf16*)d_in[5];
    p.dsk = (const bf16*)d_in[6];
    p.wr = (const bf16*)d_in[8];
    p.out = (bf16*)d_out;
    static PFN_tmEncode enc = nullptr;
    static void* scratch = nullptr;
    if (!enc) {
        cudaFuncSetAttribute(fused_kernel, cudaFuncAttributeMaxDynamicSharedMemorySize, SMEM_TOTAL);
        void* fn = nullptr;
        cudaDriverEntryPointQueryResult qr;
        cudaGetDriverEntryPoint("cuTensorMapEncodeTiled", &fn, cudaEnableDefault, &qr);
        enc = (PFN_tmEncode)fn;
        cudaGetSymbolAddress(&scratch, g_scratch);
    }
    p.s = (Scratch*)scratch;
    CUtensorMap tm_g, tm_u, tm_d, tm_x, tm_y, tm_z;
    const cuuint64_t dims[2] = {FF, DM}, strides[1] = {FF * 2};
    const cuuint32_t box[2] = {72, 48}, es[2] = {1, 1};
    enc(&tm_g, CU_TENSOR_MAP_DATA_TYPE_BFLOAT16, 2, d_in[9], dims, strides, box, es, CU_TENSOR_MAP_INTERLEAVE_NONE, CU_TENSOR_MAP_SWIZZLE_NONE,
        CU_TENSOR_MAP_L2_PROMOTION_NONE, CU_TENSOR_MAP_FLOAT_OOB_FILL_NONE);
    const cuuint32_t ubox[2] = {72, 144}, es3[3] = {1, 1, 1};
    enc(&tm_u, CU_TENSOR_MAP_DATA_TYPE_BFLOAT16, 2, d_in[10], dims, strides, ubox, es, CU_TENSOR_MAP_INTERLEAVE_NONE, CU_TENSOR_MAP_SWIZZLE_NONE,
        CU_TENSOR_MAP_L2_PROMOTION_NONE, CU_TENSOR_MAP_FLOAT_OOB_FILL_NONE);
    const cuuint64_t ddims[2] = {DM, FF}, dstrides[1] = {DM * 2};
    const cuuint32_t dbox[2] = {64, 72};
    enc(&tm_d, CU_TENSOR_MAP_DATA_TYPE_BFLOAT16, 2, d_in[11], ddims, dstrides, dbox, es, CU_TENSOR_MAP_INTERLEAVE_NONE, CU_TENSOR_MAP_SWIZZLE_128B,
        CU_TENSOR_MAP_L2_PROMOTION_NONE, CU_TENSOR_MAP_FLOAT_OOB_FILL_NONE);
    const cuuint64_t xdims[3] = {DM, LSEQ / 16, 16}, xstrides[2] = {16 * DM * 2, DM * 2};
    const cuuint32_t xbox[3] = {8, LSEQ / 16, 8};
    enc(&tm_x, CU_TENSOR_MAP_DATA_TYPE_BFLOAT16, 3, d_in[0], xdims, xstrides, xbox, es3, CU_TENSOR_MAP_INTERLEAVE_NONE, CU_TENSOR_MAP_SWIZZLE_NONE,
        CU_TENSOR_MAP_L2_PROMOTION_NONE, CU_TENSOR_MAP_FLOAT_OOB_FILL_NONE);
    const cuuint64_t ydims[3] = {DM * 32, 16, 4}, ystrides[2] = {DM * 64, 16 * DM * 64};
    const cuuint32_t ybox[3] = {128, 16, 2}, zbox[3] = {32, 16, 2};
    enc(&tm_y, CU_TENSOR_MAP_DATA_TYPE_BFLOAT16, 3, p.s->y, ydims, ystrides, ybox, es3, CU_TENSOR_MAP_INTERLEAVE_NONE, CU_TENSOR_MAP_SWIZZLE_NONE,
        CU_TENSOR_MAP_L2_PROMOTION_NONE, CU_TENSOR_MAP_FLOAT_OOB_FILL_NONE);
    enc(&tm_z, CU_TENSOR_MAP_DATA_TYPE_BFLOAT16, 3, p.s->y, ydims, ystrides, zbox, es3, CU_TENSOR_MAP_INTERLEAVE_NONE, CU_TENSOR_MAP_SWIZZLE_NONE,
        CU_TENSOR_MAP_L2_PROMOTION_NONE, CU_TENSOR_MAP_FLOAT_OOB_FILL_NONE);
    fused_kernel<<<NCTA, NTHR, SMEM_TOTAL>>>(p, tm_g, tm_u, tm_d, tm_x, tm_y, tm_z);
}
```

```cpp
#include <cuda_runtime.h>
#include <cuda.h>
#include <cuda_fp16.h>
#include <cuda_bf16.h>
#include <stdint.h>

#define LSEQ 2048
#define DM 576
#define NST 128
#define FF 4608
#define NSEL 8
#define NCTA 128
#define NTHR 640
#define NWRK 640

typedef __nv_bfloat16 bf16;

#define SM_WD 0
#define SM_WG 46080
#define SM_WU 87552
#define W_PITCH 144
#define SM_ZERO 36864
#define SM_XC 18432
#define SM_TB 96000
#define SM_PL 129024
#define PL_B 10752
#define SM_XT (SM_TB + 20 * TBW)
#define SM_U (SM_XT + 18432)
#define UPAD 8
#define ULO_B ((UPAD + 128) * 16)
#define USLOT_B (2 * ULO_B)
#define SM_KW (SM_U + 5 * USLOT_B)
#define KW_B 3600
#define KW_T2 1152
#define KW_KH 656
#define KW_T3 2464
#define SM_MISC (SM_KW + 5 * KW_B)
#define SM_LNP (SM_MISC + 576)
#define SMEM_TOTAL (SM_LNP + 3840)
#define TBP 112
#define TBW (32 * TBP)
#define SM_OUT SM_PL
#define OUT_PITCH 1216
#define SM_XS (SM_PL + 19456)
#define XS_PITCH 592
#define SM_EX (SM_PL + 24320)
#define SM_FIN SM_KW
#define SM_GU (SM_PL + 33536)

struct __align__(128) Scratch {
    unsigned hint[8 * 32];
    unsigned flag[32];
    uint32_t sc[NCTA * 32];
    uint32_t st[LSEQ * 2];
    uint32_t uT[64 * (LSEQ / 2)];
    uint32_t y[NCTA * DM * 8];
    uint32_t part[72 * 64 * 32];
    uint32_t rows[(2 * NCTA + NSEL) * DM];
};
__device__ Scratch g_scratch;
#define STAMP(i)
#define DBG(i, v)

__device__ __forceinline__ float rbf(float x) {
    uint32_t r;
    asm("cvt.rn.bf16x2.f32 %0, %1, %2;\n" : "=r"(r) : "f"(x), "f"(0.f));
    return __uint_as_float(r & 0xffff0000u);
}
__device__ __forceinline__ uint32_t pack_bf16(float lo, float hi) {
    uint32_t r;
    asm("cvt.rn.bf16x2.f32 %0, %1, %2;\n" : "=r"(r) : "f"(hi), "f"(lo));
    return r;
}
__device__ __forceinline__ uint32_t pack_f16(float lo, float hi) {
    uint32_t r;
    asm("cvt.rn.f16x2.f32 %0, %1, %2;\n" : "=r"(r) : "f"(hi), "f"(lo));
    return r;
}
__device__ __forceinline__ uint32_t pack_f16_rz(float lo, float hi) {
    uint32_t r;
    asm("cvt.rz.f16x2.f32 %0, %1, %2;\n" : "=r"(r) : "f"(hi), "f"(lo));
    return r;
}
__device__ __forceinline__ float bf_lo(uint32_t w) { return __uint_as_float(w << 16); }
__device__ __forceinline__ float bf_hi(uint32_t w) { return __uint_as_float(w & 0xffff0000u); }
__device__ __forceinline__ uint32_t hadd2_bf(uint32_t a, uint32_t b) {
    __nv_bfloat162 r = __hadd2_rn(*reinterpret_cast<__nv_bfloat162*>(&a), *reinterpret_cast<__nv_bfloat162*>(&b));
    return *reinterpret_cast<uint32_t*>(&r);
}
__device__ __forceinline__ uint32_t hsub2_bf(uint32_t a, uint32_t b) {
    __nv_bfloat162 r = __hsub2_rn(*reinterpret_cast<__nv_bfloat162*>(&a), *reinterpret_cast<__nv_bfloat162*>(&b));
    return *reinterpret_cast<uint32_t*>(&r);
}
__device__ __forceinline__ uint32_t hmul2_bf(uint32_t a, uint32_t b) {
    __nv_bfloat162 r = __hmul2_rn(*reinterpret_cast<__nv_bfloat162*>(&a), *reinterpret_cast<__nv_bfloat162*>(&b));
    return *reinterpret_cast<uint32_t*>(&r);
}
__device__ __forceinline__ uint32_t hfma2_bf(uint32_t a, uint32_t b, uint32_t c) { uint32_t r; asm("fma.rn.bf16x2 %0, %1, %2, %3;\n" : "=r"(r) : "r"(a), "r"(b), "r"(c)); return r; }
__device__ __forceinline__ uint32_t hmul2(uint32_t a, uint32_t b) { uint32_t r; asm("mul.rn.f16x2 %0, %1, %2;\n" : "=r"(r) : "r"(a), "r"(b)); return r; }
__device__ __forceinline__ uint32_t hadd2(uint32_t a, uint32_t b) { uint32_t r; asm("add.rn.f16x2 %0, %1, %2;\n" : "=r"(r) : "r"(a), "r"(b)); return r; }
__device__ __forceinline__ uint32_t hfma2(uint32_t a, uint32_t b, uint32_t c) { uint32_t r; asm("fma.rn.f16x2 %0, %1, %2, %3;\n" : "=r"(r) : "r"(a), "r"(b), "r"(c)); return r; }
__device__ __forceinline__ uint32_t nzw(uint32_t w) { return w ? w : 0x8000u; }
__device__ __forceinline__ uint32_t nzf(float f) { const uint32_t w = __float_as_uint(f); return w ? w : 0x80000000u; }
__device__ __forceinline__ uint32_t smem_u32(const void* p) { return (uint32_t)__cvta_generic_to_shared(p); }
__device__ __forceinline__ uint32_t lds32(uint32_t addr) {
    uint32_t v;
    asm volatile("ld.shared.u32 %0, [%1];\n" : "=r"(v) : "r"(addr) : "memory");
    return v;
}
__device__ __forceinline__ uint32_t lds16(uint32_t addr) {
    unsigned short v;
    asm volatile("ld.shared.u16 %0, [%1];\n" : "=h"(v) : "r"(addr) : "memory");
    return v;
}
__device__ __forceinline__ uint2 lds64(uint32_t addr) {
    uint2 v;
    asm volatile("ld.shared.v2.u32 {%0,%1}, [%2];\n" : "=r"(v.x), "=r"(v.y) : "r"(addr) : "memory");
    return v;
}
__device__ __forceinline__ uint4 lds128(uint32_t addr) {
    uint4 v;
    asm volatile("ld.shared.v4.u32 {%0,%1,%2,%3}, [%4];\n" : "=r"(v.x), "=r"(v.y), "=r"(v.z), "=r"(v.w) : "r"(addr) : "memory");
    return v;
}
__device__ __forceinline__ float ldsf(uint32_t addr) { return __uint_as_float(lds32(addr)); }
__device__ __forceinline__ void sts32(uint32_t addr, uint32_t v) { asm volatile("st.shared.u32 [%0], %1;\n" ::"r"(addr), "r"(v) : "memory"); }
__device__ __forceinline__ void stsf(uint32_t addr, float v) { sts32(addr, __float_as_uint(v)); }
__device__ __forceinline__ void sts64(uint32_t addr, uint32_t a, uint32_t b) { asm volatile("st.shared.v2.u32 [%0], {%1,%2};\n" ::"r"(addr), "r"(a), "r"(b) : "memory"); }
__device__ __forceinline__ void sts64f(uint32_t addr, float a, float b) { sts64(addr, __float_as_uint(a), __float_as_uint(b)); }
__device__ __forceinline__ void sts128(uint32_t addr, uint32_t a, uint32_t b, uint32_t c, uint32_t d) {
    asm volatile("st.shared.v4.u32 [%0], {%1,%2,%3,%4};\n" ::"r"(addr), "r"(a), "r"(b), "r"(c), "r"(d) : "memory");
}
__device__ __forceinline__ void sts128f(uint32_t addr, const float (&v)[4]) {
    sts128(addr, __float_as_uint(v[0]), __float_as_uint(v[1]), __float_as_uint(v[2]), __float_as_uint(v[3]));
}
__device__ __forceinline__ void ldsm_x4(uint32_t& r0, uint32_t& r1, uint32_t& r2, uint32_t& r3, uint32_t addr) {
    asm volatile("ldmatrix.sync.aligned.m8n8.x4.shared.b16 {%0,%1,%2,%3}, [%4];\n"
                 : "=r"(r0), "=r"(r1), "=r"(r2), "=r"(r3) : "r"(addr) : "memory");
}
__device__ __forceinline__ void ldsm_x4_t(uint32_t& r0, uint32_t& r1, uint32_t& r2, uint32_t& r3, uint32_t addr) {
    asm volatile("ldmatrix.sync.aligned.m8n8.x4.trans.shared.b16 {%0,%1,%2,%3}, [%4];\n"
                 : "=r"(r0), "=r"(r1), "=r"(r2), "=r"(r3) : "r"(addr) : "memory");
}
__device__ __forceinline__ void ldsm_x2_t(uint32_t& r0, uint32_t& r1, uint32_t addr) {
    asm volatile("ldmatrix.sync.aligned.m8n8.x2.trans.shared.b16 {%0,%1}, [%2];\n" : "=r"(r0), "=r"(r1) : "r"(addr) : "memory");
}
__device__ __forceinline__ void ldsm_x1_t(uint32_t& r0, uint32_t addr) {
    asm volatile("ldmatrix.sync.aligned.m8n8.x1.trans.shared.b16 {%0}, [%1];\n" : "=r"(r0) : "r"(addr) : "memory");
}
__device__ __forceinline__ uint32_t movm(uint32_t a) {
    uint32_t d;
    asm volatile("movmatrix.sync.aligned.m8n8.trans.b16 %0, %1;\n" : "=r"(d) : "r"(a));
    return d;
}
__device__ __forceinline__ void mma_f16(float (&c)[4], uint32_t a0, uint32_t a1, uint32_t a2, uint32_t a3, uint32_t b0, uint32_t b1) {
    asm volatile(
        "mma.sync.aligned.m16n8k16.row.col.f32.f16.f16.f32 {%0,%1,%2,%3}, {%4,%5,%6,%7}, {%8,%9}, {%0,%1,%2,%3};\n"
        : "+f"(c[0]), "+f"(c[1]), "+f"(c[2]), "+f"(c[3])
        : "r"(a0), "r"(a1), "r"(a2), "r"(a3), "r"(b0), "r"(b1));
}
__device__ __forceinline__ void mma_bf16(float (&c)[4], uint32_t a0, uint32_t a1, uint32_t a2, uint32_t a3, uint32_t b0, uint32_t b1) {
    asm volatile(
        "mma.sync.aligned.m16n8k16.row.col.f32.bf16.bf16.f32 {%0,%1,%2,%3}, {%4,%5,%6,%7}, {%8,%9}, {%0,%1,%2,%3};\n"
        : "+f"(c[0]), "+f"(c[1]), "+f"(c[2]), "+f"(c[3])
        : "r"(a0), "r"(a1), "r"(a2), "r"(a3), "r"(b0), "r"(b1));
}
__device__ __forceinline__ void mma_bf16_k8(float (&c)[4], uint32_t a0, uint32_t a1, uint32_t b0) {
    asm volatile("mma.sync.aligned.m16n8k8.row.col.f32.bf16.bf16.f32 {%0,%1,%2,%3}, {%4,%5}, {%6}, {%0,%1,%2,%3};\n"
        : "+f"(c[0]), "+f"(c[1]), "+f"(c[2]), "+f"(c[3]) : "r"(a0), "r"(a1), "r"(b0));
}
__device__ __forceinline__ void bar_sync(int id, int n) { asm volatile("bar.sync %0, %1;\n" ::"r"(id), "r"(n) : "memory"); }
__device__ __forceinline__ void bar_arrive(int id, int n) { asm volatile("bar.arrive %0, %1;\n" ::"r"(id), "r"(n) : "memory"); }
__device__ __forceinline__ bool bar_or(int id, int n, bool v) {
    uint32_t r;
    asm volatile("{\n.reg .pred p, q;\nsetp.ne.u32 p, %3, 0;\nbar.red.or.pred q, %1, %2, p;\nselp.u32 %0, 1, 0, q;\n}\n" : "=r"(r) : "r"(id), "r"(n), "r"((uint32_t)v) : "memory");
    return r;
}
__device__ __forceinline__ uint4 ld_poll(const void* p) {
    uint4 v;
    asm volatile("ld.relaxed.gpu.global.v4.u32 {%0,%1,%2,%3}, [%4];\n" : "=r"(v.x), "=r"(v.y), "=r"(v.z), "=r"(v.w) : "l"(p) : "memory");
    return v;
}
template <class T> __device__ __forceinline__ T* pin(T* p, uint32_t z) {
    uint32_t lo, hi;
    asm volatile("mov.b64 {%0, %1}, %2;\n" : "=r"(lo), "=r"(hi) : "l"(p));
    asm volatile("xor.b32 %0, %0, %1;\n" : "+r"(lo) : "r"(z));
    asm volatile("xor.b32 %0, %0, %1;\n" : "+r"(hi) : "r"(z));
    asm volatile("mov.b64 %0, {%1, %2};\n" : "=l"(p) : "r"(lo), "r"(hi));
    return p;
}
__device__ __forceinline__ uint32_t pin(uint32_t a, uint32_t z) { asm volatile("xor.b32 %0, %0, %1;\n" : "+r"(a) : "r"(z)); return a; }
__device__ __forceinline__ uint2 ld_poll64(const void* p) {
    uint2 v;
    asm volatile("ld.relaxed.gpu.global.v2.u32 {%0,%1}, [%2];\n" : "=r"(v.x), "=r"(v.y) : "l"(p) : "memory");
    return v;
}
__device__ __forceinline__ uint32_t ld_poll32(const void* p) {
    uint32_t v;
    asm volatile("ld.relaxed.gpu.global.u32 %0, [%1];\n" : "=r"(v) : "l"(p) : "memory");
    return v;
}
__device__ __forceinline__ uint4 ldg128(const void* p) {
    uint4 v;
    asm volatile("ld.global.nc.v4.u32 {%0,%1,%2,%3}, [%4];\n" : "=r"(v.x), "=r"(v.y), "=r"(v.z), "=r"(v.w) : "l"(p));
    return v;
}
__device__ __forceinline__ uint2 ldg64(const void* p) {
    uint2 v;
    asm volatile("ld.global.nc.v2.u32 {%0,%1}, [%2];\n" : "=r"(v.x), "=r"(v.y) : "l"(p));
    return v;
}
__device__ __forceinline__ uint32_t ldg16(const void* p) {
    uint32_t v;
    asm volatile("ld.global.nc.u16 %0, [%1];\n" : "=r"(v) : "l"(p));
    return v;
}
__device__ __forceinline__ void stg128(void* p, uint32_t a, uint32_t b, uint32_t c, uint32_t d) {
    asm volatile("st.global.v4.u32 [%0], {%1,%2,%3,%4};\n" ::"l"(p), "r"(a), "r"(b), "r"(c), "r"(d) : "memory");
}
__device__ __forceinline__ void stg64(void* p, uint32_t a, uint32_t b) { asm volatile("st.global.v2.u32 [%0], {%1,%2};\n" ::"l"(p), "r"(a), "r"(b) : "memory"); }
__device__ __forceinline__ void stg32(void* p, uint32_t a) { asm volatile("st.global.u32 [%0], %1;\n" ::"l"(p), "r"(a) : "memory"); }
__device__ __forceinline__ bool all_nz(const uint4& v) { return v.x && v.y && v.z && v.w; }
#define SPIN_LIMIT (1 << 21)
#define TRAP() __trap()
__device__ __forceinline__ void hint_arrive(unsigned* g_hint, int idx, int sub) {
    asm volatile("red.relaxed.gpu.global.add.u32 [%0], 1;\n" ::"l"(&g_hint[sub * 32 + idx]) : "memory");
}
__device__ __forceinline__ void hint_wait(const unsigned* g_hint, int idx, unsigned target) {
    unsigned l;
    asm volatile("mov.u32 %0, %%laneid;" : "=r"(l));
    const unsigned* c = &g_hint[(l & 7) * 32 + idx];
    int it = 0;
    while (__any_sync(0xffffffffu, (int)(ld_poll32(c) - target) < 0)) { if (++it > SPIN_LIMIT) TRAP(); }
}
__device__ __forceinline__ void mbar_init(uint32_t bar, uint32_t cnt) { asm volatile("mbarrier.init.shared::cta.b64 [%0], %1;\n" ::"r"(bar), "r"(cnt) : "memory"); }
__device__ __forceinline__ void mbar_expect(uint32_t bar, uint32_t bytes) {
    asm volatile("mbarrier.arrive.expect_tx.shared::cta.b64 _, [%0], %1;\n" ::"r"(bar), "r"(bytes) : "memory");
}
__device__ __forceinline__ void mbar_arrive(uint32_t bar) { asm volatile("mbarrier.arrive.shared::cta.b64 _, [%0];\n" ::"r"(bar) : "memory"); }
__device__ __forceinline__ void mbar_wait_cluster(uint32_t bar) {
    asm volatile(
        "{\n.reg .pred p;\n"
        "W_%=:\n"
        "mbarrier.try_wait.parity.acquire.cluster.shared::cta.b64 p, [%0], 0;\n"
        "@!p bra W_%=;\n}\n" ::"r"(bar) : "memory");
}
__device__ __forceinline__ void mbar_wait(uint32_t bar) {
    asm volatile(
        "{\n.reg .pred p;\n"
        "W_%=:\n"
        "mbarrier.try_wait.parity.shared::cta.b64 p, [%0], 0;\n"
        "@!p bra W_%=;\n}\n" ::"r"(bar) : "memory");
}
__device__ __forceinline__ void mbar_wait_parity(uint32_t bar, uint32_t par) {
    asm volatile(
        "{\n.reg .pred p;\n"
        "W_%=:\n"
        "mbarrier.try_wait.parity.shared::cta.b64 p, [%0], %1;\n"
        "@!p bra W_%=;\n}\n" ::"r"(bar), "r"(par) : "memory");
}
__device__ __forceinline__ bool mbar_test(uint32_t bar) {
    uint32_t r;
    asm volatile("{\n.reg .pred p;\nmbarrier.test_wait.parity.shared::cta.b64 p, [%1], 0;\nselp.u32 %0, 1, 0, p;\n}\n" : "=r"(r) : "r"(bar) : "memory");
    return __any_sync(0xffffffffu, r);
}
__device__ __forceinline__ void bulk_g2s(uint32_t dst, const void* src, uint32_t bytes, uint32_t bar) {
    asm volatile("cp.async.bulk.shared::cluster.global.mbarrier::complete_tx::bytes [%0], [%1], %2, [%3];\n" ::"r"(dst), "l"(src), "r"(bytes), "r"(bar) : "memory");
}
__device__ __forceinline__ void bulk_s2g(void* dst, uint32_t src, uint32_t bytes) {
    asm volatile("cp.async.bulk.global.shared::cta.bulk_group [%0], [%1], %2;\ncp.async.bulk.commit_group;\n" ::"l"(dst), "r"(src), "r"(bytes) : "memory");
}
__device__ __forceinline__ void tma_2d(uint32_t dst, const CUtensorMap* tm, int c0, int c1, uint32_t bar) {
    asm volatile("cp.async.bulk.tensor.2d.shared::cluster.global.mbarrier::complete_tx::bytes [%0], [%1, {%3, %4}], [%2];\n"
                 ::"r"(dst), "l"(tm), "r"(bar), "r"(c0), "r"(c1) : "memory");
}
__device__ __forceinline__ void tma_3d(uint32_t dst, const CUtensorMap* tm, int c0, int c1, int c2, uint32_t bar) {
    asm volatile("cp.async.bulk.tensor.3d.shared::cluster.global.mbarrier::complete_tx::bytes [%0], [%1, {%3, %4, %5}], [%2];\n"
                 ::"r"(dst), "l"(tm), "r"(bar), "r"(c0), "r"(c1), "r"(c2) : "memory");
}
__device__ __forceinline__ void tma_3d_mc(uint32_t dst, const CUtensorMap* tm, int c0, int c1, int c2, uint32_t bar) {
    asm volatile("cp.async.bulk.tensor.3d.shared::cluster.global.mbarrier::complete_tx::bytes.multicast::cluster [%0], [%1, {%3, %4, %5}], [%2], %6;\n"
                 ::"r"(dst), "l"(tm), "r"(bar), "r"(c0), "r"(c1), "r"(c2), "h"((unsigned short)3) : "memory");
}
__device__ __forceinline__ void tma_st_3d(const CUtensorMap* tm, uint32_t src, int c0, int c1, int c2) {
    asm volatile("cp.async.bulk.tensor.3d.global.shared::cta.bulk_group [%0, {%2, %3, %4}], [%1];\ncp.async.bulk.commit_group;\n"
                 ::"l"(tm), "r"(src), "r"(c0), "r"(c1), "r"(c2) : "memory");
}
__device__ __forceinline__ void l2_prefetch(const void* src, uint32_t bytes) {
    asm volatile("cp.async.bulk.prefetch.L2.global [%0], %1;\n" ::"l"(src), "r"(bytes) : "memory");
}
__device__ __forceinline__ bool elect_one() {
    uint32_t r;
    asm volatile("{\n.reg .pred p;\nelect.sync _|p, 0xffffffff;\nselp.u32 %0, 1, 0, p;\n}\n" : "=r"(r));
    return r;
}
__device__ __forceinline__ void fence_async() { asm volatile("fence.proxy.async.shared::cta;\n" ::: "memory"); }

__device__ __forceinline__ float2 cmul(float2 a, float2 b) {
    return make_float2(fmaf(a.x, b.x, -a.y * b.y), fmaf(a.x, b.y, a.y * b.x));
}
__device__ __forceinline__ float2 csq(float2 a) {
    float p = a.x * a.y;
    return make_float2(fmaf(a.x, a.x, -a.y * a.y), p + p);
}
__device__ __forceinline__ float2 cexp_e(float lr2, float rh, float rl, float e) {
    float m;
    asm("ex2.approx.ftz.f32 %0, %1;\n" : "=f"(m) : "f"(lr2 * e));
    const float a = rh * e;
    const float r = fmaf(rl, e, a - rintf(a)) * 6.283185307179586f;
    return make_float2(m * __cosf(r), m * __sinf(r));
}
__device__ __forceinline__ float rcp_approx(float x) { float r; asm("rcp.approx.ftz.f32 %0, %1;\n" : "=f"(r) : "f"(x)); return r; }
__device__ __forceinline__ float ex2_approx(float x) { float r; asm("ex2.approx.ftz.f32 %0, %1;\n" : "=f"(r) : "f"(x)); return r; }
__device__ __forceinline__ float sqrt_approx(float x) { float r; asm("sqrt.approx.ftz.f32 %0, %1;\n" : "=f"(r) : "f"(x)); return r; }

__device__ __forceinline__ void wg_fence() { asm volatile("wgmma.fence.sync.aligned;\n" ::: "memory"); }
__device__ __forceinline__ void wg_commit() { asm volatile("wgmma.commit_group.sync.aligned;\n" ::: "memory"); }
__device__ __forceinline__ void wg_wait0() { asm volatile("wgmma.wait_group.sync.aligned 0;\n" ::: "memory"); }
template <int T0, int NT> __device__ __forceinline__ void wg_h(uint32_t (&acc)[32], const uint32_t (&a)[4], uint64_t desc);
template <> __device__ __forceinline__ void wg_h<0, 16>(uint32_t (&acc)[32], const uint32_t (&a)[4], uint64_t desc) {
    asm volatile("wgmma.mma_async.sync.aligned.m64n128k16.f16.f16.f16 {%0,%1,%2,%3,%4,%5,%6,%7,%8,%9,%10,%11,%12,%13,%14,%15,%16,%17,%18,%19,%20,%21,%22,%23,%24,%25,%26,%27,%28,%29,%30,%31}, {%32,%33,%34,%35}, %36, 1, 1, 1, 0;\n"
                 : "+r"(acc[0]), "+r"(acc[1]), "+r"(acc[2]), "+r"(acc[3]), "+r"(acc[4]), "+r"(acc[5]), "+r"(acc[6]), "+r"(acc[7]), "+r"(acc[8]), "+r"(acc[9]), "+r"(acc[10]), "+r"(acc[11]), "+r"(acc[12]), "+r"(acc[13]), "+r"(acc[14]), "+r"(acc[15]), "+r"(acc[16]), "+r"(acc[17]), "+r"(acc[18]), "+r"(acc[19]), "+r"(acc[20]), "+r"(acc[21]), "+r"(acc[22]), "+r"(acc[23]), "+r"(acc[24]), "+r"(acc[25]), "+r"(acc[26]), "+r"(acc[27]), "+r"(acc[28]), "+r"(acc[29]), "+r"(acc[30]), "+r"(acc[31])
                 : "r"(a[0]), "r"(a[1]), "r"(a[2]), "r"(a[3]), "l"(desc));
}
template <> __device__ __forceinline__ void wg_h<4, 4>(uint32_t (&acc)[32], const uint32_t (&a)[4], uint64_t desc) {
    asm volatile("wgmma.mma_async.sync.aligned.m64n32k16.f16.f16.f16 {%0,%1,%2,%3,%4,%5,%6,%7}, {%8,%9,%10,%11}, %12, 1, 1, 1, 0;\n"
                 : "+r"(acc[8]), "+r"(acc[9]), "+r"(acc[10]), "+r"(acc[11]), "+r"(acc[12]), "+r"(acc[13]), "+r"(acc[14]), "+r"(acc[15])
                 : "r"(a[0]), "r"(a[1]), "r"(a[2]), "r"(a[3]), "l"(desc));
}
template <> __device__ __forceinline__ void wg_h<8, 4>(uint32_t (&acc)[32], const uint32_t (&a)[4], uint64_t desc) {
    asm volatile("wgmma.mma_async.sync.aligned.m64n32k16.f16.f16.f16 {%0,%1,%2,%3,%4,%5,%6,%7}, {%8,%9,%10,%11}, %12, 1, 1, 1, 0;\n"
                 : "+r"(acc[16]), "+r"(acc[17]), "+r"(acc[18]), "+r"(acc[19]), "+r"(acc[20]), "+r"(acc[21]), "+r"(acc[22]), "+r"(acc[23])
                 : "r"(a[0]), "r"(a[1]), "r"(a[2]), "r"(a[3]), "l"(desc));
}
template <> __device__ __forceinline__ void wg_h<12, 4>(uint32_t (&acc)[32], const uint32_t (&a)[4], uint64_t desc) {
    asm volatile("wgmma.mma_async.sync.aligned.m64n32k16.f16.f16.f16 {%0,%1,%2,%3,%4,%5,%6,%7}, {%8,%9,%10,%11}, %12, 1, 1, 1, 0;\n"
                 : "+r"(acc[24]), "+r"(acc[25]), "+r"(acc[26]), "+r"(acc[27]), "+r"(acc[28]), "+r"(acc[29]), "+r"(acc[30]), "+r"(acc[31])
                 : "r"(a[0]), "r"(a[1]), "r"(a[2]), "r"(a[3]), "l"(desc));
}
template <> __device__ __forceinline__ void wg_h<0, 8>(uint32_t (&acc)[32], const uint32_t (&a)[4], uint64_t desc) {
    asm volatile("wgmma.mma_async.sync.aligned.m64n64k16.f16.f16.f16 {%0,%1,%2,%3,%4,%5,%6,%7,%8,%9,%10,%11,%12,%13,%14,%15}, {%16,%17,%18,%19}, %20, 1, 1, 1, 0;\n"
                 : "+r"(acc[0]), "+r"(acc[1]), "+r"(acc[2]), "+r"(acc[3]), "+r"(acc[4]), "+r"(acc[5]), "+r"(acc[6]), "+r"(acc[7]), "+r"(acc[8]), "+r"(acc[9]), "+r"(acc[10]), "+r"(acc[11]), "+r"(acc[12]), "+r"(acc[13]), "+r"(acc[14]), "+r"(acc[15])
                 : "r"(a[0]), "r"(a[1]), "r"(a[2]), "r"(a[3]), "l"(desc));
}
template <> __device__ __forceinline__ void wg_h<4, 12>(uint32_t (&acc)[32], const uint32_t (&a)[4], uint64_t desc) {
    asm volatile("wgmma.mma_async.sync.aligned.m64n96k16.f16.f16.f16 {%0,%1,%2,%3,%4,%5,%6,%7,%8,%9,%10,%11,%12,%13,%14,%15,%16,%17,%18,%19,%20,%21,%22,%23}, {%24,%25,%26,%27}, %28, 1, 1, 1, 0;\n"
                 : "+r"(acc[8]), "+r"(acc[9]), "+r"(acc[10]), "+r"(acc[11]), "+r"(acc[12]), "+r"(acc[13]), "+r"(acc[14]), "+r"(acc[15]), "+r"(acc[16]), "+r"(acc[17]), "+r"(acc[18]), "+r"(acc[19]), "+r"(acc[20]), "+r"(acc[21]), "+r"(acc[22]), "+r"(acc[23]), "+r"(acc[24]), "+r"(acc[25]), "+r"(acc[26]), "+r"(acc[27]), "+r"(acc[28]), "+r"(acc[29]), "+r"(acc[30]), "+r"(acc[31])
                 : "r"(a[0]), "r"(a[1]), "r"(a[2]), "r"(a[3]), "l"(desc));
}

#define PBYTES 4608
#define HINTW 10
#define WAS 0x0005
#define WA0 (WAS >> 12)
#define WA1 ((WAS >> 8) & 15)
#define WA2 ((WAS >> 4) & 15)
#define WA3 (WAS & 15)
#define WDAT 1
#define PAUSE 2
#define PCNT (32 + ((PAUSE & 1) ? 288 : 0) + ((PAUSE & 6) ? 320 : 64))
#define LNAT 2
#define UW 8
#define FINAT 3
#define UAT 2
#define HK 9
#define TOKEN_OF(g) (16 * ((g) & 1) + ((g) >> 2) + 2 * ((g) & 2))
#define HI2(a, b) (pack_f16_rz(__uint_as_float(a), __uint_as_float(b)) & 0xfff8fff8u)
struct Params {
    const bf16 *x, *lar, *aim, *cre, *cim, *ldt, *dsk;
    Scratch* s;
    const bf16* wr;
    bf16* out;
};

template <int NK>
__device__ __forceinline__ void ln_partial(const uint32_t (&H)[2][NK], const uint32_t (&bw)[NK], uint32_t lp, int warp, int g, int t) {
    float cs[4] = {0.f, 0.f, 0.f, 0.f}, cl[4] = {0.f, 0.f, 0.f, 0.f}, ch[4] = {0.f, 0.f, 0.f, 0.f};
#pragma unroll
    for (int k = 0; k < NK; k += 2) {
        uint32_t a0, a1, a2, a3;
        asm volatile("prmt.b32 %0, %4, %4, %8;\nprmt.b32 %1, %5, %5, %8;\nprmt.b32 %2, %6, %6, %8;\nprmt.b32 %3, %7, %7, %8;\n"
                     : "=r"(a0), "=r"(a1), "=r"(a2), "=r"(a3) : "r"(H[0][k]), "r"(H[1][k]), "r"(H[0][k + 1]), "r"(H[1][k + 1]), "r"(0x3210u + (warp >> 8)));
        mma_bf16(cl, a0, a1, a2, a3, H[0][k], H[0][k + 1]);
        mma_bf16(ch, a0, a1, a2, a3, H[1][k], H[1][k + 1]);
        mma_bf16(cs, a0, a1, a2, a3, bw[k], bw[k + 1]);
    }
    const uint32_t a = lp + (g * 20 + warp) * 4;
    if (t == 0) {
        stsf(a, cs[1]); stsf(a + 8 * 80, cs[3]);
    }
    if (t == (g >> 1)) { stsf(a + 16 * 80, (g & 1) ? cl[1] : cl[0]); stsf(a + 24 * 80, (g & 1) ? ch[3] : ch[2]); }
}
__device__ __forceinline__ float sum18(uint32_t a) {
    const uint4 p = lds128(a), q = lds128(a + 16), r = lds128(a + 32), s = lds128(a + 48);
    const uint2 u = lds64(a + 64);
#define F(x) __uint_as_float(x)
    return (((F(p.x) + F(p.y)) + (F(p.z) + F(p.w))) + ((F(q.x) + F(q.y)) + (F(q.z) + F(q.w)))) +
           (((F(r.x) + F(r.y)) + (F(r.z) + F(r.w))) + ((F(s.x) + F(s.y)) + (F(s.z) + F(s.w))) + (F(u.x) + F(u.y)));
#undef F
}
__device__ __forceinline__ float sum9(uint32_t a) {
    const uint4 p = lds128(a), q = lds128(a + 16);
#define F(x) __uint_as_float(x)
    return (((F(p.x) + F(p.y)) + (F(p.z) + F(p.w))) + ((F(q.x) + F(q.y)) + (F(q.z) + F(q.w)))) + ldsf(a + 32);
#undef F
}
template <int N>
__device__ __forceinline__ void ln_finish(uint32_t lp, int lane, float& mb, float& rc) {
    const float v = N == 9 ? sum9(lp + lane * 80) : sum18(lp + lane * 80);
    const float o = __shfl_xor_sync(0xffffffffu, v, 16);
    const float m0 = v * (1.0f / 576.0f);
    const float mean = fmaf(fmaf(-m0, 576.0f, v), 1.0f / 576.0f, m0);
    const float var = fmaxf(fmaf(-mean, mean, o * (1.0f / 576.0f)), 0.f);
    mb = rbf(mean);
    rc = rcp_approx(rbf(sqrt_approx(rbf(rbf(var) + 1e-5f))));
}
__device__ __forceinline__ uint32_t ln_apply(uint32_t w, const uint2& st) {
    uint32_t r;
    asm("{\n.reg .b16 m, t, h, l;\n.reg .b32 mm, hh, ll, d, e;\nmov.b32 {m, t}, %2;\nmov.b32 {h, l}, %3;\nmov.b32 mm, {m, m};\nmov.b32 hh, {h, h};\nmov.b32 ll, {l, l};\n"
        "sub.rn.bf16x2 d, %1, mm;\nmul.rn.bf16x2 e, d, ll;\nfma.rn.bf16x2 %0, d, hh, e;\n}\n" : "=r"(r) : "r"(w), "r"(st.x), "r"(st.y));
    return r;
}
__device__ __forceinline__ void stat_store(uint32_t a, float mb, float rc, uint32_t extra) {
    const float rh = rbf(rc);
    sts64(a, (__float_as_uint(mb) >> 16) | (extra << 16), pack_bf16(rh, rc - rh));
}

__device__ __forceinline__ void hcmul(uint32_t re, uint32_t im, uint32_t z, uint32_t& ore, uint32_t& oim) {
    asm("{\n.reg .b16 x, y;\n.reg .b32 xx, yy, ny, a, b;\nmov.b32 {x, y}, %4;\nmov.b32 xx, {x, x};\nmov.b32 yy, {y, y};\nneg.f16x2 ny, yy;\n"
        "mul.rn.f16x2 a, %2, xx;\nfma.rn.f16x2 %0, %3, ny, a;\nmul.rn.f16x2 b, %3, xx;\nfma.rn.f16x2 %1, %2, yy, b;\n}\n" : "=&r"(ore), "=r"(oim) : "r"(re), "r"(im), "r"(z));
}
__device__ __forceinline__ void hcmul(uint32_t re, uint32_t im, uint32_t zx, uint32_t zy, uint32_t& ore, uint32_t& oim) {
    asm("{\n.reg .b32 ny, a, b;\nneg.f16x2 ny, %5;\n"
        "mul.rn.f16x2 a, %2, %4;\nfma.rn.f16x2 %0, %3, ny, a;\nmul.rn.f16x2 b, %3, %4;\nfma.rn.f16x2 %1, %2, %5, b;\n}\n" : "=&r"(ore), "=r"(oim) : "r"(re), "r"(im), "r"(zx), "r"(zy));
}

struct KGen {
    uint32_t Af[4][4];
    float2 z1, z8, z64, z128, T[9];
    uint32_t zw;
};
__device__ __forceinline__ void kgen_setup(KGen& k, uint32_t pa, float dt) {
    const float A = rbf(expf(bf_lo(pa)));
    const float lr2 = -(A * dt) * 1.4426950408889634f;
    const float li = bf_hi(pa) * dt;
    const float rh = li * 0.15915494309189535f;
    const float rl = fmaf(li, 6.4206382986e-9f, fmaf(li, 0.15915494309189535f, -rh));
    k.z1 = cexp_e(lr2, rh, rl, 1.0f);
    k.z8 = cexp_e(lr2, rh, rl, 8.0f);
    k.z64 = cexp_e(lr2, rh, rl, 64.0f);
}
__device__ __forceinline__ void kgen_rows(KGen& k, uint32_t tb, int lane) {
    const float2 z8 = k.z8, z64 = k.z64;
    const uint32_t row = tb + lane * TBP;
    k.z128 = csq(z64);
    const float2 z16 = csq(z8), z32 = csq(z16), z48 = cmul(z32, z16), z80 = cmul(z64, z16), z96 = cmul(z64, z32), z112 = cmul(z64, z48);
    uint32_t re[4], im[4], a[4], b[4];
    re[0] = pack_f16(1.0f, z16.x); im[0] = pack_f16(0.0f, z16.y);
    re[1] = pack_f16(z32.x, z48.x); im[1] = pack_f16(z32.y, z48.y);
    re[2] = pack_f16(z64.x, z80.x); im[2] = pack_f16(z64.y, z80.y);
    re[3] = pack_f16(z96.x, z112.x); im[3] = pack_f16(z96.y, z112.y);
    sts128(row, re[0], re[1], re[2], re[3]);
    sts128(row + 32, im[0], im[1], im[2], im[3]);
    const uint32_t zz = pack_f16(z8.x, z8.y);
#pragma unroll
    for (int j = 0; j < 4; j++) hcmul(re[j], im[j], zz, a[j], b[j]);
    sts128(row + 16, a[0], a[1], a[2], a[3]);
    sts128(row + 48, b[0], b[1], b[2], b[3]);
    __syncwarp();
    const int mi = lane >> 3;
    const uint32_t ad = tb + (lane & 7) * TBP + mi * 16;
#pragma unroll
    for (int ks = 0; ks < 4; ks++) ldsm_x4_t(k.Af[ks][0], k.Af[ks][1], k.Af[ks][2], k.Af[ks][3], ad + ks * 8 * TBP);
}
__device__ __forceinline__ void kgen_chain(KGen& k, uint32_t pc, float cs) {
    k.T[0] = make_float2(bf_lo(pc) * cs, -bf_hi(pc) * cs);
    const float2 y1 = make_float2(k.z1.x, -k.z1.y);
#pragma unroll
    for (int c = 1; c < 8; c++) k.T[c] = cmul(k.T[c - 1], y1);
    k.T[8] = cmul(k.T[0], make_float2(k.z8.x, -k.z8.y));
}
__device__ __forceinline__ void kgen_cols(KGen& k, uint32_t tb, int lane) {
    const uint32_t row = tb + lane * TBP;
    const float2 (&T)[9] = k.T;
    const uint32_t zv = pack_f16(k.z128.x, k.z128.y), zo = __shfl_xor_sync(0xffffffffu, zv, 1);
    k.zw = (lane & 1) ? __byte_perm(zo, zv, 0x7632) : __byte_perm(zv, zo, 0x5410);
    const float2 y256 = csq(make_float2(k.z128.x, -k.z128.y)), y512 = csq(y256), y768 = cmul(y512, y256), y1024 = csq(y512);
    const float2 c1032 = cmul(T[8], y1024);
    const uint32_t r04 = pack_f16(T[0].x, T[4].x), i04 = pack_f16(T[0].y, T[4].y), r26 = pack_f16(T[2].x, T[6].x), i26 = pack_f16(T[2].y, T[6].y);
    const uint32_t r48 = pack_f16(T[4].x, T[8].x), i48 = pack_f16(T[4].y, T[8].y);
    __syncwarp();
    sts128(row, r04, pack_f16(T[1].x, T[5].x), r26, pack_f16(T[3].x, T[7].x));
    sts128(row + 16, i04, pack_f16(T[1].y, T[5].y), i26, pack_f16(T[3].y, T[7].y));
    uint32_t a[4], b[4];
    {
        const uint32_t zz = pack_f16(y256.x, y256.y);
        hcmul(r04, i04, zz, a[0], b[0]);
        hcmul(r26, i26, zz, a[2], b[2]);
        hcmul(r48, i48, zz, a[3], b[3]);
    }
    sts128(row + 32, a[0], a[0], a[2], a[3]);
    sts128(row + 48, b[0], b[0], b[2], b[3]);
    {
        hcmul(r48, i48, pack_f16(y512.x, y512.y), a[0], b[0]);
        hcmul(r48, i48, pack_f16(y768.x, y768.y), a[1], b[1]);
        const uint32_t zz = pack_f16(c1032.x, c1032.y);
        hcmul(pack_f16(1.0f, y256.x), pack_f16(0.0f, y256.y), zz, a[2], b[2]);
        hcmul(pack_f16(y512.x, y768.x), pack_f16(y512.y, y768.y), zz, a[3], b[3]);
    }
    sts128(row + 64, a[0], a[1], a[2], a[3]);
    sts128(row + 80, b[0], b[1], b[2], b[3]);
}
__device__ __forceinline__ void kgen_mma(const KGen& k, uint32_t tb, int lane) {
    const int t = lane & 3;
    const uint32_t zw = k.zw;
    uint32_t zx[4], zy[4];
#pragma unroll
    for (int ks = 0; ks < 4; ks++) { zx[ks] = __shfl_sync(0xffffffffu, zw, 8 * ks + 2 * t); zy[ks] = __shfl_sync(0xffffffffu, zw, 8 * ks + 2 * t + 1); }
    __syncwarp();
    float acc[2][3][4];
#pragma unroll
    for (int i = 0; i < 6; i++)
#pragma unroll
        for (int j = 0; j < 4; j++) acc[i / 3][i % 3][j] = 0.f;
    {
        const int mi = lane >> 3;
        const uint32_t bd = tb + ((lane & 7) + 8 * (mi >> 1)) * TBP + (mi & 1) * 16;
#pragma unroll
        for (int kp = 0; kp < 2; kp++) {
            uint32_t b[3][4];
#pragma unroll
            for (int j = 0; j < 3; j++) ldsm_x4_t(b[j][0], b[j][1], b[j][2], b[j][3], bd + kp * 16 * TBP + j * 32);
#pragma unroll
            for (int h = 0; h < 2; h++) {
                const int ks = 2 * kp + h;
                uint32_t d[4];
                hcmul(k.Af[ks][0], k.Af[ks][2], zx[ks], zy[ks], d[0], d[2]);
                hcmul(k.Af[ks][1], k.Af[ks][3], zx[ks], zy[ks], d[1], d[3]);
#pragma unroll
                for (int j = 0; j < 3; j++) {
                    mma_f16(acc[0][j], k.Af[ks][0], k.Af[ks][1], k.Af[ks][2], k.Af[ks][3], b[j][2 * h], b[j][2 * h + 1]);
                    mma_f16(acc[1][j], d[0], d[1], d[2], d[3], b[j][2 * h], b[j][2 * h + 1]);
                }
            }
        }
    }
    __syncwarp();
#pragma unroll
    for (int h = 0; h < 2; h++) {
        sts64(tb + h * 256 + lane * 8, pack_f16(acc[h][0][0], acc[h][0][1]), pack_f16(acc[h][0][2], acc[h][0][3]));
        sts64(tb + 512 + h * 256 + lane * 8, pack_f16(acc[h][1][0], acc[h][1][1]), pack_f16(acc[h][1][2], acc[h][1][3]));
        sts32(tb + 1024 + h * 256 + lane * 4, pack_f16(acc[h][2][0], t < 2 ? acc[h][2][1] : acc[h][2][2]));
        sts32(tb + 1152 + h * 256 + lane * 4, pack_f16(t < 2 ? acc[h][2][2] : acc[h][2][1], acc[h][2][3]));
    }
}
__device__ __forceinline__ uint32_t table_buf(uint32_t sb, int warp) { return sb + SM_TB + warp * TBW; }

__device__ __forceinline__ void kgen_combine(uint32_t sb, int warp, int lane, uint32_t kw, uint32_t ao) {
    const int wq = warp & 3;
    const uint32_t a = table_buf(sb, warp & ~3) + wq * 256 + lane * 8, c = table_buf(sb, warp & ~3) + 1024 + wq * 128 + lane * 4;
    const int t = lane & 3;
    const uint32_t o0 = (t < 2 ? KW_T2 + KW_KH + 16 + t * 256 - (wq & 1) * KW_KH : KW_T3 + 16 - 1024 + t * 512 + (wq & 1) * 256) + (lane >> 2) * 16;
    const uint4 o = make_uint4(o0 + t * 36, o0 + (t ^ 1) * 36, o0 + (t ^ 2) * 36, o0 + (t ^ 3) * 36);
    const uint2 u = lds64(a), v = lds64(a + TBW), w = lds64(a + 2 * TBW), x = lds64(a + 3 * TBW);
    const uint32_t kt = hadd2(hadd2(lds32(c), lds32(c + TBW)), hadd2(lds32(c + 2 * TBW), lds32(c + 3 * TBW)));
    const uint32_t k23 = hadd2(hadd2(u.y, v.y), hadd2(w.y, x.y));
    sts64(kw + wq * 64 + ao, hadd2(hadd2(u.x, v.x), hadd2(w.x, x.x)), k23);
    const uint32_t d = kw + (wq >> 1) * 128;
    const uint32_t kh = hmul2(kt, 0x38003800u);
    sts32(d + o.x, kh); sts32(d + o.y, kh); sts32(d + o.z, kh); sts32(d + o.w, kh);
    if (wq == 3) {
        if (lane == 31) { sts32(kw + 264, k23 >> 16); sts32(kw + 288 + 264, k23 >> 16); sts32(kw + 576 + 264, k23 >> 16); }
        if (lane == 29) { sts32(kw + 864 + 280, kt >> 16); sts32(kw + 280, kt & 0xffff0000u); }
    }
}

__device__ __forceinline__ int c_exponent(const uint2& r, const uint2& i) {
    uint32_t mx = __vmaxu2(__vmaxu2(r.x & 0x7fff7fffu, r.y & 0x7fff7fffu), __vmaxu2(i.x & 0x7fff7fffu, i.y & 0x7fff7fffu));
    mx = __reduce_max_sync(0xffffffffu, max(mx & 0xffffu, mx >> 16));
    return min(max((int)(mx >> 7), 4), 240);
}

__device__ __forceinline__ int warp_v() { int l; asm volatile("mov.u32 %0, %%tid.x;" : "=r"(l)); return __shfl_sync(0xffffffffu, l >> 5, 0); }
__device__ __forceinline__ int lane_v() { int l; asm volatile("mov.u32 %0, %%laneid;" : "=r"(l)); return l; }
__device__ __forceinline__ uint32_t prmt(uint32_t a, uint32_t b, uint32_t s) { uint32_t d; asm("prmt.b32 %0, %1, %2, %3;\n" : "=r"(d) : "r"(a), "r"(b), "r"(s)); return d; }
__device__ __forceinline__ uint32_t prmt_v(uint32_t a, uint32_t b, uint32_t s) { uint32_t d; asm volatile("prmt.b32 %0, %1, %2, %3;\n" : "=r"(d) : "r"(a), "r"(b), "r"(s)); return d; }
__device__ __forceinline__ void mmah16(uint32_t& d0, uint32_t& d1, uint32_t a0, uint32_t a1, uint32_t a2, uint32_t a3, uint32_t b0, uint32_t b1, uint32_t c0, uint32_t c1) {
    asm volatile("mma.sync.aligned.m16n8k16.row.col.f16.f16.f16.f16 {%0,%1}, {%2,%3,%4,%5}, {%6,%7}, {%8,%9};\n"
                 : "=r"(d0), "=r"(d1) : "r"(a0), "r"(a1), "r"(a2), "r"(a3), "r"(b0), "r"(b1), "r"(c0), "r"(c1));
}
__device__ __forceinline__ void mmah8(uint32_t& d0, uint32_t& d1, uint32_t a0, uint32_t a1, uint32_t b0, uint32_t c0, uint32_t c1) {
    asm volatile("mma.sync.aligned.m16n8k8.row.col.f16.f16.f16.f16 {%0,%1}, {%2,%3}, {%4}, {%5,%6};\n"
                 : "=r"(d0), "=r"(d1) : "r"(a0), "r"(a1), "r"(b0), "r"(c0), "r"(c1));
}
template <int A = 8, int B = 32>
__device__ __forceinline__ void conv_rename(uint32_t (&acc)[32]) {
#pragma unroll
    for (int i = A; i < B; i++) { uint32_t v; asm volatile("mov.b32 %0, %1;\n" : "=r"(v) : "r"(acc[i])); acc[i] = v; }
}
__host__ __device__ constexpr uint32_t band_bits(int hw, int sh) {
    uint32_t c = 0;
    for (int s = 0; s <= 10; s++)
        for (int e = 0; e < 2; e++) {
            const int v = s - 3 + sh - 4 * e;
            if (v <= hw && v >= -hw) c |= 1u << (14 + 16 * e - s);
        }
    return c;
}
template <int HW, int SH, int J> __device__ __forceinline__ uint32_t band(uint32_t p2) {
    uint32_t d;
    asm volatile("{\n.reg .b32 t;\nmul.lo.u32 t, %1, %2;\nand.b32 %0, t, 0x40004000;\n}\n" : "=r"(d) : "r"(p2), "n"(band_bits(HW, SH) | J));
    return d;
}
template <int H0, int SH> __device__ __forceinline__ void band_pair(uint4& l, uint4& u, uint32_t p2) {
    l = make_uint4(band<H0, 8, 1>(p2), band<H0 - 1, SH + 8, 2>(p2), band<H0, 0, 1>(p2), band<H0 - 1, SH, 1>(p2));
    u = make_uint4(band<H0, 0, 2>(p2), band<H0 - 1, SH, 2>(p2), band<H0, -8, 1>(p2), band<H0 - 1, SH - 8, 1>(p2));
}
__device__ __forceinline__ void run_sums(uint32_t (&G)[3][2], const uint32_t (&c)[5], const uint4& l, const uint4& u) {
    mmah8(G[0][0], G[0][1], l.x, l.y, c[0], 0u, 0u);
    mmah8(G[1][0], G[1][1], u.z, u.w, c[3], 0u, 0u);
    mmah8(G[2][0], G[2][1], l.x, l.y, c[2], 0u, 0u);
    mmah16(G[0][0], G[0][1], u.x, u.y, u.z, u.w, c[1], c[2], G[0][0], G[0][1]);
    mmah16(G[1][0], G[1][1], l.x, l.y, l.z, l.w, c[1], c[2], G[1][0], G[1][1]);
    mmah16(G[2][0], G[2][1], u.x, u.y, u.z, u.w, c[3], c[4], G[2][0], G[2][1]);
}
__device__ __forceinline__ float h_lo(uint32_t w) { return __half2float(__ushort_as_half((unsigned short)(w & 0xffffu))); }
__device__ __forceinline__ float h_hi(uint32_t w) { return __half2float(__ushort_as_half((unsigned short)(w >> 16))); }
__device__ __forceinline__ uint64_t smem_desc(uint32_t sb, uint32_t o16, uint32_t lbo) {
    uint64_t d;
    asm("mov.b64 %0, {%1, %2};" : "=l"(d) : "r"(((sb & 0x3FFFF) >> 4) + o16 + (lbo << 12)), "r"(8));
    return d;
}
template <int I> struct IC { static constexpr int value = I; };

struct Conv {
    uint32_t u[3][5];
    uint32_t q2[3][2][4];
    uint32_t q3[2][4];
    uint32_t r[18];
};
struct ConvPre {
    uint32_t a[5], b[5];
    uint32_t t[4];
};
__device__ __forceinline__ void conv_pre(ConvPre& e, uint32_t ka, uint32_t ks, uint32_t sel) {
    const uint4 r = lds128(ka + 256), s = lds128(ka + 272);
    ldsm_x4(e.t[0], e.t[1], e.t[2], e.t[3], ks);
    const uint32_t sw = sel ^ 0x4444u;
    e.a[0] = prmt(r.y, r.z, sel); e.a[1] = prmt(r.w, r.z, sw); e.a[2] = prmt(r.x, r.y, sel); e.a[3] = prmt(r.z, r.y, sw); e.a[4] = prmt(r.z, r.w, sel);
    e.b[0] = prmt(s.y, s.z, sel); e.b[1] = prmt(s.w, s.z, sw); e.b[2] = prmt(s.x, s.y, sel); e.b[3] = prmt(s.z, s.y, sw); e.b[4] = prmt(s.z, s.w, sel);
}
__device__ __forceinline__ void conv_sums(Conv& c, uint32_t (&acc)[32], const ConvPre& e, uint32_t a0, uint32_t a1, const uint4 (&bd)[4], uint32_t ka, uint32_t sel, int wq, uint32_t zr) {
    {
        uint32_t x;
        ldsm_x4(c.u[0][1], c.u[0][2], c.u[0][3], c.u[0][4], a1);
        ldsm_x4(c.u[0][0], c.u[1][0], c.u[2][0], x, a0);
#pragma unroll
        for (int q = 1; q < 3; q++) ldsm_x4(c.u[q][1], c.u[q][2], c.u[q][3], c.u[q][4], a1 + q * 512);
    }
#pragma unroll
    for (int i = 0; i < 32; i++) acc[i] = 0u;
    uint32_t G[3][2];
#pragma unroll
    for (int q = 0; q < 3; q++) {
        mmah8(acc[8 * q + 8], acc[8 * q + 9], e.a[4], 0u, c.u[q][2], acc[8 * q + 8], acc[8 * q + 9]);
        mmah16(acc[8 * q + 8], acc[8 * q + 9], e.a[0], e.a[1], e.a[2], e.a[3], c.u[q][3], c.u[q][4], acc[8 * q + 8], acc[8 * q + 9]);
        if (q < 2) {
            mmah8(acc[8 * q + 16], acc[8 * q + 17], e.b[4], 0u, c.u[q][2], 0u, 0u);
            mmah16(acc[8 * q + 16], acc[8 * q + 17], e.b[0], e.b[1], e.b[2], e.b[3], c.u[q][3], c.u[q][4], acc[8 * q + 16], acc[8 * q + 17]);
            run_sums(G, c.u[q], bd[2], bd[3]);
            c.q3[q][0] = prmt(G[1][1], G[0][0], 0x7632u); c.q3[q][1] = prmt(G[2][1], G[1][0], 0x7632u);
            c.q3[q][2] = prmt(G[1][1], G[0][0], 0x5410u); c.q3[q][3] = prmt(G[2][1], G[1][0], 0x5410u);
        }
    }
    {
        const uint32_t a = (ka + wq * 64) ^ (((acc[8] | acc[16] | acc[24]) | (c.q3[0][0] | c.q3[0][1]) | (c.q3[1][0] | c.q3[1][1])) & zr);
#pragma unroll
        for (int i = 0; i < 4; i++) { const uint4 v = lds128(a + i * 16); c.r[4 * i] = v.x; c.r[4 * i + 1] = v.y; c.r[4 * i + 2] = v.z; c.r[4 * i + 3] = v.w; }
        const uint2 v = lds64(a + 64);
        c.r[16] = v.x; c.r[17] = v.y;
    }
#pragma unroll
    for (int q = 0; q < 3; q++) {
        run_sums(G, c.u[q], bd[0], bd[1]);
#pragma unroll
        for (int h = 0; h < 2; h++) {
            const uint32_t s = h ? 0x7632u : 0x5410u;
            c.q2[q][h][0] = prmt(G[0][1], G[0][0], s); c.q2[q][h][1] = prmt(G[1][1], G[1][0], s);
            c.q2[q][h][2] = prmt(G[1][0], G[1][1], s ^ 0x4444u); c.q2[q][h][3] = prmt(G[2][1], G[2][0], s);
            if (q < 2) mmah16(acc[8 * q + 16], acc[8 * q + 17], c.q2[q][h][0], c.q2[q][h][1], c.q2[q][h][2], c.q2[q][h][3], e.t[2 * h], e.t[2 * h + 1], acc[8 * q + 16], acc[8 * q + 17]);
        }
    }
    if (sel == 0u) {
#pragma unroll
        for (int i = 0; i < 6; i++) sts128(ka + i * 16, c.q2[i >> 1][i & 1][0], c.q2[i >> 1][i & 1][1], c.q2[i >> 1][i & 1][2], c.q2[i >> 1][i & 1][3]);
#pragma unroll
        for (int i = 0; i < 2; i++) sts128(ka + i * 16, c.q3[i][0], c.q3[i][1], c.q3[i][2], c.q3[i][3]);
#pragma unroll
        for (int i = 1; i < 4; i++) sts64(ka + i * 16, acc[8 * i], acc[8 * i + 1]);
    }
    conv_rename(acc);
}
#define SPACE 120
#define SPN 3
#define GATE 2
#define HAND 2
#define GA 6
#define GB 4
template <int TA, int TB, int IA, class FG>
__device__ __forceinline__ void conv_tail(uint32_t (&acc)[32], const uint32_t (&a)[8][4], uint32_t sb, unsigned char* gy0, int warp, size_t ycopy, FG fg) {
    const int wg = warp >> 2, wq = warp & 3, ord = TA == 0 && TB == 16 ? 3 - wg : 4;
    const uint32_t ub = sb + SM_U + wg * USLOT_B + UPAD * 16, turn = sb + SM_MISC + 376 + ord * 8, sfs = sb + SM_MISC + 256 + wg * 8;
    const uint32_t du = wg * (USLOT_B / 16) + (SM_U / 16 + UPAD + TA * 8);
    uint32_t ud[8], fs;
    auto skip = [&]() {
        const int lane = lane_v();
        const uint32_t ua = ub + ((lane >> 3) & 1) * ULO_B + (8 * wq + (lane & 7)) * 16 + (lane >> 4) * 512;
        if (IA == 0) ldsm_x4_t(ud[0], ud[1], ud[2], ud[3], ua);
        if (TB == 16) ldsm_x4_t(ud[4], ud[5], ud[6], ud[7], ua + 1024);
        const uint2 fd = lds64(sfs);
        fs = fd.x;
        const float dsk = __uint_as_float(fd.y);
#pragma unroll
        for (int i = 2 * IA; i < TB / 2; i++) ud[i] = pack_bf16(h_lo(ud[i]) * dsk, h_hi(ud[i]) * dsk);
    };
    conv_rename<2 * TA, 2 * TB>(acc);
    if (__builtin_expect(ord != 0, 0)) {
        skip();
        mbar_wait(turn);
    }
    if (TA == 0 && TB == 16) asm volatile("{\n.reg .pred p;\nelect.sync _|p, 0xffffffff;\n@p mbarrier.arrive.shared::cta.b64 _, [%0];\n}\n" ::"r"(turn + 40) : "memory");
    fg(IC<8>());
    wg_fence();
#pragma unroll
    for (int m = 7; m >= 0; m--) {
        wg_h<TA, TB - TA>(acc, a[m], smem_desc(sb, du - m, ULO_B));
        if (m == GA || m == GB || m == HAND) wg_commit();
        if (m == GB) asm volatile("wgmma.wait_group.sync.aligned 1;\n" ::: "memory");
    }
    wg_commit();
    if (TA == 0 && TB == 16) {
        asm volatile("wgmma.wait_group.sync.aligned 1;\n" ::: "memory");
        asm volatile("{\n.reg .pred p;\nelect.sync _|p, 0xffffffff;\n@p mbarrier.arrive.shared::cta.b64 _, [%0];\n}\n" ::"r"(turn + 8) : "memory");
    }
    __syncwarp();
    fg(IC<3>());
    if (!ord) skip();
    fg(IC<4>());
    const int lane = lane_v();
    const uint32_t lp = sb + SM_PL + (ord >= 3 ? ord - 3 : ord) * PL_B + lane * 8;
    unsigned char* gy = gy0 + ((4 * wq + (lane & 3)) * DM + (TA == 0 && TB == 16 ? 4 * blockIdx.x + wg : 512 + (blockIdx.x >> 1))) * 64 + (lane >> 2) * 8;
    const uint32_t st = lp + (wq * 12 - ((wq * (wq - 1)) >> 1)) * 256;
    uint32_t ld[3];
#pragma unroll
    for (int s = 1; s < 4; s++) {
        const int w = (wq - s) & 3;
        ld[s - 1] = lp + (w * 12 - ((w * (w - 1)) >> 1) + s - 1 - (wq < s ? 3 : 0)) * 256;
    }
    if (ord >= 3) bar_sync(9 + ord, 256);
    wg_wait0();
    fg(IC<6>());
#pragma unroll
    for (int j = TA; j < TB; j++)
        if ((j & 3) && j + 3 >= 4 * IA && (j + 3 < TB || j + wq < TB)) sts64(st + (j - 1 - (j >> 2)) * 256, acc[2 * j], acc[2 * j + 1]);
    bar_sync(1 + wg, 128);
    fg(IC<7>());
    uint2 v[4][3];
#pragma unroll
    for (int i = IA; i < TB / 4; i++)
#pragma unroll
        for (int s = 0; s < 3; s++) {
            if (i == 0) { v[i][s] = make_uint2(0u, 0u); if (wq > s) v[i][s] = lds64(ld[s]); }
            else v[i][s] = lds64(ld[s] + i * 768);
        }
    fg(IC<5>());
#pragma unroll
    for (int i = IA; i < TB / 4; i++) {
        const uint32_t x0 = hadd2(v[i][0].x, acc[8 * i]), x1 = hadd2(v[i][1].x, v[i][2].x), y0 = hadd2(v[i][0].y, acc[8 * i + 1]), y1 = hadd2(v[i][1].y, v[i][2].y);
        const uint32_t x = hadd2(x0, x1), y = hadd2(y0, y1);
        const uint32_t lo = pack_bf16(h_lo(x), h_hi(x)), hi = pack_bf16(h_lo(y), h_hi(y));
        const uint32_t o0 = max(hfma2_bf(lo, fs, ud[2 * i]), 1u), o1 = hfma2_bf(hi, fs, ud[2 * i + 1]);
        stg64(gy + i * 16 * DM * 64, o0, o1);
        if (SPACE && TA == 0 && TB == 16 && i < 3 && ord < SPN) { const unsigned c0 = clock(); while (clock() - c0 < SPACE) {} }
    }
    if (TA == 0 && TB == 16 && ord < 2) bar_arrive(12 + ord, 256);
}
template <int M0, int M1>
__device__ __forceinline__ void conv_frags(uint32_t (&a)[8][4], const uint32_t (&r)[18], uint32_t sel, uint32_t dep, int warp) {
    const uint32_t s = prmt_v(sel, dep, 0x3210u + (warp >> 8)), sw = s ^ 0x4444u;
#pragma unroll
    for (int m = M0; m < M1; m++) {
        a[m][0] = prmt_v(r[2 * m + 1], r[2 * m + 2], s); a[m][1] = prmt_v(r[2 * m + 2], r[2 * m + 3], s);
        a[m][2] = prmt_v(r[2 * m + 1], r[2 * m], sw); a[m][3] = prmt_v(r[2 * m + 2], r[2 * m + 1], sw);
    }
}
template <class FG>
__device__ __forceinline__ void conv_main(const Conv& c, uint32_t (&acc)[32], uint32_t sb, uint32_t sel, unsigned char* gy, int warp, size_t ycopy, FG fg) {
    const uint32_t kw = (warp >> 2) * (KW_B / 16) + SM_KW / 16;
    const uint64_t d2 = smem_desc(sb, kw + KW_T2 / 16, KW_KH), d2b = smem_desc(sb, kw + KW_T2 / 16 + 1, KW_KH), d3 = smem_desc(sb, kw + KW_T3 / 16, 16), d3b = smem_desc(sb, kw + KW_T3 / 16 + 32, 16);
    uint32_t a[8][4];
    {
        const int ord = warp < 16 ? 3 - (warp >> 2) : 4;
        if (__builtin_expect(ord >= GATE, 0)) {
            fg(IC<1>());
            mbar_wait(sb + SM_MISC + 376 + 40 + (ord - GATE) * 8);
        }
    }
    wg_fence();
    wg_h<12, 4>(acc, c.q3[0], d3b); wg_h<8, 4>(acc, c.q3[0], d3); wg_h<4, 4>(acc, c.q2[0][0], d2b);
    wg_h<12, 4>(acc, c.q3[1], d3); wg_h<8, 4>(acc, c.q2[1][0], d2b);
    wg_h<12, 4>(acc, c.q2[2][0], d2b); wg_h<4, 4>(acc, c.q2[0][1], d2); wg_h<8, 4>(acc, c.q2[1][1], d2);
    wg_h<12, 4>(acc, c.q2[2][1], d2);
    wg_commit(); __syncwarp();
    fg(IC<0>());
    wg_wait0();
    conv_frags<0, 8>(a, c.r, sel, acc[16], warp);
    fg(IC<2>());
    if (warp >= 16) {
        if (blockIdx.x & 1) conv_tail<4, 16, 2>(acc, a, sb, gy, warp, ycopy, fg);
        else conv_tail<0, 8, 0>(acc, a, sb, gy, warp, ycopy, fg);
    } else {
        conv_tail<0, 16, 0>(acc, a, sb, gy, warp, ycopy, fg);
    }
}
#define CONV_LT6 const int dd = (lane >> 3) + (lane & 4) - (lane & 3); \
        const uint4 lt6 = make_uint4(prmt_v((dd & 3) * 288, 0u, idn), prmt_v(0x3254u + (dd >> 2) * 0x2222u, 0u, idn), \
            prmt_v(UPAD * 16 + (lane & 7) * 16 + ULO_B - 32 + (lane >> 3) * 512, 0u, idn), prmt_v(UPAD * 16 + (lane & 7) * 16 + ((lane >> 3) & 1) * ULO_B - 16 + (lane & 16), 0u, idn));
#define CONV_PRE \
        CONV_LT6 \
        const uint32_t ka = kw + lt6.x, sel = lt6.y, ks = kw + lt7.x; \
        const uint32_t ca0 = sb + SM_U + wg * USLOT_B + (warp & 3) * 128 + lt6.z, ca1 = sb + SM_U + wg * USLOT_B + (warp & 3) * 128 + lt6.w; \
        uint4 bd[4]; \
        band_pair<2, 4>(bd[0], bd[1], lt7.w); band_pair<4, 0>(bd[2], bd[3], lt7.w);
#define CONV_PRE2 ConvPre ce_; conv_pre(ce_, ka, ks, sel);
#define CONV_BODY \
        Conv c; \
        uint32_t acc[32]; \
        conv_sums(c, acc, ce_, ca0, ca1, bd, ka, sel, warp & 3, warp >> 8);
#define WS 0__1_2_3_46_57___a_b______ce_d_
#define WS_STR2(x) #x
#define WS_STR(x) WS_STR2(x)
__device__ constexpr char wunit(int pt, int k) {
    constexpr char t[] = WS_STR(WS);
    int i = 0;
    for (; pt > 0 && t[i]; i++) pt -= t[i] == '_';
    for (; k > 0 && t[i] && t[i] != '_'; i++) k--;
    return t[i] == '_' ? 0 : t[i];
}
__device__ constexpr bool wsched_ok() {
    int seen = 0;
    for (int p = 0; p < 21; p++)
        for (int k = 0; wunit(p, k); k++) {
            const char c = wunit(p, k);
            const int bit = 1 << (c >= 'a' ? c - 'a' + 8 : c - '0');
            if ((seen & bit) || k >= (p < 16 ? 4 : 2) || (p < 5 && c >= '6' && c <= '7') || (p < 6 && c >= 'c') || (p < 16 && c == 'e')) return false;
            seen |= bit;
        }
    return seen == 0x1fff;
}
static_assert((PAUSE & 2) && GATE <= 2, "resets");
static_assert(wsched_ok(), "weight schedule");
template <int PT, int K>
__device__ __forceinline__ void weight_units(uint32_t sb, const CUtensorMap* tg, const CUtensorMap* tu, const CUtensorMap* td, int w) {
    constexpr char U = wunit(PT, K);
    if constexpr (U != 0) {
        if (w == K && elect_one()) {
            if constexpr (U == 'e') { if (!(blockIdx.x & 1)) tma_2d(sb + SM_WD + 4 * 9216, td, 256, 72 * (blockIdx.x >> 1), sb + SM_MISC + 352); }
            else if constexpr (U >= 'a') tma_2d(sb + SM_WD + (U - 'a') * 9216, td, 320 * (blockIdx.x & 1) + 64 * (U - 'a'), 72 * (blockIdx.x >> 1), sb + SM_MISC + 336);
            else if constexpr (U < '6') tma_2d(sb + SM_WG + (U - '0') * 6912, tg, 72 * (blockIdx.x >> 1), 288 * (blockIdx.x & 1) + (U - '0') * 48, sb + SM_MISC + 328);
            else tma_2d(sb + SM_WU + (U - '6') * 20736, tu, 72 * (blockIdx.x >> 1), 288 * (blockIdx.x & 1) + (U - '6') * 144, sb + SM_MISC + 328);
        }
        weight_units<PT, K + 1>(sb, tg, tu, td, w);
    }
}
#define WPOINT(i, w) do { weight_units<i, 0>(sb, &tm_g, &tm_u, &tm_d, w); } while (0)

__global__ void __launch_bounds__(NTHR, 1) __cluster_dims__(2, 1, 1)
fused_kernel(const Params p, const __grid_constant__ CUtensorMap tm_g, const __grid_constant__ CUtensorMap tm_u, const __grid_constant__ CUtensorMap tm_d, const __grid_constant__ CUtensorMap tm_x,
             const __grid_constant__ CUtensorMap tm_y, const __grid_constant__ CUtensorMap tm_z) {
    extern __shared__ __align__(1024) unsigned char smem[];
    const uint32_t sb = smem_u32(smem);
    const int tid = threadIdx.x, warp = __shfl_sync(0xffffffffu, tid >> 5, 0), lane = tid & 31;
    const int b = blockIdx.x, P = b >> 1, odd = b & 1;
    const int g = lane >> 2, t = lane & 3;
    const int wg = warp >> 2, t128 = tid & 127;
    const uint32_t s_stat = sb + SM_MISC;
    const uint32_t s_key = sb + SM_MISC + 128;
    const uint32_t s_wm = sb + SM_MISC + 256;
    const uint32_t s_k16 = sb + SM_MISC + 192;
    const uint32_t s_fs = sb + SM_MISC + 256;
    const uint32_t s_cnt = sb + SM_MISC + 320;
    const uint32_t bar_w = sb + SM_MISC + 328, bar_d = bar_w + 8, bar_g = bar_w + 16, bar_r = bar_w + 32, bar_h = bar_w + 40, bar_x = bar_w + 48;
    STAMP(0);

    const bool lnw = (unsigned)(warp - 10) < 9u;
    const unsigned pm = tid + (tid < 512 ? 512 * b : 65024 + 128 * P), pq = (pm & ~127u) + 4 * lane;
    uint32_t pl = ldg16(p.lar + pm), ldt = ldg16(p.ldt + (pm >> 7));
    const uint32_t pa2 = ldg16(p.aim + pm), pc = ldg16(p.cre + pm), pi = ldg16(p.cim + pm);
    const uint2 call_re = ldg64(p.cre + pq), call_im = ldg64(p.cim + pq);
    const uint32_t dskl = ldg16(p.dsk + (pm >> 7));
    const uint32_t ep = ld_poll32(p.s->hint + (b & 7) * 32 + 1 + (lane >> 5));
    if ((unsigned)(tid - 320) < 288u) {
        const bf16* xp = p.x + (unsigned)((32 * P + 2 * odd + TOKEN_OF(g)) * DM + ((tid - 320) & ~31) + 8 * t);
        const uint32_t xt = sb + SM_XT + ((tid - 320) & ~31) * 32 + lane * 16;
        asm volatile("cp.async.cg.shared.global [%0], [%1], 16;\ncp.async.cg.shared.global [%0 + 512], [%1 + 9216], 16;\n"
                     "cp.async.cg.shared.global [%0 + 9216], [%1 + 576], 16;\ncp.async.cg.shared.global [%0 + 9728], [%1 + 9792], 16;\n" ::"r"(xt), "l"(xp) : "memory");
    }
    uint32_t* const std_ = p.s->st + ((lane & 12) * 128 + odd * 256 + 4 * P + 2 * (lane & 1) + ((lane >> 1) & 1)) * 2;
    unsigned char* const ud = reinterpret_cast<unsigned char*>(p.s->uT) + (32 * (warp - UW) + 8 * (g >> 1) + (g & 1)) * 4096 + b * 32 + t * 8;
    if (warp == 0) {
        if (lane == 0) {
            mbar_init(bar_x, 1); mbar_init(bar_w, 1); mbar_init(bar_d, 1); mbar_init(bar_d + 16, 1); mbar_init(bar_g, 1); mbar_init(bar_h, 3); mbar_init(bar_r, 1);
            #pragma unroll
            for (int i = 1; i < 9; i++) mbar_init(bar_x + 8 * i, 4);
            asm volatile("fence.mbarrier_init.release.cluster;\n" ::: "memory");
            mbar_expect(bar_x, 16384); mbar_expect(bar_r, 8192);
            mbar_expect(bar_w, 2 * 41472); mbar_expect(bar_d, 36864); mbar_expect(bar_d + 16, 9216); mbar_expect(bar_g, 9 * 512);
        }
        __syncwarp();
        bar_arrive(0, NWRK);
    }
    if (warp == 0 && elect_one()) tma_3d(sb + SM_XC, &tm_x, 8 * P, 0, 8 * odd, bar_x);
    asm volatile("barrier.cluster.arrive.relaxed.aligned;\n" ::: "memory");
    const uint32_t kw = sb + SM_KW + wg * KW_B;
    if (t128 < 2 * UPAD) sts128(sb + SM_U + wg * USLOT_B + (t128 & 1) * ULO_B + (t128 >> 1) * 16, 0u, 0u, 0u, 0u);
    sts128(kw + t128 * 16, 0u, 0u, 0u, 0u);
    if (t128 < KW_B / 16 - 128) sts128(kw + 2048 + t128 * 16, 0u, 0u, 0u, 0u);
    if (tid < 96) {
#pragma unroll
        for (int i = 0; i < 6; i++) sts128(sb + SM_ZERO + i * 1536 + tid * 16, 0u, 0u, 0u, 0u);
    }
    if (warp != 0) bar_sync(0, NWRK);
    STAMP(1);
    if (warp == 19 || warp == UW || warp == UW + 1) {
        if (warp == 19) {
            if (lane < 16) stg64(std_, 0u, 0u);
            if (lane < 9) asm volatile("prefetch.global.L2 [%0];\n" ::"l"(p.wr + lane * 64));
        } else {
#pragma unroll
            for (int k = 0; k < 4; k++) stg64(ud + k * 8192, 0u, 0u);
        }
    }
    uint32_t X[2][8];
    auto partial = [&]() {
        const uint32_t xt = sb + SM_XT + (warp - 10) * 1024 + lane * 16;
        asm volatile("cp.async.wait_all;\n" ::: "memory");
        STAMP(23);
        const uint4 a = lds128(xt), c = lds128(xt + 512), d = lds128(xt + 9216), e = lds128(xt + 9728);
        X[0][0] = a.x; X[0][1] = a.y; X[0][2] = a.z; X[0][3] = a.w; X[0][4] = d.x; X[0][5] = d.y; X[0][6] = d.z; X[0][7] = d.w;
        X[1][0] = c.x; X[1][1] = c.y; X[1][2] = c.z; X[1][3] = c.w; X[1][4] = e.x; X[1][5] = e.y; X[1][6] = e.z; X[1][7] = e.w;
        const uint32_t one[8] = {0x3f803f80u, 0x3f803f80u, 0x3f803f80u, 0x3f803f80u, 0x3f803f80u, 0x3f803f80u, 0x3f803f80u, 0x3f803f80u};
        ln_partial<8>(X, one, sb + SM_LNP, warp - 10, g, t);
        bar_arrive(6, 320);
        if (PAUSE & 1) bar_sync(7, PCNT);
    };
    if (LNAT == 0 && lnw) {
        partial();
        pl = prmt_v(pl, X[0][0], 0x3210u + (warp >> 8)); ldt = prmt_v(ldt, X[0][0], 0x3210u + (warp >> 8));
    }
    auto finish = [&]() {
        bar_sync(6, 320);
        float mb, rc;
        ln_finish<9>(sb + SM_LNP, lane, mb, rc);
        const float rh = rbf(rc);
        const uint32_t s0 = (__float_as_uint(mb) >> 16) | (((ep & 0x7fffu) + 1u) << 16), s1 = pack_bf16(rh, rc - rh);
        if (lane < 16) { stg64(std_, s0, s1); sts64(s_stat + lane * 8, s0, s1); }
        if (lane == 16) sts32(s_cnt + 4, ep);
        bar_arrive(7, PCNT);
        STAMP(28);
    };
    auto upub = [&]() {
        if (!(PAUSE & 6)) bar_sync(7, PCNT);
        const uint32_t utag = ((ep & 3u) + 1u) * 0x10001u;
        uint32_t U[2][4];
#pragma unroll
        for (int hf = 0; hf < 2; hf++) {
            const uint2 st = lds64(s_stat + (g + 8 * hf) * 8);
            const uint4 xv = lds128(sb + SM_XT + (16 + warp - UW) * 1024 + hf * 512 + lane * 16);
            const uint32_t xs[4] = {xv.x, xv.y, xv.z, xv.w};
#pragma unroll
            for (int k = 0; k < 4; k++) {
                const uint32_t u = ln_apply(xs[k], st);
                U[hf][k] = movm((pack_f16_rz(bf_lo(u), __uint_as_float(u)) & 0xfff8fff8u) | utag);
            }
        }
#pragma unroll
        for (int k = 0; k < 4; k++) stg64(ud + k * 8192, U[0][k], U[1][k]);
    };
    if (FINAT == 0 && warp == 19) finish();
    const uint32_t tb = table_buf(sb, warp);
    const float dt = rbf(expf(bf_lo(ldt)));
    KGen kg;
    kgen_setup(kg, pl | (pa2 << 16), dt);
    if (LNAT == 1 && lnw) {
        partial();
        kg.z8.x = __uint_as_float(prmt_v(__float_as_uint(kg.z8.x), X[0][0], 0x3210u + (warp >> 8)));
        kg.z1.x = __uint_as_float(prmt_v(__float_as_uint(kg.z1.x), X[0][0], 0x3210u + (warp >> 8)));
    }
    if (FINAT == 1 && warp == 19) finish();
    if (UAT == 0 && (warp == UW || warp == UW + 1)) upub();
    kgen_rows(kg, tb, lane);
    if (wg == 0) fence_async();
    if (LNAT == 2 && lnw) {
        partial();
        kg.z128.x = __uint_as_float(prmt_v(__float_as_uint(kg.z128.x), X[0][0], 0x3210u + (warp >> 8)));
        kg.z1.x = __uint_as_float(prmt_v(__float_as_uint(kg.z1.x), X[0][0], 0x3210u + (warp >> 8)));
    }
    if (FINAT == 2 && warp == 19) finish();
    if (UAT == 1 && (warp == UW || warp == UW + 1)) upub();
    STAMP(2);
    WPOINT(0, warp - 4);
    const int ce = c_exponent(call_re, call_im);
    if (t128 == 0) sts64(s_fs + wg * 8, (uint32_t)min(max(ce + (int)(__float_as_uint(dt) >> 23) - 116, 0), 254) * 0x800080u, dskl << 16);
    kgen_chain(kg, pc | (pi << 16), __uint_as_float(((uint32_t)(244 - ce) << 23) | (__float_as_uint(dt) & 0x7fffffu)));
    if ((PAUSE & 4) && warp < 10) bar_sync(7, PCNT);
    if (UAT == 4 && (warp == UW || warp == UW + 1)) upub();
    STAMP(3);
    WPOINT(1, warp - 6);
    kgen_cols(kg, tb, lane);
    if (LNAT == 3 && lnw) partial();
    if (FINAT == 3 && warp == 19) finish();
    if ((PAUSE & 2) && warp < 10) bar_sync(7, PCNT);
    if (UAT == 2 && (warp == UW || warp == UW + 1)) upub();
    STAMP(4);
    WPOINT(2, warp - 8);
    const uint4* usrc = wg < 4 ? reinterpret_cast<const uint4*>(p.s->st) + odd * 512 + (lane & 1) * 128 + 16 * (warp & 7) + (lane >> 1)
                               : reinterpret_cast<const uint4*>(p.s->uT) + P * 256 + 2 * t128;
    const int ustep = wg < 4 ? 256 : 1;
    uint4 uv0, uv1;
    kgen_mma(kg, tb, lane);
    if (UAT == 3 && (warp == UW || warp == UW + 1)) upub();
    STAMP(26);
    WPOINT(3, warp - 5);
    const uint32_t idn = 0x3210u + (warp >> 8);
    const uint4 lt7 = make_uint4(prmt_v(KW_T2 + ((lane >> 3) & 1) * KW_KH + (33 + (lane & 7)) * 16 - (lane & 16), 0u, idn), t * 288 + g * 8 + 8, (lane & 1) * 4096 + (lane >> 1) * 16,
                                 prmt_v(8u << ((lane >> 3) + (lane & 4)) >> (lane & 3), 0u, idn));
    asm volatile("barrier.cluster.wait.acquire.aligned;\n" ::: "memory");
    bar_sync(1 + wg, 128);
    uv0 = ld_poll(usrc); uv1 = ld_poll(usrc + ustep);
    kgen_combine(sb, warp, lane, kw, lt7.y);
    if (warp < 3 || warp > 6) bar_arrive(14, NWRK);
    CONV_PRE
    STAMP(5);
    WPOINT(4, warp - 7);
    if (wg < 4) {
        mbar_wait(bar_x);
        const bool far = warp < 8;
        const uint32_t xa = sb + SM_XC + (warp & 7) * 256 + (odd ^ far) * 8 + lt7.z;
        uint2 xv[4] = {lds64(xa), lds64(xa + 8192), lds64(xa + 2048), lds64(xa + 10240)};
        const uint32_t tag = ((ep & 0x7fffu) + 1u) << 16;
        int it = 0;
        while (true) {
            const bool bad = (((uv0.x ^ tag) | (uv0.z ^ tag)) | ((uv1.x ^ tag) | (uv1.z ^ tag))) >> 16;
            if (!__any_sync(0xffffffffu, bad)) break;
            if (++it > SPIN_LIMIT) TRAP();
            if (bad) { uv0 = ld_poll(usrc); uv1 = ld_poll(usrc + 256); }
        }
        STAMP(6);
        DBG(wg, it);
        const uint2 st[4] = {make_uint2(uv0.x, uv0.y), make_uint2(uv0.z, uv0.w), make_uint2(uv1.x, uv1.y), make_uint2(uv1.z, uv1.w)};
#pragma unroll
        for (int i = 0; i < 4; i++) {
            xv[i].x = ln_apply(xv[i].x, st[i]);
            xv[i].y = ln_apply(xv[i].y, st[i]);
        }
        const uint32_t ub = sb + SM_U + UPAD * 16 + odd * ULO_B + (warp & 7) * 256 + lane * 8;
        const uint32_t w[4][2] = {{pack_f16(bf_lo(xv[0].x), bf_lo(xv[1].x)), pack_f16(bf_lo(xv[2].x), bf_lo(xv[3].x))}, {HI2(xv[0].x, xv[1].x), HI2(xv[2].x, xv[3].x)},
                                  {pack_f16(bf_lo(xv[0].y), bf_lo(xv[1].y)), pack_f16(bf_lo(xv[2].y), bf_lo(xv[3].y))}, {HI2(xv[0].y, xv[1].y), HI2(xv[2].y, xv[3].y)}};
#pragma unroll
        for (int i = 0; i < 4; i++) {
            if (far) asm volatile("st.async.shared::cluster.mbarrier::complete_tx::bytes.v2.b32 [%0], {%1,%2}, [%3];\n" ::"r"((ub ^ 0x1000000u) + i * USLOT_B), "r"(w[i][0]), "r"(w[i][1]), "r"(bar_r ^ 0x1000000u) : "memory");
            else sts64(ub + i * USLOT_B, w[i][0], w[i][1]);
        }
    } else {
        const uint32_t utag = ((ep & 3u) + 1u) * 0x10001u;
        int it = 0;
        while (true) {
            const bool bad = (((uv0.x ^ utag) | (uv0.y ^ utag) | (uv0.z ^ utag) | (uv0.w ^ utag)) | ((uv1.x ^ utag) | (uv1.y ^ utag) | (uv1.z ^ utag) | (uv1.w ^ utag))) & 0x70007u;
            if (!__any_sync(0xffffffffu, bad)) break;
            if (++it > SPIN_LIMIT) TRAP();
            if (bad) { uv0 = ld_poll(usrc); uv1 = ld_poll(usrc + 1); }
        }
        STAMP(6);
        DBG(4, it);
        const uint32_t ub = sb + SM_U + UPAD * 16 + 4 * USLOT_B + (t128 >> 1) * 32 + (t128 & 1) * 8;
        sts64(ub, prmt(uv0.x, uv0.z, 0x5410u) ^ utag, prmt(uv1.x, uv1.z, 0x5410u) ^ utag);
        sts64(ub + 16, prmt(uv0.x, uv0.z, 0x7632u) ^ utag, prmt(uv1.x, uv1.z, 0x7632u) ^ utag);
        sts64(ub + ULO_B, prmt(uv0.y, uv0.w, 0x5410u) ^ utag, prmt(uv1.y, uv1.w, 0x5410u) ^ utag);
        sts64(ub + ULO_B + 16, prmt(uv0.y, uv0.w, 0x7632u) ^ utag, prmt(uv1.y, uv1.w, 0x7632u) ^ utag);
    }
    if (warp < 3 && elect_one()) tma_st_3d(warp < 2 ? &tm_y : &tm_z, sb + SM_ZERO, warp < 2 ? 128 * b : 32 * (512 + P), 0, 2 * (warp < 2 ? warp : odd));
    if (warp >= 3 && warp <= 6) {
        bar_sync(14, NWRK);
        WPOINT(5, warp - 3);
    }
    bar_sync(1 + wg, 128);
    CONV_PRE2
    mbar_wait(bar_r);
    fence_async();
    bar_sync(0, NWRK);
    STAMP(7);
    uint32_t hv0 = 0;
    {
        WPOINT(6, 19 - warp);
        CONV_BODY
        WPOINT(7, 19 - warp);
        bar_sync(0, NWRK);
        STAMP(8);
        size_t ycopy = 0;
        auto hook = [&](auto gi) {
                     constexpr int G = decltype(gi)::value;
                     if (G == 4 && warp == HINTW) hv0 = ld_poll32(p.s->hint + (lane_v() & 7) * 32);
                     if (G == 5) mbar_wait(bar_h);
                     if (G == 1 || G == 2) WPOINT(7 + G, warp - 16);
                     if (G == 3) { WPOINT(10, warp - 12); WPOINT(12, warp - 8); WPOINT(14, warp - 4); }
                     if (G == 5) { WPOINT(11, warp - 13); WPOINT(13, warp - 9); WPOINT(15, warp - 5); }
                     if (G == 1 && warp >= 17 && elect_one())
                         bulk_s2g(warp == 17 ? p.s->part + b * (PBYTES / 4) : warp == 18 ? p.s->rows + b * 1152 : p.s->sc + b * 32, sb + SM_ZERO, warp == 17 ? PBYTES : warp == 18 ? 4608 : 32);
                     if (G == 4 && warp >= 17 && elect_one()) {
                         asm volatile("cp.async.bulk.wait_group 0;\n" ::: "memory");
                         hint_arrive(p.s->hint, 2, b & 7);
                     }
                     if (G == 1 && warp < 3) {
                         if (elect_one()) {
                             asm volatile("cp.async.bulk.wait_group 0;\n" ::: "memory");
                             mbar_arrive(bar_h);
                             hint_arrive(p.s->hint, 0, b & 7);
                         }
                         __syncwarp();
                         STAMP(17);
                     }
                 };
        conv_main(c, acc, sb, sel, reinterpret_cast<unsigned char*>(p.s->y), warp, ycopy, hook);
        STAMP(10);
    }
    {
    const int warp = warp_v(), lane = lane_v(), tid = 32 * warp + lane, g = lane >> 2, t = lane & 3;
    if (warp == HINTW) {
        const uint32_t target = (lds32(s_cnt + 4) + 1u) * 48u;
        if (__any_sync(0xffffffffu, (int)(hv0 - target) < 0)) hint_wait(p.s->hint, 0, target);
    }
    const unsigned char* ys = reinterpret_cast<const unsigned char*>(p.s->y) + ((size_t)P * DM + 32 * warp + 8 * (g >> 1) + (g & 1)) * 64 + odd * 32 + t * 8;
    STAMP(27);
    bar_sync(0, NWRK);
    STAMP(11);
    const uint32_t zr = warp >> 8;
    auto late_rows = [&](auto pub) {
        const uint32_t k = lds32(s_key + (lane & 7) * 4), ep = lds32(s_cnt + 4);
        const bool late = k & 256u, mine = late && ((k & 255u) >> 1) == (uint32_t)b;
        uint32_t todo = __ballot_sync(0xffffffffu, mine) & 0xffu;
        if (todo) {
#pragma unroll 1
            while (todo) {
                const int s = __ffs(todo) - 1, row = (__shfl_sync(0xffffffffu, k, s) >> 9) & 15;
                todo &= todo - 1;
                if ((row & 7) == g) pub(row & 8, 2 * NCTA + s);
            }
            __threadfence();
            bar_sync(0, NWRK);
            if (tid < NSEL && mine) *reinterpret_cast<volatile unsigned*>(p.s->flag + tid) = ep + 1u;
        }
        int it = 0;
        while (__any_sync(0xffffffffu, late && ld_poll32(p.s->flag + (lane & 7)) != ep + 1u)) { if (++it > SPIN_LIMIT) TRAP(); }
        __threadfence();
        const int gs = tid / 36;
        const uint4* src = reinterpret_cast<const uint4*>(p.s->rows) + __shfl_sync(0xffffffffu, late ? 2 * NCTA + (lane & 7) : (k & 255u), gs & 7) * 144 + 36 * odd + (tid - gs * 36);
        if (tid < 288) {
            uint4 v0;
            do { v0 = ld_poll(src); if (++it > SPIN_LIMIT) TRAP(); } while (!v0.x);
            sts128(sb + SM_XS + gs * XS_PITCH + (tid - gs * 36) * 16, v0.x, v0.y, v0.z, v0.w);
        }
        bar_sync(0, NWRK);
    };
    if (warp >= 18) {
        if (warp == 18) {
            uint32_t* const kp = pin(p.s->sc + 32 * b, zr);
            const uint32_t kid = pin(0x30000000u | ((lane & 15) << 9) | 2 * b, zr), ka = pin(s_k16 + (lane & 15) * 4, zr), kb = pin(s_k16 + (lane & 16) * 2, zr);
            bar_sync(8, 640);
            float mb, rc;
            ln_finish<18>(sb + SM_LNP, lane, mb, rc);
            if (lane < 16) stat_store(s_stat + lane * 8, mb, rc, 0u);
            bar_arrive(13, 608);
            bar_sync(10, 608);
            const float r = sum18(sb + SM_LNP + (32 + (lane & 15)) * 80);
            const uint32_t bits = pack_bf16(0.f, r);
            const uint32_t me = (((bits ^ ((uint32_t)((int)bits >> 31) & 0x7fffffffu)) >> 3) & 0x1fffe000u) ^ kid;
            sts32(ka, me);
            __syncwarp();
            const uint4 v = lds128(kb), w = lds128(kb + 16);
#define GT(x) ((me - (x)) >> 31)
            uint32_t rank = pin(GT(v.x) + GT(v.y) + GT(v.z), zr) + pin(GT(v.w) + GT(w.x) + GT(w.y), zr) + pin(GT(w.z) + GT(w.w), zr);
#undef GT
            rank += __shfl_xor_sync(0xffffffffu, rank, 16);
            if (lane < 16) { if (rank < 8) stg32(kp + rank, me + (rank < 2 ? rank : 256u)); }
            else sts32(ka + (s_wm - s_k16), rank);
            bar_arrive(11, 640);
            weight_units<19, 0>(sb, &tm_g, &tm_u, &tm_d, 0); weight_units<19, 1>(sb, &tm_g, &tm_u, &tm_d, 1);
        }
        const uint4* ksrc = pin(reinterpret_cast<const uint4*>(p.s->sc) + 8 * lane, zr);
        const uint4* rsrc = pin(reinterpret_cast<const uint4*>(p.s->rows) + 36 * odd + t, zr);
        if (warp == 19) {
            weight_units<20, 0>(sb, &tm_g, &tm_u, &tm_d, 0); weight_units<20, 1>(sb, &tm_g, &tm_u, &tm_d, 1);
            bar_sync(8, 640);
            weight_units<16, 0>(sb, &tm_g, &tm_u, &tm_d, 0); weight_units<16, 1>(sb, &tm_g, &tm_u, &tm_d, 1);
            hint_wait(p.s->hint, 2, (lds32(s_cnt + 4) + 1u) * 48u);
            bar_sync(11, 640);
        }
        bool slow = false;
        int it = 0;
        if (warp == 19) {
        uint4 q[4];
#pragma unroll
        for (int i = 0; i < 4; i++) q[i] = ld_poll(ksrc + 256 * i);
        while (true) {
            uint32_t a[4];
#pragma unroll
            for (int i = 0; i < 4; i++) a[i] = q[i].x & q[i].y & q[i].z & q[i].w;
            if (__all_sync(0xffffffffu, a[0] & a[1] & a[2] & a[3])) break;
#pragma unroll
            for (int i = 0; i < 4; i++)
                if (!a[i]) q[i] = ld_poll(ksrc + 256 * i);
            if (++it > SPIN_LIMIT) TRAP();
        }
        bar_arrive(9, 608);
        STAMP(16);
        auto merge = [](const uint4& x, const uint4& y) {
            const uint32_t a = max(x.x, y.w), c = max(x.y, y.z), d = max(x.z, y.y), e = max(x.w, y.x);
            const uint32_t a2 = max(a, d), d2 = min(a, d), c2 = max(c, e), e2 = min(c, e);
            return make_uint4(max(a2, c2), min(a2, c2), max(d2, e2), min(d2, e2));
        };
        uint4 h = merge(merge(q[0], q[1]), merge(q[2], q[3]));
        uint4 v[9];
        uint32_t key = 0;
#pragma unroll
        for (int s = 0; s < 8; s++) {
            const uint32_t m = __reduce_max_sync(0xffffffffu, h.x);
            const bool w = h.x == m;
            h.x = w ? h.y : h.x; h.y = w ? h.z : h.y; h.z = w ? h.w : h.z; h.w = w ? 0u : h.w;
            if (g == s) key = m;
        }
        rsrc += (key & 255u) * 144;
#pragma unroll
        for (int j = 0; j < 9; j++) v[j] = ld_poll(rsrc + 4 * j);
        slow = __any_sync(0xffffffffu, key & 256u);
        STAMP(18);
        if (__any_sync(0xffffffffu, h.x == 0u)) {
            uint4 r[4];
            it = 0;
            while (true) {
#pragma unroll
                for (int i = 0; i < 4; i++) r[i] = ld_poll(ksrc + 256 * i + 1);
                if (__all_sync(0xffffffffu, all_nz(r[0]) && all_nz(r[1]) && all_nz(r[2]) && all_nz(r[3]))) break;
                if (++it > SPIN_LIMIT) TRAP();
            }
            uint32_t m = 1u << 30;
#pragma unroll 1
            for (int s = 0; s < 8; s++) {
                uint32_t x = 0;
#pragma unroll
                for (int i = 0; i < 4; i++) {
                    x = max(max(max(x, q[i].x - m), max(q[i].y - m, q[i].z - m)), q[i].w - m);
                    x = max(max(max(x, r[i].x - m), max(r[i].y - m, r[i].z - m)), r[i].w - m);
                }
                m += __reduce_max_sync(0xffffffffu, x);
                if (g == s) key = m;
            }
            slow = true;
        }
        const uint32_t xsa = sb + SM_XS + g * XS_PITCH + t * 16;
        sts32(s_key + g * 4, key);
        sts32(xsa, 0u);
        bar_arrive(12, 608);
#pragma unroll
        for (int j = 0; j < 9; j++) sts128(xsa + j * 64, v[j].x, v[j].y, v[j].z, v[j].w);
        slow = slow || min(min(min(min(v[0].x, v[1].x), v[2].x), min(min(v[3].x, v[4].x), v[5].x)), min(min(v[6].x, v[7].x), v[8].x)) == 0u;
        }
        if (bar_or(0, NWRK, slow)) late_rows([](bool, int) {});
        STAMP(19);
        const int fl = 16 * (b & 1) + ((tid >> 2) & 15), fc = 16 * (b >> 1) + (fl >> 2) + 8 * ((tid >> 1) & 1), fsl = 2 * (fl & 3) + (tid & 1);
        const uint32_t kk = lds32(s_key + fsl * 4);
        const uint32_t* fsrc = p.s->rows + ((kk & 256u) ? 2 * NCTA + fsl : (kk & 255u)) * DM + (fc >> 1);
        uint32_t hw = 1u, uw = 1u;
        if (b < 72) { uw = ld_poll32(fsrc); hw = ld_poll32(fsrc + 288); }
        if (b < 72) {
            it = 0;
            while (!hw || !uw) { uw = ld_poll32(fsrc); hw = ld_poll32(fsrc + 288); if (++it > SPIN_LIMIT) TRAP(); }
            const int row = (kk >> 9) & 15, ftok = 8 * (kk & 252u) + (kk & 2u) + TOKEN_OF(row & 7) + (row & 8);
            const unsigned k16 = (kk >> 13) & 0xffffu;
            const unsigned bits = (k16 & 0x8000u) ? (k16 & 0x7fffu) : (~k16 & 0xffffu);
            const float rs = 512.0f * rbf(__fdividef(1.0f, 1.0f + __expf(-__uint_as_float(bits << 16))));
            bf16* const op = p.out + (unsigned)(ftok * DM + fc);
            const float uv = (fc & 1) ? bf_hi(uw) : bf_lo(uw), hv = (fc & 1) ? bf_hi(hw) : bf_lo(hw);
            const uint32_t a = sb + SM_FIN + (tid - 576) * 80;
            sts128(a + 64, __float_as_uint(rs), __float_as_uint(uv), __float_as_uint(hv), (uint32_t)(size_t)op ^ (uint32_t)((size_t)op >> 32));
            bar_sync(14, 576);
            const uint4 p0 = lds128(a), p1 = lds128(a + 16), p2 = lds128(a + 32), p3 = lds128(a + 48);
#define F4(p) ((__uint_as_float(p.x) + __uint_as_float(p.y)) + (__uint_as_float(p.z) + __uint_as_float(p.w)))
            const float v0 = F4(p0), v1 = F4(p1), v2 = F4(p2), v3 = F4(p3);
#undef F4
            const float y3 = rbf(rbf((v0 + v1) + (v2 + v3)) * rs);
            asm volatile("st.global.u16 [%0], %1;\n" ::"l"(op), "h"((unsigned short)pack_bf16(hv + rbf(uv + y3), 0.f)) : "memory");
        }
        if (b == 0 && tid >= 632) *reinterpret_cast<volatile unsigned*>(p.s->hint + (tid & 7) * 32 + 1) = lds32(s_cnt + 4) + 1u;
    } else {
        uint32_t H[2][4], U2[2][4], WA[9][4], WD[18], WE[18];
        const int fkh = warp >= 9, fmt = warp - 9 * fkh;
        auto load_wa = [&](auto k0, auto k1) {
            if (k0.value >= k1.value) return;
            if (k0.value == 0) mbar_wait(bar_w);
            const int mi = lane >> 3, rr = lane & 7;
            const uint32_t aad = sb + SM_WG + (mi & 1) * (SM_WU - SM_WG) + (fkh * 144 + rr + 8 * (mi >> 1)) * W_PITCH + fmt * 16;
#pragma unroll
            for (int k = k0.value; k < k1.value; k++) ldsm_x4_t(WA[k][0], WA[k][1], WA[k][2], WA[k][3], aad + k * 16 * W_PITCH);
        };
        auto load_wd = [&](uint32_t (&WD)[18], int tile) {
            mbar_wait(bar_d + (tile & 16));
            const int mi = lane >> 3, rr = lane & 7;
            const uint32_t base = sb + SM_WD + (tile >> 2) * 9216 + rr * 128 + (((2 * tile + (mi & 1)) & 7) ^ rr) * 16;
#pragma unroll
            for (int k = 0; k < 4; k++) ldsm_x4_t(WD[4 * k], WD[4 * k + 1], WD[4 * k + 2], WD[4 * k + 3], base + (k * 16 + 8 * (mi >> 1)) * 128);
            ldsm_x2_t(WD[16], WD[17], base + 64 * 128);
        };
        auto publish = [&](bool hi, int slot) {
            uint4* rowp = reinterpret_cast<uint4*>(p.s->rows) + slot * 144 + warp * 4 + t;
            stg128(rowp, nzw(hi ? U2[1][0] : U2[0][0]), nzw(hi ? U2[1][1] : U2[0][1]), nzw(hi ? U2[1][2] : U2[0][2]), nzw(hi ? U2[1][3] : U2[0][3]));
            stg128(rowp + 72, nzw(hi ? H[1][0] : H[0][0]), nzw(hi ? H[1][1] : H[0][1]), nzw(hi ? H[1][2] : H[0][2]), nzw(hi ? H[1][3] : H[0][3]));
        };
        uint4 wr = make_uint4(0x3f803f80u, 0x3f803f80u, 0x3f803f80u, 0x3f803f80u);
        {
            uint2 yv[4];
#pragma unroll
            for (int k = 0; k < 4; k++) yv[k] = ld_poll64(ys + k * 128);
            if (g == 0) wr = ldg128(p.wr + 32 * warp + 8 * t);
            const uint4 x0 = lds128(sb + SM_XT + warp * 1024 + lane * 16), x1 = lds128(sb + SM_XT + warp * 1024 + 512 + lane * 16);
            load_wa(IC<0>(), IC<WA0>());
            int it = 0;
            while (!__all_sync(0xffffffffu, yv[0].x && yv[1].x && yv[2].x && yv[3].x)) {
#pragma unroll
                for (int k = 0; k < 4; k++) yv[k] = ld_poll64(ys + k * 128);
                if (++it > SPIN_LIMIT) TRAP();
            }
            STAMP(12);
            const uint32_t Z[2][4] = {{x0.x, x0.y, x0.z, x0.w}, {x1.x, x1.y, x1.z, x1.w}};
#pragma unroll
            for (int k = 0; k < 4; k++) {
                H[0][k] = hadd2_bf(Z[0][k], movm(yv[k].x));
                H[1][k] = hadd2_bf(Z[1][k], movm(yv[k].y));
            }
            const uint32_t bw[4] = {wr.x, wr.y, wr.z, wr.w};
            ln_partial<4>(H, bw, sb + SM_LNP, warp, g, t);
        }
        bar_arrive(8, 640);
        load_wa(IC<WA0>(), IC<WA1>());
        STAMP(13);
        bar_sync(13, 608);
        STAMP(14);
#pragma unroll
        for (int hf = 0; hf < 2; hf++) {
            const uint2 st = lds64(s_stat + (g + 8 * hf) * 8);
#pragma unroll
            for (int k = 0; k < 4; k++) U2[hf][k] = ln_apply(H[hf][k], st);
        }
        {
            float cs[4] = {0.f, 0.f, 0.f, 0.f};
            mma_bf16(cs, U2[0][0], U2[1][0], U2[0][1], U2[1][1], wr.x, wr.y);
            mma_bf16(cs, U2[0][2], U2[1][2], U2[0][3], U2[1][3], wr.z, wr.w);
            if (t == 0) { stsf(sb + SM_LNP + ((32 + g) * 20 + warp) * 4, cs[0]); stsf(sb + SM_LNP + ((40 + g) * 20 + warp) * 4, cs[2]); }
            bar_arrive(10, 608);
        }
        load_wa(IC<WA1>(), IC<WA2>());
        bar_sync(11, 640);
        {
            const uint32_t rk[2] = {lds32(s_wm + g * 4), lds32(s_wm + 32 + g * 4)};
            uint32_t lo = min(rk[0], rk[1]), hi = max(rk[0], rk[1]);
#pragma unroll 1
            while (lo < 2) { publish(lo == rk[1], 2 * b + lo); lo = hi; hi = 16; }
        }
        load_wa(IC<WA2>(), IC<WA3>());
        bar_sync(9, 608);
        load_wa(IC<WA3>(), IC<9>());
#pragma unroll
        for (int hf = 0; hf < 2; hf++)
            sts128(sb + SM_OUT + (g + 8 * hf) * OUT_PITCH + warp * 64 + t * 16,
                   hadd2_bf(H[hf][0], U2[hf][0]), hadd2_bf(H[hf][1], U2[hf][1]), hadd2_bf(H[hf][2], U2[hf][2]), hadd2_bf(H[hf][3], U2[hf][3]));
        fence_async();
        WPOINT(17, warp - 16);
        if ((WDAT == 0 || (WDAT == 2 && fkh)) && (warp < 16 || !odd)) load_wd(WD, warp);
        const uint32_t bad = pin(sb + SM_XS + (lane & 7) * XS_PITCH + (fkh * 144 + 8 * (lane >> 3)) * 2, zr), ex = pin(sb + SM_EX + warp * 512 + lane * 16, zr);
        uint32_t* pp = pin(p.s->part + ((size_t)(2 * (20 * odd + warp) + (lane >> 4)) * 64 + P) * 32 + (lane & 15) * 2, zr);
        bar_sync(12, 608);
        if (warp < 16 && !__any_sync(0xffffffffu, (lds32(s_key + (lane & 7) * 4) & 0x1efeu) == (uint32_t)((warp << 9) | 2 * b)) && elect_one())
            bulk_s2g(p.out + (size_t)(32 * P + 2 * odd + TOKEN_OF(warp & 7) + (warp & 8)) * DM, sb + SM_OUT + warp * OUT_PITCH, DM * 2);
        WPOINT(18, warp - 16);
        STAMP(15);
        if (bar_or(0, NWRK, false)) late_rows(publish);
        STAMP(19);
        float gp[4];
        {
            float c4[3][4];
#pragma unroll
            for (int i = 0; i < 3; i++)
#pragma unroll
                for (int j = 0; j < 4; j++) c4[i][j] = 0.f;
#pragma unroll
            for (int k = 0; k < 10; k += 2) {
                uint32_t b0, b1, b2, b3;
                ldsm_x4(b0, b1, b2, b3, bad + k * 32);
                mma_bf16(c4[k % 3], WA[k][0], WA[k][1], WA[k][2], WA[k][3], b0, b1);
                if (k < 8) mma_bf16(c4[(k + 1) % 3], WA[k + 1][0], WA[k + 1][1], WA[k + 1][2], WA[k + 1][3], b2, b3);
            }
#pragma unroll
            for (int j = 0; j < 4; j++) gp[j] = c4[0][j] + (c4[1][j] + c4[2][j]);
            if (warp >= 9) {
                sts128f(ex, gp);
                bar_arrive(6, 576);
            } else {
                bar_sync(6, 576);
                const uint4 o = lds128(ex + 4608);
                gp[0] += __uint_as_float(o.x); gp[1] += __uint_as_float(o.y); gp[2] += __uint_as_float(o.z); gp[3] += __uint_as_float(o.w);
                asm volatile("st.async.shared::cluster.mbarrier::complete_tx::bytes.v4.b32 [%0], {%1,%2,%3,%4}, [%5];\n"
                             ::"r"(ex ^ 0x1000000u), "r"(__float_as_uint(gp[0])), "r"(__float_as_uint(gp[1])), "r"(__float_as_uint(gp[2])), "r"(__float_as_uint(gp[3])), "r"(bar_g ^ 0x1000000u) : "memory");
                if (WDAT == 2) load_wd(WD, warp);
            }
            if (WDAT == 1 && (warp < 16 || !odd)) load_wd(WD, warp);
            if (warp >= 16 && !odd) load_wd(WE, warp + 2);
        }
        STAMP(20);
        if (warp < 9) {
            mbar_wait(bar_g);
            const uint4 u = lds128(ex);
            const uint32_t G = pack_bf16(gp[0] + __uint_as_float(u.x), gp[1] + __uint_as_float(u.y)), U = pack_bf16(gp[2] + __uint_as_float(u.z), gp[3] + __uint_as_float(u.w));
            const float G0 = bf_lo(G), G1 = bf_hi(G);
            sts32(sb + SM_GU + tid * 4, hmul2_bf(pack_bf16(G0 * rcp_approx(1.0f + ex2_approx(G0 * -1.4426950408889634f)), G1 * rcp_approx(1.0f + ex2_approx(G1 * -1.4426950408889634f))), U));
        }
        bar_sync(7, 576);
        STAMP(21);
        if (warp < 16 || !odd) {
            uint32_t gb[9];
            ldsm_x4_t(gb[0], gb[1], gb[2], gb[3], sb + SM_GU + lane * 16);
            ldsm_x4_t(gb[4], gb[5], gb[6], gb[7], sb + SM_GU + 512 + lane * 16);
            ldsm_x1_t(gb[8], sb + SM_GU + 1024 + (lane & 7) * 16);
            auto down = [&](const uint32_t (&W)[18], uint32_t* dst) {
                float c4[4] = {0.f, 0.f, 0.f, 0.f}, d4[4] = {0.f, 0.f, 0.f, 0.f}, e4[4] = {0.f, 0.f, 0.f, 0.f};
                mma_bf16(c4, W[0], W[1], W[2], W[3], gb[0], gb[1]);
                mma_bf16(d4, W[4], W[5], W[6], W[7], gb[2], gb[3]);
                mma_bf16(e4, W[8], W[9], W[10], W[11], gb[4], gb[5]);
                mma_bf16_k8(c4, W[16], W[17], gb[8]);
                mma_bf16(d4, W[12], W[13], W[14], W[15], gb[6], gb[7]);
                const float v0 = (c4[0] + e4[0]) + d4[0], v1 = (c4[1] + e4[1]) + d4[1], v2 = (c4[2] + e4[2]) + d4[2], v3 = (c4[3] + e4[3]) + d4[3];
                const uint32_t e = max(max(__float_as_uint(fmaxf(fabsf(v0), fabsf(v1))), __float_as_uint(fmaxf(fabsf(v2), fabsf(v3)))), 16u << 23) >> 23;
                const float sc = __uint_as_float((245u - e) << 23);
                stg64(dst, pack_f16(v0 * sc, v1 * sc) | ((e * 0x8002000u) & 0x60006000u), pack_f16(v2 * sc, v3 * sc) | ((e * 0x800200u) & 0x60006000u));
            };
            if (warp >= 16) { down(WE, pp + 4 * 64 * 32); down(WD, pp); }
            else down(WD, pp);
        }
        asm volatile("cp.async.bulk.wait_group.read 0;\n" ::: "memory");
        STAMP(22);
        if (b < 72 && warp < 16) {
            const uint2* src = reinterpret_cast<const uint2*>(p.s->part) + (unsigned)(b * 1024 + tid);
            uint2 a, c;
            int it = 0;
            a = ld_poll64(src); c = ld_poll64(src + 512);
            while (!__all_sync(0xffffffffu, a.y && c.y)) {
                a = ld_poll64(src); c = ld_poll64(src + 512);
                if (++it > SPIN_LIMIT) TRAP();
            }
            STAMP(24);
            const float ea = __uint_as_float((((a.y & 0x60006000u) | ((a.x >> 4) & 0x06000600u)) * 0x4001u) & 0x7f800000u);
            const float ec = __uint_as_float((((c.y & 0x60006000u) | ((c.x >> 4) & 0x06000600u)) * 0x4001u) & 0x7f800000u);
            a.x &= 0x9fff9fffu; a.y &= 0x9fff9fffu; c.x &= 0x9fff9fffu; c.y &= 0x9fff9fffu;
            const float s0 = fmaf(h_lo(a.x), ea, h_lo(c.x) * ec), s1 = fmaf(h_hi(a.x), ea, h_hi(c.x) * ec), s2 = fmaf(h_lo(a.y), ea, h_lo(c.y) * ec), s3 = fmaf(h_hi(a.y), ea, h_hi(c.y) * ec);
            const bool up = lane & 16;
            const float r0 = __shfl_xor_sync(0xffffffffu, up ? s0 : s2, 16), r1 = __shfl_xor_sync(0xffffffffu, up ? s1 : s3, 16);
            const uint32_t fa = sb + SM_FIN + ((lane & 15) * 4 + (up ? 2 : 0)) * 80 + warp * 4;
            stsf(fa, (up ? s2 : s0) + r0); stsf(fa + 80, (up ? s3 : s1) + r1);
            bar_arrive(14, 576);
        }
    }
    STAMP(25);
    }
}

typedef CUresult (*PFN_tmEncode)(CUtensorMap*, CUtensorMapDataType, cuuint32_t, void*, const cuuint64_t*, const cuuint64_t*, const cuuint32_t*,
                                 const cuuint32_t*, CUtensorMapInterleave, CUtensorMapSwizzle, CUtensorMapL2promotion, CUtensorMapFloatOOBfill);

extern "C" void kernel_launch(void* const* d_in, const int* in_sizes, int n_in, void* d_out, int out_size) {
    Params p;
    p.x = (const bf16*)d_in[0];
    p.lar = (const bf16*)d_in[1];
    p.aim = (const bf16*)d_in[2];
    p.cre = (const bf16*)d_in[3];
    p.cim = (const bf16*)d_in[4];
    p.ldt = (const bf16*)d_in[5];
    p.dsk = (const bf16*)d_in[6];
    p.wr = (const bf16*)d_in[8];
    p.out = (bf16*)d_out;
    static PFN_tmEncode enc = nullptr;
    static void* scratch = nullptr;
    if (!enc) {
        cudaFuncSetAttribute(fused_kernel, cudaFuncAttributeMaxDynamicSharedMemorySize, SMEM_TOTAL);
        void* fn = nullptr;
        cudaDriverEntryPointQueryResult qr;
        cudaGetDriverEntryPoint("cuTensorMapEncodeTiled", &fn, cudaEnableDefault, &qr);
        enc = (PFN_tmEncode)fn;
        cudaGetSymbolAddress(&scratch, g_scratch);
    }
    p.s = (Scratch*)scratch;
    CUtensorMap tm_g, tm_u, tm_d, tm_x, tm_y, tm_z;
    const cuuint64_t dims[2] = {FF, DM}, strides[1] = {FF * 2};
    const cuuint32_t box[2] = {72, 48}, es[2] = {1, 1};
    enc(&tm_g, CU_TENSOR_MAP_DATA_TYPE_BFLOAT16, 2, d_in[9], dims, strides, box, es, CU_TENSOR_MAP_INTERLEAVE_NONE, CU_TENSOR_MAP_SWIZZLE_NONE,
        CU_TENSOR_MAP_L2_PROMOTION_NONE, CU_TENSOR_MAP_FLOAT_OOB_FILL_NONE);
    const cuuint32_t ubox[2] = {72, 144}, es3[3] = {1, 1, 1};
    enc(&tm_u, CU_TENSOR_MAP_DATA_TYPE_BFLOAT16, 2, d_in[10], dims, strides, ubox, es, CU_TENSOR_MAP_INTERLEAVE_NONE, CU_TENSOR_MAP_SWIZZLE_NONE,
        CU_TENSOR_MAP_L2_PROMOTION_NONE, CU_TENSOR_MAP_FLOAT_OOB_FILL_NONE);
    const cuuint64_t ddims[2] = {DM, FF}, dstrides[1] = {DM * 2};
    const cuuint32_t dbox[2] = {64, 72};
    enc(&tm_d, CU_TENSOR_MAP_DATA_TYPE_BFLOAT16, 2, d_in[11], ddims, dstrides, dbox, es, CU_TENSOR_MAP_INTERLEAVE_NONE, CU_TENSOR_MAP_SWIZZLE_128B,
        CU_TENSOR_MAP_L2_PROMOTION_NONE, CU_TENSOR_MAP_FLOAT_OOB_FILL_NONE);
    const cuuint64_t xdims[3] = {DM, LSEQ / 16, 16}, xstrides[2] = {16 * DM * 2, DM * 2};
    const cuuint32_t xbox[3] = {8, LSEQ / 16, 8};
    enc(&tm_x, CU_TENSOR_MAP_DATA_TYPE_BFLOAT16, 3, d_in[0], xdims, xstrides, xbox, es3, CU_TENSOR_MAP_INTERLEAVE_NONE, CU_TENSOR_MAP_SWIZZLE_NONE,
        CU_TENSOR_MAP_L2_PROMOTION_NONE, CU_TENSOR_MAP_FLOAT_OOB_FILL_NONE);
    const cuuint64_t ydims[3] = {DM * 32, 16, 4}, ystrides[2] = {DM * 64, 16 * DM * 64};
    const cuuint32_t ybox[3] = {128, 16, 2}, zbox[3] = {32, 16, 2};
    enc(&tm_y, CU_TENSOR_MAP_DATA_TYPE_BFLOAT16, 3, p.s->y, ydims, ystrides, ybox, es3, CU_TENSOR_MAP_INTERLEAVE_NONE, CU_TENSOR_MAP_SWIZZLE_NONE,
        CU_TENSOR_MAP_L2_PROMOTION_NONE, CU_TENSOR_MAP_FLOAT_OOB_FILL_NONE);
    enc(&tm_z, CU_TENSOR_MAP_DATA_TYPE_BFLOAT16, 3, p.s->y, ydims, ystrides, zbox, es3, CU_TENSOR_MAP_INTERLEAVE_NONE, CU_TENSOR_MAP_SWIZZLE_NONE,
        CU_TENSOR_MAP_L2_PROMOTION_NONE, CU_TENSOR_MAP_FLOAT_OOB_FILL_NONE);
    fused_kernel<<<NCTA, NTHR, SMEM_TOTAL>>>(p, tm_g, tm_u, tm_d, tm_x, tm_y, tm_z);
}
```

```cpp
#include <cuda_runtime.h>
#include <cuda.h>
#include <cuda_fp16.h>
#include <cuda_bf16.h>
#include <stdint.h>

#define LSEQ 2048
#define DM 576
#define NST 128
#define FF 4608
#define NSEL 8
#define NCTA 128
#define NTHR 640
#define NWRK 640

typedef __nv_bfloat16 bf16;

#define SM_WD 0
#define SM_WG 46080
#define SM_WR 82944
#define SM_WU 92160
#define SM_ZERO 32768
#define SM_XC 16384
#define SM_TB 96000
#define SM_PL 129024
#define PL_B 10752
#define SM_XT (SM_TB + 20 * TBW)
#define SM_U (SM_XT + 18432)
#define UPAD 8
#define ULO_B ((UPAD + 128) * 16)
#define USLOT_B (2 * ULO_B)
#define SM_KW (SM_U + 5 * USLOT_B)
#define KW_B 3600
#define KW_T2 1152
#define KW_KH 656
#define KW_T3 2464
#define SM_MISC (SM_KW + 5 * KW_B)
#define SM_LNP (SM_MISC + 576)
#define SMEM_TOTAL (SM_LNP + 3840)
#define TBP 112
#define TBW (32 * TBP)
#define SM_OUT SM_PL
#define OUT_PITCH 1216
#define SM_XS (SM_PL + 19456)
#define XS_PITCH 592
#define SM_EX (SM_PL + 24320)
#define SM_FIN SM_KW
#define SM_GU (SM_PL + 33536)

struct __align__(128) Scratch {
    unsigned hint[8 * 32];
    unsigned flag[32];
    uint32_t sc[NCTA * 32];
    uint32_t st[LSEQ * 2];
    uint32_t uT[64 * (LSEQ / 2)];
    uint32_t y[NCTA * DM * 8];
    uint32_t part[72 * 64 * 32];
    uint32_t rows[(2 * NCTA + NSEL) * DM];
};
__device__ Scratch g_scratch;
#define STAMP(i)
#define DBG(i, v)

__device__ __forceinline__ float rbf(float x) {
    uint32_t r;
    asm("cvt.rn.bf16x2.f32 %0, %1, %2;\n" : "=r"(r) : "f"(x), "f"(0.f));
    return __uint_as_float(r & 0xffff0000u);
}
__device__ __forceinline__ uint32_t pack_bf16(float lo, float hi) {
    uint32_t r;
    asm("cvt.rn.bf16x2.f32 %0, %1, %2;\n" : "=r"(r) : "f"(hi), "f"(lo));
    return r;
}
__device__ __forceinline__ uint32_t pack_f16(float lo, float hi) {
    uint32_t r;
    asm("cvt.rn.f16x2.f32 %0, %1, %2;\n" : "=r"(r) : "f"(hi), "f"(lo));
    return r;
}
__device__ __forceinline__ uint32_t pack_f16_rz(float lo, float hi) {
    uint32_t r;
    asm("cvt.rz.f16x2.f32 %0, %1, %2;\n" : "=r"(r) : "f"(hi), "f"(lo));
    return r;
}
__device__ __forceinline__ float bf_lo(uint32_t w) { return __uint_as_float(w << 16); }
__device__ __forceinline__ float bf_hi(uint32_t w) { return __uint_as_float(w & 0xffff0000u); }
__device__ __forceinline__ uint32_t hadd2_bf(uint32_t a, uint32_t b) {
    __nv_bfloat162 r = __hadd2_rn(*reinterpret_cast<__nv_bfloat162*>(&a), *reinterpret_cast<__nv_bfloat162*>(&b));
    return *reinterpret_cast<uint32_t*>(&r);
}
__device__ __forceinline__ uint32_t hsub2_bf(uint32_t a, uint32_t b) {
    __nv_bfloat162 r = __hsub2_rn(*reinterpret_cast<__nv_bfloat162*>(&a), *reinterpret_cast<__nv_bfloat162*>(&b));
    return *reinterpret_cast<uint32_t*>(&r);
}
__device__ __forceinline__ uint32_t hmul2_bf(uint32_t a, uint32_t b) {
    __nv_bfloat162 r = __hmul2_rn(*reinterpret_cast<__nv_bfloat162*>(&a), *reinterpret_cast<__nv_bfloat162*>(&b));
    return *reinterpret_cast<uint32_t*>(&r);
}
__device__ __forceinline__ uint32_t hfma2_bf(uint32_t a, uint32_t b, uint32_t c) { uint32_t r; asm("fma.rn.bf16x2 %0, %1, %2, %3;\n" : "=r"(r) : "r"(a), "r"(b), "r"(c)); return r; }
__device__ __forceinline__ uint32_t hmul2(uint32_t a, uint32_t b) { uint32_t r; asm("mul.rn.f16x2 %0, %1, %2;\n" : "=r"(r) : "r"(a), "r"(b)); return r; }
__device__ __forceinline__ uint32_t hadd2(uint32_t a, uint32_t b) { uint32_t r; asm("add.rn.f16x2 %0, %1, %2;\n" : "=r"(r) : "r"(a), "r"(b)); return r; }
__device__ __forceinline__ uint32_t hfma2(uint32_t a, uint32_t b, uint32_t c) { uint32_t r; asm("fma.rn.f16x2 %0, %1, %2, %3;\n" : "=r"(r) : "r"(a), "r"(b), "r"(c)); return r; }
__device__ __forceinline__ uint32_t nzw(uint32_t w) { return w ? w : 0x8000u; }
__device__ __forceinline__ uint32_t nzf(float f) { const uint32_t w = __float_as_uint(f); return w ? w : 0x80000000u; }
__device__ __forceinline__ uint32_t smem_u32(const void* p) { return (uint32_t)__cvta_generic_to_shared(p); }
__device__ __forceinline__ uint32_t lds32(uint32_t addr) {
    uint32_t v;
    asm volatile("ld.shared.u32 %0, [%1];\n" : "=r"(v) : "r"(addr) : "memory");
    return v;
}
__device__ __forceinline__ uint32_t lds16(uint32_t addr) {
    unsigned short v;
    asm volatile("ld.shared.u16 %0, [%1];\n" : "=h"(v) : "r"(addr) : "memory");
    return v;
}
__device__ __forceinline__ uint2 lds64(uint32_t addr) {
    uint2 v;
    asm volatile("ld.shared.v2.u32 {%0,%1}, [%2];\n" : "=r"(v.x), "=r"(v.y) : "r"(addr) : "memory");
    return v;
}
__device__ __forceinline__ uint4 lds128(uint32_t addr) {
    uint4 v;
    asm volatile("ld.shared.v4.u32 {%0,%1,%2,%3}, [%4];\n" : "=r"(v.x), "=r"(v.y), "=r"(v.z), "=r"(v.w) : "r"(addr) : "memory");
    return v;
}
__device__ __forceinline__ float ldsf(uint32_t addr) { return __uint_as_float(lds32(addr)); }
__device__ __forceinline__ void sts32(uint32_t addr, uint32_t v) { asm volatile("st.shared.u32 [%0], %1;\n" ::"r"(addr), "r"(v) : "memory"); }
__device__ __forceinline__ void stsf(uint32_t addr, float v) { sts32(addr, __float_as_uint(v)); }
__device__ __forceinline__ void sts64(uint32_t addr, uint32_t a, uint32_t b) { asm volatile("st.shared.v2.u32 [%0], {%1,%2};\n" ::"r"(addr), "r"(a), "r"(b) : "memory"); }
__device__ __forceinline__ void sts64f(uint32_t addr, float a, float b) { sts64(addr, __float_as_uint(a), __float_as_uint(b)); }
__device__ __forceinline__ void sts128(uint32_t addr, uint32_t a, uint32_t b, uint32_t c, uint32_t d) {
    asm volatile("st.shared.v4.u32 [%0], {%1,%2,%3,%4};\n" ::"r"(addr), "r"(a), "r"(b), "r"(c), "r"(d) : "memory");
}
__device__ __forceinline__ void sts128f(uint32_t addr, const float (&v)[4]) {
    sts128(addr, __float_as_uint(v[0]), __float_as_uint(v[1]), __float_as_uint(v[2]), __float_as_uint(v[3]));
}
__device__ __forceinline__ void ldsm_x4(uint32_t& r0, uint32_t& r1, uint32_t& r2, uint32_t& r3, uint32_t addr) {
    asm volatile("ldmatrix.sync.aligned.m8n8.x4.shared.b16 {%0,%1,%2,%3}, [%4];\n"
                 : "=r"(r0), "=r"(r1), "=r"(r2), "=r"(r3) : "r"(addr) : "memory");
}
__device__ __forceinline__ void ldsm_x4_t(uint32_t& r0, uint32_t& r1, uint32_t& r2, uint32_t& r3, uint32_t addr) {
    asm volatile("ldmatrix.sync.aligned.m8n8.x4.trans.shared.b16 {%0,%1,%2,%3}, [%4];\n"
                 : "=r"(r0), "=r"(r1), "=r"(r2), "=r"(r3) : "r"(addr) : "memory");
}
__device__ __forceinline__ void ldsm_x2_t(uint32_t& r0, uint32_t& r1, uint32_t addr) {
    asm volatile("ldmatrix.sync.aligned.m8n8.x2.trans.shared.b16 {%0,%1}, [%2];\n" : "=r"(r0), "=r"(r1) : "r"(addr) : "memory");
}
__device__ __forceinline__ void ldsm_x1_t(uint32_t& r0, uint32_t addr) {
    asm volatile("ldmatrix.sync.aligned.m8n8.x1.trans.shared.b16 {%0}, [%1];\n" : "=r"(r0) : "r"(addr) : "memory");
}
__device__ __forceinline__ uint32_t movm(uint32_t a) {
    uint32_t d;
    asm volatile("movmatrix.sync.aligned.m8n8.trans.b16 %0, %1;\n" : "=r"(d) : "r"(a));
    return d;
}
__device__ __forceinline__ void mma_f16(float (&c)[4], uint32_t a0, uint32_t a1, uint32_t a2, uint32_t a3, uint32_t b0, uint32_t b1) {
    asm volatile(
        "mma.sync.aligned.m16n8k16.row.col.f32.f16.f16.f32 {%0,%1,%2,%3}, {%4,%5,%6,%7}, {%8,%9}, {%0,%1,%2,%3};\n"
        : "+f"(c[0]), "+f"(c[1]), "+f"(c[2]), "+f"(c[3])
        : "r"(a0), "r"(a1), "r"(a2), "r"(a3), "r"(b0), "r"(b1));
}
__device__ __forceinline__ void mma_bf16(float (&c)[4], uint32_t a0, uint32_t a1, uint32_t a2, uint32_t a3, uint32_t b0, uint32_t b1) {
    asm volatile(
        "mma.sync.aligned.m16n8k16.row.col.f32.bf16.bf16.f32 {%0,%1,%2,%3}, {%4,%5,%6,%7}, {%8,%9}, {%0,%1,%2,%3};\n"
        : "+f"(c[0]), "+f"(c[1]), "+f"(c[2]), "+f"(c[3])
        : "r"(a0), "r"(a1), "r"(a2), "r"(a3), "r"(b0), "r"(b1));
}
__device__ __forceinline__ void mma_bf16_k8(float (&c)[4], uint32_t a0, uint32_t a1, uint32_t b0) {
    asm volatile("mma.sync.aligned.m16n8k8.row.col.f32.bf16.bf16.f32 {%0,%1,%2,%3}, {%4,%5}, {%6}, {%0,%1,%2,%3};\n"
        : "+f"(c[0]), "+f"(c[1]), "+f"(c[2]), "+f"(c[3]) : "r"(a0), "r"(a1), "r"(b0));
}
__device__ __forceinline__ void bar_sync(int id, int n) { asm volatile("bar.sync %0, %1;\n" ::"r"(id), "r"(n) : "memory"); }
__device__ __forceinline__ void bar_arrive(int id, int n) { asm volatile("bar.arrive %0, %1;\n" ::"r"(id), "r"(n) : "memory"); }
__device__ __forceinline__ bool bar_or(int id, int n, bool v) {
    uint32_t r;
    asm volatile("{\n.reg .pred p, q;\nsetp.ne.u32 p, %3, 0;\nbar.red.or.pred q, %1, %2, p;\nselp.u32 %0, 1, 0, q;\n}\n" : "=r"(r) : "r"(id), "r"(n), "r"((uint32_t)v) : "memory");
    return r;
}
__device__ __forceinline__ uint4 ld_poll(const void* p) {
    uint4 v;
    asm volatile("ld.relaxed.gpu.global.v4.u32 {%0,%1,%2,%3}, [%4];\n" : "=r"(v.x), "=r"(v.y), "=r"(v.z), "=r"(v.w) : "l"(p) : "memory");
    return v;
}
template <class T> __device__ __forceinline__ T* pin(T* p, uint32_t z) {
    uint32_t lo, hi;
    asm volatile("mov.b64 {%0, %1}, %2;\n" : "=r"(lo), "=r"(hi) : "l"(p));
    asm volatile("xor.b32 %0, %0, %1;\n" : "+r"(lo) : "r"(z));
    asm volatile("xor.b32 %0, %0, %1;\n" : "+r"(hi) : "r"(z));
    asm volatile("mov.b64 %0, {%1, %2};\n" : "=l"(p) : "r"(lo), "r"(hi));
    return p;
}
__device__ __forceinline__ uint32_t pin(uint32_t a, uint32_t z) { asm volatile("xor.b32 %0, %0, %1;\n" : "+r"(a) : "r"(z)); return a; }
__device__ __forceinline__ uint2 ld_poll64(const void* p) {
    uint2 v;
    asm volatile("ld.relaxed.gpu.global.v2.u32 {%0,%1}, [%2];\n" : "=r"(v.x), "=r"(v.y) : "l"(p) : "memory");
    return v;
}
__device__ __forceinline__ uint32_t ld_poll32(const void* p) {
    uint32_t v;
    asm volatile("ld.relaxed.gpu.global.u32 %0, [%1];\n" : "=r"(v) : "l"(p) : "memory");
    return v;
}
__device__ __forceinline__ uint4 ldg128(const void* p) {
    uint4 v;
    asm volatile("ld.global.nc.v4.u32 {%0,%1,%2,%3}, [%4];\n" : "=r"(v.x), "=r"(v.y), "=r"(v.z), "=r"(v.w) : "l"(p));
    return v;
}
__device__ __forceinline__ uint2 ldg64(const void* p) {
    uint2 v;
    asm volatile("ld.global.nc.v2.u32 {%0,%1}, [%2];\n" : "=r"(v.x), "=r"(v.y) : "l"(p));
    return v;
}
__device__ __forceinline__ uint32_t ldg16(const void* p) {
    uint32_t v;
    asm volatile("ld.global.nc.u16 %0, [%1];\n" : "=r"(v) : "l"(p));
    return v;
}
__device__ __forceinline__ void stg128(void* p, uint32_t a, uint32_t b, uint32_t c, uint32_t d) {
    asm volatile("st.global.v4.u32 [%0], {%1,%2,%3,%4};\n" ::"l"(p), "r"(a), "r"(b), "r"(c), "r"(d) : "memory");
}
__device__ __forceinline__ void stg64(void* p, uint32_t a, uint32_t b) { asm volatile("st.global.v2.u32 [%0], {%1,%2};\n" ::"l"(p), "r"(a), "r"(b) : "memory"); }
__device__ __forceinline__ void stg32(void* p, uint32_t a) { asm volatile("st.global.u32 [%0], %1;\n" ::"l"(p), "r"(a) : "memory"); }
__device__ __forceinline__ bool all_nz(const uint4& v) { return v.x && v.y && v.z && v.w; }
#define SPIN_LIMIT (1 << 21)
#define TRAP() __trap()
__device__ __forceinline__ void hint_arrive(unsigned* g_hint, int idx, int sub) {
    asm volatile("red.relaxed.gpu.global.add.u32 [%0], 1;\n" ::"l"(&g_hint[sub * 32 + idx]) : "memory");
}
__device__ __forceinline__ void hint_wait(const unsigned* g_hint, int idx, unsigned target) {
    unsigned l;
    asm volatile("mov.u32 %0, %%laneid;" : "=r"(l));
    const unsigned* c = &g_hint[(l & 7) * 32 + idx];
    int it = 0;
    while (__any_sync(0xffffffffu, (int)(ld_poll32(c) - target) < 0)) { if (++it > SPIN_LIMIT) TRAP(); }
}
__device__ __forceinline__ void mbar_init(uint32_t bar, uint32_t cnt) { asm volatile("mbarrier.init.shared::cta.b64 [%0], %1;\n" ::"r"(bar), "r"(cnt) : "memory"); }
__device__ __forceinline__ void mbar_expect(uint32_t bar, uint32_t bytes) {
    asm volatile("mbarrier.arrive.expect_tx.shared::cta.b64 _, [%0], %1;\n" ::"r"(bar), "r"(bytes) : "memory");
}
__device__ __forceinline__ void mbar_arrive(uint32_t bar) { asm volatile("mbarrier.arrive.shared::cta.b64 _, [%0];\n" ::"r"(bar) : "memory"); }
__device__ __forceinline__ void mbar_wait_cluster(uint32_t bar) {
    asm volatile(
        "{\n.reg .pred p;\n"
        "W_%=:\n"
        "mbarrier.try_wait.parity.acquire.cluster.shared::cta.b64 p, [%0], 0;\n"
        "@!p bra W_%=;\n}\n" ::"r"(bar) : "memory");
}
__device__ __forceinline__ void mbar_wait(uint32_t bar) {
    asm volatile(
        "{\n.reg .pred p;\n"
        "W_%=:\n"
        "mbarrier.try_wait.parity.shared::cta.b64 p, [%0], 0;\n"
        "@!p bra W_%=;\n}\n" ::"r"(bar) : "memory");
}
__device__ __forceinline__ void mbar_wait_parity(uint32_t bar, uint32_t par) {
    asm volatile(
        "{\n.reg .pred p;\n"
        "W_%=:\n"
        "mbarrier.try_wait.parity.shared::cta.b64 p, [%0], %1;\n"
        "@!p bra W_%=;\n}\n" ::"r"(bar), "r"(par) : "memory");
}
__device__ __forceinline__ bool mbar_test(uint32_t bar) {
    uint32_t r;
    asm volatile("{\n.reg .pred p;\nmbarrier.test_wait.parity.shared::cta.b64 p, [%1], 0;\nselp.u32 %0, 1, 0, p;\n}\n" : "=r"(r) : "r"(bar) : "memory");
    return __any_sync(0xffffffffu, r);
}
__device__ __forceinline__ void bulk_g2s(uint32_t dst, const void* src, uint32_t bytes, uint32_t bar) {
    asm volatile("cp.async.bulk.shared::cluster.global.mbarrier::complete_tx::bytes [%0], [%1], %2, [%3];\n" ::"r"(dst), "l"(src), "r"(bytes), "r"(bar) : "memory");
}
__device__ __forceinline__ void bulk_s2g(void* dst, uint32_t src, uint32_t bytes) {
    asm volatile("cp.async.bulk.global.shared::cta.bulk_group [%0], [%1], %2;\ncp.async.bulk.commit_group;\n" ::"l"(dst), "r"(src), "r"(bytes) : "memory");
}
__device__ __forceinline__ void tma_2d(uint32_t dst, const CUtensorMap* tm, int c0, int c1, uint32_t bar) {
    asm volatile("cp.async.bulk.tensor.2d.shared::cluster.global.mbarrier::complete_tx::bytes [%0], [%1, {%3, %4}], [%2];\n"
                 ::"r"(dst), "l"(tm), "r"(bar), "r"(c0), "r"(c1) : "memory");
}
__device__ __forceinline__ void tma_3d(uint32_t dst, const CUtensorMap* tm, int c0, int c1, int c2, uint32_t bar) {
    asm volatile("cp.async.bulk.tensor.3d.shared::cluster.global.mbarrier::complete_tx::bytes [%0], [%1, {%3, %4, %5}], [%2];\n"
                 ::"r"(dst), "l"(tm), "r"(bar), "r"(c0), "r"(c1), "r"(c2) : "memory");
}
__device__ __forceinline__ void tma_3d_mc(uint32_t dst, const CUtensorMap* tm, int c0, int c1, int c2, uint32_t bar) {
    asm volatile("cp.async.bulk.tensor.3d.shared::cluster.global.mbarrier::complete_tx::bytes.multicast::cluster [%0], [%1, {%3, %4, %5}], [%2], %6;\n"
                 ::"r"(dst), "l"(tm), "r"(bar), "r"(c0), "r"(c1), "r"(c2), "h"((unsigned short)3) : "memory");
}
__device__ __forceinline__ void tma_st_3d(const CUtensorMap* tm, uint32_t src, int c0, int c1, int c2) {
    asm volatile("cp.async.bulk.tensor.3d.global.shared::cta.bulk_group [%0, {%2, %3, %4}], [%1];\ncp.async.bulk.commit_group;\n"
                 ::"l"(tm), "r"(src), "r"(c0), "r"(c1), "r"(c2) : "memory");
}
__device__ __forceinline__ void l2_prefetch(const void* src, uint32_t bytes) {
    asm volatile("cp.async.bulk.prefetch.L2.global [%0], %1;\n" ::"l"(src), "r"(bytes) : "memory");
}
__device__ __forceinline__ bool elect_one() {
    uint32_t r;
    asm volatile("{\n.reg .pred p;\nelect.sync _|p, 0xffffffff;\nselp.u32 %0, 1, 0, p;\n}\n" : "=r"(r));
    return r;
}
__device__ __forceinline__ void fence_async() { asm volatile("fence.proxy.async.shared::cta;\n" ::: "memory"); }

__device__ __forceinline__ float2 cmul(float2 a, float2 b) {
    return make_float2(fmaf(a.x, b.x, -a.y * b.y), fmaf(a.x, b.y, a.y * b.x));
}
__device__ __forceinline__ float2 csq(float2 a) {
    float p = a.x * a.y;
    return make_float2(fmaf(a.x, a.x, -a.y * a.y), p + p);
}
__device__ __forceinline__ float2 cexp_e(float lr2, float rh, float rl, float e) {
    float m;
    asm("ex2.approx.ftz.f32 %0, %1;\n" : "=f"(m) : "f"(lr2 * e));
    const float a = rh * e;
    const float r = fmaf(rl, e, a - rintf(a)) * 6.283185307179586f;
    return make_float2(m * __cosf(r), m * __sinf(r));
}
__device__ __forceinline__ float rcp_approx(float x) { float r; asm("rcp.approx.ftz.f32 %0, %1;\n" : "=f"(r) : "f"(x)); return r; }
__device__ __forceinline__ float ex2_approx(float x) { float r; asm("ex2.approx.ftz.f32 %0, %1;\n" : "=f"(r) : "f"(x)); return r; }
__device__ __forceinline__ float sqrt_approx(float x) { float r; asm("sqrt.approx.ftz.f32 %0, %1;\n" : "=f"(r) : "f"(x)); return r; }

__device__ __forceinline__ void wg_fence() { asm volatile("wgmma.fence.sync.aligned;\n" ::: "memory"); }
__device__ __forceinline__ void wg_commit() { asm volatile("wgmma.commit_group.sync.aligned;\n" ::: "memory"); }
__device__ __forceinline__ void wg_wait0() { asm volatile("wgmma.wait_group.sync.aligned 0;\n" ::: "memory"); }
template <int T0, int NT> __device__ __forceinline__ void wg_h(uint32_t (&acc)[32], const uint32_t (&a)[4], uint64_t desc);
template <> __device__ __forceinline__ void wg_h<0, 16>(uint32_t (&acc)[32], const uint32_t (&a)[4], uint64_t desc) {
    asm volatile("wgmma.mma_async.sync.aligned.m64n128k16.f16.f16.f16 {%0,%1,%2,%3,%4,%5,%6,%7,%8,%9,%10,%11,%12,%13,%14,%15,%16,%17,%18,%19,%20,%21,%22,%23,%24,%25,%26,%27,%28,%29,%30,%31}, {%32,%33,%34,%35}, %36, 1, 1, 1, 0;\n"
                 : "+r"(acc[0]), "+r"(acc[1]), "+r"(acc[2]), "+r"(acc[3]), "+r"(acc[4]), "+r"(acc[5]), "+r"(acc[6]), "+r"(acc[7]), "+r"(acc[8]), "+r"(acc[9]), "+r"(acc[10]), "+r"(acc[11]), "+r"(acc[12]), "+r"(acc[13]), "+r"(acc[14]), "+r"(acc[15]), "+r"(acc[16]), "+r"(acc[17]), "+r"(acc[18]), "+r"(acc[19]), "+r"(acc[20]), "+r"(acc[21]), "+r"(acc[22]), "+r"(acc[23]), "+r"(acc[24]), "+r"(acc[25]), "+r"(acc[26]), "+r"(acc[27]), "+r"(acc[28]), "+r"(acc[29]), "+r"(acc[30]), "+r"(acc[31])
                 : "r"(a[0]), "r"(a[1]), "r"(a[2]), "r"(a[3]), "l"(desc));
}
template <> __device__ __forceinline__ void wg_h<4, 4>(uint32_t (&acc)[32], const uint32_t (&a)[4], uint64_t desc) {
    asm volatile("wgmma.mma_async.sync.aligned.m64n32k16.f16.f16.f16 {%0,%1,%2,%3,%4,%5,%6,%7}, {%8,%9,%10,%11}, %12, 1, 1, 1, 0;\n"
                 : "+r"(acc[8]), "+r"(acc[9]), "+r"(acc[10]), "+r"(acc[11]), "+r"(acc[12]), "+r"(acc[13]), "+r"(acc[14]), "+r"(acc[15])
                 : "r"(a[0]), "r"(a[1]), "r"(a[2]), "r"(a[3]), "l"(desc));
}
template <> __device__ __forceinline__ void wg_h<8, 4>(uint32_t (&acc)[32], const uint32_t (&a)[4], uint64_t desc) {
    asm volatile("wgmma.mma_async.sync.aligned.m64n32k16.f16.f16.f16 {%0,%1,%2,%3,%4,%5,%6,%7}, {%8,%9,%10,%11}, %12, 1, 1, 1, 0;\n"
                 : "+r"(acc[16]), "+r"(acc[17]), "+r"(acc[18]), "+r"(acc[19]), "+r"(acc[20]), "+r"(acc[21]), "+r"(acc[22]), "+r"(acc[23])
                 : "r"(a[0]), "r"(a[1]), "r"(a[2]), "r"(a[3]), "l"(desc));
}
template <> __device__ __forceinline__ void wg_h<12, 4>(uint32_t (&acc)[32], const uint32_t (&a)[4], uint64_t desc) {
    asm volatile("wgmma.mma_async.sync.aligned.m64n32k16.f16.f16.f16 {%0,%1,%2,%3,%4,%5,%6,%7}, {%8,%9,%10,%11}, %12, 1, 1, 1, 0;\n"
                 : "+r"(acc[24]), "+r"(acc[25]), "+r"(acc[26]), "+r"(acc[27]), "+r"(acc[28]), "+r"(acc[29]), "+r"(acc[30]), "+r"(acc[31])
                 : "r"(a[0]), "r"(a[1]), "r"(a[2]), "r"(a[3]), "l"(desc));
}
template <> __device__ __forceinline__ void wg_h<0, 8>(uint32_t (&acc)[32], const uint32_t (&a)[4], uint64_t desc) {
    asm volatile("wgmma.mma_async.sync.aligned.m64n64k16.f16.f16.f16 {%0,%1,%2,%3,%4,%5,%6,%7,%8,%9,%10,%11,%12,%13,%14,%15}, {%16,%17,%18,%19}, %20, 1, 1, 1, 0;\n"
                 : "+r"(acc[0]), "+r"(acc[1]), "+r"(acc[2]), "+r"(acc[3]), "+r"(acc[4]), "+r"(acc[5]), "+r"(acc[6]), "+r"(acc[7]), "+r"(acc[8]), "+r"(acc[9]), "+r"(acc[10]), "+r"(acc[11]), "+r"(acc[12]), "+r"(acc[13]), "+r"(acc[14]), "+r"(acc[15])
                 : "r"(a[0]), "r"(a[1]), "r"(a[2]), "r"(a[3]), "l"(desc));
}
template <> __device__ __forceinline__ void wg_h<4, 12>(uint32_t (&acc)[32], const uint32_t (&a)[4], uint64_t desc) {
    asm volatile("wgmma.mma_async.sync.aligned.m64n96k16.f16.f16.f16 {%0,%1,%2,%3,%4,%5,%6,%7,%8,%9,%10,%11,%12,%13,%14,%15,%16,%17,%18,%19,%20,%21,%22,%23}, {%24,%25,%26,%27}, %28, 1, 1, 1, 0;\n"
                 : "+r"(acc[8]), "+r"(acc[9]), "+r"(acc[10]), "+r"(acc[11]), "+r"(acc[12]), "+r"(acc[13]), "+r"(acc[14]), "+r"(acc[15]), "+r"(acc[16]), "+r"(acc[17]), "+r"(acc[18]), "+r"(acc[19]), "+r"(acc[20]), "+r"(acc[21]), "+r"(acc[22]), "+r"(acc[23]), "+r"(acc[24]), "+r"(acc[25]), "+r"(acc[26]), "+r"(acc[27]), "+r"(acc[28]), "+r"(acc[29]), "+r"(acc[30]), "+r"(acc[31])
                 : "r"(a[0]), "r"(a[1]), "r"(a[2]), "r"(a[3]), "l"(desc));
}

#define PBYTES 4608
#define HINTW 10
#define WAS 0x0005
#define WA0 (WAS >> 12)
#define WA1 ((WAS >> 8) & 15)
#define WA2 ((WAS >> 4) & 15)
#define WA3 (WAS & 15)
#define WDAT 1
#define PAUSE 2
#define PCNT (32 + ((PAUSE & 1) ? 288 : 0) + ((PAUSE & 6) ? 320 : 64))
#define LNAT 2
#define UW 8
#define FINAT 3
#define UAT 2
#define HK 9
#define TOKEN_OF(g) (16 * ((g) & 1) + ((g) >> 2) + 2 * ((g) & 2))
#define HI2(a, b) (pack_f16_rz(__uint_as_float(a), __uint_as_float(b)) & 0xfff8fff8u)
struct Params {
    const bf16 *x, *lar, *aim, *cre, *cim, *ldt, *dsk;
    Scratch* s;
    const bf16* wr;
    bf16* out;
};

template <int NK>
__device__ __forceinline__ void ln_partial(const uint32_t (&H)[2][NK], const uint32_t (&bw)[NK], uint32_t lp, int warp, int g, int t) {
    float cs[4] = {0.f, 0.f, 0.f, 0.f}, cl[4] = {0.f, 0.f, 0.f, 0.f}, ch[4] = {0.f, 0.f, 0.f, 0.f};
#pragma unroll
    for (int k = 0; k < NK; k += 2) {
        uint32_t a0, a1, a2, a3;
        asm volatile("prmt.b32 %0, %4, %4, %8;\nprmt.b32 %1, %5, %5, %8;\nprmt.b32 %2, %6, %6, %8;\nprmt.b32 %3, %7, %7, %8;\n"
                     : "=r"(a0), "=r"(a1), "=r"(a2), "=r"(a3) : "r"(H[0][k]), "r"(H[1][k]), "r"(H[0][k + 1]), "r"(H[1][k + 1]), "r"(0x3210u + (warp >> 8)));
        mma_bf16(cl, a0, a1, a2, a3, H[0][k], H[0][k + 1]);
        mma_bf16(ch, a0, a1, a2, a3, H[1][k], H[1][k + 1]);
        mma_bf16(cs, a0, a1, a2, a3, bw[k], bw[k + 1]);
    }
    const uint32_t a = lp + (g * 20 + warp) * 4;
    if (t == 0) {
        stsf(a, cs[1]); stsf(a + 8 * 80, cs[3]);
    }
    if (t == (g >> 1)) { stsf(a + 16 * 80, (g & 1) ? cl[1] : cl[0]); stsf(a + 24 * 80, (g & 1) ? ch[3] : ch[2]); }
}
__device__ __forceinline__ float sum18(uint32_t a) {
    const uint4 p = lds128(a), q = lds128(a + 16), r = lds128(a + 32), s = lds128(a + 48);
    const uint2 u = lds64(a + 64);
#define F(x) __uint_as_float(x)
    return (((F(p.x) + F(p.y)) + (F(p.z) + F(p.w))) + ((F(q.x) + F(q.y)) + (F(q.z) + F(q.w)))) +
           (((F(r.x) + F(r.y)) + (F(r.z) + F(r.w))) + ((F(s.x) + F(s.y)) + (F(s.z) + F(s.w))) + (F(u.x) + F(u.y)));
#undef F
}
__device__ __forceinline__ float sum9(uint32_t a) {
    const uint4 p = lds128(a), q = lds128(a + 16);
#define F(x) __uint_as_float(x)
    return (((F(p.x) + F(p.y)) + (F(p.z) + F(p.w))) + ((F(q.x) + F(q.y)) + (F(q.z) + F(q.w)))) + ldsf(a + 32);
#undef F
}
template <int N>
__device__ __forceinline__ void ln_finish(uint32_t lp, int lane, float& mb, float& rc) {
    const float v = N == 9 ? sum9(lp + lane * 80) : sum18(lp + lane * 80);
    const float o = __shfl_xor_sync(0xffffffffu, v, 16);
    const float m0 = v * (1.0f / 576.0f);
    const float mean = fmaf(fmaf(-m0, 576.0f, v), 1.0f / 576.0f, m0);
    const float var = fmaxf(fmaf(-mean, mean, o * (1.0f / 576.0f)), 0.f);
    mb = rbf(mean);
    rc = rcp_approx(rbf(sqrt_approx(rbf(rbf(var) + 1e-5f))));
}
__device__ __forceinline__ uint32_t ln_apply(uint32_t w, const uint2& st) {
    uint32_t r;
    asm("{\n.reg .b16 m, t, h, l;\n.reg .b32 mm, hh, ll, d, e;\nmov.b32 {m, t}, %2;\nmov.b32 {h, l}, %3;\nmov.b32 mm, {m, m};\nmov.b32 hh, {h, h};\nmov.b32 ll, {l, l};\n"
        "sub.rn.bf16x2 d, %1, mm;\nmul.rn.bf16x2 e, d, ll;\nfma.rn.bf16x2 %0, d, hh, e;\n}\n" : "=r"(r) : "r"(w), "r"(st.x), "r"(st.y));
    return r;
}
__device__ __forceinline__ void stat_store(uint32_t a, float mb, float rc, uint32_t extra) {
    const float rh = rbf(rc);
    sts64(a, (__float_as_uint(mb) >> 16) | (extra << 16), pack_bf16(rh, rc - rh));
}

__device__ __forceinline__ void hcmul(uint32_t re, uint32_t im, uint32_t z, uint32_t& ore, uint32_t& oim) {
    asm("{\n.reg .b16 x, y;\n.reg .b32 xx, yy, ny, a, b;\nmov.b32 {x, y}, %4;\nmov.b32 xx, {x, x};\nmov.b32 yy, {y, y};\nneg.f16x2 ny, yy;\n"
        "mul.rn.f16x2 a, %2, xx;\nfma.rn.f16x2 %0, %3, ny, a;\nmul.rn.f16x2 b, %3, xx;\nfma.rn.f16x2 %1, %2, yy, b;\n}\n" : "=&r"(ore), "=r"(oim) : "r"(re), "r"(im), "r"(z));
}
__device__ __forceinline__ void hcmul(uint32_t re, uint32_t im, uint32_t zx, uint32_t zy, uint32_t& ore, uint32_t& oim) {
    asm("{\n.reg .b32 ny, a, b;\nneg.f16x2 ny, %5;\n"
        "mul.rn.f16x2 a, %2, %4;\nfma.rn.f16x2 %0, %3, ny, a;\nmul.rn.f16x2 b, %3, %4;\nfma.rn.f16x2 %1, %2, %5, b;\n}\n" : "=&r"(ore), "=r"(oim) : "r"(re), "r"(im), "r"(zx), "r"(zy));
}

struct KGen {
    uint32_t Af[4][4];
    float2 z1, z8, z64, z128, T[9];
    uint32_t zw;
};
__device__ __forceinline__ void kgen_setup(KGen& k, uint32_t pa, float dt) {
    const float A = rbf(expf(bf_lo(pa)));
    const float lr2 = -(A * dt) * 1.4426950408889634f;
    const float li = bf_hi(pa) * dt;
    const float rh = li * 0.15915494309189535f;
    const float rl = fmaf(li, 6.4206382986e-9f, fmaf(li, 0.15915494309189535f, -rh));
    k.z1 = cexp_e(lr2, rh, rl, 1.0f);
    k.z8 = cexp_e(lr2, rh, rl, 8.0f);
    k.z64 = cexp_e(lr2, rh, rl, 64.0f);
}
__device__ __forceinline__ void kgen_rows(KGen& k, uint32_t tb, int lane) {
    const float2 z8 = k.z8, z64 = k.z64;
    const uint32_t row = tb + lane * TBP;
    k.z128 = csq(z64);
    const float2 z16 = csq(z8), z32 = csq(z16), z48 = cmul(z32, z16), z80 = cmul(z64, z16), z96 = cmul(z64, z32), z112 = cmul(z64, z48);
    uint32_t re[4], im[4], a[4], b[4];
    re[0] = pack_f16(1.0f, z16.x); im[0] = pack_f16(0.0f, z16.y);
    re[1] = pack_f16(z32.x, z48.x); im[1] = pack_f16(z32.y, z48.y);
    re[2] = pack_f16(z64.x, z80.x); im[2] = pack_f16(z64.y, z80.y);
    re[3] = pack_f16(z96.x, z112.x); im[3] = pack_f16(z96.y, z112.y);
    sts128(row, re[0], re[1], re[2], re[3]);
    sts128(row + 32, im[0], im[1], im[2], im[3]);
    const uint32_t zz = pack_f16(z8.x, z8.y);
#pragma unroll
    for (int j = 0; j < 4; j++) hcmul(re[j], im[j], zz, a[j], b[j]);
    sts128(row + 16, a[0], a[1], a[2], a[3]);
    sts128(row + 48, b[0], b[1], b[2], b[3]);
    __syncwarp();
    const int mi = lane >> 3;
    const uint32_t ad = tb + (lane & 7) * TBP + mi * 16;
#pragma unroll
    for (int ks = 0; ks < 4; ks++) ldsm_x4_t(k.Af[ks][0], k.Af[ks][1], k.Af[ks][2], k.Af[ks][3], ad + ks * 8 * TBP);
}
__device__ __forceinline__ void kgen_chain(KGen& k, uint32_t pc, float cs) {
    k.T[0] = make_float2(bf_lo(pc) * cs, -bf_hi(pc) * cs);
    const float2 y1 = make_float2(k.z1.x, -k.z1.y);
#pragma unroll
    for (int c = 1; c < 8; c++) k.T[c] = cmul(k.T[c - 1], y1);
    k.T[8] = cmul(k.T[0], make_float2(k.z8.x, -k.z8.y));
}
__device__ __forceinline__ void kgen_cols(KGen& k, uint32_t tb, int lane) {
    const uint32_t row = tb + lane * TBP;
    const float2 (&T)[9] = k.T;
    const uint32_t zv = pack_f16(k.z128.x, k.z128.y), zo = __shfl_xor_sync(0xffffffffu, zv, 1);
    k.zw = (lane & 1) ? __byte_perm(zo, zv, 0x7632) : __byte_perm(zv, zo, 0x5410);
    const float2 y256 = csq(make_float2(k.z128.x, -k.z128.y)), y512 = csq(y256), y768 = cmul(y512, y256), y1024 = csq(y512);
    const float2 c1032 = cmul(T[8], y1024);
    const uint32_t r04 = pack_f16(T[0].x, T[4].x), i04 = pack_f16(T[0].y, T[4].y), r26 = pack_f16(T[2].x, T[6].x), i26 = pack_f16(T[2].y, T[6].y);
    const uint32_t r48 = pack_f16(T[4].x, T[8].x), i48 = pack_f16(T[4].y, T[8].y);
    __syncwarp();
    sts128(row, r04, pack_f16(T[1].x, T[5].x), r26, pack_f16(T[3].x, T[7].x));
    sts128(row + 16, i04, pack_f16(T[1].y, T[5].y), i26, pack_f16(T[3].y, T[7].y));
    uint32_t a[4], b[4];
    {
        const uint32_t zz = pack_f16(y256.x, y256.y);
        hcmul(r04, i04, zz, a[0], b[0]);
        hcmul(r26, i26, zz, a[2], b[2]);
        hcmul(r48, i48, zz, a[3], b[3]);
    }
    sts128(row + 32, a[0], a[0], a[2], a[3]);
    sts128(row + 48, b[0], b[0], b[2], b[3]);
    {
        hcmul(r48, i48, pack_f16(y512.x, y512.y), a[0], b[0]);
        hcmul(r48, i48, pack_f16(y768.x, y768.y), a[1], b[1]);
        const uint32_t zz = pack_f16(c1032.x, c1032.y);
        hcmul(pack_f16(1.0f, y256.x), pack_f16(0.0f, y256.y), zz, a[2], b[2]);
        hcmul(pack_f16(y512.x, y768.x), pack_f16(y512.y, y768.y), zz, a[3], b[3]);
    }
    sts128(row + 64, a[0], a[1], a[2], a[3]);
    sts128(row + 80, b[0], b[1], b[2], b[3]);
}
__device__ __forceinline__ void kgen_mma(const KGen& k, uint32_t tb, int lane) {
    const int t = lane & 3;
    const uint32_t zw = k.zw;
    uint32_t zx[4], zy[4];
#pragma unroll
    for (int ks = 0; ks < 4; ks++) { zx[ks] = __shfl_sync(0xffffffffu, zw, 8 * ks + 2 * t); zy[ks] = __shfl_sync(0xffffffffu, zw, 8 * ks + 2 * t + 1); }
    __syncwarp();
    float acc[2][3][4];
#pragma unroll
    for (int i = 0; i < 6; i++)
#pragma unroll
        for (int j = 0; j < 4; j++) acc[i / 3][i % 3][j] = 0.f;
    {
        const int mi = lane >> 3;
        const uint32_t bd = tb + ((lane & 7) + 8 * (mi >> 1)) * TBP + (mi & 1) * 16;
#pragma unroll
        for (int kp = 0; kp < 2; kp++) {
            uint32_t b[3][4];
#pragma unroll
            for (int j = 0; j < 3; j++) ldsm_x4_t(b[j][0], b[j][1], b[j][2], b[j][3], bd + kp * 16 * TBP + j * 32);
#pragma unroll
            for (int h = 0; h < 2; h++) {
                const int ks = 2 * kp + h;
                uint32_t d[4];
                hcmul(k.Af[ks][0], k.Af[ks][2], zx[ks], zy[ks], d[0], d[2]);
                hcmul(k.Af[ks][1], k.Af[ks][3], zx[ks], zy[ks], d[1], d[3]);
#pragma unroll
                for (int j = 0; j < 3; j++) {
                    mma_f16(acc[0][j], k.Af[ks][0], k.Af[ks][1], k.Af[ks][2], k.Af[ks][3], b[j][2 * h], b[j][2 * h + 1]);
                    mma_f16(acc[1][j], d[0], d[1], d[2], d[3], b[j][2 * h], b[j][2 * h + 1]);
                }
            }
        }
    }
    __syncwarp();
#pragma unroll
    for (int h = 0; h < 2; h++) {
        sts64(tb + h * 256 + lane * 8, pack_f16(acc[h][0][0], acc[h][0][1]), pack_f16(acc[h][0][2], acc[h][0][3]));
        sts64(tb + 512 + h * 256 + lane * 8, pack_f16(acc[h][1][0], acc[h][1][1]), pack_f16(acc[h][1][2], acc[h][1][3]));
        sts32(tb + 1024 + h * 256 + lane * 4, pack_f16(acc[h][2][0], t < 2 ? acc[h][2][1] : acc[h][2][2]));
        sts32(tb + 1152 + h * 256 + lane * 4, pack_f16(t < 2 ? acc[h][2][2] : acc[h][2][1], acc[h][2][3]));
    }
}
__device__ __forceinline__ uint32_t table_buf(uint32_t sb, int warp) { return sb + SM_TB + warp * TBW; }

__device__ __forceinline__ void kgen_combine(uint32_t sb, int warp, int lane, uint32_t kw, uint32_t ao) {
    const int wq = warp & 3;
    const uint32_t a = table_buf(sb, warp & ~3) + wq * 256 + lane * 8, c = table_buf(sb, warp & ~3) + 1024 + wq * 128 + lane * 4;
    const int t = lane & 3;
    const uint32_t o0 = (t < 2 ? KW_T2 + KW_KH + 16 + t * 256 - (wq & 1) * KW_KH : KW_T3 + 16 - 1024 + t * 512 + (wq & 1) * 256) + (lane >> 2) * 16;
    const uint4 o = make_uint4(o0 + t * 36, o0 + (t ^ 1) * 36, o0 + (t ^ 2) * 36, o0 + (t ^ 3) * 36);
    const uint2 u = lds64(a), v = lds64(a + TBW), w = lds64(a + 2 * TBW), x = lds64(a + 3 * TBW);
    const uint32_t kt = hadd2(hadd2(lds32(c), lds32(c + TBW)), hadd2(lds32(c + 2 * TBW), lds32(c + 3 * TBW)));
    const uint32_t k23 = hadd2(hadd2(u.y, v.y), hadd2(w.y, x.y));
    sts64(kw + wq * 64 + ao, hadd2(hadd2(u.x, v.x), hadd2(w.x, x.x)), k23);
    const uint32_t d = kw + (wq >> 1) * 128;
    const uint32_t kh = hmul2(kt, 0x38003800u);
    sts32(d + o.x, kh); sts32(d + o.y, kh); sts32(d + o.z, kh); sts32(d + o.w, kh);
    if (wq == 3) {
        if (lane == 31) { sts32(kw + 264, k23 >> 16); sts32(kw + 288 + 264, k23 >> 16); sts32(kw + 576 + 264, k23 >> 16); }
        if (lane == 29) { sts32(kw + 864 + 280, kt >> 16); sts32(kw + 280, kt & 0xffff0000u); }
    }
}

__device__ __forceinline__ int c_exponent(const uint2& r, const uint2& i) {
    uint32_t mx = __vmaxu2(__vmaxu2(r.x & 0x7fff7fffu, r.y & 0x7fff7fffu), __vmaxu2(i.x & 0x7fff7fffu, i.y & 0x7fff7fffu));
    mx = __reduce_max_sync(0xffffffffu, max(mx & 0xffffu, mx >> 16));
    return min(max((int)(mx >> 7), 4), 240);
}

__device__ __forceinline__ int warp_v() { int l; asm volatile("mov.u32 %0, %%tid.x;" : "=r"(l)); return __shfl_sync(0xffffffffu, l >> 5, 0); }
__device__ __forceinline__ int lane_v() { int l; asm volatile("mov.u32 %0, %%laneid;" : "=r"(l)); return l; }
__device__ __forceinline__ unsigned clock32() { unsigned c; asm volatile("mov.u32 %0, %%clock;" : "=r"(c)); return c; }
__device__ __forceinline__ uint32_t prmt(uint32_t a, uint32_t b, uint32_t s) { uint32_t d; asm("prmt.b32 %0, %1, %2, %3;\n" : "=r"(d) : "r"(a), "r"(b), "r"(s)); return d; }
__device__ __forceinline__ uint32_t prmt_v(uint32_t a, uint32_t b, uint32_t s) { uint32_t d; asm volatile("prmt.b32 %0, %1, %2, %3;\n" : "=r"(d) : "r"(a), "r"(b), "r"(s)); return d; }
__device__ __forceinline__ void mmah16(uint32_t& d0, uint32_t& d1, uint32_t a0, uint32_t a1, uint32_t a2, uint32_t a3, uint32_t b0, uint32_t b1, uint32_t c0, uint32_t c1) {
    asm volatile("mma.sync.aligned.m16n8k16.row.col.f16.f16.f16.f16 {%0,%1}, {%2,%3,%4,%5}, {%6,%7}, {%8,%9};\n"
                 : "=r"(d0), "=r"(d1) : "r"(a0), "r"(a1), "r"(a2), "r"(a3), "r"(b0), "r"(b1), "r"(c0), "r"(c1));
}
__device__ __forceinline__ void mmah8(uint32_t& d0, uint32_t& d1, uint32_t a0, uint32_t a1, uint32_t b0, uint32_t c0, uint32_t c1) {
    asm volatile("mma.sync.aligned.m16n8k8.row.col.f16.f16.f16.f16 {%0,%1}, {%2,%3}, {%4}, {%5,%6};\n"
                 : "=r"(d0), "=r"(d1) : "r"(a0), "r"(a1), "r"(b0), "r"(c0), "r"(c1));
}
template <int A = 8, int B = 32>
__device__ __forceinline__ void conv_rename(uint32_t (&acc)[32]) {
#pragma unroll
    for (int i = A; i < B; i++) { uint32_t v; asm volatile("mov.b32 %0, %1;\n" : "=r"(v) : "r"(acc[i])); acc[i] = v; }
}
__host__ __device__ constexpr uint32_t band_bits(int hw, int sh) {
    uint32_t c = 0;
    for (int s = 0; s <= 10; s++)
        for (int e = 0; e < 2; e++) {
            const int v = s - 3 + sh - 4 * e;
            if (v <= hw && v >= -hw) c |= 1u << (14 + 16 * e - s);
        }
    return c;
}
template <int HW, int SH, int J> __device__ __forceinline__ uint32_t band(uint32_t p2) {
    uint32_t d;
    asm volatile("{\n.reg .b32 t;\nmul.lo.u32 t, %1, %2;\nand.b32 %0, t, 0x40004000;\n}\n" : "=r"(d) : "r"(p2), "n"(band_bits(HW, SH) | J));
    return d;
}
template <int H0, int SH> __device__ __forceinline__ void band_pair(uint4& l, uint4& u, uint32_t p2) {
    l = make_uint4(band<H0, 8, 1>(p2), band<H0 - 1, SH + 8, 2>(p2), band<H0, 0, 1>(p2), band<H0 - 1, SH, 1>(p2));
    u = make_uint4(band<H0, 0, 2>(p2), band<H0 - 1, SH, 2>(p2), band<H0, -8, 1>(p2), band<H0 - 1, SH - 8, 1>(p2));
}
__device__ __forceinline__ void run_sums(uint32_t (&G)[3][2], const uint32_t (&c)[5], const uint4& l, const uint4& u) {
    mmah8(G[0][0], G[0][1], l.x, l.y, c[0], 0u, 0u);
    mmah8(G[1][0], G[1][1], u.z, u.w, c[3], 0u, 0u);
    mmah8(G[2][0], G[2][1], l.x, l.y, c[2], 0u, 0u);
    mmah16(G[0][0], G[0][1], u.x, u.y, u.z, u.w, c[1], c[2], G[0][0], G[0][1]);
    mmah16(G[1][0], G[1][1], l.x, l.y, l.z, l.w, c[1], c[2], G[1][0], G[1][1]);
    mmah16(G[2][0], G[2][1], u.x, u.y, u.z, u.w, c[3], c[4], G[2][0], G[2][1]);
}
__device__ __forceinline__ float h_lo(uint32_t w) { return __half2float(__ushort_as_half((unsigned short)(w & 0xffffu))); }
__device__ __forceinline__ float h_hi(uint32_t w) { return __half2float(__ushort_as_half((unsigned short)(w >> 16))); }
__device__ __forceinline__ uint64_t smem_desc(uint32_t sb, uint32_t o16, uint32_t lbo) {
    uint64_t d;
    asm("mov.b64 %0, {%1, %2};" : "=l"(d) : "r"(((sb & 0x3FFFF) >> 4) + o16 + (lbo << 12)), "r"(8));
    return d;
}
template <int I> struct IC { static constexpr int value = I; };

struct Conv {
    uint32_t u[3][5];
    uint32_t q2[3][2][4];
    uint32_t q3[2][4];
    uint32_t r[18];
};
struct ConvPre {
    uint32_t a[5], b[5];
    uint32_t t[4];
};
__device__ __forceinline__ void conv_pre(ConvPre& e, uint32_t ka, uint32_t ks, uint32_t sel) {
    const uint4 r = lds128(ka + 256), s = lds128(ka + 272);
    ldsm_x4(e.t[0], e.t[1], e.t[2], e.t[3], ks);
    const uint32_t sw = sel ^ 0x4444u;
    e.a[0] = prmt(r.y, r.z, sel); e.a[1] = prmt(r.w, r.z, sw); e.a[2] = prmt(r.x, r.y, sel); e.a[3] = prmt(r.z, r.y, sw); e.a[4] = prmt(r.z, r.w, sel);
    e.b[0] = prmt(s.y, s.z, sel); e.b[1] = prmt(s.w, s.z, sw); e.b[2] = prmt(s.x, s.y, sel); e.b[3] = prmt(s.z, s.y, sw); e.b[4] = prmt(s.z, s.w, sel);
}
__device__ __forceinline__ void conv_sums(Conv& c, uint32_t (&acc)[32], const ConvPre& e, uint32_t a0, uint32_t a1, const uint4 (&bd)[4], uint32_t ka, uint32_t sel, int wq, uint32_t zr) {
    {
        uint32_t x;
        ldsm_x4(c.u[0][1], c.u[0][2], c.u[0][3], c.u[0][4], a1);
        ldsm_x4(c.u[0][0], c.u[1][0], c.u[2][0], x, a0);
#pragma unroll
        for (int q = 1; q < 3; q++) ldsm_x4(c.u[q][1], c.u[q][2], c.u[q][3], c.u[q][4], a1 + q * 512);
    }
#pragma unroll
    for (int i = 0; i < 32; i++) acc[i] = 0u;
    uint32_t G[3][2];
#pragma unroll
    for (int q = 0; q < 3; q++) {
        mmah8(acc[8 * q + 8], acc[8 * q + 9], e.a[4], 0u, c.u[q][2], acc[8 * q + 8], acc[8 * q + 9]);
        mmah16(acc[8 * q + 8], acc[8 * q + 9], e.a[0], e.a[1], e.a[2], e.a[3], c.u[q][3], c.u[q][4], acc[8 * q + 8], acc[8 * q + 9]);
        if (q < 2) {
            mmah8(acc[8 * q + 16], acc[8 * q + 17], e.b[4], 0u, c.u[q][2], 0u, 0u);
            mmah16(acc[8 * q + 16], acc[8 * q + 17], e.b[0], e.b[1], e.b[2], e.b[3], c.u[q][3], c.u[q][4], acc[8 * q + 16], acc[8 * q + 17]);
            run_sums(G, c.u[q], bd[2], bd[3]);
            c.q3[q][0] = prmt(G[1][1], G[0][0], 0x7632u); c.q3[q][1] = prmt(G[2][1], G[1][0], 0x7632u);
            c.q3[q][2] = prmt(G[1][1], G[0][0], 0x5410u); c.q3[q][3] = prmt(G[2][1], G[1][0], 0x5410u);
        }
    }
    {
        const uint32_t a = (ka + wq * 64) ^ (((acc[8] | acc[16] | acc[24]) | (c.q3[0][0] | c.q3[0][1]) | (c.q3[1][0] | c.q3[1][1])) & zr);
#pragma unroll
        for (int i = 0; i < 4; i++) { const uint4 v = lds128(a + i * 16); c.r[4 * i] = v.x; c.r[4 * i + 1] = v.y; c.r[4 * i + 2] = v.z; c.r[4 * i + 3] = v.w; }
        const uint2 v = lds64(a + 64);
        c.r[16] = v.x; c.r[17] = v.y;
    }
#pragma unroll
    for (int q = 0; q < 3; q++) {
        run_sums(G, c.u[q], bd[0], bd[1]);
#pragma unroll
        for (int h = 0; h < 2; h++) {
            const uint32_t s = h ? 0x7632u : 0x5410u;
            c.q2[q][h][0] = prmt(G[0][1], G[0][0], s); c.q2[q][h][1] = prmt(G[1][1], G[1][0], s);
            c.q2[q][h][2] = prmt(G[1][0], G[1][1], s ^ 0x4444u); c.q2[q][h][3] = prmt(G[2][1], G[2][0], s);
            if (q < 2) mmah16(acc[8 * q + 16], acc[8 * q + 17], c.q2[q][h][0], c.q2[q][h][1], c.q2[q][h][2], c.q2[q][h][3], e.t[2 * h], e.t[2 * h + 1], acc[8 * q + 16], acc[8 * q + 17]);
        }
    }
    if (sel == 0u) {
#pragma unroll
        for (int i = 0; i < 6; i++) sts128(ka + i * 16, c.q2[i >> 1][i & 1][0], c.q2[i >> 1][i & 1][1], c.q2[i >> 1][i & 1][2], c.q2[i >> 1][i & 1][3]);
#pragma unroll
        for (int i = 0; i < 2; i++) sts128(ka + i * 16, c.q3[i][0], c.q3[i][1], c.q3[i][2], c.q3[i][3]);
#pragma unroll
        for (int i = 1; i < 4; i++) sts64(ka + i * 16, acc[8 * i], acc[8 * i + 1]);
    }
    conv_rename(acc);
}
#define SPACE 100
#define SPN 3
#define O4 4
#define B2L 1
#define GATE 2
#define HAND 2
#define GA 6
#define GB 4
template <int TA, int TB, int IA, class FG>
__device__ __forceinline__ void conv_tail(uint32_t (&acc)[32], const uint32_t (&a)[8][4], uint32_t sb, unsigned char* gy0, int warp, size_t ycopy, FG fg) {
    const int wg = warp >> 2, wq = warp & 3, ord = TA == 0 && TB == 16 ? 3 - wg + (3 - wg >= O4) : O4;
    const uint32_t ub = sb + SM_U + wg * USLOT_B + UPAD * 16, turn = sb + SM_MISC + 376 + ord * 8, sfs = sb + SM_MISC + 256 + wg * 8;
    const uint32_t du = wg * (USLOT_B / 16) + (SM_U / 16 + UPAD + TA * 8);
    uint32_t ud[8], fs;
    auto skip = [&]() {
        const int lane = lane_v();
        const uint32_t ua = ub + ((lane >> 3) & 1) * ULO_B + (8 * wq + (lane & 7)) * 16 + (lane >> 4) * 512;
        if (IA == 0) ldsm_x4_t(ud[0], ud[1], ud[2], ud[3], ua);
        if (TB == 16) ldsm_x4_t(ud[4], ud[5], ud[6], ud[7], ua + 1024);
        const uint2 fd = lds64(sfs);
        fs = fd.x;
        const float dsk = __uint_as_float(fd.y);
#pragma unroll
        for (int i = 2 * IA; i < TB / 2; i++) ud[i] = pack_bf16(h_lo(ud[i]) * dsk, h_hi(ud[i]) * dsk);
    };
    conv_rename<2 * TA, 2 * TB>(acc);
    if (__builtin_expect(ord != 0, 0)) {
        skip();
        mbar_wait(turn);
    } else if (B2L) {
        bar_sync(0, NWRK);
    }
    if (O4 < 4 || (TA == 0 && TB == 16)) asm volatile("{\n.reg .pred p;\nelect.sync _|p, 0xffffffff;\n@p mbarrier.arrive.shared::cta.b64 _, [%0];\n}\n" ::"r"(turn + 48) : "memory");
    fg(IC<8>());
    wg_fence();
#pragma unroll
    for (int m = 7; m >= 0; m--) {
        wg_h<TA, TB - TA>(acc, a[m], smem_desc(sb, du - m, ULO_B));
        if (m == GA || m == GB || m == HAND) wg_commit();
        if (m == GB) asm volatile("wgmma.wait_group.sync.aligned 1;\n" ::: "memory");
    }
    wg_commit();
    if (O4 < 4 || (TA == 0 && TB == 16)) {
        asm volatile("wgmma.wait_group.sync.aligned 1;\n" ::: "memory");
        asm volatile("{\n.reg .pred p;\nelect.sync _|p, 0xffffffff;\n@p mbarrier.arrive.shared::cta.b64 _, [%0];\n}\n" ::"r"(turn + 8) : "memory");
    }
    __syncwarp();
    fg(IC<3>());
    if (!ord) skip();
    fg(IC<4>());
    const int lane = lane_v();
    const uint32_t lp = sb + SM_PL + (ord >= 3 ? ord - 3 : ord) * PL_B + lane * 8;
    unsigned char* gy = gy0 + ((4 * wq + (lane & 3)) * DM + (TA == 0 && TB == 16 ? 4 * blockIdx.x + wg : 512 + (blockIdx.x >> 1))) * 64 + (lane >> 2) * 8;
    const uint32_t st = lp + (wq * 12 - ((wq * (wq - 1)) >> 1)) * 256;
    uint32_t ld[3];
#pragma unroll
    for (int s = 1; s < 4; s++) {
        const int w = (wq - s) & 3;
        ld[s - 1] = lp + (w * 12 - ((w * (w - 1)) >> 1) + s - 1 - (wq < s ? 3 : 0)) * 256;
    }
    const uint32_t one = 1u + (warp >> 8);
    if (one == 0u) stg64(gy, ld[0], ld[1]);
    if (ord >= 3) bar_sync(9 + ord, 256);
    wg_wait0();
    fg(IC<6>());
#pragma unroll
    for (int j = TA; j < TB; j++)
        if ((j & 3) && j + 3 >= 4 * IA && (j + 3 < TB || j + wq < TB)) sts64(st + (j - 1 - (j >> 2)) * 256, acc[2 * j], acc[2 * j + 1]);
    bar_sync(1 + wg, 128);
    fg(IC<7>());
    uint2 v[4][3];
#pragma unroll
    for (int i = IA; i < TB / 4; i++)
#pragma unroll
        for (int s = 0; s < 3; s++) {
            if (i == 0) { v[i][s] = make_uint2(0u, 0u); if (wq > s) v[i][s] = lds64(ld[s]); }
            else v[i][s] = lds64(ld[s] + i * 768);
        }
    fg(IC<5>());
#pragma unroll
    for (int i = IA; i < TB / 4; i++) {
        const uint32_t x0 = hadd2(v[i][0].x, acc[8 * i]), x1 = hadd2(v[i][1].x, v[i][2].x), y0 = hadd2(v[i][0].y, acc[8 * i + 1]), y1 = hadd2(v[i][1].y, v[i][2].y);
        const uint32_t x = hadd2(x0, x1), y = hadd2(y0, y1);
        const uint32_t lo = pack_bf16(h_lo(x), h_hi(x)), hi = pack_bf16(h_lo(y), h_hi(y));
        ud[2 * i] = max(hfma2_bf(lo, fs, ud[2 * i]), one); ud[2 * i + 1] = hfma2_bf(hi, fs, ud[2 * i + 1]);
    }
    if (SPACE && TA == 0 && TB == 16 && ord < SPN) {
#pragma unroll
        for (int i = 0; i < 4; i++) {
            stg64(gy + i * 16 * DM * 64, ud[2 * i], ud[2 * i + 1]);
            if (i < 3) { const unsigned c0 = clock32(); while (clock32() - c0 < SPACE) {} }
        }
    } else {
#pragma unroll
        for (int i = IA; i < TB / 4; i++) stg64(gy + i * 16 * DM * 64, ud[2 * i], ud[2 * i + 1]);
    }
    if (ord < 2) bar_arrive(12 + ord, 256);
}
template <int M0, int M1>
__device__ __forceinline__ void conv_frags(uint32_t (&a)[8][4], const uint32_t (&r)[18], uint32_t sel, uint32_t dep, int warp) {
    const uint32_t s = prmt_v(sel, dep, 0x3210u + (warp >> 8)), sw = s ^ 0x4444u;
#pragma unroll
    for (int m = M0; m < M1; m++) {
        a[m][0] = prmt_v(r[2 * m + 1], r[2 * m + 2], s); a[m][1] = prmt_v(r[2 * m + 2], r[2 * m + 3], s);
        a[m][2] = prmt_v(r[2 * m + 1], r[2 * m], sw); a[m][3] = prmt_v(r[2 * m + 2], r[2 * m + 1], sw);
    }
}
template <class FG>
__device__ __forceinline__ void conv_main(const Conv& c, uint32_t (&acc)[32], uint32_t sb, uint32_t sel, unsigned char* gy, int warp, size_t ycopy, FG fg) {
    const uint32_t kw = (warp >> 2) * (KW_B / 16) + SM_KW / 16;
    const uint64_t d2 = smem_desc(sb, kw + KW_T2 / 16, KW_KH), d2b = smem_desc(sb, kw + KW_T2 / 16 + 1, KW_KH), d3 = smem_desc(sb, kw + KW_T3 / 16, 16), d3b = smem_desc(sb, kw + KW_T3 / 16 + 32, 16);
    uint32_t a[8][4];
    {
        const int ord = warp < 16 ? 3 - (warp >> 2) + (3 - (warp >> 2) >= O4) : O4;
        if (__builtin_expect(ord >= GATE, 0)) {
            fg(IC<1>());
            mbar_wait(sb + SM_MISC + 376 + 48 + (ord - GATE) * 8);
        }
    }
    wg_fence();
    wg_h<12, 4>(acc, c.q3[0], d3b); wg_h<8, 4>(acc, c.q3[0], d3); wg_h<4, 4>(acc, c.q2[0][0], d2b);
    wg_h<12, 4>(acc, c.q3[1], d3); wg_h<8, 4>(acc, c.q2[1][0], d2b);
    wg_h<12, 4>(acc, c.q2[2][0], d2b); wg_h<4, 4>(acc, c.q2[0][1], d2); wg_h<8, 4>(acc, c.q2[1][1], d2);
    wg_h<12, 4>(acc, c.q2[2][1], d2);
    wg_commit(); __syncwarp();
    fg(IC<0>());
    wg_wait0();
    conv_frags<0, 8>(a, c.r, sel, acc[16], warp);
    fg(IC<2>());
    if (warp >= 16) {
        if (blockIdx.x & 1) conv_tail<4, 16, 2>(acc, a, sb, gy, warp, ycopy, fg);
        else conv_tail<0, 8, 0>(acc, a, sb, gy, warp, ycopy, fg);
    } else {
        conv_tail<0, 16, 0>(acc, a, sb, gy, warp, ycopy, fg);
    }
}
#define CONV_LT6 const int dd = (lane >> 3) + (lane & 4) - (lane & 3); \
        const uint4 lt6 = make_uint4(prmt_v((dd & 3) * 288, 0u, idn), prmt_v(0x3254u + (dd >> 2) * 0x2222u, 0u, idn), \
            prmt_v(UPAD * 16 + (lane & 7) * 16 + ULO_B - 32 + (lane >> 3) * 512, 0u, idn), prmt_v(UPAD * 16 + (lane & 7) * 16 + ((lane >> 3) & 1) * ULO_B - 16 + (lane & 16), 0u, idn));
#define CONV_PRE \
        CONV_LT6 \
        const uint32_t ka = kw + lt6.x, sel = lt6.y, ks = kw + lt7.x; \
        const uint32_t ca0 = sb + SM_U + wg * USLOT_B + (warp & 3) * 128 + lt6.z, ca1 = sb + SM_U + wg * USLOT_B + (warp & 3) * 128 + lt6.w; \
        uint4 bd[4]; \
        band_pair<2, 4>(bd[0], bd[1], lt7.w); band_pair<4, 0>(bd[2], bd[3], lt7.w);
#define CONV_PRE2 ConvPre ce_; conv_pre(ce_, ka, ks, sel);
#define CONV_BODY \
        Conv c; \
        uint32_t acc[32]; \
        conv_sums(c, acc, ce_, ca0, ca1, bd, ka, sel, warp & 3, warp >> 8);
#define WS a_b_0_1_2_34_xy_56_7__c__r____de__
#define WS_STR2(x) #x
#define WS_STR(x) WS_STR2(x)
__device__ constexpr char wunit(int pt, int k) {
    constexpr char t[] = WS_STR(WS);
    int i = 0;
    for (; pt > 0 && t[i]; i++) pt -= t[i] == '_';
    for (; k > 0 && t[i] && t[i] != '_'; i++) k--;
    return t[i] == '_' ? 0 : t[i];
}
__device__ constexpr bool wsched_ok() {
    int seen = 0;
    for (int p = 0; p < 21; p++)
        for (int k = 0; wunit(p, k); k++) {
            const char c = wunit(p, k);
            const int bit = 1 << (c == 'r' ? 13 : c >= 'x' ? c - 'x' + 14 : c >= 'a' ? c - 'a' + 8 : c - '0');
            if ((seen & bit) || k >= (p < 16 ? 4 : 2) || (p < 5 && c >= '4' && c <= '7') || (p < 6 && (c == 'c' || c == 'd')) || (p < 16 && c == 'e')) return false;
            seen |= bit;
        }
    return seen == 0xffff;
}
struct WMaps { CUtensorMap g, u, gr, ur, d, dr; };
static_assert((PAUSE & 2) && GATE <= 2 && O4 >= 2, "resets");
static_assert(wsched_ok(), "weight schedule");
template <int PT, int K>
__device__ __forceinline__ void weight_units(uint32_t sb, const WMaps& m, int w) {
    constexpr char U = wunit(PT, K);
    if constexpr (U != 0) {
        if (w == K && elect_one()) {
            const int P = blockIdx.x >> 1, odd = blockIdx.x & 1;
            constexpr int bar = SM_MISC + (U == 'e' ? 352 : U >= 'a' && U <= 'r' ? 336 : 328);
            if constexpr (U == 'e') { if (!odd) tma_2d(sb + SM_WD + 4 * 8192, &m.d, 256, 64 * P, sb + bar); }
            else if constexpr (U == 'r') tma_3d(sb + SM_WD + 40960, &m.dr, 0, 4096 + 8 * P, 5 * odd, sb + bar);
            else if constexpr (U >= 'x') tma_3d(sb + SM_WR + (U - 'x') * 4608, U == 'x' ? &m.gr : &m.ur, 4096 + 8 * P, 0, 2 * odd, sb + bar);
            else if constexpr (U >= 'a') tma_2d(sb + SM_WD + (U - 'a') * 8192, &m.d, 320 * odd + 64 * (U - 'a'), 64 * P, sb + bar);
            else tma_2d(sb + (U < '4' ? SM_WG : SM_WU) + (U & 3) * 9216, U < '4' ? &m.g : &m.u, 64 * P, 288 * odd + (U & 3) * 72, sb + bar);
        }
        weight_units<PT, K + 1>(sb, m, w);
    }
}
#define WPOINT(i, w) do { weight_units<i, 0>(sb, wm, w); } while (0)

__global__ void __launch_bounds__(NTHR, 1) __cluster_dims__(2, 1, 1)
fused_kernel(const Params p, const __grid_constant__ WMaps wm, const __grid_constant__ CUtensorMap tm_x,
             const __grid_constant__ CUtensorMap tm_y, const __grid_constant__ CUtensorMap tm_z) {
    extern __shared__ __align__(1024) unsigned char smem[];
    const uint32_t sb = smem_u32(smem);
    const int tid = threadIdx.x, warp = __shfl_sync(0xffffffffu, tid >> 5, 0), lane = tid & 31;
    const int b = blockIdx.x, P = b >> 1, odd = b & 1;
    const int g = lane >> 2, t = lane & 3;
    const int wg = warp >> 2, t128 = tid & 127;
    const uint32_t s_stat = sb + SM_MISC;
    const uint32_t s_key = sb + SM_MISC + 128;
    const uint32_t s_wm = sb + SM_MISC + 256;
    const uint32_t s_k16 = sb + SM_MISC + 192;
    const uint32_t s_fs = sb + SM_MISC + 256;
    const uint32_t s_cnt = sb + SM_MISC + 320;
    const uint32_t bar_w = sb + SM_MISC + 328, bar_d = bar_w + 8, bar_g = bar_w + 16, bar_r = bar_w + 32, bar_h = bar_w + 40, bar_x = bar_w + 48;
    STAMP(0);

    const bool lnw = (unsigned)(warp - 10) < 9u;
    const unsigned pm = tid + (tid < 512 ? 512 * b : 65024 + 128 * P), pq = (pm & ~127u) + 4 * lane;
    uint32_t pl = ldg16(p.lar + pm), ldt = ldg16(p.ldt + (pm >> 7));
    const uint32_t pa2 = ldg16(p.aim + pm), pc = ldg16(p.cre + pm), pi = ldg16(p.cim + pm);
    const uint2 call_re = ldg64(p.cre + pq), call_im = ldg64(p.cim + pq);
    const uint32_t dskl = ldg16(p.dsk + (pm >> 7));
    const uint32_t ep = ld_poll32(p.s->hint + (b & 7) * 32 + 1 + (lane >> 5));
    if ((unsigned)(tid - 320) < 288u) {
        const bf16* xp = p.x + (unsigned)((32 * P + 2 * odd + TOKEN_OF(g)) * DM + ((tid - 320) & ~31) + 8 * t);
        const uint32_t xt = sb + SM_XT + ((tid - 320) & ~31) * 32 + lane * 16;
        asm volatile("cp.async.cg.shared.global [%0], [%1], 16;\ncp.async.cg.shared.global [%0 + 512], [%1 + 9216], 16;\n"
                     "cp.async.cg.shared.global [%0 + 9216], [%1 + 576], 16;\ncp.async.cg.shared.global [%0 + 9728], [%1 + 9792], 16;\n" ::"r"(xt), "l"(xp) : "memory");
    }
    uint32_t* const std_ = p.s->st + ((lane & 12) * 128 + odd * 256 + 4 * P + 2 * (lane & 1) + ((lane >> 1) & 1)) * 2;
    unsigned char* const ud = reinterpret_cast<unsigned char*>(p.s->uT) + (32 * (warp - UW) + 8 * (g >> 1) + (g & 1)) * 4096 + b * 32 + t * 8;
    if (warp == 0) {
        if (lane == 0) {
            mbar_init(bar_x, 1); mbar_init(bar_w, 1); mbar_init(bar_d, 1); mbar_init(bar_d + 16, 1); mbar_init(bar_g, 1); mbar_init(bar_h, 3); mbar_init(bar_r, 1);
            #pragma unroll
            for (int i = 1; i < 11; i++) mbar_init(bar_x + 8 * i, 4);
            asm volatile("fence.mbarrier_init.release.cluster;\n" ::: "memory");
            mbar_expect(bar_x, 16384); mbar_expect(bar_r, 8192);
            mbar_expect(bar_w, 2 * 41472); mbar_expect(bar_d, 32768 + 5120); mbar_expect(bar_d + 16, 8192); mbar_expect(bar_g, 9 * 512);
        }
        __syncwarp();
        bar_arrive(0, NWRK);
    }
    if (warp == 0 && elect_one()) tma_3d(sb + SM_XC, &tm_x, 8 * P, 0, 8 * odd, bar_x);
    asm volatile("barrier.cluster.arrive.relaxed.aligned;\n" ::: "memory");
    const uint32_t kw = sb + SM_KW + wg * KW_B;
    if (t128 < 2 * UPAD) sts128(sb + SM_U + wg * USLOT_B + (t128 & 1) * ULO_B + (t128 >> 1) * 16, 0u, 0u, 0u, 0u);
    sts128(kw + t128 * 16, 0u, 0u, 0u, 0u);
    if (t128 < KW_B / 16 - 128) sts128(kw + 2048 + t128 * 16, 0u, 0u, 0u, 0u);
    if (tid < 128) {
#pragma unroll
        for (int i = 0; i < 4; i++) sts128(sb + SM_ZERO + i * 2048 + tid * 16, 0u, 0u, 0u, 0u);
    }
    if (warp != 0) bar_sync(0, NWRK);
    STAMP(1);
    if (warp == 19 || warp == UW || warp == UW + 1) {
        if (warp == 19) {
            if (lane < 16) stg64(std_, 0u, 0u);
            if (lane < 9) asm volatile("prefetch.global.L2 [%0];\n" ::"l"(p.wr + lane * 64));
        } else {
#pragma unroll
            for (int k = 0; k < 4; k++) stg64(ud + k * 8192, 0u, 0u);
        }
    }
    uint32_t X[2][8];
    auto partial = [&]() {
        const uint32_t xt = sb + SM_XT + (warp - 10) * 1024 + lane * 16;
        asm volatile("cp.async.wait_all;\n" ::: "memory");
        STAMP(23);
        const uint4 a = lds128(xt), c = lds128(xt + 512), d = lds128(xt + 9216), e = lds128(xt + 9728);
        X[0][0] = a.x; X[0][1] = a.y; X[0][2] = a.z; X[0][3] = a.w; X[0][4] = d.x; X[0][5] = d.y; X[0][6] = d.z; X[0][7] = d.w;
        X[1][0] = c.x; X[1][1] = c.y; X[1][2] = c.z; X[1][3] = c.w; X[1][4] = e.x; X[1][5] = e.y; X[1][6] = e.z; X[1][7] = e.w;
        const uint32_t one[8] = {0x3f803f80u, 0x3f803f80u, 0x3f803f80u, 0x3f803f80u, 0x3f803f80u, 0x3f803f80u, 0x3f803f80u, 0x3f803f80u};
        ln_partial<8>(X, one, sb + SM_LNP, warp - 10, g, t);
        bar_arrive(6, 320);
        if (PAUSE & 1) bar_sync(7, PCNT);
    };
    if (LNAT == 0 && lnw) {
        partial();
        pl = prmt_v(pl, X[0][0], 0x3210u + (warp >> 8)); ldt = prmt_v(ldt, X[0][0], 0x3210u + (warp >> 8));
    }
    auto finish = [&]() {
        bar_sync(6, 320);
        float mb, rc;
        ln_finish<9>(sb + SM_LNP, lane, mb, rc);
        const float rh = rbf(rc);
        const uint32_t s0 = (__float_as_uint(mb) >> 16) | (((ep & 0x7fffu) + 1u) << 16), s1 = pack_bf16(rh, rc - rh);
        if (lane < 16) { stg64(std_, s0, s1); sts64(s_stat + lane * 8, s0, s1); }
        if (lane == 16) sts32(s_cnt + 4, ep);
        bar_arrive(7, PCNT);
        STAMP(28);
    };
    auto upub = [&]() {
        if (!(PAUSE & 6)) bar_sync(7, PCNT);
        const uint32_t utag = ((ep & 3u) + 1u) * 0x10001u;
        uint32_t U[2][4];
#pragma unroll
        for (int hf = 0; hf < 2; hf++) {
            const uint2 st = lds64(s_stat + (g + 8 * hf) * 8);
            const uint4 xv = lds128(sb + SM_XT + (16 + warp - UW) * 1024 + hf * 512 + lane * 16);
            const uint32_t xs[4] = {xv.x, xv.y, xv.z, xv.w};
#pragma unroll
            for (int k = 0; k < 4; k++) {
                const uint32_t u = ln_apply(xs[k], st);
                U[hf][k] = movm((pack_f16_rz(bf_lo(u), __uint_as_float(u)) & 0xfff8fff8u) | utag);
            }
        }
#pragma unroll
        for (int k = 0; k < 4; k++) stg64(ud + k * 8192, U[0][k], U[1][k]);
    };
    if (FINAT == 0 && warp == 19) finish();
    const uint32_t tb = table_buf(sb, warp);
    const float dt = rbf(expf(bf_lo(ldt)));
    KGen kg;
    kgen_setup(kg, pl | (pa2 << 16), dt);
    if (LNAT == 1 && lnw) {
        partial();
        kg.z8.x = __uint_as_float(prmt_v(__float_as_uint(kg.z8.x), X[0][0], 0x3210u + (warp >> 8)));
        kg.z1.x = __uint_as_float(prmt_v(__float_as_uint(kg.z1.x), X[0][0], 0x3210u + (warp >> 8)));
    }
    if (FINAT == 1 && warp == 19) finish();
    if (UAT == 0 && (warp == UW || warp == UW + 1)) upub();
    kgen_rows(kg, tb, lane);
    if (wg == 0) fence_async();
    if (LNAT == 2 && lnw) {
        partial();
        kg.z128.x = __uint_as_float(prmt_v(__float_as_uint(kg.z128.x), X[0][0], 0x3210u + (warp >> 8)));
        kg.z1.x = __uint_as_float(prmt_v(__float_as_uint(kg.z1.x), X[0][0], 0x3210u + (warp >> 8)));
    }
    if (FINAT == 2 && warp == 19) finish();
    if (UAT == 1 && (warp == UW || warp == UW + 1)) upub();
    STAMP(2);
    WPOINT(0, warp - 4);
    const int ce = c_exponent(call_re, call_im);
    if (t128 == 0) sts64(s_fs + wg * 8, (uint32_t)min(max(ce + (int)(__float_as_uint(dt) >> 23) - 116, 0), 254) * 0x800080u, dskl << 16);
    kgen_chain(kg, pc | (pi << 16), __uint_as_float(((uint32_t)(244 - ce) << 23) | (__float_as_uint(dt) & 0x7fffffu)));
    if ((PAUSE & 4) && warp < 10) bar_sync(7, PCNT);
    if (UAT == 4 && (warp == UW || warp == UW + 1)) upub();
    STAMP(3);
    WPOINT(1, warp - 6);
    kgen_cols(kg, tb, lane);
    if (LNAT == 3 && lnw) partial();
    if (FINAT == 3 && warp == 19) finish();
    if ((PAUSE & 2) && warp < 10) bar_sync(7, PCNT);
    if (UAT == 2 && (warp == UW || warp == UW + 1)) upub();
    STAMP(4);
    WPOINT(2, warp - 8);
    const uint4* usrc = wg < 4 ? reinterpret_cast<const uint4*>(p.s->st) + odd * 512 + (lane & 1) * 128 + 16 * (warp & 7) + (lane >> 1)
                               : reinterpret_cast<const uint4*>(p.s->uT) + P * 256 + 2 * t128;
    const int ustep = wg < 4 ? 256 : 1;
    uint4 uv0, uv1;
    kgen_mma(kg, tb, lane);
    if (UAT == 3 && (warp == UW || warp == UW + 1)) upub();
    STAMP(26);
    WPOINT(3, warp - 5);
    const uint32_t idn = 0x3210u + (warp >> 8);
    const uint4 lt7 = make_uint4(prmt_v(KW_T2 + ((lane >> 3) & 1) * KW_KH + (33 + (lane & 7)) * 16 - (lane & 16), 0u, idn), t * 288 + g * 8 + 8, (lane & 1) * 4096 + (lane >> 1) * 16,
                                 prmt_v(8u << ((lane >> 3) + (lane & 4)) >> (lane & 3), 0u, idn));
    asm volatile("barrier.cluster.wait.acquire.aligned;\n" ::: "memory");
    bar_sync(1 + wg, 128);
    uv0 = ld_poll(usrc); uv1 = ld_poll(usrc + ustep);
    kgen_combine(sb, warp, lane, kw, lt7.y);
    if (warp < 3 || warp > 6) bar_arrive(14, NWRK);
    CONV_PRE
    STAMP(5);
    WPOINT(4, warp - 7);
    if (wg < 4) {
        mbar_wait(bar_x);
        const bool far = warp < 8;
        const uint32_t xa = sb + SM_XC + (warp & 7) * 256 + (odd ^ far) * 8 + lt7.z;
        uint2 xv[4] = {lds64(xa), lds64(xa + 8192), lds64(xa + 2048), lds64(xa + 10240)};
        const uint32_t tag = ((ep & 0x7fffu) + 1u) << 16;
        int it = 0;
        while (true) {
            const bool bad = (((uv0.x ^ tag) | (uv0.z ^ tag)) | ((uv1.x ^ tag) | (uv1.z ^ tag))) >> 16;
            if (!__any_sync(0xffffffffu, bad)) break;
            if (++it > SPIN_LIMIT) TRAP();
            if (bad) { uv0 = ld_poll(usrc); uv1 = ld_poll(usrc + 256); }
        }
        STAMP(6);
        DBG(wg, it);
        const uint2 st[4] = {make_uint2(uv0.x, uv0.y), make_uint2(uv0.z, uv0.w), make_uint2(uv1.x, uv1.y), make_uint2(uv1.z, uv1.w)};
#pragma unroll
        for (int i = 0; i < 4; i++) {
            xv[i].x = ln_apply(xv[i].x, st[i]);
            xv[i].y = ln_apply(xv[i].y, st[i]);
        }
        const uint32_t ub = sb + SM_U + UPAD * 16 + odd * ULO_B + (warp & 7) * 256 + lane * 8;
        const uint32_t w[4][2] = {{pack_f16(bf_lo(xv[0].x), bf_lo(xv[1].x)), pack_f16(bf_lo(xv[2].x), bf_lo(xv[3].x))}, {HI2(xv[0].x, xv[1].x), HI2(xv[2].x, xv[3].x)},
                                  {pack_f16(bf_lo(xv[0].y), bf_lo(xv[1].y)), pack_f16(bf_lo(xv[2].y), bf_lo(xv[3].y))}, {HI2(xv[0].y, xv[1].y), HI2(xv[2].y, xv[3].y)}};
#pragma unroll
        for (int i = 0; i < 4; i++) {
            if (far) asm volatile("st.async.shared::cluster.mbarrier::complete_tx::bytes.v2.b32 [%0], {%1,%2}, [%3];\n" ::"r"((ub ^ 0x1000000u) + i * USLOT_B), "r"(w[i][0]), "r"(w[i][1]), "r"(bar_r ^ 0x1000000u) : "memory");
            else sts64(ub + i * USLOT_B, w[i][0], w[i][1]);
        }
    } else {
        const uint32_t utag = ((ep & 3u) + 1u) * 0x10001u;
        int it = 0;
        while (true) {
            const bool bad = (((uv0.x ^ utag) | (uv0.y ^ utag) | (uv0.z ^ utag) | (uv0.w ^ utag)) | ((uv1.x ^ utag) | (uv1.y ^ utag) | (uv1.z ^ utag) | (uv1.w ^ utag))) & 0x70007u;
            if (!__any_sync(0xffffffffu, bad)) break;
            if (++it > SPIN_LIMIT) TRAP();
            if (bad) { uv0 = ld_poll(usrc); uv1 = ld_poll(usrc + 1); }
        }
        STAMP(6);
        DBG(4, it);
        const uint32_t ub = sb + SM_U + UPAD * 16 + 4 * USLOT_B + (t128 >> 1) * 32 + (t128 & 1) * 8;
        sts64(ub, prmt(uv0.x, uv0.z, 0x5410u) ^ utag, prmt(uv1.x, uv1.z, 0x5410u) ^ utag);
        sts64(ub + 16, prmt(uv0.x, uv0.z, 0x7632u) ^ utag, prmt(uv1.x, uv1.z, 0x7632u) ^ utag);
        sts64(ub + ULO_B, prmt(uv0.y, uv0.w, 0x5410u) ^ utag, prmt(uv1.y, uv1.w, 0x5410u) ^ utag);
        sts64(ub + ULO_B + 16, prmt(uv0.y, uv0.w, 0x7632u) ^ utag, prmt(uv1.y, uv1.w, 0x7632u) ^ utag);
    }
    if (warp < 3 && elect_one()) tma_st_3d(warp < 2 ? &tm_y : &tm_z, sb + SM_ZERO, warp < 2 ? 128 * b : 32 * (512 + P), 0, 2 * (warp < 2 ? warp : odd));
    if (warp >= 3 && warp <= 6) {
        bar_sync(14, NWRK);
        WPOINT(5, warp - 3);
    }
    bar_sync(1 + wg, 128);
    CONV_PRE2
    mbar_wait(bar_r);
    fence_async();
    bar_sync(0, NWRK);
    STAMP(7);
    uint32_t hv0 = 0;
    {
        WPOINT(6, 19 - warp);
        CONV_BODY
        WPOINT(7, 19 - warp);
        if (!B2L) bar_sync(0, NWRK); else if (wg != 3) bar_arrive(0, NWRK);
        STAMP(8);
        size_t ycopy = 0;
        auto hook = [&](auto gi) {
                     constexpr int G = decltype(gi)::value;
                     if (G == 4 && warp == HINTW) hv0 = ld_poll32(p.s->hint + (lane_v() & 7) * 32);
                     if (G == 4) mbar_wait(bar_h);
                     if (G == 1 || G == 2) WPOINT(7 + G, warp - 16);
                     if (G == 3) { WPOINT(10, warp - 12); WPOINT(12, warp - 8); WPOINT(14, warp - 4); }
                     if (G == 5) { WPOINT(11, warp - 13); WPOINT(13, warp - 9); WPOINT(15, warp - 5); }
                     if (G == 1 && warp >= 17 && elect_one())
                         bulk_s2g(warp == 17 ? p.s->part + b * (PBYTES / 4) : warp == 18 ? p.s->rows + b * 1152 : p.s->sc + b * 32, sb + SM_ZERO, warp == 17 ? PBYTES : warp == 18 ? 4608 : 32);
                     if (G == 4 && warp >= 17 && elect_one()) {
                         asm volatile("cp.async.bulk.wait_group 0;\n" ::: "memory");
                         hint_arrive(p.s->hint, 2, b & 7);
                     }
                     if (G == 1 && warp < 3) {
                         if (elect_one()) {
                             asm volatile("cp.async.bulk.wait_group 0;\n" ::: "memory");
                             mbar_arrive(bar_h);
                             hint_arrive(p.s->hint, 0, b & 7);
                         }
                         __syncwarp();
                         STAMP(17);
                     }
                 };
        conv_main(c, acc, sb, sel, reinterpret_cast<unsigned char*>(p.s->y), warp, ycopy, hook);
        STAMP(10);
    }
    {
    const int warp = warp_v(), lane = lane_v(), tid = 32 * warp + lane, g = lane >> 2, t = lane & 3;
    if (warp == HINTW) {
        const uint32_t target = (lds32(s_cnt + 4) + 1u) * 48u;
        if (__any_sync(0xffffffffu, (int)(hv0 - target) < 0)) hint_wait(p.s->hint, 0, target);
    }
    const unsigned char* ys = reinterpret_cast<const unsigned char*>(p.s->y) + ((size_t)P * DM + 32 * warp + 8 * (g >> 1) + (g & 1)) * 64 + odd * 32 + t * 8;
    STAMP(27);
    bar_sync(0, NWRK);
    STAMP(11);
    const uint32_t zr = warp >> 8;
    auto late_rows = [&](auto pub) {
        const uint32_t k = lds32(s_key + (lane & 7) * 4), ep = lds32(s_cnt + 4);
        const bool late = k & 256u, mine = late && ((k & 255u) >> 1) == (uint32_t)b;
        uint32_t todo = __ballot_sync(0xffffffffu, mine) & 0xffu;
        if (todo) {
#pragma unroll 1
            while (todo) {
                const int s = __ffs(todo) - 1, row = (__shfl_sync(0xffffffffu, k, s) >> 9) & 15;
                todo &= todo - 1;
                if ((row & 7) == g) pub(row & 8, 2 * NCTA + s);
            }
            __threadfence();
            bar_sync(0, NWRK);
            if (tid < NSEL && mine) *reinterpret_cast<volatile unsigned*>(p.s->flag + tid) = ep + 1u;
        }
        int it = 0;
        while (__any_sync(0xffffffffu, late && ld_poll32(p.s->flag + (lane & 7)) != ep + 1u)) { if (++it > SPIN_LIMIT) TRAP(); }
        __threadfence();
        const int gs = tid / 36;
        const uint4* src = reinterpret_cast<const uint4*>(p.s->rows) + __shfl_sync(0xffffffffu, late ? 2 * NCTA + (lane & 7) : (k & 255u), gs & 7) * 144 + 36 * odd + (tid - gs * 36);
        if (tid < 288) {
            uint4 v0;
            do { v0 = ld_poll(src); if (++it > SPIN_LIMIT) TRAP(); } while (!v0.x);
            sts128(sb + SM_XS + gs * XS_PITCH + (tid - gs * 36) * 16, v0.x, v0.y, v0.z, v0.w);
        }
        bar_sync(0, NWRK);
    };
    if (warp >= 18) {
        if (warp == 18) {
            uint32_t* const kp = pin(p.s->sc + 32 * b, zr);
            const uint32_t kid = pin(0x30000000u | ((lane & 15) << 9) | 2 * b, zr), ka = pin(s_k16 + (lane & 15) * 4, zr), kb = pin(s_k16 + (lane & 16) * 2, zr);
            bar_sync(8, 640);
            float mb, rc;
            ln_finish<18>(sb + SM_LNP, lane, mb, rc);
            if (lane < 16) stat_store(s_stat + lane * 8, mb, rc, 0u);
            bar_arrive(13, 608);
            bar_sync(10, 608);
            const float r = sum18(sb + SM_LNP + (32 + (lane & 15)) * 80);
            const uint32_t bits = pack_bf16(0.f, r);
            const uint32_t me = (((bits ^ ((uint32_t)((int)bits >> 31) & 0x7fffffffu)) >> 3) & 0x1fffe000u) ^ kid;
            sts32(ka, me);
            __syncwarp();
            const uint4 v = lds128(kb), w = lds128(kb + 16);
#define GT(x) ((me - (x)) >> 31)
            uint32_t rank = pin(GT(v.x) + GT(v.y) + GT(v.z), zr) + pin(GT(v.w) + GT(w.x) + GT(w.y), zr) + pin(GT(w.z) + GT(w.w), zr);
#undef GT
            rank += __shfl_xor_sync(0xffffffffu, rank, 16);
            if (lane < 16) { if (rank < 8) stg32(kp + rank, me + (rank < 2 ? rank : 256u)); }
            else sts32(ka + (s_wm - s_k16), rank);
            bar_arrive(11, 640);
            weight_units<19, 0>(sb, wm, 0); weight_units<19, 1>(sb, wm, 1);
        }
        const uint4* ksrc = pin(reinterpret_cast<const uint4*>(p.s->sc) + 8 * lane, zr);
        const uint4* rsrc = pin(reinterpret_cast<const uint4*>(p.s->rows) + 36 * odd + t, zr);
        if (warp == 19) {
            weight_units<20, 0>(sb, wm, 0); weight_units<20, 1>(sb, wm, 1);
            bar_sync(8, 640);
            weight_units<16, 0>(sb, wm, 0); weight_units<16, 1>(sb, wm, 1);
            hint_wait(p.s->hint, 2, (lds32(s_cnt + 4) + 1u) * 48u);
            bar_sync(11, 640);
        }
        bool slow = false;
        int it = 0;
        if (warp == 19) {
        uint4 q[4];
#pragma unroll
        for (int i = 0; i < 4; i++) q[i] = ld_poll(ksrc + 256 * i);
        while (true) {
            uint32_t a[4];
#pragma unroll
            for (int i = 0; i < 4; i++) a[i] = q[i].x & q[i].y & q[i].z & q[i].w;
            if (__all_sync(0xffffffffu, a[0] & a[1] & a[2] & a[3])) break;
#pragma unroll
            for (int i = 0; i < 4; i++)
                if (!a[i]) q[i] = ld_poll(ksrc + 256 * i);
            if (++it > SPIN_LIMIT) TRAP();
        }
        bar_arrive(9, 608);
        STAMP(16);
        auto merge = [](const uint4& x, const uint4& y) {
            const uint32_t a = max(x.x, y.w), c = max(x.y, y.z), d = max(x.z, y.y), e = max(x.w, y.x);
            const uint32_t a2 = max(a, d), d2 = min(a, d), c2 = max(c, e), e2 = min(c, e);
            return make_uint4(max(a2, c2), min(a2, c2), max(d2, e2), min(d2, e2));
        };
        uint4 h = merge(merge(q[0], q[1]), merge(q[2], q[3]));
        uint4 v[9];
        uint32_t key = 0;
#pragma unroll
        for (int s = 0; s < 8; s++) {
            const uint32_t m = __reduce_max_sync(0xffffffffu, h.x);
            const bool w = h.x == m;
            h.x = w ? h.y : h.x; h.y = w ? h.z : h.y; h.z = w ? h.w : h.z; h.w = w ? 0u : h.w;
            if (g == s) key = m;
        }
        rsrc += (key & 255u) * 144;
#pragma unroll
        for (int j = 0; j < 9; j++) v[j] = ld_poll(rsrc + 4 * j);
        slow = __any_sync(0xffffffffu, key & 256u);
        STAMP(18);
        if (__any_sync(0xffffffffu, h.x == 0u)) {
            uint4 r[4];
            it = 0;
            while (true) {
#pragma unroll
                for (int i = 0; i < 4; i++) r[i] = ld_poll(ksrc + 256 * i + 1);
                if (__all_sync(0xffffffffu, all_nz(r[0]) && all_nz(r[1]) && all_nz(r[2]) && all_nz(r[3]))) break;
                if (++it > SPIN_LIMIT) TRAP();
            }
            uint32_t m = 1u << 30;
#pragma unroll 1
            for (int s = 0; s < 8; s++) {
                uint32_t x = 0;
#pragma unroll
                for (int i = 0; i < 4; i++) {
                    x = max(max(max(x, q[i].x - m), max(q[i].y - m, q[i].z - m)), q[i].w - m);
                    x = max(max(max(x, r[i].x - m), max(r[i].y - m, r[i].z - m)), r[i].w - m);
                }
                m += __reduce_max_sync(0xffffffffu, x);
                if (g == s) key = m;
            }
            slow = true;
        }
        const uint32_t xsa = sb + SM_XS + g * XS_PITCH + t * 16;
        sts32(s_key + g * 4, key);
        sts32(xsa, 0u);
        bar_arrive(12, 608);
#pragma unroll
        for (int j = 0; j < 9; j++) sts128(xsa + j * 64, v[j].x, v[j].y, v[j].z, v[j].w);
        slow = slow || min(min(min(min(v[0].x, v[1].x), v[2].x), min(min(v[3].x, v[4].x), v[5].x)), min(min(v[6].x, v[7].x), v[8].x)) == 0u;
        }
        if (bar_or(0, NWRK, slow)) late_rows([](bool, int) {});
        STAMP(19);
        const int fl = 16 * (b & 1) + ((tid >> 2) & 15), fc = 16 * (b >> 1) + (fl >> 2) + 8 * ((tid >> 1) & 1), fsl = 2 * (fl & 3) + (tid & 1);
        const uint32_t kk = lds32(s_key + fsl * 4);
        const uint32_t* fsrc = p.s->rows + ((kk & 256u) ? 2 * NCTA + fsl : (kk & 255u)) * DM + (fc >> 1);
        uint32_t hw = 1u, uw = 1u;
        if (b < 72) { uw = ld_poll32(fsrc); hw = ld_poll32(fsrc + 288); }
        if (b < 72) {
            it = 0;
            while (!hw || !uw) { uw = ld_poll32(fsrc); hw = ld_poll32(fsrc + 288); if (++it > SPIN_LIMIT) TRAP(); }
            const int row = (kk >> 9) & 15, ftok = 8 * (kk & 252u) + (kk & 2u) + TOKEN_OF(row & 7) + (row & 8);
            const unsigned k16 = (kk >> 13) & 0xffffu;
            const unsigned bits = (k16 & 0x8000u) ? (k16 & 0x7fffu) : (~k16 & 0xffffu);
            const float rs = 512.0f * rbf(__fdividef(1.0f, 1.0f + __expf(-__uint_as_float(bits << 16))));
            bf16* const op = p.out + (unsigned)(ftok * DM + fc);
            const float uv = (fc & 1) ? bf_hi(uw) : bf_lo(uw), hv = (fc & 1) ? bf_hi(hw) : bf_lo(hw);
            const uint32_t a = sb + SM_FIN + (tid - 576) * 80;
            sts128(a + 64, __float_as_uint(rs), __float_as_uint(uv), __float_as_uint(hv), (uint32_t)(size_t)op ^ (uint32_t)((size_t)op >> 32));
            bar_sync(14, 576);
            const uint4 p0 = lds128(a), p1 = lds128(a + 16), p2 = lds128(a + 32), p3 = lds128(a + 48);
#define F4(p) ((__uint_as_float(p.x) + __uint_as_float(p.y)) + (__uint_as_float(p.z) + __uint_as_float(p.w)))
            const float v0 = F4(p0), v1 = F4(p1), v2 = F4(p2), v3 = F4(p3);
#undef F4
            const float y3 = rbf(rbf((v0 + v1) + (v2 + v3)) * rs);
            asm volatile("st.global.u16 [%0], %1;\n" ::"l"(op), "h"((unsigned short)pack_bf16(hv + rbf(uv + y3), 0.f)) : "memory");
        }
        if (b == 0 && tid >= 632) *reinterpret_cast<volatile unsigned*>(p.s->hint + (tid & 7) * 32 + 1) = lds32(s_cnt + 4) + 1u;
    } else {
        uint32_t H[2][4], U2[2][4], WA[9][4], WD[18], WE[18];
        const int fkh = warp >= 9, fmt = warp - 9 * fkh;
        auto load_wa = [&](auto k0, auto k1) {
            if (k0.value >= k1.value) return;
            if (k0.value == 0) mbar_wait(bar_w);
            const int mi = lane >> 3, rr = lane & 7;
            const int row = fkh * 144 + rr + 8 * (mi >> 1);
            const uint32_t aad = sb + (fmt < 8 ? SM_WG + (mi & 1) * (SM_WU - SM_WG) + row * 128 + (fmt ^ rr) * 16 : SM_WR + (mi & 1) * 4608 + row * 16), ks = fmt < 8 ? 2048 : 256;
#pragma unroll
            for (int k = k0.value; k < k1.value; k++) ldsm_x4_t(WA[k][0], WA[k][1], WA[k][2], WA[k][3], aad + k * ks);
        };
        auto load_wd = [&](uint32_t (&WD)[18], int tile) {
            mbar_wait(bar_d);
            if (tile & 16) mbar_wait(bar_d + 16);
            const int mi = lane >> 3, rr = lane & 7;
            const uint32_t base = sb + SM_WD + rr * 128 + (((2 * tile + (mi & 1)) & 7) ^ rr) * 16;
#pragma unroll
            for (int k = 0; k < 4; k++) ldsm_x4_t(WD[4 * k], WD[4 * k + 1], WD[4 * k + 2], WD[4 * k + 3], base + (tile >> 2) * 8192 + (k * 16 + 8 * (mi >> 1)) * 128);
            ldsm_x2_t(WD[16], WD[17], base + 40960 + (tile >> 2) * 1024);
        };
        auto publish = [&](bool hi, int slot) {
            uint4* rowp = reinterpret_cast<uint4*>(p.s->rows) + slot * 144 + warp * 4 + t;
            stg128(rowp, nzw(hi ? U2[1][0] : U2[0][0]), nzw(hi ? U2[1][1] : U2[0][1]), nzw(hi ? U2[1][2] : U2[0][2]), nzw(hi ? U2[1][3] : U2[0][3]));
            stg128(rowp + 72, nzw(hi ? H[1][0] : H[0][0]), nzw(hi ? H[1][1] : H[0][1]), nzw(hi ? H[1][2] : H[0][2]), nzw(hi ? H[1][3] : H[0][3]));
        };
        uint4 wr = make_uint4(0x3f803f80u, 0x3f803f80u, 0x3f803f80u, 0x3f803f80u);
        {
            uint2 yv[4];
#pragma unroll
            for (int k = 0; k < 4; k++) yv[k] = ld_poll64(ys + k * 128);
            if (g == 0) wr = ldg128(p.wr + 32 * warp + 8 * t);
            const uint4 x0 = lds128(sb + SM_XT + warp * 1024 + lane * 16), x1 = lds128(sb + SM_XT + warp * 1024 + 512 + lane * 16);
            load_wa(IC<0>(), IC<WA0>());
            int it = 0;
            while (!__all_sync(0xffffffffu, yv[0].x && yv[1].x && yv[2].x && yv[3].x)) {
#pragma unroll
                for (int k = 0; k < 4; k++) yv[k] = ld_poll64(ys + k * 128);
                if (++it > SPIN_LIMIT) TRAP();
            }
            STAMP(12);
            const uint32_t Z[2][4] = {{x0.x, x0.y, x0.z, x0.w}, {x1.x, x1.y, x1.z, x1.w}};
#pragma unroll
            for (int k = 0; k < 4; k++) {
                H[0][k] = hadd2_bf(Z[0][k], movm(yv[k].x));
                H[1][k] = hadd2_bf(Z[1][k], movm(yv[k].y));
            }
            const uint32_t bw[4] = {wr.x, wr.y, wr.z, wr.w};
            ln_partial<4>(H, bw, sb + SM_LNP, warp, g, t);
        }
        bar_arrive(8, 640);
        load_wa(IC<WA0>(), IC<WA1>());
        STAMP(13);
        bar_sync(13, 608);
        STAMP(14);
#pragma unroll
        for (int hf = 0; hf < 2; hf++) {
            const uint2 st = lds64(s_stat + (g + 8 * hf) * 8);
#pragma unroll
            for (int k = 0; k < 4; k++) U2[hf][k] = ln_apply(H[hf][k], st);
        }
        {
            float cs[4] = {0.f, 0.f, 0.f, 0.f};
            mma_bf16(cs, U2[0][0], U2[1][0], U2[0][1], U2[1][1], wr.x, wr.y);
            mma_bf16(cs, U2[0][2], U2[1][2], U2[0][3], U2[1][3], wr.z, wr.w);
            if (t == 0) { stsf(sb + SM_LNP + ((32 + g) * 20 + warp) * 4, cs[0]); stsf(sb + SM_LNP + ((40 + g) * 20 + warp) * 4, cs[2]); }
            bar_arrive(10, 608);
        }
        load_wa(IC<WA1>(), IC<WA2>());
        bar_sync(11, 640);
        {
            const uint32_t rk[2] = {lds32(s_wm + g * 4), lds32(s_wm + 32 + g * 4)};
            uint32_t lo = min(rk[0], rk[1]), hi = max(rk[0], rk[1]);
#pragma unroll 1
            while (lo < 2) { publish(lo == rk[1], 2 * b + lo); lo = hi; hi = 16; }
        }
        load_wa(IC<WA2>(), IC<WA3>());
        bar_sync(9, 608);
        load_wa(IC<WA3>(), IC<9>());
#pragma unroll
        for (int hf = 0; hf < 2; hf++)
            sts128(sb + SM_OUT + (g + 8 * hf) * OUT_PITCH + warp * 64 + t * 16,
                   hadd2_bf(H[hf][0], U2[hf][0]), hadd2_bf(H[hf][1], U2[hf][1]), hadd2_bf(H[hf][2], U2[hf][2]), hadd2_bf(H[hf][3], U2[hf][3]));
        fence_async();
        WPOINT(17, warp - 16);
        if ((WDAT == 0 || (WDAT == 2 && fkh)) && (warp < 16 || !odd)) load_wd(WD, warp);
        const uint32_t bad = pin(sb + SM_XS + (lane & 7) * XS_PITCH + (fkh * 144 + 8 * (lane >> 3)) * 2, zr), ex = pin(sb + SM_EX + warp * 512 + lane * 16, zr);
        uint32_t* pp = pin(p.s->part + ((size_t)(2 * (20 * odd + warp) + (lane >> 4)) * 64 + P) * 32 + (lane & 15) * 2, zr);
        bar_sync(12, 608);
        if (warp < 16 && !__any_sync(0xffffffffu, (lds32(s_key + (lane & 7) * 4) & 0x1efeu) == (uint32_t)((warp << 9) | 2 * b)) && elect_one())
            bulk_s2g(p.out + (size_t)(32 * P + 2 * odd + TOKEN_OF(warp & 7) + (warp & 8)) * DM, sb + SM_OUT + warp * OUT_PITCH, DM * 2);
        WPOINT(18, warp - 16);
        STAMP(15);
        if (bar_or(0, NWRK, false)) late_rows(publish);
        STAMP(19);
        float gp[4];
        {
            float c4[3][4];
#pragma unroll
            for (int i = 0; i < 3; i++)
#pragma unroll
                for (int j = 0; j < 4; j++) c4[i][j] = 0.f;
#pragma unroll
            for (int k = 0; k < 10; k += 2) {
                uint32_t b0, b1, b2, b3;
                ldsm_x4(b0, b1, b2, b3, bad + k * 32);
                mma_bf16(c4[k % 3], WA[k][0], WA[k][1], WA[k][2], WA[k][3], b0, b1);
                if (k < 8) mma_bf16(c4[(k + 1) % 3], WA[k + 1][0], WA[k + 1][1], WA[k + 1][2], WA[k + 1][3], b2, b3);
            }
#pragma unroll
            for (int j = 0; j < 4; j++) gp[j] = c4[0][j] + (c4[1][j] + c4[2][j]);
            if (warp >= 9) {
                sts128f(ex, gp);
                bar_arrive(6, 576);
            } else {
                bar_sync(6, 576);
                const uint4 o = lds128(ex + 4608);
                gp[0] += __uint_as_float(o.x); gp[1] += __uint_as_float(o.y); gp[2] += __uint_as_float(o.z); gp[3] += __uint_as_float(o.w);
                asm volatile("st.async.shared::cluster.mbarrier::complete_tx::bytes.v4.b32 [%0], {%1,%2,%3,%4}, [%5];\n"
                             ::"r"(ex ^ 0x1000000u), "r"(__float_as_uint(gp[0])), "r"(__float_as_uint(gp[1])), "r"(__float_as_uint(gp[2])), "r"(__float_as_uint(gp[3])), "r"(bar_g ^ 0x1000000u) : "memory");
                if (WDAT == 2) load_wd(WD, warp);
            }
            if (WDAT == 1 && (warp < 16 || !odd)) load_wd(WD, warp);
            if (warp >= 16 && !odd) load_wd(WE, warp + 2);
        }
        STAMP(20);
        if (warp < 9) {
            mbar_wait(bar_g);
            const uint4 u = lds128(ex);
            const uint32_t G = pack_bf16(gp[0] + __uint_as_float(u.x), gp[1] + __uint_as_float(u.y)), U = pack_bf16(gp[2] + __uint_as_float(u.z), gp[3] + __uint_as_float(u.w));
            const float G0 = bf_lo(G), G1 = bf_hi(G);
            sts32(sb + SM_GU + tid * 4, hmul2_bf(pack_bf16(G0 * rcp_approx(1.0f + ex2_approx(G0 * -1.4426950408889634f)), G1 * rcp_approx(1.0f + ex2_approx(G1 * -1.4426950408889634f))), U));
        }
        bar_sync(7, 576);
        STAMP(21);
        if (warp < 16 || !odd) {
            uint32_t gb[9];
            ldsm_x4_t(gb[0], gb[1], gb[2], gb[3], sb + SM_GU + lane * 16);
            ldsm_x4_t(gb[4], gb[5], gb[6], gb[7], sb + SM_GU + 512 + lane * 16);
            ldsm_x1_t(gb[8], sb + SM_GU + 1024 + (lane & 7) * 16);
            auto down = [&](const uint32_t (&W)[18], uint32_t* dst) {
                float c4[4] = {0.f, 0.f, 0.f, 0.f}, d4[4] = {0.f, 0.f, 0.f, 0.f}, e4[4] = {0.f, 0.f, 0.f, 0.f};
                mma_bf16(c4, W[0], W[1], W[2], W[3], gb[0], gb[1]);
                mma_bf16(d4, W[4], W[5], W[6], W[7], gb[2], gb[3]);
                mma_bf16(e4, W[8], W[9], W[10], W[11], gb[4], gb[5]);
                mma_bf16_k8(c4, W[16], W[17], gb[8]);
                mma_bf16(d4, W[12], W[13], W[14], W[15], gb[6], gb[7]);
                const float v0 = (c4[0] + e4[0]) + d4[0], v1 = (c4[1] + e4[1]) + d4[1], v2 = (c4[2] + e4[2]) + d4[2], v3 = (c4[3] + e4[3]) + d4[3];
                const uint32_t e = max(max(__float_as_uint(fmaxf(fabsf(v0), fabsf(v1))), __float_as_uint(fmaxf(fabsf(v2), fabsf(v3)))), 16u << 23) >> 23;
                const float sc = __uint_as_float((245u - e) << 23);
                stg64(dst, pack_f16(v0 * sc, v1 * sc) | ((e * 0x8002000u) & 0x60006000u), pack_f16(v2 * sc, v3 * sc) | ((e * 0x800200u) & 0x60006000u));
            };
            if (warp >= 16) { down(WE, pp + 4 * 64 * 32); down(WD, pp); }
            else down(WD, pp);
        }
        asm volatile("cp.async.bulk.wait_group.read 0;\n" ::: "memory");
        STAMP(22);
        if (b < 72 && warp < 16) {
            const uint2* src = reinterpret_cast<const uint2*>(p.s->part) + (unsigned)(b * 1024 + tid);
            uint2 a, c;
            int it = 0;
            a = ld_poll64(src); c = ld_poll64(src + 512);
            while (!__all_sync(0xffffffffu, a.y && c.y)) {
                a = ld_poll64(src); c = ld_poll64(src + 512);
                if (++it > SPIN_LIMIT) TRAP();
            }
            STAMP(24);
            const float ea = __uint_as_float((((a.y & 0x60006000u) | ((a.x >> 4) & 0x06000600u)) * 0x4001u) & 0x7f800000u);
            const float ec = __uint_as_float((((c.y & 0x60006000u) | ((c.x >> 4) & 0x06000600u)) * 0x4001u) & 0x7f800000u);
            a.x &= 0x9fff9fffu; a.y &= 0x9fff9fffu; c.x &= 0x9fff9fffu; c.y &= 0x9fff9fffu;
            const float s0 = fmaf(h_lo(a.x), ea, h_lo(c.x) * ec), s1 = fmaf(h_hi(a.x), ea, h_hi(c.x) * ec), s2 = fmaf(h_lo(a.y), ea, h_lo(c.y) * ec), s3 = fmaf(h_hi(a.y), ea, h_hi(c.y) * ec);
            const bool up = lane & 16;
            const float r0 = __shfl_xor_sync(0xffffffffu, up ? s0 : s2, 16), r1 = __shfl_xor_sync(0xffffffffu, up ? s1 : s3, 16);
            const uint32_t fa = sb + SM_FIN + ((lane & 15) * 4 + (up ? 2 : 0)) * 80 + warp * 4;
            stsf(fa, (up ? s2 : s0) + r0); stsf(fa + 80, (up ? s3 : s1) + r1);
            bar_arrive(14, 576);
        }
    }
    STAMP(25);
    }
}

typedef CUresult (*PFN_tmEncode)(CUtensorMap*, CUtensorMapDataType, cuuint32_t, void*, const cuuint64_t*, const cuuint64_t*, const cuuint32_t*,
                                 const cuuint32_t*, CUtensorMapInterleave, CUtensorMapSwizzle, CUtensorMapL2promotion, CUtensorMapFloatOOBfill);

extern "C" void kernel_launch(void* const* d_in, const int* in_sizes, int n_in, void* d_out, int out_size) {
    Params p;
    p.x = (const bf16*)d_in[0];
    p.lar = (const bf16*)d_in[1];
    p.aim = (const bf16*)d_in[2];
    p.cre = (const bf16*)d_in[3];
    p.cim = (const bf16*)d_in[4];
    p.ldt = (const bf16*)d_in[5];
    p.dsk = (const bf16*)d_in[6];
    p.wr = (const bf16*)d_in[8];
    p.out = (bf16*)d_out;
    static PFN_tmEncode enc = nullptr;
    static void* scratch = nullptr;
    if (!enc) {
        cudaFuncSetAttribute(fused_kernel, cudaFuncAttributeMaxDynamicSharedMemorySize, SMEM_TOTAL);
        void* fn = nullptr;
        cudaDriverEntryPointQueryResult qr;
        cudaGetDriverEntryPoint("cuTensorMapEncodeTiled", &fn, cudaEnableDefault, &qr);
        enc = (PFN_tmEncode)fn;
        cudaGetSymbolAddress(&scratch, g_scratch);
    }
    p.s = (Scratch*)scratch;
    WMaps wm;
    CUtensorMap tm_x, tm_y, tm_z;
    const cuuint64_t dims[2] = {FF, DM}, strides[1] = {FF * 2}, rdims[3] = {FF, 144, 4}, rstrides[2] = {FF * 2, 144 * FF * 2};
    const cuuint32_t box[2] = {64, 72}, rbox[3] = {8, 144, 2}, es3[3] = {1, 1, 1};
    for (int i = 0; i < 2; i++) {
        enc(i ? &wm.u : &wm.g, CU_TENSOR_MAP_DATA_TYPE_BFLOAT16, 2, d_in[9 + i], dims, strides, box, es3, CU_TENSOR_MAP_INTERLEAVE_NONE, CU_TENSOR_MAP_SWIZZLE_128B,
            CU_TENSOR_MAP_L2_PROMOTION_NONE, CU_TENSOR_MAP_FLOAT_OOB_FILL_NONE);
        enc(i ? &wm.ur : &wm.gr, CU_TENSOR_MAP_DATA_TYPE_BFLOAT16, 3, d_in[9 + i], rdims, rstrides, rbox, es3, CU_TENSOR_MAP_INTERLEAVE_NONE, CU_TENSOR_MAP_SWIZZLE_NONE,
            CU_TENSOR_MAP_L2_PROMOTION_NONE, CU_TENSOR_MAP_FLOAT_OOB_FILL_NONE);
    }
    const cuuint64_t ddims[2] = {DM, FF}, dstrides[1] = {DM * 2}, edims[3] = {64, FF, 9}, estrides[2] = {DM * 2, 128};
    const cuuint32_t dbox[2] = {64, 64}, ebox[3] = {64, 8, 5};
    enc(&wm.d, CU_TENSOR_MAP_DATA_TYPE_BFLOAT16, 2, d_in[11], ddims, dstrides, dbox, es3, CU_TENSOR_MAP_INTERLEAVE_NONE, CU_TENSOR_MAP_SWIZZLE_128B,
        CU_TENSOR_MAP_L2_PROMOTION_NONE, CU_TENSOR_MAP_FLOAT_OOB_FILL_NONE);
    enc(&wm.dr, CU_TENSOR_MAP_DATA_TYPE_BFLOAT16, 3, d_in[11], edims, estrides, ebox, es3, CU_TENSOR_MAP_INTERLEAVE_NONE, CU_TENSOR_MAP_SWIZZLE_128B,
        CU_TENSOR_MAP_L2_PROMOTION_NONE, CU_TENSOR_MAP_FLOAT_OOB_FILL_NONE);
    const cuuint64_t xdims[3] = {DM, LSEQ / 16, 16}, xstrides[2] = {16 * DM * 2, DM * 2};
    const cuuint32_t xbox[3] = {8, LSEQ / 16, 8};
    enc(&tm_x, CU_TENSOR_MAP_DATA_TYPE_BFLOAT16, 3, d_in[0], xdims, xstrides, xbox, es3, CU_TENSOR_MAP_INTERLEAVE_NONE, CU_TENSOR_MAP_SWIZZLE_NONE,
        CU_TENSOR_MAP_L2_PROMOTION_NONE, CU_TENSOR_MAP_FLOAT_OOB_FILL_NONE);
    const cuuint64_t ydims[3] = {DM * 32, 16, 4}, ystrides[2] = {DM * 64, 16 * DM * 64};
    const cuuint32_t ybox[3] = {128, 16, 2}, zbox[3] = {32, 16, 2};
    enc(&tm_y, CU_TENSOR_MAP_DATA_TYPE_BFLOAT16, 3, p.s->y, ydims, ystrides, ybox, es3, CU_TENSOR_MAP_INTERLEAVE_NONE, CU_TENSOR_MAP_SWIZZLE_NONE,
        CU_TENSOR_MAP_L2_PROMOTION_NONE, CU_TENSOR_MAP_FLOAT_OOB_FILL_NONE);
    enc(&tm_z, CU_TENSOR_MAP_DATA_TYPE_BFLOAT16, 3, p.s->y, ydims, ystrides, zbox, es3, CU_TENSOR_MAP_INTERLEAVE_NONE, CU_TENSOR_MAP_SWIZZLE_NONE,
        CU_TENSOR_MAP_L2_PROMOTION_NONE, CU_TENSOR_MAP_FLOAT_OOB_FILL_NONE);
    fused_kernel<<<NCTA, NTHR, SMEM_TOTAL>>>(p, wm, tm_x, tm_y, tm_z);
}
```

```cpp
#include <cuda_runtime.h>
#include <cuda.h>
#include <cuda_fp16.h>
#include <cuda_bf16.h>
#include <stdint.h>

#define LSEQ 2048
#define DM 576
#define NST 128
#define FF 4608
#define NSEL 8
#define NCTA 128
#define NTHR 640
#define NWRK 640

typedef __nv_bfloat16 bf16;

#define SM_WD 0
#define SM_WG 46080
#define SM_WR 82944
#define SM_WU 92160
#define SM_ZERO 32768
#define SM_XC 16384
#define SM_TB 96000
#define SM_PL 129024
#define PL_B 10752
#define SM_XT (SM_TB + 20 * TBW)
#define SM_U (SM_XT + 18432)
#define UPAD 8
#define ULO_B ((UPAD + 128) * 16)
#define USLOT_B (2 * ULO_B)
#define SM_KW (SM_U + 5 * USLOT_B)
#define KW_B 3600
#define KW_T2 1152
#define KW_KH 656
#define KW_T3 2464
#define SM_MISC (SM_KW + 5 * KW_B)
#define SM_LNP (SM_MISC + 576)
#define SMEM_TOTAL (SM_LNP + 3840)
#define TBP 112
#define TBW (32 * TBP)
#define SM_OUT SM_PL
#define OUT_PITCH 1216
#define SM_XS (SM_PL + 19456)
#define XS_PITCH 592
#define SM_EX (SM_PL + 24320)
#define SM_FIN SM_KW
#define SM_GU (SM_PL + 33536)

struct __align__(128) Scratch {
    unsigned hint[8 * 32];
    unsigned flag[32];
    uint32_t sc[NCTA * 32];
    uint32_t st[LSEQ * 2];
    uint32_t uT[64 * (LSEQ / 2)];
    uint32_t y[NCTA * DM * 8];
    uint32_t part[72 * 64 * 32];
    uint32_t rows[(2 * NCTA + NSEL) * DM];
};
__device__ Scratch g_scratch;
#define STAMP(i)
#define DBG(i, v)

__device__ __forceinline__ float rbf(float x) {
    uint32_t r;
    asm("cvt.rn.bf16x2.f32 %0, %1, %2;\n" : "=r"(r) : "f"(x), "f"(0.f));
    return __uint_as_float(r & 0xffff0000u);
}
__device__ __forceinline__ uint32_t pack_bf16(float lo, float hi) {
    uint32_t r;
    asm("cvt.rn.bf16x2.f32 %0, %1, %2;\n" : "=r"(r) : "f"(hi), "f"(lo));
    return r;
}
__device__ __forceinline__ uint32_t pack_f16(float lo, float hi) {
    uint32_t r;
    asm("cvt.rn.f16x2.f32 %0, %1, %2;\n" : "=r"(r) : "f"(hi), "f"(lo));
    return r;
}
__device__ __forceinline__ uint32_t pack_f16_rz(float lo, float hi) {
    uint32_t r;
    asm("cvt.rz.f16x2.f32 %0, %1, %2;\n" : "=r"(r) : "f"(hi), "f"(lo));
    return r;
}
__device__ __forceinline__ float bf_lo(uint32_t w) { return __uint_as_float(w << 16); }
__device__ __forceinline__ float bf_hi(uint32_t w) { return __uint_as_float(w & 0xffff0000u); }
__device__ __forceinline__ uint32_t hadd2_bf(uint32_t a, uint32_t b) {
    __nv_bfloat162 r = __hadd2_rn(*reinterpret_cast<__nv_bfloat162*>(&a), *reinterpret_cast<__nv_bfloat162*>(&b));
    return *reinterpret_cast<uint32_t*>(&r);
}
__device__ __forceinline__ uint32_t hsub2_bf(uint32_t a, uint32_t b) {
    __nv_bfloat162 r = __hsub2_rn(*reinterpret_cast<__nv_bfloat162*>(&a), *reinterpret_cast<__nv_bfloat162*>(&b));
    return *reinterpret_cast<uint32_t*>(&r);
}
__device__ __forceinline__ uint32_t hmul2_bf(uint32_t a, uint32_t b) {
    __nv_bfloat162 r = __hmul2_rn(*reinterpret_cast<__nv_bfloat162*>(&a), *reinterpret_cast<__nv_bfloat162*>(&b));
    return *reinterpret_cast<uint32_t*>(&r);
}
__device__ __forceinline__ uint32_t hfma2_bf(uint32_t a, uint32_t b, uint32_t c) { uint32_t r; asm("fma.rn.bf16x2 %0, %1, %2, %3;\n" : "=r"(r) : "r"(a), "r"(b), "r"(c)); return r; }
__device__ __forceinline__ uint32_t hmul2(uint32_t a, uint32_t b) { uint32_t r; asm("mul.rn.f16x2 %0, %1, %2;\n" : "=r"(r) : "r"(a), "r"(b)); return r; }
__device__ __forceinline__ uint32_t hadd2(uint32_t a, uint32_t b) { uint32_t r; asm("add.rn.f16x2 %0, %1, %2;\n" : "=r"(r) : "r"(a), "r"(b)); return r; }
__device__ __forceinline__ uint32_t hfma2(uint32_t a, uint32_t b, uint32_t c) { uint32_t r; asm("fma.rn.f16x2 %0, %1, %2, %3;\n" : "=r"(r) : "r"(a), "r"(b), "r"(c)); return r; }
__device__ __forceinline__ uint32_t nzw(uint32_t w) { return w ? w : 0x8000u; }
__device__ __forceinline__ uint32_t nzf(float f) { const uint32_t w = __float_as_uint(f); return w ? w : 0x80000000u; }
__device__ __forceinline__ uint32_t smem_u32(const void* p) { return (uint32_t)__cvta_generic_to_shared(p); }
__device__ __forceinline__ uint32_t lds32(uint32_t addr) {
    uint32_t v;
    asm volatile("ld.shared.u32 %0, [%1];\n" : "=r"(v) : "r"(addr) : "memory");
    return v;
}
__device__ __forceinline__ uint32_t lds16(uint32_t addr) {
    unsigned short v;
    asm volatile("ld.shared.u16 %0, [%1];\n" : "=h"(v) : "r"(addr) : "memory");
    return v;
}
__device__ __forceinline__ uint2 lds64(uint32_t addr) {
    uint2 v;
    asm volatile("ld.shared.v2.u32 {%0,%1}, [%2];\n" : "=r"(v.x), "=r"(v.y) : "r"(addr) : "memory");
    return v;
}
__device__ __forceinline__ uint4 lds128(uint32_t addr) {
    uint4 v;
    asm volatile("ld.shared.v4.u32 {%0,%1,%2,%3}, [%4];\n" : "=r"(v.x), "=r"(v.y), "=r"(v.z), "=r"(v.w) : "r"(addr) : "memory");
    return v;
}
__device__ __forceinline__ float ldsf(uint32_t addr) { return __uint_as_float(lds32(addr)); }
__device__ __forceinline__ void sts32(uint32_t addr, uint32_t v) { asm volatile("st.shared.u32 [%0], %1;\n" ::"r"(addr), "r"(v) : "memory"); }
__device__ __forceinline__ void stsf(uint32_t addr, float v) { sts32(addr, __float_as_uint(v)); }
__device__ __forceinline__ void sts64(uint32_t addr, uint32_t a, uint32_t b) { asm volatile("st.shared.v2.u32 [%0], {%1,%2};\n" ::"r"(addr), "r"(a), "r"(b) : "memory"); }
__device__ __forceinline__ void sts64f(uint32_t addr, float a, float b) { sts64(addr, __float_as_uint(a), __float_as_uint(b)); }
__device__ __forceinline__ void sts128(uint32_t addr, uint32_t a, uint32_t b, uint32_t c, uint32_t d) {
    asm volatile("st.shared.v4.u32 [%0], {%1,%2,%3,%4};\n" ::"r"(addr), "r"(a), "r"(b), "r"(c), "r"(d) : "memory");
}
__device__ __forceinline__ void sts128f(uint32_t addr, const float (&v)[4]) {
    sts128(addr, __float_as_uint(v[0]), __float_as_uint(v[1]), __float_as_uint(v[2]), __float_as_uint(v[3]));
}
__device__ __forceinline__ void ldsm_x4(uint32_t& r0, uint32_t& r1, uint32_t& r2, uint32_t& r3, uint32_t addr) {
    asm volatile("ldmatrix.sync.aligned.m8n8.x4.shared.b16 {%0,%1,%2,%3}, [%4];\n"
                 : "=r"(r0), "=r"(r1), "=r"(r2), "=r"(r3) : "r"(addr) : "memory");
}
__device__ __forceinline__ void ldsm_x4_t(uint32_t& r0, uint32_t& r1, uint32_t& r2, uint32_t& r3, uint32_t addr) {
    asm volatile("ldmatrix.sync.aligned.m8n8.x4.trans.shared.b16 {%0,%1,%2,%3}, [%4];\n"
                 : "=r"(r0), "=r"(r1), "=r"(r2), "=r"(r3) : "r"(addr) : "memory");
}
__device__ __forceinline__ void ldsm_x2_t(uint32_t& r0, uint32_t& r1, uint32_t addr) {
    asm volatile("ldmatrix.sync.aligned.m8n8.x2.trans.shared.b16 {%0,%1}, [%2];\n" : "=r"(r0), "=r"(r1) : "r"(addr) : "memory");
}
__device__ __forceinline__ void ldsm_x1_t(uint32_t& r0, uint32_t addr) {
    asm volatile("ldmatrix.sync.aligned.m8n8.x1.trans.shared.b16 {%0}, [%1];\n" : "=r"(r0) : "r"(addr) : "memory");
}
__device__ __forceinline__ uint32_t movm(uint32_t a) {
    uint32_t d;
    asm volatile("movmatrix.sync.aligned.m8n8.trans.b16 %0, %1;\n" : "=r"(d) : "r"(a));
    return d;
}
__device__ __forceinline__ void mma_f16(float (&c)[4], uint32_t a0, uint32_t a1, uint32_t a2, uint32_t a3, uint32_t b0, uint32_t b1) {
    asm volatile(
        "mma.sync.aligned.m16n8k16.row.col.f32.f16.f16.f32 {%0,%1,%2,%3}, {%4,%5,%6,%7}, {%8,%9}, {%0,%1,%2,%3};\n"
        : "+f"(c[0]), "+f"(c[1]), "+f"(c[2]), "+f"(c[3])
        : "r"(a0), "r"(a1), "r"(a2), "r"(a3), "r"(b0), "r"(b1));
}
__device__ __forceinline__ void mma_bf16(float (&c)[4], uint32_t a0, uint32_t a1, uint32_t a2, uint32_t a3, uint32_t b0, uint32_t b1) {
    asm volatile(
        "mma.sync.aligned.m16n8k16.row.col.f32.bf16.bf16.f32 {%0,%1,%2,%3}, {%4,%5,%6,%7}, {%8,%9}, {%0,%1,%2,%3};\n"
        : "+f"(c[0]), "+f"(c[1]), "+f"(c[2]), "+f"(c[3])
        : "r"(a0), "r"(a1), "r"(a2), "r"(a3), "r"(b0), "r"(b1));
}
__device__ __forceinline__ void mma_bf16_k8(float (&c)[4], uint32_t a0, uint32_t a1, uint32_t b0) {
    asm volatile("mma.sync.aligned.m16n8k8.row.col.f32.bf16.bf16.f32 {%0,%1,%2,%3}, {%4,%5}, {%6}, {%0,%1,%2,%3};\n"
        : "+f"(c[0]), "+f"(c[1]), "+f"(c[2]), "+f"(c[3]) : "r"(a0), "r"(a1), "r"(b0));
}
__device__ __forceinline__ void bar_sync(int id, int n) { asm volatile("bar.sync %0, %1;\n" ::"r"(id), "r"(n) : "memory"); }
__device__ __forceinline__ void bar_arrive(int id, int n) { asm volatile("bar.arrive %0, %1;\n" ::"r"(id), "r"(n) : "memory"); }
__device__ __forceinline__ bool bar_or(int id, int n, bool v) {
    uint32_t r;
    asm volatile("{\n.reg .pred p, q;\nsetp.ne.u32 p, %3, 0;\nbar.red.or.pred q, %1, %2, p;\nselp.u32 %0, 1, 0, q;\n}\n" : "=r"(r) : "r"(id), "r"(n), "r"((uint32_t)v) : "memory");
    return r;
}
__device__ __forceinline__ uint4 ld_poll(const void* p) {
    uint4 v;
    asm volatile("ld.relaxed.gpu.global.v4.u32 {%0,%1,%2,%3}, [%4];\n" : "=r"(v.x), "=r"(v.y), "=r"(v.z), "=r"(v.w) : "l"(p) : "memory");
    return v;
}
template <class T> __device__ __forceinline__ T* pin(T* p, uint32_t z) {
    uint32_t lo, hi;
    asm volatile("mov.b64 {%0, %1}, %2;\n" : "=r"(lo), "=r"(hi) : "l"(p));
    asm volatile("xor.b32 %0, %0, %1;\n" : "+r"(lo) : "r"(z));
    asm volatile("xor.b32 %0, %0, %1;\n" : "+r"(hi) : "r"(z));
    asm volatile("mov.b64 %0, {%1, %2};\n" : "=l"(p) : "r"(lo), "r"(hi));
    return p;
}
__device__ __forceinline__ uint32_t pin(uint32_t a, uint32_t z) { asm volatile("xor.b32 %0, %0, %1;\n" : "+r"(a) : "r"(z)); return a; }
__device__ __forceinline__ uint2 ld_poll64(const void* p) {
    uint2 v;
    asm volatile("ld.relaxed.gpu.global.v2.u32 {%0,%1}, [%2];\n" : "=r"(v.x), "=r"(v.y) : "l"(p) : "memory");
    return v;
}
__device__ __forceinline__ uint32_t ld_poll32(const void* p) {
    uint32_t v;
    asm volatile("ld.relaxed.gpu.global.u32 %0, [%1];\n" : "=r"(v) : "l"(p) : "memory");
    return v;
}
__device__ __forceinline__ uint4 ldg128(const void* p) {
    uint4 v;
    asm volatile("ld.global.nc.v4.u32 {%0,%1,%2,%3}, [%4];\n" : "=r"(v.x), "=r"(v.y), "=r"(v.z), "=r"(v.w) : "l"(p));
    return v;
}
__device__ __forceinline__ uint2 ldg64(const void* p) {
    uint2 v;
    asm volatile("ld.global.nc.v2.u32 {%0,%1}, [%2];\n" : "=r"(v.x), "=r"(v.y) : "l"(p));
    return v;
}
__device__ __forceinline__ uint32_t ldg16(const void* p) {
    uint32_t v;
    asm volatile("ld.global.nc.u16 %0, [%1];\n" : "=r"(v) : "l"(p));
    return v;
}
__device__ __forceinline__ void stg128(void* p, uint32_t a, uint32_t b, uint32_t c, uint32_t d) {
    asm volatile("st.global.v4.u32 [%0], {%1,%2,%3,%4};\n" ::"l"(p), "r"(a), "r"(b), "r"(c), "r"(d) : "memory");
}
__device__ __forceinline__ void stg64(void* p, uint32_t a, uint32_t b) { asm volatile("st.global.v2.u32 [%0], {%1,%2};\n" ::"l"(p), "r"(a), "r"(b) : "memory"); }
__device__ __forceinline__ void stg32(void* p, uint32_t a) { asm volatile("st.global.u32 [%0], %1;\n" ::"l"(p), "r"(a) : "memory"); }
__device__ __forceinline__ bool all_nz(const uint4& v) { return v.x && v.y && v.z && v.w; }
#define SPIN_LIMIT (1 << 21)
#define TRAP() __trap()
__device__ __forceinline__ void hint_arrive(unsigned* g_hint, int idx, int sub) {
    asm volatile("red.relaxed.gpu.global.add.u32 [%0], 1;\n" ::"l"(&g_hint[sub * 32 + idx]) : "memory");
}
__device__ __forceinline__ void hint_wait(const unsigned* g_hint, int idx, unsigned target) {
    unsigned l;
    asm volatile("mov.u32 %0, %%laneid;" : "=r"(l));
    const unsigned* c = &g_hint[(l & 7) * 32 + idx];
    int it = 0;
    while (__any_sync(0xffffffffu, (int)(ld_poll32(c) - target) < 0)) { if (++it > SPIN_LIMIT) TRAP(); }
}
__device__ __forceinline__ void mbar_init(uint32_t bar, uint32_t cnt) { asm volatile("mbarrier.init.shared::cta.b64 [%0], %1;\n" ::"r"(bar), "r"(cnt) : "memory"); }
__device__ __forceinline__ void mbar_expect(uint32_t bar, uint32_t bytes) {
    asm volatile("mbarrier.arrive.expect_tx.shared::cta.b64 _, [%0], %1;\n" ::"r"(bar), "r"(bytes) : "memory");
}
__device__ __forceinline__ void mbar_arrive(uint32_t bar) { asm volatile("mbarrier.arrive.shared::cta.b64 _, [%0];\n" ::"r"(bar) : "memory"); }
__device__ __forceinline__ void mbar_wait_cluster(uint32_t bar) {
    asm volatile(
        "{\n.reg .pred p;\n"
        "W_%=:\n"
        "mbarrier.try_wait.parity.acquire.cluster.shared::cta.b64 p, [%0], 0;\n"
        "@!p bra W_%=;\n}\n" ::"r"(bar) : "memory");
}
__device__ __forceinline__ void mbar_wait(uint32_t bar) {
    asm volatile(
        "{\n.reg .pred p;\n"
        "W_%=:\n"
        "mbarrier.try_wait.parity.shared::cta.b64 p, [%0], 0;\n"
        "@!p bra W_%=;\n}\n" ::"r"(bar) : "memory");
}
__device__ __forceinline__ void mbar_wait_parity(uint32_t bar, uint32_t par) {
    asm volatile(
        "{\n.reg .pred p;\n"
        "W_%=:\n"
        "mbarrier.try_wait.parity.shared::cta.b64 p, [%0], %1;\n"
        "@!p bra W_%=;\n}\n" ::"r"(bar), "r"(par) : "memory");
}
__device__ __forceinline__ bool mbar_test(uint32_t bar) {
    uint32_t r;
    asm volatile("{\n.reg .pred p;\nmbarrier.test_wait.parity.shared::cta.b64 p, [%1], 0;\nselp.u32 %0, 1, 0, p;\n}\n" : "=r"(r) : "r"(bar) : "memory");
    return __any_sync(0xffffffffu, r);
}
__device__ __forceinline__ void bulk_g2s(uint32_t dst, const void* src, uint32_t bytes, uint32_t bar) {
    asm volatile("cp.async.bulk.shared::cluster.global.mbarrier::complete_tx::bytes [%0], [%1], %2, [%3];\n" ::"r"(dst), "l"(src), "r"(bytes), "r"(bar) : "memory");
}
__device__ __forceinline__ void bulk_s2g(void* dst, uint32_t src, uint32_t bytes) {
    asm volatile("cp.async.bulk.global.shared::cta.bulk_group [%0], [%1], %2;\ncp.async.bulk.commit_group;\n" ::"l"(dst), "r"(src), "r"(bytes) : "memory");
}
__device__ __forceinline__ void tma_2d(uint32_t dst, const CUtensorMap* tm, int c0, int c1, uint32_t bar) {
    asm volatile("cp.async.bulk.tensor.2d.shared::cluster.global.mbarrier::complete_tx::bytes [%0], [%1, {%3, %4}], [%2];\n"
                 ::"r"(dst), "l"(tm), "r"(bar), "r"(c0), "r"(c1) : "memory");
}
__device__ __forceinline__ void tma_3d(uint32_t dst, const CUtensorMap* tm, int c0, int c1, int c2, uint32_t bar) {
    asm volatile("cp.async.bulk.tensor.3d.shared::cluster.global.mbarrier::complete_tx::bytes [%0], [%1, {%3, %4, %5}], [%2];\n"
                 ::"r"(dst), "l"(tm), "r"(bar), "r"(c0), "r"(c1), "r"(c2) : "memory");
}
__device__ __forceinline__ void tma_3d_mc(uint32_t dst, const CUtensorMap* tm, int c0, int c1, int c2, uint32_t bar) {
    asm volatile("cp.async.bulk.tensor.3d.shared::cluster.global.mbarrier::complete_tx::bytes.multicast::cluster [%0], [%1, {%3, %4, %5}], [%2], %6;\n"
                 ::"r"(dst), "l"(tm), "r"(bar), "r"(c0), "r"(c1), "r"(c2), "h"((unsigned short)3) : "memory");
}
__device__ __forceinline__ void tma_st_3d(const CUtensorMap* tm, uint32_t src, int c0, int c1, int c2) {
    asm volatile("cp.async.bulk.tensor.3d.global.shared::cta.bulk_group [%0, {%2, %3, %4}], [%1];\ncp.async.bulk.commit_group;\n"
                 ::"l"(tm), "r"(src), "r"(c0), "r"(c1), "r"(c2) : "memory");
}
__device__ __forceinline__ void l2_prefetch(const void* src, uint32_t bytes) {
    asm volatile("cp.async.bulk.prefetch.L2.global [%0], %1;\n" ::"l"(src), "r"(bytes) : "memory");
}
__device__ __forceinline__ bool elect_one() {
    uint32_t r;
    asm volatile("{\n.reg .pred p;\nelect.sync _|p, 0xffffffff;\nselp.u32 %0, 1, 0, p;\n}\n" : "=r"(r));
    return r;
}
__device__ __forceinline__ void fence_async() { asm volatile("fence.proxy.async.shared::cta;\n" ::: "memory"); }

__device__ __forceinline__ float2 cmul(float2 a, float2 b) {
    return make_float2(fmaf(a.x, b.x, -a.y * b.y), fmaf(a.x, b.y, a.y * b.x));
}
__device__ __forceinline__ float2 csq(float2 a) {
    float p = a.x * a.y;
    return make_float2(fmaf(a.x, a.x, -a.y * a.y), p + p);
}
__device__ __forceinline__ float2 cexp_e(float lr2, float rh, float rl, float e) {
    float m;
    asm("ex2.approx.ftz.f32 %0, %1;\n" : "=f"(m) : "f"(lr2 * e));
    const float a = rh * e;
    const float r = fmaf(rl, e, a - rintf(a)) * 6.283185307179586f;
    return make_float2(m * __cosf(r), m * __sinf(r));
}
__device__ __forceinline__ float rcp_approx(float x) { float r; asm("rcp.approx.ftz.f32 %0, %1;\n" : "=f"(r) : "f"(x)); return r; }
__device__ __forceinline__ float ex2_approx(float x) { float r; asm("ex2.approx.ftz.f32 %0, %1;\n" : "=f"(r) : "f"(x)); return r; }
__device__ __forceinline__ float sqrt_approx(float x) { float r; asm("sqrt.approx.ftz.f32 %0, %1;\n" : "=f"(r) : "f"(x)); return r; }

__device__ __forceinline__ void wg_fence() { asm volatile("wgmma.fence.sync.aligned;\n" ::: "memory"); }
__device__ __forceinline__ void wg_commit() { asm volatile("wgmma.commit_group.sync.aligned;\n" ::: "memory"); }
__device__ __forceinline__ void wg_wait0() { asm volatile("wgmma.wait_group.sync.aligned 0;\n" ::: "memory"); }
template <int T0, int NT> __device__ __forceinline__ void wg_h(uint32_t (&acc)[32], const uint32_t (&a)[4], uint64_t desc);
template <> __device__ __forceinline__ void wg_h<0, 16>(uint32_t (&acc)[32], const uint32_t (&a)[4], uint64_t desc) {
    asm volatile("wgmma.mma_async.sync.aligned.m64n128k16.f16.f16.f16 {%0,%1,%2,%3,%4,%5,%6,%7,%8,%9,%10,%11,%12,%13,%14,%15,%16,%17,%18,%19,%20,%21,%22,%23,%24,%25,%26,%27,%28,%29,%30,%31}, {%32,%33,%34,%35}, %36, 1, 1, 1, 0;\n"
                 : "+r"(acc[0]), "+r"(acc[1]), "+r"(acc[2]), "+r"(acc[3]), "+r"(acc[4]), "+r"(acc[5]), "+r"(acc[6]), "+r"(acc[7]), "+r"(acc[8]), "+r"(acc[9]), "+r"(acc[10]), "+r"(acc[11]), "+r"(acc[12]), "+r"(acc[13]), "+r"(acc[14]), "+r"(acc[15]), "+r"(acc[16]), "+r"(acc[17]), "+r"(acc[18]), "+r"(acc[19]), "+r"(acc[20]), "+r"(acc[21]), "+r"(acc[22]), "+r"(acc[23]), "+r"(acc[24]), "+r"(acc[25]), "+r"(acc[26]), "+r"(acc[27]), "+r"(acc[28]), "+r"(acc[29]), "+r"(acc[30]), "+r"(acc[31])
                 : "r"(a[0]), "r"(a[1]), "r"(a[2]), "r"(a[3]), "l"(desc));
}
template <> __device__ __forceinline__ void wg_h<4, 4>(uint32_t (&acc)[32], const uint32_t (&a)[4], uint64_t desc) {
    asm volatile("wgmma.mma_async.sync.aligned.m64n32k16.f16.f16.f16 {%0,%1,%2,%3,%4,%5,%6,%7}, {%8,%9,%10,%11}, %12, 1, 1, 1, 0;\n"
                 : "+r"(acc[8]), "+r"(acc[9]), "+r"(acc[10]), "+r"(acc[11]), "+r"(acc[12]), "+r"(acc[13]), "+r"(acc[14]), "+r"(acc[15])
                 : "r"(a[0]), "r"(a[1]), "r"(a[2]), "r"(a[3]), "l"(desc));
}
template <> __device__ __forceinline__ void wg_h<8, 4>(uint32_t (&acc)[32], const uint32_t (&a)[4], uint64_t desc) {
    asm volatile("wgmma.mma_async.sync.aligned.m64n32k16.f16.f16.f16 {%0,%1,%2,%3,%4,%5,%6,%7}, {%8,%9,%10,%11}, %12, 1, 1, 1, 0;\n"
                 : "+r"(acc[16]), "+r"(acc[17]), "+r"(acc[18]), "+r"(acc[19]), "+r"(acc[20]), "+r"(acc[21]), "+r"(acc[22]), "+r"(acc[23])
                 : "r"(a[0]), "r"(a[1]), "r"(a[2]), "r"(a[3]), "l"(desc));
}
template <> __device__ __forceinline__ void wg_h<12, 4>(uint32_t (&acc)[32], const uint32_t (&a)[4], uint64_t desc) {
    asm volatile("wgmma.mma_async.sync.aligned.m64n32k16.f16.f16.f16 {%0,%1,%2,%3,%4,%5,%6,%7}, {%8,%9,%10,%11}, %12, 1, 1, 1, 0;\n"
                 : "+r"(acc[24]), "+r"(acc[25]), "+r"(acc[26]), "+r"(acc[27]), "+r"(acc[28]), "+r"(acc[29]), "+r"(acc[30]), "+r"(acc[31])
                 : "r"(a[0]), "r"(a[1]), "r"(a[2]), "r"(a[3]), "l"(desc));
}
template <> __device__ __forceinline__ void wg_h<0, 8>(uint32_t (&acc)[32], const uint32_t (&a)[4], uint64_t desc) {
    asm volatile("wgmma.mma_async.sync.aligned.m64n64k16.f16.f16.f16 {%0,%1,%2,%3,%4,%5,%6,%7,%8,%9,%10,%11,%12,%13,%14,%15}, {%16,%17,%18,%19}, %20, 1, 1, 1, 0;\n"
                 : "+r"(acc[0]), "+r"(acc[1]), "+r"(acc[2]), "+r"(acc[3]), "+r"(acc[4]), "+r"(acc[5]), "+r"(acc[6]), "+r"(acc[7]), "+r"(acc[8]), "+r"(acc[9]), "+r"(acc[10]), "+r"(acc[11]), "+r"(acc[12]), "+r"(acc[13]), "+r"(acc[14]), "+r"(acc[15])
                 : "r"(a[0]), "r"(a[1]), "r"(a[2]), "r"(a[3]), "l"(desc));
}
template <> __device__ __forceinline__ void wg_h<4, 12>(uint32_t (&acc)[32], const uint32_t (&a)[4], uint64_t desc) {
    asm volatile("wgmma.mma_async.sync.aligned.m64n96k16.f16.f16.f16 {%0,%1,%2,%3,%4,%5,%6,%7,%8,%9,%10,%11,%12,%13,%14,%15,%16,%17,%18,%19,%20,%21,%22,%23}, {%24,%25,%26,%27}, %28, 1, 1, 1, 0;\n"
                 : "+r"(acc[8]), "+r"(acc[9]), "+r"(acc[10]), "+r"(acc[11]), "+r"(acc[12]), "+r"(acc[13]), "+r"(acc[14]), "+r"(acc[15]), "+r"(acc[16]), "+r"(acc[17]), "+r"(acc[18]), "+r"(acc[19]), "+r"(acc[20]), "+r"(acc[21]), "+r"(acc[22]), "+r"(acc[23]), "+r"(acc[24]), "+r"(acc[25]), "+r"(acc[26]), "+r"(acc[27]), "+r"(acc[28]), "+r"(acc[29]), "+r"(acc[30]), "+r"(acc[31])
                 : "r"(a[0]), "r"(a[1]), "r"(a[2]), "r"(a[3]), "l"(desc));
}

#define PBYTES 4608
#define DELAY(n) do { if (n) { const unsigned c0_ = clock32(); while ((int)(clock32() - c0_) < (n)) {} } } while (0)
#define YDEL 0
#define YSEL 0
#define KDEL 300
#define PDEL 300
#define P4D 0
#define W2 8
#define HINTW 10
#define WAS 0x0005
#define WA0 (WAS >> 12)
#define WA1 ((WAS >> 8) & 15)
#define WA2 ((WAS >> 4) & 15)
#define WA3 (WAS & 15)
#define WDAT 1
#define PAUSE 2
#define PCNT (32 + ((PAUSE & 1) ? 288 : 0) + ((PAUSE & 6) ? 320 : 64))
#define LNAT 2
#define UW 8
#define FINAT 3
#define UAT 2
#define HK 9
#define TOKEN_OF(g) (16 * ((g) & 1) + ((g) >> 2) + 2 * ((g) & 2))
#define HI2(a, b) (pack_f16_rz(__uint_as_float(a), __uint_as_float(b)) & 0xfff8fff8u)
struct Params {
    const bf16 *x, *lar, *aim, *cre, *cim, *ldt, *dsk;
    Scratch* s;
    const bf16* wr;
    bf16* out;
};

template <int NK>
__device__ __forceinline__ void ln_partial(const uint32_t (&H)[2][NK], const uint32_t (&bw)[NK], uint32_t lp, int warp, int g, int t) {
    float cs[4] = {0.f, 0.f, 0.f, 0.f}, cl[4] = {0.f, 0.f, 0.f, 0.f}, ch[4] = {0.f, 0.f, 0.f, 0.f};
#pragma unroll
    for (int k = 0; k < NK; k += 2) {
        uint32_t a0, a1, a2, a3;
        asm volatile("prmt.b32 %0, %4, %4, %8;\nprmt.b32 %1, %5, %5, %8;\nprmt.b32 %2, %6, %6, %8;\nprmt.b32 %3, %7, %7, %8;\n"
                     : "=r"(a0), "=r"(a1), "=r"(a2), "=r"(a3) : "r"(H[0][k]), "r"(H[1][k]), "r"(H[0][k + 1]), "r"(H[1][k + 1]), "r"(0x3210u + (warp >> 8)));
        mma_bf16(cl, a0, a1, a2, a3, H[0][k], H[0][k + 1]);
        mma_bf16(ch, a0, a1, a2, a3, H[1][k], H[1][k + 1]);
        mma_bf16(cs, a0, a1, a2, a3, bw[k], bw[k + 1]);
    }
    const uint32_t a = lp + (g * 20 + warp) * 4;
    if (t == 0) {
        stsf(a, cs[1]); stsf(a + 8 * 80, cs[3]);
    }
    if (t == (g >> 1)) { stsf(a + 16 * 80, (g & 1) ? cl[1] : cl[0]); stsf(a + 24 * 80, (g & 1) ? ch[3] : ch[2]); }
}
__device__ __forceinline__ float sum18(uint32_t a) {
    const uint4 p = lds128(a), q = lds128(a + 16), r = lds128(a + 32), s = lds128(a + 48);
    const uint2 u = lds64(a + 64);
#define F(x) __uint_as_float(x)
    return (((F(p.x) + F(p.y)) + (F(p.z) + F(p.w))) + ((F(q.x) + F(q.y)) + (F(q.z) + F(q.w)))) +
           (((F(r.x) + F(r.y)) + (F(r.z) + F(r.w))) + ((F(s.x) + F(s.y)) + (F(s.z) + F(s.w))) + (F(u.x) + F(u.y)));
#undef F
}
__device__ __forceinline__ float sum9(uint32_t a) {
    const uint4 p = lds128(a), q = lds128(a + 16);
#define F(x) __uint_as_float(x)
    return (((F(p.x) + F(p.y)) + (F(p.z) + F(p.w))) + ((F(q.x) + F(q.y)) + (F(q.z) + F(q.w)))) + ldsf(a + 32);
#undef F
}
template <int N>
__device__ __forceinline__ void ln_finish(uint32_t lp, int lane, float& mb, float& rc) {
    const float v = N == 9 ? sum9(lp + lane * 80) : sum18(lp + lane * 80);
    const float o = __shfl_xor_sync(0xffffffffu, v, 16);
    const float m0 = v * (1.0f / 576.0f);
    const float mean = fmaf(fmaf(-m0, 576.0f, v), 1.0f / 576.0f, m0);
    const float var = fmaxf(fmaf(-mean, mean, o * (1.0f / 576.0f)), 0.f);
    mb = rbf(mean);
    rc = rcp_approx(rbf(sqrt_approx(rbf(rbf(var) + 1e-5f))));
}
__device__ __forceinline__ uint32_t ln_apply(uint32_t w, const uint2& st) {
    uint32_t r;
    asm("{\n.reg .b16 m, t, h, l;\n.reg .b32 mm, hh, ll, d, e;\nmov.b32 {m, t}, %2;\nmov.b32 {h, l}, %3;\nmov.b32 mm, {m, m};\nmov.b32 hh, {h, h};\nmov.b32 ll, {l, l};\n"
        "sub.rn.bf16x2 d, %1, mm;\nmul.rn.bf16x2 e, d, ll;\nfma.rn.bf16x2 %0, d, hh, e;\n}\n" : "=r"(r) : "r"(w), "r"(st.x), "r"(st.y));
    return r;
}
__device__ __forceinline__ void stat_store(uint32_t a, float mb, float rc, uint32_t extra) {
    const float rh = rbf(rc);
    sts64(a, (__float_as_uint(mb) >> 16) | (extra << 16), pack_bf16(rh, rc - rh));
}

__device__ __forceinline__ void hcmul(uint32_t re, uint32_t im, uint32_t z, uint32_t& ore, uint32_t& oim) {
    asm("{\n.reg .b16 x, y;\n.reg .b32 xx, yy, ny, a, b;\nmov.b32 {x, y}, %4;\nmov.b32 xx, {x, x};\nmov.b32 yy, {y, y};\nneg.f16x2 ny, yy;\n"
        "mul.rn.f16x2 a, %2, xx;\nfma.rn.f16x2 %0, %3, ny, a;\nmul.rn.f16x2 b, %3, xx;\nfma.rn.f16x2 %1, %2, yy, b;\n}\n" : "=&r"(ore), "=r"(oim) : "r"(re), "r"(im), "r"(z));
}
__device__ __forceinline__ void hcmul(uint32_t re, uint32_t im, uint32_t zx, uint32_t zy, uint32_t& ore, uint32_t& oim) {
    asm("{\n.reg .b32 ny, a, b;\nneg.f16x2 ny, %5;\n"
        "mul.rn.f16x2 a, %2, %4;\nfma.rn.f16x2 %0, %3, ny, a;\nmul.rn.f16x2 b, %3, %4;\nfma.rn.f16x2 %1, %2, %5, b;\n}\n" : "=&r"(ore), "=r"(oim) : "r"(re), "r"(im), "r"(zx), "r"(zy));
}

struct KGen {
    uint32_t Af[4][4];
    float2 z1, z8, z64, z128, T[9];
    uint32_t zw;
};
__device__ __forceinline__ void kgen_setup(KGen& k, uint32_t pa, float dt) {
    const float A = rbf(expf(bf_lo(pa)));
    const float lr2 = -(A * dt) * 1.4426950408889634f;
    const float li = bf_hi(pa) * dt;
    const float rh = li * 0.15915494309189535f;
    const float rl = fmaf(li, 6.4206382986e-9f, fmaf(li, 0.15915494309189535f, -rh));
    k.z1 = cexp_e(lr2, rh, rl, 1.0f);
    k.z8 = cexp_e(lr2, rh, rl, 8.0f);
    k.z64 = cexp_e(lr2, rh, rl, 64.0f);
}
__device__ __forceinline__ void kgen_rows(KGen& k, uint32_t tb, int lane) {
    const float2 z8 = k.z8, z64 = k.z64;
    const uint32_t row = tb + lane * TBP;
    k.z128 = csq(z64);
    const float2 z16 = csq(z8), z32 = csq(z16), z48 = cmul(z32, z16), z80 = cmul(z64, z16), z96 = cmul(z64, z32), z112 = cmul(z64, z48);
    uint32_t re[4], im[4], a[4], b[4];
    re[0] = pack_f16(1.0f, z16.x); im[0] = pack_f16(0.0f, z16.y);
    re[1] = pack_f16(z32.x, z48.x); im[1] = pack_f16(z32.y, z48.y);
    re[2] = pack_f16(z64.x, z80.x); im[2] = pack_f16(z64.y, z80.y);
    re[3] = pack_f16(z96.x, z112.x); im[3] = pack_f16(z96.y, z112.y);
    sts128(row, re[0], re[1], re[2], re[3]);
    sts128(row + 32, im[0], im[1], im[2], im[3]);
    const uint32_t zz = pack_f16(z8.x, z8.y);
#pragma unroll
    for (int j = 0; j < 4; j++) hcmul(re[j], im[j], zz, a[j], b[j]);
    sts128(row + 16, a[0], a[1], a[2], a[3]);
    sts128(row + 48, b[0], b[1], b[2], b[3]);
    __syncwarp();
    const int mi = lane >> 3;
    const uint32_t ad = tb + (lane & 7) * TBP + mi * 16;
#pragma unroll
    for (int ks = 0; ks < 4; ks++) ldsm_x4_t(k.Af[ks][0], k.Af[ks][1], k.Af[ks][2], k.Af[ks][3], ad + ks * 8 * TBP);
}
__device__ __forceinline__ void kgen_chain(KGen& k, uint32_t pc, float cs) {
    k.T[0] = make_float2(bf_lo(pc) * cs, -bf_hi(pc) * cs);
    const float2 y1 = make_float2(k.z1.x, -k.z1.y);
#pragma unroll
    for (int c = 1; c < 8; c++) k.T[c] = cmul(k.T[c - 1], y1);
    k.T[8] = cmul(k.T[0], make_float2(k.z8.x, -k.z8.y));
}
__device__ __forceinline__ void kgen_cols(KGen& k, uint32_t tb, int lane) {
    const uint32_t row = tb + lane * TBP;
    const float2 (&T)[9] = k.T;
    const uint32_t zv = pack_f16(k.z128.x, k.z128.y), zo = __shfl_xor_sync(0xffffffffu, zv, 1);
    k.zw = (lane & 1) ? __byte_perm(zo, zv, 0x7632) : __byte_perm(zv, zo, 0x5410);
    const float2 y256 = csq(make_float2(k.z128.x, -k.z128.y)), y512 = csq(y256), y768 = cmul(y512, y256), y1024 = csq(y512);
    const float2 c1032 = cmul(T[8], y1024);
    const uint32_t r04 = pack_f16(T[0].x, T[4].x), i04 = pack_f16(T[0].y, T[4].y), r26 = pack_f16(T[2].x, T[6].x), i26 = pack_f16(T[2].y, T[6].y);
    const uint32_t r48 = pack_f16(T[4].x, T[8].x), i48 = pack_f16(T[4].y, T[8].y);
    __syncwarp();
    sts128(row, r04, pack_f16(T[1].x, T[5].x), r26, pack_f16(T[3].x, T[7].x));
    sts128(row + 16, i04, pack_f16(T[1].y, T[5].y), i26, pack_f16(T[3].y, T[7].y));
    uint32_t a[4], b[4];
    {
        const uint32_t zz = pack_f16(y256.x, y256.y);
        hcmul(r04, i04, zz, a[0], b[0]);
        hcmul(r26, i26, zz, a[2], b[2]);
        hcmul(r48, i48, zz, a[3], b[3]);
    }
    sts128(row + 32, a[0], a[0], a[2], a[3]);
    sts128(row + 48, b[0], b[0], b[2], b[3]);
    {
        hcmul(r48, i48, pack_f16(y512.x, y512.y), a[0], b[0]);
        hcmul(r48, i48, pack_f16(y768.x, y768.y), a[1], b[1]);
        const uint32_t zz = pack_f16(c1032.x, c1032.y);
        hcmul(pack_f16(1.0f, y256.x), pack_f16(0.0f, y256.y), zz, a[2], b[2]);
        hcmul(pack_f16(y512.x, y768.x), pack_f16(y512.y, y768.y), zz, a[3], b[3]);
    }
    sts128(row + 64, a[0], a[1], a[2], a[3]);
    sts128(row + 80, b[0], b[1], b[2], b[3]);
}
__device__ __forceinline__ void kgen_mma(const KGen& k, uint32_t tb, int lane) {
    const int t = lane & 3;
    const uint32_t zw = k.zw;
    uint32_t zx[4], zy[4];
#pragma unroll
    for (int ks = 0; ks < 4; ks++) { zx[ks] = __shfl_sync(0xffffffffu, zw, 8 * ks + 2 * t); zy[ks] = __shfl_sync(0xffffffffu, zw, 8 * ks + 2 * t + 1); }
    __syncwarp();
    float acc[2][3][4];
#pragma unroll
    for (int i = 0; i < 6; i++)
#pragma unroll
        for (int j = 0; j < 4; j++) acc[i / 3][i % 3][j] = 0.f;
    {
        const int mi = lane >> 3;
        const uint32_t bd = tb + ((lane & 7) + 8 * (mi >> 1)) * TBP + (mi & 1) * 16;
#pragma unroll
        for (int kp = 0; kp < 2; kp++) {
            uint32_t b[3][4];
#pragma unroll
            for (int j = 0; j < 3; j++) ldsm_x4_t(b[j][0], b[j][1], b[j][2], b[j][3], bd + kp * 16 * TBP + j * 32);
#pragma unroll
            for (int h = 0; h < 2; h++) {
                const int ks = 2 * kp + h;
                uint32_t d[4];
                hcmul(k.Af[ks][0], k.Af[ks][2], zx[ks], zy[ks], d[0], d[2]);
                hcmul(k.Af[ks][1], k.Af[ks][3], zx[ks], zy[ks], d[1], d[3]);
#pragma unroll
                for (int j = 0; j < 3; j++) {
                    mma_f16(acc[0][j], k.Af[ks][0], k.Af[ks][1], k.Af[ks][2], k.Af[ks][3], b[j][2 * h], b[j][2 * h + 1]);
                    mma_f16(acc[1][j], d[0], d[1], d[2], d[3], b[j][2 * h], b[j][2 * h + 1]);
                }
            }
        }
    }
    __syncwarp();
#pragma unroll
    for (int h = 0; h < 2; h++) {
        sts64(tb + h * 256 + lane * 8, pack_f16(acc[h][0][0], acc[h][0][1]), pack_f16(acc[h][0][2], acc[h][0][3]));
        sts64(tb + 512 + h * 256 + lane * 8, pack_f16(acc[h][1][0], acc[h][1][1]), pack_f16(acc[h][1][2], acc[h][1][3]));
        sts32(tb + 1024 + h * 256 + lane * 4, pack_f16(acc[h][2][0], t < 2 ? acc[h][2][1] : acc[h][2][2]));
        sts32(tb + 1152 + h * 256 + lane * 4, pack_f16(t < 2 ? acc[h][2][2] : acc[h][2][1], acc[h][2][3]));
    }
}
__device__ __forceinline__ uint32_t table_buf(uint32_t sb, int warp) { return sb + SM_TB + warp * TBW; }

__device__ __forceinline__ void kgen_combine(uint32_t sb, int warp, int lane, uint32_t kw, uint32_t ao) {
    const int wq = warp & 3;
    const uint32_t a = table_buf(sb, warp & ~3) + wq * 256 + lane * 8, c = table_buf(sb, warp & ~3) + 1024 + wq * 128 + lane * 4;
    const int t = lane & 3;
    const uint32_t o0 = (t < 2 ? KW_T2 + KW_KH + 16 + t * 256 - (wq & 1) * KW_KH : KW_T3 + 16 - 1024 + t * 512 + (wq & 1) * 256) + (lane >> 2) * 16;
    const uint4 o = make_uint4(o0 + t * 36, o0 + (t ^ 1) * 36, o0 + (t ^ 2) * 36, o0 + (t ^ 3) * 36);
    const uint2 u = lds64(a), v = lds64(a + TBW), w = lds64(a + 2 * TBW), x = lds64(a + 3 * TBW);
    const uint32_t kt = hadd2(hadd2(lds32(c), lds32(c + TBW)), hadd2(lds32(c + 2 * TBW), lds32(c + 3 * TBW)));
    const uint32_t k23 = hadd2(hadd2(u.y, v.y), hadd2(w.y, x.y));
    sts64(kw + wq * 64 + ao, hadd2(hadd2(u.x, v.x), hadd2(w.x, x.x)), k23);
    const uint32_t d = kw + (wq >> 1) * 128;
    const uint32_t kh = hmul2(kt, 0x38003800u);
    sts32(d + o.x, kh); sts32(d + o.y, kh); sts32(d + o.z, kh); sts32(d + o.w, kh);
    if (wq == 3) {
        if (lane == 31) { sts32(kw + 264, k23 >> 16); sts32(kw + 288 + 264, k23 >> 16); sts32(kw + 576 + 264, k23 >> 16); }
        if (lane == 29) { sts32(kw + 864 + 280, kt >> 16); sts32(kw + 280, kt & 0xffff0000u); }
    }
}

__device__ __forceinline__ int c_exponent(const uint2& r, const uint2& i) {
    uint32_t mx = __vmaxu2(__vmaxu2(r.x & 0x7fff7fffu, r.y & 0x7fff7fffu), __vmaxu2(i.x & 0x7fff7fffu, i.y & 0x7fff7fffu));
    mx = __reduce_max_sync(0xffffffffu, max(mx & 0xffffu, mx >> 16));
    return min(max((int)(mx >> 7), 4), 240);
}

__device__ __forceinline__ int warp_v() { int l; asm volatile("mov.u32 %0, %%tid.x;" : "=r"(l)); return __shfl_sync(0xffffffffu, l >> 5, 0); }
__device__ __forceinline__ int lane_v() { int l; asm volatile("mov.u32 %0, %%laneid;" : "=r"(l)); return l; }
__device__ __forceinline__ unsigned clock32() { unsigned c; asm volatile("mov.u32 %0, %%clock;" : "=r"(c)); return c; }
__device__ __forceinline__ uint32_t prmt(uint32_t a, uint32_t b, uint32_t s) { uint32_t d; asm("prmt.b32 %0, %1, %2, %3;\n" : "=r"(d) : "r"(a), "r"(b), "r"(s)); return d; }
__device__ __forceinline__ uint32_t prmt_v(uint32_t a, uint32_t b, uint32_t s) { uint32_t d; asm volatile("prmt.b32 %0, %1, %2, %3;\n" : "=r"(d) : "r"(a), "r"(b), "r"(s)); return d; }
__device__ __forceinline__ void mmah16(uint32_t& d0, uint32_t& d1, uint32_t a0, uint32_t a1, uint32_t a2, uint32_t a3, uint32_t b0, uint32_t b1, uint32_t c0, uint32_t c1) {
    asm volatile("mma.sync.aligned.m16n8k16.row.col.f16.f16.f16.f16 {%0,%1}, {%2,%3,%4,%5}, {%6,%7}, {%8,%9};\n"
                 : "=r"(d0), "=r"(d1) : "r"(a0), "r"(a1), "r"(a2), "r"(a3), "r"(b0), "r"(b1), "r"(c0), "r"(c1));
}
__device__ __forceinline__ void mmah8(uint32_t& d0, uint32_t& d1, uint32_t a0, uint32_t a1, uint32_t b0, uint32_t c0, uint32_t c1) {
    asm volatile("mma.sync.aligned.m16n8k8.row.col.f16.f16.f16.f16 {%0,%1}, {%2,%3}, {%4}, {%5,%6};\n"
                 : "=r"(d0), "=r"(d1) : "r"(a0), "r"(a1), "r"(b0), "r"(c0), "r"(c1));
}
template <int A = 8, int B = 32>
__device__ __forceinline__ void conv_rename(uint32_t (&acc)[32]) {
#pragma unroll
    for (int i = A; i < B; i++) { uint32_t v; asm volatile("mov.b32 %0, %1;\n" : "=r"(v) : "r"(acc[i])); acc[i] = v; }
}
__host__ __device__ constexpr uint32_t band_bits(int hw, int sh) {
    uint32_t c = 0;
    for (int s = 0; s <= 10; s++)
        for (int e = 0; e < 2; e++) {
            const int v = s - 3 + sh - 4 * e;
            if (v <= hw && v >= -hw) c |= 1u << (14 + 16 * e - s);
        }
    return c;
}
template <int HW, int SH, int J> __device__ __forceinline__ uint32_t band(uint32_t p2) {
    uint32_t d;
    asm volatile("{\n.reg .b32 t;\nmul.lo.u32 t, %1, %2;\nand.b32 %0, t, 0x40004000;\n}\n" : "=r"(d) : "r"(p2), "n"(band_bits(HW, SH) | J));
    return d;
}
template <int H0, int SH> __device__ __forceinline__ void band_pair(uint4& l, uint4& u, uint32_t p2) {
    l = make_uint4(band<H0, 8, 1>(p2), band<H0 - 1, SH + 8, 2>(p2), band<H0, 0, 1>(p2), band<H0 - 1, SH, 1>(p2));
    u = make_uint4(band<H0, 0, 2>(p2), band<H0 - 1, SH, 2>(p2), band<H0, -8, 1>(p2), band<H0 - 1, SH - 8, 1>(p2));
}
__device__ __forceinline__ void run_sums(uint32_t (&G)[3][2], const uint32_t (&c)[5], const uint4& l, const uint4& u) {
    mmah8(G[0][0], G[0][1], l.x, l.y, c[0], 0u, 0u);
    mmah8(G[1][0], G[1][1], u.z, u.w, c[3], 0u, 0u);
    mmah8(G[2][0], G[2][1], l.x, l.y, c[2], 0u, 0u);
    mmah16(G[0][0], G[0][1], u.x, u.y, u.z, u.w, c[1], c[2], G[0][0], G[0][1]);
    mmah16(G[1][0], G[1][1], l.x, l.y, l.z, l.w, c[1], c[2], G[1][0], G[1][1]);
    mmah16(G[2][0], G[2][1], u.x, u.y, u.z, u.w, c[3], c[4], G[2][0], G[2][1]);
}
__device__ __forceinline__ float h_lo(uint32_t w) { return __half2float(__ushort_as_half((unsigned short)(w & 0xffffu))); }
__device__ __forceinline__ float h_hi(uint32_t w) { return __half2float(__ushort_as_half((unsigned short)(w >> 16))); }
__device__ __forceinline__ uint64_t smem_desc(uint32_t sb, uint32_t o16, uint32_t lbo) {
    uint64_t d;
    asm("mov.b64 %0, {%1, %2};" : "=l"(d) : "r"(((sb & 0x3FFFF) >> 4) + o16 + (lbo << 12)), "r"(8));
    return d;
}
template <int I> struct IC { static constexpr int value = I; };

struct Conv {
    uint32_t u[3][5];
    uint32_t q2[3][2][4];
    uint32_t q3[2][4];
    uint32_t r[18];
};
struct ConvPre {
    uint32_t a[5], b[5];
    uint32_t t[4];
};
__device__ __forceinline__ void conv_pre(ConvPre& e, uint32_t ka, uint32_t ks, uint32_t sel) {
    const uint4 r = lds128(ka + 256), s = lds128(ka + 272);
    ldsm_x4(e.t[0], e.t[1], e.t[2], e.t[3], ks);
    const uint32_t sw = sel ^ 0x4444u;
    e.a[0] = prmt(r.y, r.z, sel); e.a[1] = prmt(r.w, r.z, sw); e.a[2] = prmt(r.x, r.y, sel); e.a[3] = prmt(r.z, r.y, sw); e.a[4] = prmt(r.z, r.w, sel);
    e.b[0] = prmt(s.y, s.z, sel); e.b[1] = prmt(s.w, s.z, sw); e.b[2] = prmt(s.x, s.y, sel); e.b[3] = prmt(s.z, s.y, sw); e.b[4] = prmt(s.z, s.w, sel);
}
__device__ __forceinline__ void conv_sums(Conv& c, uint32_t (&acc)[32], const ConvPre& e, uint32_t a0, uint32_t a1, const uint4 (&bd)[4], uint32_t ka, uint32_t sel, int wq, uint32_t zr) {
    {
        uint32_t x;
        ldsm_x4(c.u[0][1], c.u[0][2], c.u[0][3], c.u[0][4], a1);
        ldsm_x4(c.u[0][0], c.u[1][0], c.u[2][0], x, a0);
#pragma unroll
        for (int q = 1; q < 3; q++) ldsm_x4(c.u[q][1], c.u[q][2], c.u[q][3], c.u[q][4], a1 + q * 512);
    }
#pragma unroll
    for (int i = 0; i < 32; i++) acc[i] = 0u;
    uint32_t G[3][2];
#pragma unroll
    for (int q = 0; q < 3; q++) {
        mmah8(acc[8 * q + 8], acc[8 * q + 9], e.a[4], 0u, c.u[q][2], acc[8 * q + 8], acc[8 * q + 9]);
        mmah16(acc[8 * q + 8], acc[8 * q + 9], e.a[0], e.a[1], e.a[2], e.a[3], c.u[q][3], c.u[q][4], acc[8 * q + 8], acc[8 * q + 9]);
        if (q < 2) {
            mmah8(acc[8 * q + 16], acc[8 * q + 17], e.b[4], 0u, c.u[q][2], 0u, 0u);
            mmah16(acc[8 * q + 16], acc[8 * q + 17], e.b[0], e.b[1], e.b[2], e.b[3], c.u[q][3], c.u[q][4], acc[8 * q + 16], acc[8 * q + 17]);
            run_sums(G, c.u[q], bd[2], bd[3]);
            c.q3[q][0] = prmt(G[1][1], G[0][0], 0x7632u); c.q3[q][1] = prmt(G[2][1], G[1][0], 0x7632u);
            c.q3[q][2] = prmt(G[1][1], G[0][0], 0x5410u); c.q3[q][3] = prmt(G[2][1], G[1][0], 0x5410u);
        }
    }
    {
        const uint32_t a = (ka + wq * 64) ^ (((acc[8] | acc[16] | acc[24]) | (c.q3[0][0] | c.q3[0][1]) | (c.q3[1][0] | c.q3[1][1])) & zr);
#pragma unroll
        for (int i = 0; i < 4; i++) { const uint4 v = lds128(a + i * 16); c.r[4 * i] = v.x; c.r[4 * i + 1] = v.y; c.r[4 * i + 2] = v.z; c.r[4 * i + 3] = v.w; }
        const uint2 v = lds64(a + 64);
        c.r[16] = v.x; c.r[17] = v.y;
    }
#pragma unroll
    for (int q = 0; q < 3; q++) {
        run_sums(G, c.u[q], bd[0], bd[1]);
#pragma unroll
        for (int h = 0; h < 2; h++) {
            const uint32_t s = h ? 0x7632u : 0x5410u;
            c.q2[q][h][0] = prmt(G[0][1], G[0][0], s); c.q2[q][h][1] = prmt(G[1][1], G[1][0], s);
            c.q2[q][h][2] = prmt(G[1][0], G[1][1], s ^ 0x4444u); c.q2[q][h][3] = prmt(G[2][1], G[2][0], s);
            if (q < 2) mmah16(acc[8 * q + 16], acc[8 * q + 17], c.q2[q][h][0], c.q2[q][h][1], c.q2[q][h][2], c.q2[q][h][3], e.t[2 * h], e.t[2 * h + 1], acc[8 * q + 16], acc[8 * q + 17]);
        }
    }
    if (sel == 0u) {
#pragma unroll
        for (int i = 0; i < 6; i++) sts128(ka + i * 16, c.q2[i >> 1][i & 1][0], c.q2[i >> 1][i & 1][1], c.q2[i >> 1][i & 1][2], c.q2[i >> 1][i & 1][3]);
#pragma unroll
        for (int i = 0; i < 2; i++) sts128(ka + i * 16, c.q3[i][0], c.q3[i][1], c.q3[i][2], c.q3[i][3]);
#pragma unroll
        for (int i = 1; i < 4; i++) sts64(ka + i * 16, acc[8 * i], acc[8 * i + 1]);
    }
    conv_rename(acc);
}
#define SPACE 100
#define SPN 3
#define O4 4
#define B2L 1
#define GATE 2
#define HAND 2
#define GA 6
#define GB 4
template <int TA, int TB, int IA, class FG>
__device__ __forceinline__ void conv_tail(uint32_t (&acc)[32], const uint32_t (&a)[8][4], uint32_t sb, unsigned char* gy0, int warp, size_t ycopy, FG fg) {
    const int wg = warp >> 2, wq = warp & 3, ord = TA == 0 && TB == 16 ? 3 - wg + (3 - wg >= O4) : O4;
    const uint32_t ub = sb + SM_U + wg * USLOT_B + UPAD * 16, turn = sb + SM_MISC + 376 + ord * 8, sfs = sb + SM_MISC + 256 + wg * 8;
    const uint32_t du = wg * (USLOT_B / 16) + (SM_U / 16 + UPAD + TA * 8);
    uint32_t ud[8], fs;
    auto skip = [&]() {
        const int lane = lane_v();
        const uint32_t ua = ub + ((lane >> 3) & 1) * ULO_B + (8 * wq + (lane & 7)) * 16 + (lane >> 4) * 512;
        if (IA == 0) ldsm_x4_t(ud[0], ud[1], ud[2], ud[3], ua);
        if (TB == 16) ldsm_x4_t(ud[4], ud[5], ud[6], ud[7], ua + 1024);
        const uint2 fd = lds64(sfs);
        fs = fd.x;
        const float dsk = __uint_as_float(fd.y);
#pragma unroll
        for (int i = 2 * IA; i < TB / 2; i++) ud[i] = pack_bf16(h_lo(ud[i]) * dsk, h_hi(ud[i]) * dsk);
    };
    conv_rename<2 * TA, 2 * TB>(acc);
    if (__builtin_expect(ord != 0, 0)) {
        skip();
        mbar_wait(turn);
    } else if (B2L) {
        bar_sync(0, NWRK);
    }
    if (O4 < 4 || (TA == 0 && TB == 16)) asm volatile("{\n.reg .pred p;\nelect.sync _|p, 0xffffffff;\n@p mbarrier.arrive.shared::cta.b64 _, [%0];\n}\n" ::"r"(turn + 48) : "memory");
    fg(IC<8>());
    wg_fence();
#pragma unroll
    for (int m = 7; m >= 0; m--) {
        wg_h<TA, TB - TA>(acc, a[m], smem_desc(sb, du - m, ULO_B));
        if (m == GA || m == GB || m == HAND) wg_commit();
        if (m == GB) asm volatile("wgmma.wait_group.sync.aligned 1;\n" ::: "memory");
    }
    wg_commit();
    if (O4 < 4 || (TA == 0 && TB == 16)) {
        asm volatile("wgmma.wait_group.sync.aligned 1;\n" ::: "memory");
        asm volatile("{\n.reg .pred p;\nelect.sync _|p, 0xffffffff;\n@p mbarrier.arrive.shared::cta.b64 _, [%0];\n}\n" ::"r"(turn + 8) : "memory");
    }
    __syncwarp();
    fg(IC<3>());
    if (!ord) skip();
    fg(IC<4>());
    const int lane = lane_v();
    const uint32_t lp = sb + SM_PL + (ord >= 3 ? ord - 3 : ord) * PL_B + lane * 8;
    unsigned char* gy = gy0 + ((4 * wq + (lane & 3)) * DM + (TA == 0 && TB == 16 ? 4 * blockIdx.x + wg : 512 + (blockIdx.x >> 1))) * 64 + (lane >> 2) * 8;
    const uint32_t st = lp + (wq * 12 - ((wq * (wq - 1)) >> 1)) * 256;
    uint32_t ld[3];
#pragma unroll
    for (int s = 1; s < 4; s++) {
        const int w = (wq - s) & 3;
        ld[s - 1] = lp + (w * 12 - ((w * (w - 1)) >> 1) + s - 1 - (wq < s ? 3 : 0)) * 256;
    }
    const uint32_t one = 1u + (warp >> 8);
    if (one == 0u) stg64(gy, ld[0], ld[1]);
    if (ord >= 3) bar_sync(9 + ord, 256);
    wg_wait0();
    fg(IC<6>());
#pragma unroll
    for (int j = TA; j < TB; j++)
        if ((j & 3) && j + 3 >= 4 * IA && (j + 3 < TB || j + wq < TB)) sts64(st + (j - 1 - (j >> 2)) * 256, acc[2 * j], acc[2 * j + 1]);
    bar_sync(1 + wg, 128);
    fg(IC<7>());
    uint2 v[4][3];
#pragma unroll
    for (int i = IA; i < TB / 4; i++)
#pragma unroll
        for (int s = 0; s < 3; s++) {
            if (i == 0) { v[i][s] = make_uint2(0u, 0u); if (wq > s) v[i][s] = lds64(ld[s]); }
            else v[i][s] = lds64(ld[s] + i * 768);
        }
    fg(IC<5>());
#pragma unroll
    for (int i = IA; i < TB / 4; i++) {
        const uint32_t x0 = hadd2(v[i][0].x, acc[8 * i]), x1 = hadd2(v[i][1].x, v[i][2].x), y0 = hadd2(v[i][0].y, acc[8 * i + 1]), y1 = hadd2(v[i][1].y, v[i][2].y);
        const uint32_t x = hadd2(x0, x1), y = hadd2(y0, y1);
        const uint32_t lo = pack_bf16(h_lo(x), h_hi(x)), hi = pack_bf16(h_lo(y), h_hi(y));
        ud[2 * i] = max(hfma2_bf(lo, fs, ud[2 * i]), one); ud[2 * i + 1] = hfma2_bf(hi, fs, ud[2 * i + 1]);
    }
    if (SPACE && TA == 0 && TB == 16 && ord < SPN) {
#pragma unroll
        for (int i = 0; i < 4; i++) {
            stg64(gy + i * 16 * DM * 64, ud[2 * i], ud[2 * i + 1]);
            if (i < 3) { const unsigned c0 = clock32(); while (clock32() - c0 < SPACE) {} }
        }
    } else {
#pragma unroll
        for (int i = IA; i < TB / 4; i++) stg64(gy + i * 16 * DM * 64, ud[2 * i], ud[2 * i + 1]);
    }
    if (ord < 2) bar_arrive(12 + ord, 256);
}
template <int M0, int M1>
__device__ __forceinline__ void conv_frags(uint32_t (&a)[8][4], const uint32_t (&r)[18], uint32_t sel, uint32_t dep, int warp) {
    const uint32_t s = prmt_v(sel, dep, 0x3210u + (warp >> 8)), sw = s ^ 0x4444u;
#pragma unroll
    for (int m = M0; m < M1; m++) {
        a[m][0] = prmt_v(r[2 * m + 1], r[2 * m + 2], s); a[m][1] = prmt_v(r[2 * m + 2], r[2 * m + 3], s);
        a[m][2] = prmt_v(r[2 * m + 1], r[2 * m], sw); a[m][3] = prmt_v(r[2 * m + 2], r[2 * m + 1], sw);
    }
}
template <class FG>
__device__ __forceinline__ void conv_main(const Conv& c, uint32_t (&acc)[32], uint32_t sb, uint32_t sel, unsigned char* gy, int warp, size_t ycopy, FG fg) {
    const uint32_t kw = (warp >> 2) * (KW_B / 16) + SM_KW / 16;
    const uint64_t d2 = smem_desc(sb, kw + KW_T2 / 16, KW_KH), d2b = smem_desc(sb, kw + KW_T2 / 16 + 1, KW_KH), d3 = smem_desc(sb, kw + KW_T3 / 16, 16), d3b = smem_desc(sb, kw + KW_T3 / 16 + 32, 16);
    uint32_t a[8][4];
    {
        const int ord = warp < 16 ? 3 - (warp >> 2) + (3 - (warp >> 2) >= O4) : O4;
        if (__builtin_expect(ord >= GATE, 0)) {
            fg(IC<1>());
            mbar_wait(sb + SM_MISC + 376 + 48 + (ord - GATE) * 8);
        }
    }
    wg_fence();
    wg_h<12, 4>(acc, c.q3[0], d3b); wg_h<8, 4>(acc, c.q3[0], d3); wg_h<4, 4>(acc, c.q2[0][0], d2b);
    wg_h<12, 4>(acc, c.q3[1], d3); wg_h<8, 4>(acc, c.q2[1][0], d2b);
    wg_h<12, 4>(acc, c.q2[2][0], d2b); wg_h<4, 4>(acc, c.q2[0][1], d2); wg_h<8, 4>(acc, c.q2[1][1], d2);
    wg_h<12, 4>(acc, c.q2[2][1], d2);
    wg_commit(); __syncwarp();
    fg(IC<0>());
    wg_wait0();
    conv_frags<0, 8>(a, c.r, sel, acc[16], warp);
    fg(IC<2>());
    if (warp >= 16) {
        if (blockIdx.x & 1) conv_tail<4, 16, 2>(acc, a, sb, gy, warp, ycopy, fg);
        else conv_tail<0, 8, 0>(acc, a, sb, gy, warp, ycopy, fg);
    } else {
        conv_tail<0, 16, 0>(acc, a, sb, gy, warp, ycopy, fg);
    }
}
#define CONV_LT6 const int dd = (lane >> 3) + (lane & 4) - (lane & 3); \
        const uint4 lt6 = make_uint4(prmt_v((dd & 3) * 288, 0u, idn), prmt_v(0x3254u + (dd >> 2) * 0x2222u, 0u, idn), \
            prmt_v(UPAD * 16 + (lane & 7) * 16 + ULO_B - 32 + (lane >> 3) * 512, 0u, idn), prmt_v(UPAD * 16 + (lane & 7) * 16 + ((lane >> 3) & 1) * ULO_B - 16 + (lane & 16), 0u, idn));
#define CONV_PRE \
        CONV_LT6 \
        const uint32_t ka = kw + lt6.x, sel = lt6.y, ks = kw + lt7.x; \
        const uint32_t ca0 = sb + SM_U + wg * USLOT_B + (warp & 3) * 128 + lt6.z, ca1 = sb + SM_U + wg * USLOT_B + (warp & 3) * 128 + lt6.w; \
        uint4 bd[4]; \
        band_pair<2, 4>(bd[0], bd[1], lt7.w); band_pair<4, 0>(bd[2], bd[3], lt7.w);
#define CONV_PRE2 ConvPre ce_; conv_pre(ce_, ka, ks, sel);
#define CONV_BODY \
        Conv c; \
        uint32_t acc[32]; \
        conv_sums(c, acc, ce_, ca0, ca1, bd, ka, sel, warp & 3, warp >> 8);
#define WS a_b_0_1_2_34_xy_56_7__c__r____de__
#define WS_STR2(x) #x
#define WS_STR(x) WS_STR2(x)
__device__ constexpr char wunit(int pt, int k) {
    constexpr char t[] = WS_STR(WS);
    int i = 0;
    for (; pt > 0 && t[i]; i++) pt -= t[i] == '_';
    for (; k > 0 && t[i] && t[i] != '_'; i++) k--;
    return t[i] == '_' ? 0 : t[i];
}
__device__ constexpr bool wsched_ok() {
    int seen = 0;
    for (int p = 0; p < 21; p++)
        for (int k = 0; wunit(p, k); k++) {
            const char c = wunit(p, k);
            const int bit = 1 << (c == 'r' ? 13 : c >= 'x' ? c - 'x' + 14 : c >= 'a' ? c - 'a' + 8 : c - '0');
            if ((seen & bit) || k >= (p < 16 ? 4 : 2) || (p < 5 && c >= '4' && c <= '7') || (p < 6 && (c == 'c' || c == 'd')) || (p < 16 && c == 'e')) return false;
            seen |= bit;
        }
    return seen == 0xffff;
}
struct WMaps { CUtensorMap g, u, gr, ur, d, dr; };
static_assert((PAUSE & 2) && GATE <= 2 && O4 >= 2, "resets");
static_assert(wsched_ok(), "weight schedule");
template <int PT, int K>
__device__ __forceinline__ void weight_units(uint32_t sb, const WMaps& m, int w) {
    constexpr char U = wunit(PT, K);
    if constexpr (U != 0) {
        if (w == K && elect_one()) {
            const int P = blockIdx.x >> 1, odd = blockIdx.x & 1;
            constexpr int bar = SM_MISC + (U == 'e' ? 352 : U >= 'a' && U <= 'r' ? 336 : 328);
            if constexpr (U == 'e') { if (!odd) tma_2d(sb + SM_WD + 4 * 8192, &m.d, 256, 64 * P, sb + bar); }
            else if constexpr (U == 'r') tma_3d(sb + SM_WD + 40960, &m.dr, 0, 4096 + 8 * P, 5 * odd, sb + bar);
            else if constexpr (U >= 'x') tma_3d(sb + SM_WR + (U - 'x') * 4608, U == 'x' ? &m.gr : &m.ur, 4096 + 8 * P, 0, 2 * odd, sb + bar);
            else if constexpr (U >= 'a') tma_2d(sb + SM_WD + (U - 'a') * 8192, &m.d, 320 * odd + 64 * (U - 'a'), 64 * P, sb + bar);
            else tma_2d(sb + (U < '4' ? SM_WG : SM_WU) + (U & 3) * 9216, U < '4' ? &m.g : &m.u, 64 * P, 288 * odd + (U & 3) * 72, sb + bar);
        }
        weight_units<PT, K + 1>(sb, m, w);
    }
}
#define WPOINT(i, w) do { weight_units<i, 0>(sb, wm, w); } while (0)

__global__ void __launch_bounds__(NTHR, 1) __cluster_dims__(2, 1, 1)
fused_kernel(const Params p, const __grid_constant__ WMaps wm, const __grid_constant__ CUtensorMap tm_x,
             const __grid_constant__ CUtensorMap tm_y, const __grid_constant__ CUtensorMap tm_z) {
    extern __shared__ __align__(1024) unsigned char smem[];
    const uint32_t sb = smem_u32(smem);
    const int tid = threadIdx.x, warp = __shfl_sync(0xffffffffu, tid >> 5, 0), lane = tid & 31;
    const int b = blockIdx.x, P = b >> 1, odd = b & 1;
    const int g = lane >> 2, t = lane & 3;
    const int wg = warp >> 2, t128 = tid & 127;
    const uint32_t s_stat = sb + SM_MISC;
    const uint32_t s_key = sb + SM_MISC + 128;
    const uint32_t s_wm = sb + SM_MISC + 256;
    const uint32_t s_k16 = sb + SM_MISC + 192;
    const uint32_t s_fs = sb + SM_MISC + 256;
    const uint32_t s_cnt = sb + SM_MISC + 320;
    const uint32_t bar_w = sb + SM_MISC + 328, bar_d = bar_w + 8, bar_g = bar_w + 16, bar_r = bar_w + 32, bar_h = bar_w + 40, bar_x = bar_w + 48;
    STAMP(0);

    const bool lnw = (unsigned)(warp - 10) < 9u;
    const unsigned pm = tid + (tid < 512 ? 512 * b : 65024 + 128 * P), pq = (pm & ~127u) + 4 * lane;
    uint32_t pl = ldg16(p.lar + pm), ldt = ldg16(p.ldt + (pm >> 7));
    const uint32_t pa2 = ldg16(p.aim + pm), pc = ldg16(p.cre + pm), pi = ldg16(p.cim + pm);
    const uint2 call_re = ldg64(p.cre + pq), call_im = ldg64(p.cim + pq);
    const uint32_t dskl = ldg16(p.dsk + (pm >> 7));
    const uint32_t ep = ld_poll32(p.s->hint + (b & 7) * 32 + 1 + (lane >> 5));
    if ((unsigned)(tid - 320) < 288u) {
        const bf16* xp = p.x + (unsigned)((32 * P + 2 * odd + TOKEN_OF(g)) * DM + ((tid - 320) & ~31) + 8 * t);
        const uint32_t xt = sb + SM_XT + ((tid - 320) & ~31) * 32 + lane * 16;
        asm volatile("cp.async.cg.shared.global [%0], [%1], 16;\ncp.async.cg.shared.global [%0 + 512], [%1 + 9216], 16;\n"
                     "cp.async.cg.shared.global [%0 + 9216], [%1 + 576], 16;\ncp.async.cg.shared.global [%0 + 9728], [%1 + 9792], 16;\n" ::"r"(xt), "l"(xp) : "memory");
    }
    uint32_t* const std_ = p.s->st + ((lane & 12) * 128 + odd * 256 + 4 * P + 2 * (lane & 1) + ((lane >> 1) & 1)) * 2;
    unsigned char* const ud = reinterpret_cast<unsigned char*>(p.s->uT) + (32 * (warp - UW) + 8 * (g >> 1) + (g & 1)) * 4096 + b * 32 + t * 8;
    if (warp == 0) {
        if (lane == 0) {
            mbar_init(bar_x, 1); mbar_init(bar_w, 1); mbar_init(bar_d, 1); mbar_init(bar_d + 16, 1); mbar_init(bar_g, 1); mbar_init(bar_h, 3); mbar_init(bar_r, 1);
            #pragma unroll
            for (int i = 1; i < 11; i++) mbar_init(bar_x + 8 * i, 4);
            asm volatile("fence.mbarrier_init.release.cluster;\n" ::: "memory");
            mbar_expect(bar_x, 16384); mbar_expect(bar_r, 8192);
            mbar_expect(bar_w, 2 * 41472); mbar_expect(bar_d, 32768 + 5120); mbar_expect(bar_d + 16, 8192); mbar_expect(bar_g, 9 * 512);
        }
        __syncwarp();
        bar_arrive(0, NWRK);
    }
    if (warp == 0 && elect_one()) tma_3d(sb + SM_XC, &tm_x, 8 * P, 0, 8 * odd, bar_x);
    asm volatile("barrier.cluster.arrive.relaxed.aligned;\n" ::: "memory");
    const uint32_t kw = sb + SM_KW + wg * KW_B;
    if (t128 < 2 * UPAD) sts128(sb + SM_U + wg * USLOT_B + (t128 & 1) * ULO_B + (t128 >> 1) * 16, 0u, 0u, 0u, 0u);
    sts128(kw + t128 * 16, 0u, 0u, 0u, 0u);
    if (t128 < KW_B / 16 - 128) sts128(kw + 2048 + t128 * 16, 0u, 0u, 0u, 0u);
    if (tid < 128) {
#pragma unroll
        for (int i = 0; i < 4; i++) sts128(sb + SM_ZERO + i * 2048 + tid * 16, 0u, 0u, 0u, 0u);
    }
    if (warp != 0) bar_sync(0, NWRK);
    STAMP(1);
    if (warp == 19 || warp == UW || warp == UW + 1) {
        if (warp == 19) {
            if (lane < 16) stg64(std_, 0u, 0u);
            if (lane < 9) asm volatile("prefetch.global.L2 [%0];\n" ::"l"(p.wr + lane * 64));
        } else {
#pragma unroll
            for (int k = 0; k < 4; k++) stg64(ud + k * 8192, 0u, 0u);
        }
    }
    uint32_t X[2][8];
    auto partial = [&]() {
        const uint32_t xt = sb + SM_XT + (warp - 10) * 1024 + lane * 16;
        asm volatile("cp.async.wait_all;\n" ::: "memory");
        STAMP(23);
        const uint4 a = lds128(xt), c = lds128(xt + 512), d = lds128(xt + 9216), e = lds128(xt + 9728);
        X[0][0] = a.x; X[0][1] = a.y; X[0][2] = a.z; X[0][3] = a.w; X[0][4] = d.x; X[0][5] = d.y; X[0][6] = d.z; X[0][7] = d.w;
        X[1][0] = c.x; X[1][1] = c.y; X[1][2] = c.z; X[1][3] = c.w; X[1][4] = e.x; X[1][5] = e.y; X[1][6] = e.z; X[1][7] = e.w;
        const uint32_t one[8] = {0x3f803f80u, 0x3f803f80u, 0x3f803f80u, 0x3f803f80u, 0x3f803f80u, 0x3f803f80u, 0x3f803f80u, 0x3f803f80u};
        ln_partial<8>(X, one, sb + SM_LNP, warp - 10, g, t);
        bar_arrive(6, 320);
        if (PAUSE & 1) bar_sync(7, PCNT);
    };
    if (LNAT == 0 && lnw) {
        partial();
        pl = prmt_v(pl, X[0][0], 0x3210u + (warp >> 8)); ldt = prmt_v(ldt, X[0][0], 0x3210u + (warp >> 8));
    }
    auto finish = [&]() {
        bar_sync(6, 320);
        float mb, rc;
        ln_finish<9>(sb + SM_LNP, lane, mb, rc);
        const float rh = rbf(rc);
        const uint32_t s0 = (__float_as_uint(mb) >> 16) | (((ep & 0x7fffu) + 1u) << 16), s1 = pack_bf16(rh, rc - rh);
        if (lane < 16) { stg64(std_, s0, s1); sts64(s_stat + lane * 8, s0, s1); }
        if (lane == 16) sts32(s_cnt + 4, ep);
        bar_arrive(7, PCNT);
        STAMP(28);
    };
    auto upub = [&]() {
        if (!(PAUSE & 6)) bar_sync(7, PCNT);
        const uint32_t utag = ((ep & 3u) + 1u) * 0x10001u;
        uint32_t U[2][4];
#pragma unroll
        for (int hf = 0; hf < 2; hf++) {
            const uint2 st = lds64(s_stat + (g + 8 * hf) * 8);
            const uint4 xv = lds128(sb + SM_XT + (16 + warp - UW) * 1024 + hf * 512 + lane * 16);
            const uint32_t xs[4] = {xv.x, xv.y, xv.z, xv.w};
#pragma unroll
            for (int k = 0; k < 4; k++) {
                const uint32_t u = ln_apply(xs[k], st);
                U[hf][k] = movm((pack_f16_rz(bf_lo(u), __uint_as_float(u)) & 0xfff8fff8u) | utag);
            }
        }
#pragma unroll
        for (int k = 0; k < 4; k++) stg64(ud + k * 8192, U[0][k], U[1][k]);
    };
    if (FINAT == 0 && warp == 19) finish();
    const uint32_t tb = table_buf(sb, warp);
    const float dt = rbf(expf(bf_lo(ldt)));
    KGen kg;
    kgen_setup(kg, pl | (pa2 << 16), dt);
    if (LNAT == 1 && lnw) {
        partial();
        kg.z8.x = __uint_as_float(prmt_v(__float_as_uint(kg.z8.x), X[0][0], 0x3210u + (warp >> 8)));
        kg.z1.x = __uint_as_float(prmt_v(__float_as_uint(kg.z1.x), X[0][0], 0x3210u + (warp >> 8)));
    }
    if (FINAT == 1 && warp == 19) finish();
    if (UAT == 0 && (warp == UW || warp == UW + 1)) upub();
    kgen_rows(kg, tb, lane);
    if (wg == 0) fence_async();
    if (LNAT == 2 && lnw) {
        partial();
        kg.z128.x = __uint_as_float(prmt_v(__float_as_uint(kg.z128.x), X[0][0], 0x3210u + (warp >> 8)));
        kg.z1.x = __uint_as_float(prmt_v(__float_as_uint(kg.z1.x), X[0][0], 0x3210u + (warp >> 8)));
    }
    if (FINAT == 2 && warp == 19) finish();
    if (UAT == 1 && (warp == UW || warp == UW + 1)) upub();
    STAMP(2);
    WPOINT(0, warp - 4);
    const int ce = c_exponent(call_re, call_im);
    if (t128 == 0) sts64(s_fs + wg * 8, (uint32_t)min(max(ce + (int)(__float_as_uint(dt) >> 23) - 116, 0), 254) * 0x800080u, dskl << 16);
    kgen_chain(kg, pc | (pi << 16), __uint_as_float(((uint32_t)(244 - ce) << 23) | (__float_as_uint(dt) & 0x7fffffu)));
    if ((PAUSE & 4) && warp < 10) bar_sync(7, PCNT);
    if (UAT == 4 && (warp == UW || warp == UW + 1)) upub();
    STAMP(3);
    WPOINT(1, warp - 6);
    kgen_cols(kg, tb, lane);
    if (LNAT == 3 && lnw) partial();
    if (FINAT == 3 && warp == 19) finish();
    if ((PAUSE & 2) && warp < 10) bar_sync(7, PCNT);
    if (UAT == 2 && (warp == UW || warp == UW + 1)) upub();
    STAMP(4);
    WPOINT(2, warp - W2);
    const uint4* usrc = wg < 4 ? reinterpret_cast<const uint4*>(p.s->st) + odd * 512 + (lane & 1) * 128 + 16 * (warp & 7) + (lane >> 1)
                               : reinterpret_cast<const uint4*>(p.s->uT) + P * 256 + 2 * t128;
    const int ustep = wg < 4 ? 256 : 1;
    uint4 uv0, uv1;
    kgen_mma(kg, tb, lane);
    if (UAT == 3 && (warp == UW || warp == UW + 1)) upub();
    STAMP(26);
    WPOINT(3, warp - 5);
    const uint32_t idn = 0x3210u + (warp >> 8);
    uint4 lt7 = make_uint4(prmt_v(KW_T2 + ((lane >> 3) & 1) * KW_KH + (33 + (lane & 7)) * 16 - (lane & 16), 0u, idn), t * 288 + g * 8 + 8, (lane & 1) * 4096 + (lane >> 1) * 16,
                                 prmt_v(8u << ((lane >> 3) + (lane & 4)) >> (lane & 3), 0u, idn));
    asm volatile("barrier.cluster.wait.acquire.aligned;\n" ::: "memory");
    bar_sync(1 + wg, 128);
    if (P4D == 0 || wg < 4) { uv0 = ld_poll(usrc); uv1 = ld_poll(usrc + ustep); }
    kgen_combine(sb, warp, lane, kw, lt7.y);
    if (warp < 3 || warp > 6) bar_arrive(14, NWRK);
    if (P4D == 1 && wg == 4) { uv0 = ld_poll(usrc); uv1 = ld_poll(usrc + 1); }
    CONV_PRE
    STAMP(5);
    WPOINT(4, warp - 7);
    if (wg < 4) {
        mbar_wait(bar_x);
        const bool far = warp < 8;
        const uint32_t xa = sb + SM_XC + (warp & 7) * 256 + (odd ^ far) * 8 + lt7.z;
        uint2 xv[4] = {lds64(xa), lds64(xa + 8192), lds64(xa + 2048), lds64(xa + 10240)};
        const uint32_t tag = ((ep & 0x7fffu) + 1u) << 16;
        int it = 0;
        while (true) {
            const bool bad = (((uv0.x ^ tag) | (uv0.z ^ tag)) | ((uv1.x ^ tag) | (uv1.z ^ tag))) >> 16;
            if (!__any_sync(0xffffffffu, bad)) break;
            if (++it > SPIN_LIMIT) TRAP();
            if (bad) { uv0 = ld_poll(usrc); uv1 = ld_poll(usrc + 256); }
        }
        STAMP(6);
        DBG(wg, it);
        const uint2 st[4] = {make_uint2(uv0.x, uv0.y), make_uint2(uv0.z, uv0.w), make_uint2(uv1.x, uv1.y), make_uint2(uv1.z, uv1.w)};
#pragma unroll
        for (int i = 0; i < 4; i++) {
            xv[i].x = ln_apply(xv[i].x, st[i]);
            xv[i].y = ln_apply(xv[i].y, st[i]);
        }
        const uint32_t ub = sb + SM_U + UPAD * 16 + odd * ULO_B + (warp & 7) * 256 + lane * 8;
        const uint32_t w[4][2] = {{pack_f16(bf_lo(xv[0].x), bf_lo(xv[1].x)), pack_f16(bf_lo(xv[2].x), bf_lo(xv[3].x))}, {HI2(xv[0].x, xv[1].x), HI2(xv[2].x, xv[3].x)},
                                  {pack_f16(bf_lo(xv[0].y), bf_lo(xv[1].y)), pack_f16(bf_lo(xv[2].y), bf_lo(xv[3].y))}, {HI2(xv[0].y, xv[1].y), HI2(xv[2].y, xv[3].y)}};
#pragma unroll
        for (int i = 0; i < 4; i++) {
            if (far) asm volatile("st.async.shared::cluster.mbarrier::complete_tx::bytes.v2.b32 [%0], {%1,%2}, [%3];\n" ::"r"((ub ^ 0x1000000u) + i * USLOT_B), "r"(w[i][0]), "r"(w[i][1]), "r"(bar_r ^ 0x1000000u) : "memory");
            else sts64(ub + i * USLOT_B, w[i][0], w[i][1]);
        }
    } else {
        const uint32_t utag = ((ep & 3u) + 1u) * 0x10001u;
        int it = 0;
        if (P4D > 1) { DELAY(P4D); uv0 = ld_poll(usrc); uv1 = ld_poll(usrc + 1); }
        while (true) {
            const bool bad = (((uv0.x ^ utag) | (uv0.y ^ utag) | (uv0.z ^ utag) | (uv0.w ^ utag)) | ((uv1.x ^ utag) | (uv1.y ^ utag) | (uv1.z ^ utag) | (uv1.w ^ utag))) & 0x70007u;
            if (!__any_sync(0xffffffffu, bad)) break;
            if (++it > SPIN_LIMIT) TRAP();
            if (bad) { uv0 = ld_poll(usrc); uv1 = ld_poll(usrc + 1); }
        }
        STAMP(6);
        DBG(4, it);
        const uint32_t ub = sb + SM_U + UPAD * 16 + 4 * USLOT_B + (t128 >> 1) * 32 + (t128 & 1) * 8;
        sts64(ub, prmt(uv0.x, uv0.z, 0x5410u) ^ utag, prmt(uv1.x, uv1.z, 0x5410u) ^ utag);
        sts64(ub + 16, prmt(uv0.x, uv0.z, 0x7632u) ^ utag, prmt(uv1.x, uv1.z, 0x7632u) ^ utag);
        sts64(ub + ULO_B, prmt(uv0.y, uv0.w, 0x5410u) ^ utag, prmt(uv1.y, uv1.w, 0x5410u) ^ utag);
        sts64(ub + ULO_B + 16, prmt(uv0.y, uv0.w, 0x7632u) ^ utag, prmt(uv1.y, uv1.w, 0x7632u) ^ utag);
    }
    if (warp < 3 && elect_one()) tma_st_3d(warp < 2 ? &tm_y : &tm_z, sb + SM_ZERO, warp < 2 ? 128 * b : 32 * (512 + P), 0, 2 * (warp < 2 ? warp : odd));
    if (warp >= 3 && warp <= 6) {
        bar_sync(14, NWRK);
        WPOINT(5, warp - 3);
    }
    bar_sync(1 + wg, 128);
    CONV_PRE2
    mbar_wait(bar_r);
    fence_async();
    bar_sync(0, NWRK);
    STAMP(7);
    uint32_t hv0 = 0;
    {
        WPOINT(6, 19 - warp);
        CONV_BODY
        WPOINT(7, 19 - warp);
        if (!B2L) bar_sync(0, NWRK); else if (wg != 3) bar_arrive(0, NWRK);
        STAMP(8);
        size_t ycopy = 0;
        auto hook = [&](auto gi) {
                     constexpr int G = decltype(gi)::value;
                     if (G == 4 && warp == HINTW) hv0 = ld_poll32(p.s->hint + (lane_v() & 7) * 32);
                     if (G == 4) mbar_wait(bar_h);
                     if (G == 1 || G == 2) WPOINT(7 + G, warp - 16);
                     if (G == 3) { WPOINT(10, warp - 12); WPOINT(12, warp - 8); WPOINT(14, warp - 4); }
                     if (G == 5) { WPOINT(11, warp - 13); WPOINT(13, warp - 9); WPOINT(15, warp - 5); }
                     if (G == 1 && warp >= 17 && elect_one())
                         bulk_s2g(warp == 17 ? p.s->part + b * (PBYTES / 4) : warp == 18 ? p.s->rows + b * 1152 : p.s->sc + b * 32, sb + SM_ZERO, warp == 17 ? PBYTES : warp == 18 ? 4608 : 32);
                     if (G == 4 && warp >= 17 && elect_one()) {
                         asm volatile("cp.async.bulk.wait_group 0;\n" ::: "memory");
                         hint_arrive(p.s->hint, 2, b & 7);
                     }
                     if (G == 1 && warp < 3) {
                         if (elect_one()) {
                             asm volatile("cp.async.bulk.wait_group 0;\n" ::: "memory");
                             mbar_arrive(bar_h);
                             hint_arrive(p.s->hint, 0, b & 7);
                         }
                         __syncwarp();
                         STAMP(17);
                     }
                 };
        conv_main(c, acc, sb, sel, reinterpret_cast<unsigned char*>(p.s->y), warp, ycopy, hook);
        STAMP(10);
    }
    {
    const int warp = warp_v(), lane = lane_v(), tid = 32 * warp + lane, g = lane >> 2, t = lane & 3;
    if (warp == HINTW) {
        const uint32_t target = (lds32(s_cnt + 4) + 1u) * 48u;
        if (__any_sync(0xffffffffu, (int)(hv0 - target) < 0)) hint_wait(p.s->hint, 0, target);
    }
    const unsigned char* ys = reinterpret_cast<const unsigned char*>(p.s->y) + ((size_t)P * DM + 32 * warp + 8 * (g >> 1) + (g & 1)) * 64 + odd * 32 + t * 8;
    STAMP(27);
    bar_sync(0, NWRK);
    STAMP(11);
    const uint32_t zr = warp >> 8;
    auto late_rows = [&](auto pub) {
        const uint32_t k = lds32(s_key + (lane & 7) * 4), ep = lds32(s_cnt + 4);
        const bool late = k & 256u, mine = late && ((k & 255u) >> 1) == (uint32_t)b;
        uint32_t todo = __ballot_sync(0xffffffffu, mine) & 0xffu;
        if (todo) {
#pragma unroll 1
            while (todo) {
                const int s = __ffs(todo) - 1, row = (__shfl_sync(0xffffffffu, k, s) >> 9) & 15;
                todo &= todo - 1;
                if ((row & 7) == g) pub(row & 8, 2 * NCTA + s);
            }
            __threadfence();
            bar_sync(0, NWRK);
            if (tid < NSEL && mine) *reinterpret_cast<volatile unsigned*>(p.s->flag + tid) = ep + 1u;
        }
        int it = 0;
        while (__any_sync(0xffffffffu, late && ld_poll32(p.s->flag + (lane & 7)) != ep + 1u)) { if (++it > SPIN_LIMIT) TRAP(); }
        __threadfence();
        const int gs = tid / 36;
        const uint4* src = reinterpret_cast<const uint4*>(p.s->rows) + __shfl_sync(0xffffffffu, late ? 2 * NCTA + (lane & 7) : (k & 255u), gs & 7) * 144 + 36 * odd + (tid - gs * 36);
        if (tid < 288) {
            uint4 v0;
            do { v0 = ld_poll(src); if (++it > SPIN_LIMIT) TRAP(); } while (!v0.x);
            sts128(sb + SM_XS + gs * XS_PITCH + (tid - gs * 36) * 16, v0.x, v0.y, v0.z, v0.w);
        }
        bar_sync(0, NWRK);
    };
    if (warp >= 18) {
        if (warp == 18) {
            uint32_t* const kp = pin(p.s->sc + 32 * b, zr);
            const uint32_t kid = pin(0x30000000u | ((lane & 15) << 9) | 2 * b, zr), ka = pin(s_k16 + (lane & 15) * 4, zr), kb = pin(s_k16 + (lane & 16) * 2, zr);
            bar_sync(8, 640);
            float mb, rc;
            ln_finish<18>(sb + SM_LNP, lane, mb, rc);
            if (lane < 16) stat_store(s_stat + lane * 8, mb, rc, 0u);
            bar_arrive(13, 608);
            bar_sync(10, 608);
            const float r = sum18(sb + SM_LNP + (32 + (lane & 15)) * 80);
            const uint32_t bits = pack_bf16(0.f, r);
            const uint32_t me = (((bits ^ ((uint32_t)((int)bits >> 31) & 0x7fffffffu)) >> 3) & 0x1fffe000u) ^ kid;
            sts32(ka, me);
            __syncwarp();
            const uint4 v = lds128(kb), w = lds128(kb + 16);
#define GT(x) ((me - (x)) >> 31)
            uint32_t rank = pin(GT(v.x) + GT(v.y) + GT(v.z), zr) + pin(GT(v.w) + GT(w.x) + GT(w.y), zr) + pin(GT(w.z) + GT(w.w), zr);
#undef GT
            rank += __shfl_xor_sync(0xffffffffu, rank, 16);
            if (lane < 16) { if (rank < 8) stg32(kp + rank, me + (rank < 2 ? rank : 256u)); }
            else sts32(ka + (s_wm - s_k16), rank);
            bar_arrive(11, 640);
            weight_units<19, 0>(sb, wm, 0); weight_units<19, 1>(sb, wm, 1);
        }
        const uint4* ksrc = pin(reinterpret_cast<const uint4*>(p.s->sc) + 8 * lane, zr);
        const uint4* rsrc = pin(reinterpret_cast<const uint4*>(p.s->rows) + 36 * odd + t, zr);
        if (warp == 19) {
            weight_units<20, 0>(sb, wm, 0); weight_units<20, 1>(sb, wm, 1);
            bar_sync(8, 640);
            weight_units<16, 0>(sb, wm, 0); weight_units<16, 1>(sb, wm, 1);
            hint_wait(p.s->hint, 2, (lds32(s_cnt + 4) + 1u) * 48u);
            bar_sync(11, 640);
        }
        bool slow = false;
        int it = 0;
        if (warp == 19) {
        uint4 q[4];
        DELAY(KDEL);
#pragma unroll
        for (int i = 0; i < 4; i++) q[i] = ld_poll(ksrc + 256 * i);
        while (true) {
            uint32_t a[4];
#pragma unroll
            for (int i = 0; i < 4; i++) a[i] = q[i].x & q[i].y & q[i].z & q[i].w;
            if (__all_sync(0xffffffffu, a[0] & a[1] & a[2] & a[3])) break;
#pragma unroll
            for (int i = 0; i < 4; i++)
                if (!a[i]) q[i] = ld_poll(ksrc + 256 * i);
            if (++it > SPIN_LIMIT) TRAP();
        }
        bar_arrive(9, 608);
        STAMP(16);
        auto merge = [](const uint4& x, const uint4& y) {
            const uint32_t a = max(x.x, y.w), c = max(x.y, y.z), d = max(x.z, y.y), e = max(x.w, y.x);
            const uint32_t a2 = max(a, d), d2 = min(a, d), c2 = max(c, e), e2 = min(c, e);
            return make_uint4(max(a2, c2), min(a2, c2), max(d2, e2), min(d2, e2));
        };
        uint4 h = merge(merge(q[0], q[1]), merge(q[2], q[3]));
        uint4 v[9];
        uint32_t key = 0;
#pragma unroll
        for (int s = 0; s < 8; s++) {
            const uint32_t m = __reduce_max_sync(0xffffffffu, h.x);
            const bool w = h.x == m;
            h.x = w ? h.y : h.x; h.y = w ? h.z : h.y; h.z = w ? h.w : h.z; h.w = w ? 0u : h.w;
            if (g == s) key = m;
        }
        rsrc += (key & 255u) * 144;
#pragma unroll
        for (int j = 0; j < 9; j++) v[j] = ld_poll(rsrc + 4 * j);
        slow = __any_sync(0xffffffffu, key & 256u);
        STAMP(18);
        if (__any_sync(0xffffffffu, h.x == 0u)) {
            uint4 r[4];
            it = 0;
            while (true) {
#pragma unroll
                for (int i = 0; i < 4; i++) r[i] = ld_poll(ksrc + 256 * i + 1);
                if (__all_sync(0xffffffffu, all_nz(r[0]) && all_nz(r[1]) && all_nz(r[2]) && all_nz(r[3]))) break;
                if (++it > SPIN_LIMIT) TRAP();
            }
            uint32_t m = 1u << 30;
#pragma unroll 1
            for (int s = 0; s < 8; s++) {
                uint32_t x = 0;
#pragma unroll
                for (int i = 0; i < 4; i++) {
                    x = max(max(max(x, q[i].x - m), max(q[i].y - m, q[i].z - m)), q[i].w - m);
                    x = max(max(max(x, r[i].x - m), max(r[i].y - m, r[i].z - m)), r[i].w - m);
                }
                m += __reduce_max_sync(0xffffffffu, x);
                if (g == s) key = m;
            }
            slow = true;
        }
        const uint32_t xsa = sb + SM_XS + g * XS_PITCH + t * 16;
        sts32(s_key + g * 4, key);
        sts32(xsa, 0u);
        bar_arrive(12, 608);
#pragma unroll
        for (int j = 0; j < 9; j++) sts128(xsa + j * 64, v[j].x, v[j].y, v[j].z, v[j].w);
        slow = slow || min(min(min(min(v[0].x, v[1].x), v[2].x), min(min(v[3].x, v[4].x), v[5].x)), min(min(v[6].x, v[7].x), v[8].x)) == 0u;
        }
        if (bar_or(0, NWRK, slow)) late_rows([](bool, int) {});
        STAMP(19);
        const int fl = 16 * (b & 1) + ((tid >> 2) & 15), fc = 16 * (b >> 1) + (fl >> 2) + 8 * ((tid >> 1) & 1), fsl = 2 * (fl & 3) + (tid & 1);
        const uint32_t kk = lds32(s_key + fsl * 4);
        const uint32_t* fsrc = p.s->rows + ((kk & 256u) ? 2 * NCTA + fsl : (kk & 255u)) * DM + (fc >> 1);
        uint32_t hw = 1u, uw = 1u;
        if (b < 72) { uw = ld_poll32(fsrc); hw = ld_poll32(fsrc + 288); }
        if (b < 72) {
            it = 0;
            while (!hw || !uw) { uw = ld_poll32(fsrc); hw = ld_poll32(fsrc + 288); if (++it > SPIN_LIMIT) TRAP(); }
            const int row = (kk >> 9) & 15, ftok = 8 * (kk & 252u) + (kk & 2u) + TOKEN_OF(row & 7) + (row & 8);
            const unsigned k16 = (kk >> 13) & 0xffffu;
            const unsigned bits = (k16 & 0x8000u) ? (k16 & 0x7fffu) : (~k16 & 0xffffu);
            const float rs = 512.0f * rbf(__fdividef(1.0f, 1.0f + __expf(-__uint_as_float(bits << 16))));
            bf16* const op = p.out + (unsigned)(ftok * DM + fc);
            const float uv = (fc & 1) ? bf_hi(uw) : bf_lo(uw), hv = (fc & 1) ? bf_hi(hw) : bf_lo(hw);
            const uint32_t a = sb + SM_FIN + (tid - 576) * 80;
            sts128(a + 64, __float_as_uint(rs), __float_as_uint(uv), __float_as_uint(hv), (uint32_t)(size_t)op ^ (uint32_t)((size_t)op >> 32));
            bar_sync(14, 576);
            const uint4 p0 = lds128(a), p1 = lds128(a + 16), p2 = lds128(a + 32), p3 = lds128(a + 48);
#define F4(p) ((__uint_as_float(p.x) + __uint_as_float(p.y)) + (__uint_as_float(p.z) + __uint_as_float(p.w)))
            const float v0 = F4(p0), v1 = F4(p1), v2 = F4(p2), v3 = F4(p3);
#undef F4
            const float y3 = rbf(rbf((v0 + v1) + (v2 + v3)) * rs);
            asm volatile("st.global.u16 [%0], %1;\n" ::"l"(op), "h"((unsigned short)pack_bf16(hv + rbf(uv + y3), 0.f)) : "memory");
        }
        if (b == 0 && tid >= 632) *reinterpret_cast<volatile unsigned*>(p.s->hint + (tid & 7) * 32 + 1) = lds32(s_cnt + 4) + 1u;
    } else {
        uint32_t H[2][4], U2[2][4], WA[9][4], WD[18], WE[18];
        const int fkh = warp >= 9, fmt = warp - 9 * fkh;
        auto load_wa = [&](auto k0, auto k1) {
            if (k0.value >= k1.value) return;
            if (k0.value == 0) mbar_wait(bar_w);
            const int mi = lane >> 3, rr = lane & 7;
            const int row = fkh * 144 + rr + 8 * (mi >> 1);
            const uint32_t aad = sb + (fmt < 8 ? SM_WG + (mi & 1) * (SM_WU - SM_WG) + row * 128 + (fmt ^ rr) * 16 : SM_WR + (mi & 1) * 4608 + row * 16), ks = fmt < 8 ? 2048 : 256;
#pragma unroll
            for (int k = k0.value; k < k1.value; k++) ldsm_x4_t(WA[k][0], WA[k][1], WA[k][2], WA[k][3], aad + k * ks);
        };
        auto load_wd = [&](uint32_t (&WD)[18], int tile) {
            mbar_wait(bar_d);
            if (tile & 16) mbar_wait(bar_d + 16);
            const int mi = lane >> 3, rr = lane & 7;
            const uint32_t base = sb + SM_WD + rr * 128 + (((2 * tile + (mi & 1)) & 7) ^ rr) * 16;
#pragma unroll
            for (int k = 0; k < 4; k++) ldsm_x4_t(WD[4 * k], WD[4 * k + 1], WD[4 * k + 2], WD[4 * k + 3], base + (tile >> 2) * 8192 + (k * 16 + 8 * (mi >> 1)) * 128);
            ldsm_x2_t(WD[16], WD[17], base + 40960 + (tile >> 2) * 1024);
        };
        auto publish = [&](bool hi, int slot) {
            uint4* rowp = reinterpret_cast<uint4*>(p.s->rows) + slot * 144 + warp * 4 + t;
            stg128(rowp, nzw(hi ? U2[1][0] : U2[0][0]), nzw(hi ? U2[1][1] : U2[0][1]), nzw(hi ? U2[1][2] : U2[0][2]), nzw(hi ? U2[1][3] : U2[0][3]));
            stg128(rowp + 72, nzw(hi ? H[1][0] : H[0][0]), nzw(hi ? H[1][1] : H[0][1]), nzw(hi ? H[1][2] : H[0][2]), nzw(hi ? H[1][3] : H[0][3]));
        };
        uint4 wr = make_uint4(0x3f803f80u, 0x3f803f80u, 0x3f803f80u, 0x3f803f80u);
        {
            uint2 yv[4];
            DELAY(YDEL);
#pragma unroll
            for (int k = 0; k < 4; k++) yv[k] = ld_poll64(ys + k * 128);
            if (g == 0) wr = ldg128(p.wr + 32 * warp + 8 * t);
            const uint4 x0 = lds128(sb + SM_XT + warp * 1024 + lane * 16), x1 = lds128(sb + SM_XT + warp * 1024 + 512 + lane * 16);
            load_wa(IC<0>(), IC<WA0>());
            int it = 0;
            while (!__all_sync(0xffffffffu, yv[0].x && yv[1].x && yv[2].x && yv[3].x)) {
#pragma unroll
                for (int k = 0; k < 4; k++) if (!YSEL || !yv[k].x) yv[k] = ld_poll64(ys + k * 128);
                if (++it > SPIN_LIMIT) TRAP();
            }
            STAMP(12);
            const uint32_t Z[2][4] = {{x0.x, x0.y, x0.z, x0.w}, {x1.x, x1.y, x1.z, x1.w}};
#pragma unroll
            for (int k = 0; k < 4; k++) {
                H[0][k] = hadd2_bf(Z[0][k], movm(yv[k].x));
                H[1][k] = hadd2_bf(Z[1][k], movm(yv[k].y));
            }
            const uint32_t bw[4] = {wr.x, wr.y, wr.z, wr.w};
            ln_partial<4>(H, bw, sb + SM_LNP, warp, g, t);
        }
        bar_arrive(8, 640);
        load_wa(IC<WA0>(), IC<WA1>());
        STAMP(13);
        bar_sync(13, 608);
        STAMP(14);
#pragma unroll
        for (int hf = 0; hf < 2; hf++) {
            const uint2 st = lds64(s_stat + (g + 8 * hf) * 8);
#pragma unroll
            for (int k = 0; k < 4; k++) U2[hf][k] = ln_apply(H[hf][k], st);
        }
        {
            float cs[4] = {0.f, 0.f, 0.f, 0.f};
            mma_bf16(cs, U2[0][0], U2[1][0], U2[0][1], U2[1][1], wr.x, wr.y);
            mma_bf16(cs, U2[0][2], U2[1][2], U2[0][3], U2[1][3], wr.z, wr.w);
            if (t == 0) { stsf(sb + SM_LNP + ((32 + g) * 20 + warp) * 4, cs[0]); stsf(sb + SM_LNP + ((40 + g) * 20 + warp) * 4, cs[2]); }
            bar_arrive(10, 608);
        }
        load_wa(IC<WA1>(), IC<WA2>());
        bar_sync(11, 640);
        {
            const uint32_t rk[2] = {lds32(s_wm + g * 4), lds32(s_wm + 32 + g * 4)};
            uint32_t lo = min(rk[0], rk[1]), hi = max(rk[0], rk[1]);
#pragma unroll 1
            while (lo < 2) { publish(lo == rk[1], 2 * b + lo); lo = hi; hi = 16; }
        }
        load_wa(IC<WA2>(), IC<WA3>());
        bar_sync(9, 608);
        load_wa(IC<WA3>(), IC<9>());
#pragma unroll
        for (int hf = 0; hf < 2; hf++)
            sts128(sb + SM_OUT + (g + 8 * hf) * OUT_PITCH + warp * 64 + t * 16,
                   hadd2_bf(H[hf][0], U2[hf][0]), hadd2_bf(H[hf][1], U2[hf][1]), hadd2_bf(H[hf][2], U2[hf][2]), hadd2_bf(H[hf][3], U2[hf][3]));
        fence_async();
        WPOINT(17, warp - 16);
        if ((WDAT == 0 || (WDAT == 2 && fkh)) && (warp < 16 || !odd)) load_wd(WD, warp);
        const uint32_t bad = pin(sb + SM_XS + (lane & 7) * XS_PITCH + (fkh * 144 + 8 * (lane >> 3)) * 2, zr), ex = pin(sb + SM_EX + warp * 512 + lane * 16, zr);
        uint32_t* pp = pin(p.s->part + ((size_t)(2 * (20 * odd + warp) + (lane >> 4)) * 64 + P) * 32 + (lane & 15) * 2, zr);
        bar_sync(12, 608);
        if (warp < 16 && !__any_sync(0xffffffffu, (lds32(s_key + (lane & 7) * 4) & 0x1efeu) == (uint32_t)((warp << 9) | 2 * b)) && elect_one())
            bulk_s2g(p.out + (size_t)(32 * P + 2 * odd + TOKEN_OF(warp & 7) + (warp & 8)) * DM, sb + SM_OUT + warp * OUT_PITCH, DM * 2);
        WPOINT(18, warp - 16);
        STAMP(15);
        if (bar_or(0, NWRK, false)) late_rows(publish);
        STAMP(19);
        float gp[4];
        {
            float c4[3][4];
#pragma unroll
            for (int i = 0; i < 3; i++)
#pragma unroll
                for (int j = 0; j < 4; j++) c4[i][j] = 0.f;
#pragma unroll
            for (int k = 0; k < 10; k += 2) {
                uint32_t b0, b1, b2, b3;
                ldsm_x4(b0, b1, b2, b3, bad + k * 32);
                mma_bf16(c4[k % 3], WA[k][0], WA[k][1], WA[k][2], WA[k][3], b0, b1);
                if (k < 8) mma_bf16(c4[(k + 1) % 3], WA[k + 1][0], WA[k + 1][1], WA[k + 1][2], WA[k + 1][3], b2, b3);
            }
#pragma unroll
            for (int j = 0; j < 4; j++) gp[j] = c4[0][j] + (c4[1][j] + c4[2][j]);
            if (warp >= 9) {
                sts128f(ex, gp);
                bar_arrive(6, 576);
            } else {
                bar_sync(6, 576);
                const uint4 o = lds128(ex + 4608);
                gp[0] += __uint_as_float(o.x); gp[1] += __uint_as_float(o.y); gp[2] += __uint_as_float(o.z); gp[3] += __uint_as_float(o.w);
                asm volatile("st.async.shared::cluster.mbarrier::complete_tx::bytes.v4.b32 [%0], {%1,%2,%3,%4}, [%5];\n"
                             ::"r"(ex ^ 0x1000000u), "r"(__float_as_uint(gp[0])), "r"(__float_as_uint(gp[1])), "r"(__float_as_uint(gp[2])), "r"(__float_as_uint(gp[3])), "r"(bar_g ^ 0x1000000u) : "memory");
                if (WDAT == 2) load_wd(WD, warp);
            }
            if (WDAT == 1 && (warp < 16 || !odd)) load_wd(WD, warp);
            if (warp >= 16 && !odd) load_wd(WE, warp + 2);
        }
        STAMP(20);
        if (warp < 9) {
            mbar_wait(bar_g);
            const uint4 u = lds128(ex);
            const uint32_t G = pack_bf16(gp[0] + __uint_as_float(u.x), gp[1] + __uint_as_float(u.y)), U = pack_bf16(gp[2] + __uint_as_float(u.z), gp[3] + __uint_as_float(u.w));
            const float G0 = bf_lo(G), G1 = bf_hi(G);
            sts32(sb + SM_GU + tid * 4, hmul2_bf(pack_bf16(G0 * rcp_approx(1.0f + ex2_approx(G0 * -1.4426950408889634f)), G1 * rcp_approx(1.0f + ex2_approx(G1 * -1.4426950408889634f))), U));
        }
        bar_sync(7, 576);
        STAMP(21);
        if (warp < 16 || !odd) {
            uint32_t gb[9];
            ldsm_x4_t(gb[0], gb[1], gb[2], gb[3], sb + SM_GU + lane * 16);
            ldsm_x4_t(gb[4], gb[5], gb[6], gb[7], sb + SM_GU + 512 + lane * 16);
            ldsm_x1_t(gb[8], sb + SM_GU + 1024 + (lane & 7) * 16);
            auto down = [&](const uint32_t (&W)[18], uint32_t* dst) {
                float c4[4] = {0.f, 0.f, 0.f, 0.f}, d4[4] = {0.f, 0.f, 0.f, 0.f}, e4[4] = {0.f, 0.f, 0.f, 0.f};
                mma_bf16(c4, W[0], W[1], W[2], W[3], gb[0], gb[1]);
                mma_bf16(d4, W[4], W[5], W[6], W[7], gb[2], gb[3]);
                mma_bf16(e4, W[8], W[9], W[10], W[11], gb[4], gb[5]);
                mma_bf16_k8(c4, W[16], W[17], gb[8]);
                mma_bf16(d4, W[12], W[13], W[14], W[15], gb[6], gb[7]);
                const float v0 = (c4[0] + e4[0]) + d4[0], v1 = (c4[1] + e4[1]) + d4[1], v2 = (c4[2] + e4[2]) + d4[2], v3 = (c4[3] + e4[3]) + d4[3];
                const uint32_t e = max(max(__float_as_uint(fmaxf(fabsf(v0), fabsf(v1))), __float_as_uint(fmaxf(fabsf(v2), fabsf(v3)))), 16u << 23) >> 23;
                const float sc = __uint_as_float((245u - e) << 23);
                stg64(dst, pack_f16(v0 * sc, v1 * sc) | ((e * 0x8002000u) & 0x60006000u), pack_f16(v2 * sc, v3 * sc) | ((e * 0x800200u) & 0x60006000u));
            };
            if (warp >= 16) { down(WE, pp + 4 * 64 * 32); down(WD, pp); }
            else down(WD, pp);
        }
        asm volatile("cp.async.bulk.wait_group.read 0;\n" ::: "memory");
        STAMP(22);
        if (b < 72 && warp < 16) {
            const uint2* src = reinterpret_cast<const uint2*>(p.s->part) + (unsigned)(b * 1024 + tid);
            uint2 a, c;
            int it = 0;
            DELAY(PDEL);
            a = ld_poll64(src); c = ld_poll64(src + 512);
            while (!__all_sync(0xffffffffu, a.y && c.y)) {
                a = ld_poll64(src); c = ld_poll64(src + 512);
                if (++it > SPIN_LIMIT) TRAP();
            }
            STAMP(24);
            const float ea = __uint_as_float((((a.y & 0x60006000u) | ((a.x >> 4) & 0x06000600u)) * 0x4001u) & 0x7f800000u);
            const float ec = __uint_as_float((((c.y & 0x60006000u) | ((c.x >> 4) & 0x06000600u)) * 0x4001u) & 0x7f800000u);
            a.x &= 0x9fff9fffu; a.y &= 0x9fff9fffu; c.x &= 0x9fff9fffu; c.y &= 0x9fff9fffu;
            const float s0 = fmaf(h_lo(a.x), ea, h_lo(c.x) * ec), s1 = fmaf(h_hi(a.x), ea, h_hi(c.x) * ec), s2 = fmaf(h_lo(a.y), ea, h_lo(c.y) * ec), s3 = fmaf(h_hi(a.y), ea, h_hi(c.y) * ec);
            const bool up = lane & 16;
            const float r0 = __shfl_xor_sync(0xffffffffu, up ? s0 : s2, 16), r1 = __shfl_xor_sync(0xffffffffu, up ? s1 : s3, 16);
            const uint32_t fa = sb + SM_FIN + ((lane & 15) * 4 + (up ? 2 : 0)) * 80 + warp * 4;
            stsf(fa, (up ? s2 : s0) + r0); stsf(fa + 80, (up ? s3 : s1) + r1);
            bar_arrive(14, 576);
        }
    }
    STAMP(25);
    }
}

typedef CUresult (*PFN_tmEncode)(CUtensorMap*, CUtensorMapDataType, cuuint32_t, void*, const cuuint64_t*, const cuuint64_t*, const cuuint32_t*,
                                 const cuuint32_t*, CUtensorMapInterleave, CUtensorMapSwizzle, CUtensorMapL2promotion, CUtensorMapFloatOOBfill);

extern "C" void kernel_launch(void* const* d_in, const int* in_sizes, int n_in, void* d_out, int out_size) {
    Params p;
    p.x = (const bf16*)d_in[0];
    p.lar = (const bf16*)d_in[1];
    p.aim = (const bf16*)d_in[2];
    p.cre = (const bf16*)d_in[3];
    p.cim = (const bf16*)d_in[4];
    p.ldt = (const bf16*)d_in[5];
    p.dsk = (const bf16*)d_in[6];
    p.wr = (const bf16*)d_in[8];
    p.out = (bf16*)d_out;
    static PFN_tmEncode enc = nullptr;
    static void* scratch = nullptr;
    if (!enc) {
        cudaFuncSetAttribute(fused_kernel, cudaFuncAttributeMaxDynamicSharedMemorySize, SMEM_TOTAL);
        void* fn = nullptr;
        cudaDriverEntryPointQueryResult qr;
        cudaGetDriverEntryPoint("cuTensorMapEncodeTiled", &fn, cudaEnableDefault, &qr);
        enc = (PFN_tmEncode)fn;
        cudaGetSymbolAddress(&scratch, g_scratch);
    }
    p.s = (Scratch*)scratch;
    WMaps wm;
    CUtensorMap tm_x, tm_y, tm_z;
    const cuuint64_t dims[2] = {FF, DM}, strides[1] = {FF * 2}, rdims[3] = {FF, 144, 4}, rstrides[2] = {FF * 2, 144 * FF * 2};
    const cuuint32_t box[2] = {64, 72}, rbox[3] = {8, 144, 2}, es3[3] = {1, 1, 1};
    for (int i = 0; i < 2; i++) {
        enc(i ? &wm.u : &wm.g, CU_TENSOR_MAP_DATA_TYPE_BFLOAT16, 2, d_in[9 + i], dims, strides, box, es3, CU_TENSOR_MAP_INTERLEAVE_NONE, CU_TENSOR_MAP_SWIZZLE_128B,
            CU_TENSOR_MAP_L2_PROMOTION_NONE, CU_TENSOR_MAP_FLOAT_OOB_FILL_NONE);
        enc(i ? &wm.ur : &wm.gr, CU_TENSOR_MAP_DATA_TYPE_BFLOAT16, 3, d_in[9 + i], rdims, rstrides, rbox, es3, CU_TENSOR_MAP_INTERLEAVE_NONE, CU_TENSOR_MAP_SWIZZLE_NONE,
            CU_TENSOR_MAP_L2_PROMOTION_NONE, CU_TENSOR_MAP_FLOAT_OOB_FILL_NONE);
    }
    const cuuint64_t ddims[2] = {DM, FF}, dstrides[1] = {DM * 2}, edims[3] = {64, FF, 9}, estrides[2] = {DM * 2, 128};
    const cuuint32_t dbox[2] = {64, 64}, ebox[3] = {64, 8, 5};
    enc(&wm.d, CU_TENSOR_MAP_DATA_TYPE_BFLOAT16, 2, d_in[11], ddims, dstrides, dbox, es3, CU_TENSOR_MAP_INTERLEAVE_NONE, CU_TENSOR_MAP_SWIZZLE_128B,
        CU_TENSOR_MAP_L2_PROMOTION_NONE, CU_TENSOR_MAP_FLOAT_OOB_FILL_NONE);
    enc(&wm.dr, CU_TENSOR_MAP_DATA_TYPE_BFLOAT16, 3, d_in[11], edims, estrides, ebox, es3, CU_TENSOR_MAP_INTERLEAVE_NONE, CU_TENSOR_MAP_SWIZZLE_128B,
        CU_TENSOR_MAP_L2_PROMOTION_NONE, CU_TENSOR_MAP_FLOAT_OOB_FILL_NONE);
    const cuuint64_t xdims[3] = {DM, LSEQ / 16, 16}, xstrides[2] = {16 * DM * 2, DM * 2};
    const cuuint32_t xbox[3] = {8, LSEQ / 16, 8};
    enc(&tm_x, CU_TENSOR_MAP_DATA_TYPE_BFLOAT16, 3, d_in[0], xdims, xstrides, xbox, es3, CU_TENSOR_MAP_INTERLEAVE_NONE, CU_TENSOR_MAP_SWIZZLE_NONE,
        CU_TENSOR_MAP_L2_PROMOTION_NONE, CU_TENSOR_MAP_FLOAT_OOB_FILL_NONE);
    const cuuint64_t ydims[3] = {DM * 32, 16, 4}, ystrides[2] = {DM * 64, 16 * DM * 64};
    const cuuint32_t ybox[3] = {128, 16, 2}, zbox[3] = {32, 16, 2};
    enc(&tm_y, CU_TENSOR_MAP_DATA_TYPE_BFLOAT16, 3, p.s->y, ydims, ystrides, ybox, es3, CU_TENSOR_MAP_INTERLEAVE_NONE, CU_TENSOR_MAP_SWIZZLE_NONE,
        CU_TENSOR_MAP_L2_PROMOTION_NONE, CU_TENSOR_MAP_FLOAT_OOB_FILL_NONE);
    enc(&tm_z, CU_TENSOR_MAP_DATA_TYPE_BFLOAT16, 3, p.s->y, ydims, ystrides, zbox, es3, CU_TENSOR_MAP_INTERLEAVE_NONE, CU_TENSOR_MAP_SWIZZLE_NONE,
        CU_TENSOR_MAP_L2_PROMOTION_NONE, CU_TENSOR_MAP_FLOAT_OOB_FILL_NONE);
    fused_kernel<<<NCTA, NTHR, SMEM_TOTAL>>>(p, wm, tm_x, tm_y, tm_z);
}
```

```cpp
#include <cuda_runtime.h>
#include <cuda.h>
#include <cuda_fp16.h>
#include <cuda_bf16.h>
#include <stdint.h>

#define LSEQ 2048
#define DM 576
#define NST 128
#define FF 4608
#define NSEL 8
#define NCTA 128
#define NTHR 640
#define NWRK 640

typedef __nv_bfloat16 bf16;

#define SM_WD 0
#define SM_WG 46080
#define SM_WR 82944
#define SM_WU 92160
#define SM_ZERO 32768
#define SM_XC 16384
#define SM_TB 96000
#define SM_PL 129024
#define PL_B 10752
#define SM_XT (SM_TB + 20 * TBW)
#define SM_U (SM_XT + 18432)
#define UPAD 8
#define ULO_B ((UPAD + 128) * 16)
#define USLOT_B (2 * ULO_B)
#define SM_KW (SM_U + 5 * USLOT_B)
#define KW_B 3600
#define KW_T2 1152
#define KW_KH 656
#define KW_T3 2464
#define SM_MISC (SM_KW + 5 * KW_B)
#define SM_LNP (SM_MISC + 576)
#define SMEM_TOTAL (SM_LNP + 3840)
#define TBP 112
#define TBW (32 * TBP)
#define SM_OUT SM_PL
#define OUT_PITCH 1216
#define SM_XS (SM_PL + 19456)
#define XS_PITCH 592
#define SM_EX (SM_PL + 24320)
#define SM_FIN SM_KW
#define SM_GU (SM_PL + 33536)

struct __align__(128) Scratch {
    unsigned hint[8 * 32];
    unsigned flag[32];
    uint32_t sc[NCTA * 32];
    uint32_t st[LSEQ * 2];
    uint32_t uT[64 * (LSEQ / 2)];
    uint32_t y[NCTA * DM * 8];
    uint32_t part[72 * 64 * 32];
    uint32_t rows[(2 * NCTA + NSEL) * DM];
};
__device__ Scratch g_scratch;
#define STAMP(i)
#define DBG(i, v)

__device__ __forceinline__ float rbf(float x) {
    uint32_t r;
    asm("cvt.rn.bf16x2.f32 %0, %1, %2;\n" : "=r"(r) : "f"(x), "f"(0.f));
    return __uint_as_float(r & 0xffff0000u);
}
__device__ __forceinline__ uint32_t pack_bf16(float lo, float hi) {
    uint32_t r;
    asm("cvt.rn.bf16x2.f32 %0, %1, %2;\n" : "=r"(r) : "f"(hi), "f"(lo));
    return r;
}
__device__ __forceinline__ uint32_t pack_f16(float lo, float hi) {
    uint32_t r;
    asm("cvt.rn.f16x2.f32 %0, %1, %2;\n" : "=r"(r) : "f"(hi), "f"(lo));
    return r;
}
__device__ __forceinline__ uint32_t pack_f16_rz(float lo, float hi) {
    uint32_t r;
    asm("cvt.rz.f16x2.f32 %0, %1, %2;\n" : "=r"(r) : "f"(hi), "f"(lo));
    return r;
}
__device__ __forceinline__ float bf_lo(uint32_t w) { return __uint_as_float(w << 16); }
__device__ __forceinline__ float bf_hi(uint32_t w) { return __uint_as_float(w & 0xffff0000u); }
__device__ __forceinline__ uint32_t hadd2_bf(uint32_t a, uint32_t b) {
    __nv_bfloat162 r = __hadd2_rn(*reinterpret_cast<__nv_bfloat162*>(&a), *reinterpret_cast<__nv_bfloat162*>(&b));
    return *reinterpret_cast<uint32_t*>(&r);
}
__device__ __forceinline__ uint32_t hmul2_bf(uint32_t a, uint32_t b) {
    __nv_bfloat162 r = __hmul2_rn(*reinterpret_cast<__nv_bfloat162*>(&a), *reinterpret_cast<__nv_bfloat162*>(&b));
    return *reinterpret_cast<uint32_t*>(&r);
}
__device__ __forceinline__ uint32_t hfma2_bf(uint32_t a, uint32_t b, uint32_t c) { uint32_t r; asm("fma.rn.bf16x2 %0, %1, %2, %3;\n" : "=r"(r) : "r"(a), "r"(b), "r"(c)); return r; }
__device__ __forceinline__ uint32_t hmul2(uint32_t a, uint32_t b) { uint32_t r; asm("mul.rn.f16x2 %0, %1, %2;\n" : "=r"(r) : "r"(a), "r"(b)); return r; }
__device__ __forceinline__ uint32_t hadd2(uint32_t a, uint32_t b) { uint32_t r; asm("add.rn.f16x2 %0, %1, %2;\n" : "=r"(r) : "r"(a), "r"(b)); return r; }
__device__ __forceinline__ uint32_t nzw(uint32_t w) { return w ? w : 0x8000u; }
__device__ __forceinline__ uint32_t smem_u32(const void* p) { return (uint32_t)__cvta_generic_to_shared(p); }
__device__ __forceinline__ uint32_t lds32(uint32_t addr) {
    uint32_t v;
    asm volatile("ld.shared.u32 %0, [%1];\n" : "=r"(v) : "r"(addr) : "memory");
    return v;
}
__device__ __forceinline__ uint2 lds64(uint32_t addr) {
    uint2 v;
    asm volatile("ld.shared.v2.u32 {%0,%1}, [%2];\n" : "=r"(v.x), "=r"(v.y) : "r"(addr) : "memory");
    return v;
}
__device__ __forceinline__ uint4 lds128(uint32_t addr) {
    uint4 v;
    asm volatile("ld.shared.v4.u32 {%0,%1,%2,%3}, [%4];\n" : "=r"(v.x), "=r"(v.y), "=r"(v.z), "=r"(v.w) : "r"(addr) : "memory");
    return v;
}
__device__ __forceinline__ float ldsf(uint32_t addr) { return __uint_as_float(lds32(addr)); }
__device__ __forceinline__ void sts32(uint32_t addr, uint32_t v) { asm volatile("st.shared.u32 [%0], %1;\n" ::"r"(addr), "r"(v) : "memory"); }
__device__ __forceinline__ void stsf(uint32_t addr, float v) { sts32(addr, __float_as_uint(v)); }
__device__ __forceinline__ void sts64(uint32_t addr, uint32_t a, uint32_t b) { asm volatile("st.shared.v2.u32 [%0], {%1,%2};\n" ::"r"(addr), "r"(a), "r"(b) : "memory"); }
__device__ __forceinline__ void sts128(uint32_t addr, uint32_t a, uint32_t b, uint32_t c, uint32_t d) {
    asm volatile("st.shared.v4.u32 [%0], {%1,%2,%3,%4};\n" ::"r"(addr), "r"(a), "r"(b), "r"(c), "r"(d) : "memory");
}
__device__ __forceinline__ void sts128f(uint32_t addr, const float (&v)[4]) {
    sts128(addr, __float_as_uint(v[0]), __float_as_uint(v[1]), __float_as_uint(v[2]), __float_as_uint(v[3]));
}
__device__ __forceinline__ void ldsm_x4(uint32_t& r0, uint32_t& r1, uint32_t& r2, uint32_t& r3, uint32_t addr) {
    asm volatile("ldmatrix.sync.aligned.m8n8.x4.shared.b16 {%0,%1,%2,%3}, [%4];\n"
                 : "=r"(r0), "=r"(r1), "=r"(r2), "=r"(r3) : "r"(addr) : "memory");
}
__device__ __forceinline__ void ldsm_x4_t(uint32_t& r0, uint32_t& r1, uint32_t& r2, uint32_t& r3, uint32_t addr) {
    asm volatile("ldmatrix.sync.aligned.m8n8.x4.trans.shared.b16 {%0,%1,%2,%3}, [%4];\n"
                 : "=r"(r0), "=r"(r1), "=r"(r2), "=r"(r3) : "r"(addr) : "memory");
}
__device__ __forceinline__ void ldsm_x2_t(uint32_t& r0, uint32_t& r1, uint32_t addr) {
    asm volatile("ldmatrix.sync.aligned.m8n8.x2.trans.shared.b16 {%0,%1}, [%2];\n" : "=r"(r0), "=r"(r1) : "r"(addr) : "memory");
}
__device__ __forceinline__ void ldsm_x1_t(uint32_t& r0, uint32_t addr) {
    asm volatile("ldmatrix.sync.aligned.m8n8.x1.trans.shared.b16 {%0}, [%1];\n" : "=r"(r0) : "r"(addr) : "memory");
}
__device__ __forceinline__ uint32_t movm(uint32_t a) {
    uint32_t d;
    asm volatile("movmatrix.sync.aligned.m8n8.trans.b16 %0, %1;\n" : "=r"(d) : "r"(a));
    return d;
}
__device__ __forceinline__ void mma_f16(float (&c)[4], uint32_t a0, uint32_t a1, uint32_t a2, uint32_t a3, uint32_t b0, uint32_t b1) {
    asm volatile(
        "mma.sync.aligned.m16n8k16.row.col.f32.f16.f16.f32 {%0,%1,%2,%3}, {%4,%5,%6,%7}, {%8,%9}, {%0,%1,%2,%3};\n"
        : "+f"(c[0]), "+f"(c[1]), "+f"(c[2]), "+f"(c[3])
        : "r"(a0), "r"(a1), "r"(a2), "r"(a3), "r"(b0), "r"(b1));
}
__device__ __forceinline__ void mma_bf16(float (&c)[4], uint32_t a0, uint32_t a1, uint32_t a2, uint32_t a3, uint32_t b0, uint32_t b1) {
    asm volatile(
        "mma.sync.aligned.m16n8k16.row.col.f32.bf16.bf16.f32 {%0,%1,%2,%3}, {%4,%5,%6,%7}, {%8,%9}, {%0,%1,%2,%3};\n"
        : "+f"(c[0]), "+f"(c[1]), "+f"(c[2]), "+f"(c[3])
        : "r"(a0), "r"(a1), "r"(a2), "r"(a3), "r"(b0), "r"(b1));
}
__device__ __forceinline__ void mma_bf16_k8(float (&c)[4], uint32_t a0, uint32_t a1, uint32_t b0) {
    asm volatile("mma.sync.aligned.m16n8k8.row.col.f32.bf16.bf16.f32 {%0,%1,%2,%3}, {%4,%5}, {%6}, {%0,%1,%2,%3};\n"
        : "+f"(c[0]), "+f"(c[1]), "+f"(c[2]), "+f"(c[3]) : "r"(a0), "r"(a1), "r"(b0));
}
__device__ __forceinline__ void bar_sync(int id, int n) { asm volatile("bar.sync %0, %1;\n" ::"r"(id), "r"(n) : "memory"); }
__device__ __forceinline__ void bar_arrive(int id, int n) { asm volatile("bar.arrive %0, %1;\n" ::"r"(id), "r"(n) : "memory"); }
__device__ __forceinline__ bool bar_or(int id, int n, bool v) {
    uint32_t r;
    asm volatile("{\n.reg .pred p, q;\nsetp.ne.u32 p, %3, 0;\nbar.red.or.pred q, %1, %2, p;\nselp.u32 %0, 1, 0, q;\n}\n" : "=r"(r) : "r"(id), "r"(n), "r"((uint32_t)v) : "memory");
    return r;
}
__device__ __forceinline__ uint4 ld_poll(const void* p) {
    uint4 v;
    asm volatile("ld.relaxed.gpu.global.v4.u32 {%0,%1,%2,%3}, [%4];\n" : "=r"(v.x), "=r"(v.y), "=r"(v.z), "=r"(v.w) : "l"(p) : "memory");
    return v;
}
template <class T> __device__ __forceinline__ T* pin(T* p, uint32_t z) {
    uint32_t lo, hi;
    asm volatile("mov.b64 {%0, %1}, %2;\n" : "=r"(lo), "=r"(hi) : "l"(p));
    asm volatile("xor.b32 %0, %0, %1;\n" : "+r"(lo) : "r"(z));
    asm volatile("xor.b32 %0, %0, %1;\n" : "+r"(hi) : "r"(z));
    asm volatile("mov.b64 %0, {%1, %2};\n" : "=l"(p) : "r"(lo), "r"(hi));
    return p;
}
__device__ __forceinline__ uint32_t pin(uint32_t a, uint32_t z) { asm volatile("xor.b32 %0, %0, %1;\n" : "+r"(a) : "r"(z)); return a; }
__device__ __forceinline__ uint2 ld_poll64(const void* p) {
    uint2 v;
    asm volatile("ld.relaxed.gpu.global.v2.u32 {%0,%1}, [%2];\n" : "=r"(v.x), "=r"(v.y) : "l"(p) : "memory");
    return v;
}
__device__ __forceinline__ uint32_t ld_poll32(const void* p) {
    uint32_t v;
    asm volatile("ld.relaxed.gpu.global.u32 %0, [%1];\n" : "=r"(v) : "l"(p) : "memory");
    return v;
}
__device__ __forceinline__ uint4 ldg128(const void* p) {
    uint4 v;
    asm volatile("ld.global.nc.v4.u32 {%0,%1,%2,%3}, [%4];\n" : "=r"(v.x), "=r"(v.y), "=r"(v.z), "=r"(v.w) : "l"(p));
    return v;
}
__device__ __forceinline__ uint2 ldg64(const void* p) {
    uint2 v;
    asm volatile("ld.global.nc.v2.u32 {%0,%1}, [%2];\n" : "=r"(v.x), "=r"(v.y) : "l"(p));
    return v;
}
__device__ __forceinline__ uint32_t ldg16(const void* p) {
    uint32_t v;
    asm volatile("ld.global.nc.u16 %0, [%1];\n" : "=r"(v) : "l"(p));
    return v;
}
__device__ __forceinline__ void stg128(void* p, uint32_t a, uint32_t b, uint32_t c, uint32_t d) {
    asm volatile("st.global.v4.u32 [%0], {%1,%2,%3,%4};\n" ::"l"(p), "r"(a), "r"(b), "r"(c), "r"(d) : "memory");
}
__device__ __forceinline__ void stg64(void* p, uint32_t a, uint32_t b) { asm volatile("st.global.v2.u32 [%0], {%1,%2};\n" ::"l"(p), "r"(a), "r"(b) : "memory"); }
__device__ __forceinline__ void stg32(void* p, uint32_t a) { asm volatile("st.global.u32 [%0], %1;\n" ::"l"(p), "r"(a) : "memory"); }
__device__ __forceinline__ bool all_nz(const uint4& v) { return v.x && v.y && v.z && v.w; }
#define SPIN_LIMIT (1 << 21)
#define TRAP() __trap()
__device__ __forceinline__ void hint_arrive(unsigned* g_hint, int idx, int sub) {
    asm volatile("red.relaxed.gpu.global.add.u32 [%0], 1;\n" ::"l"(&g_hint[sub * 32 + idx]) : "memory");
}
__device__ __forceinline__ void hint_wait(const unsigned* g_hint, int idx, unsigned target) {
    unsigned l;
    asm volatile("mov.u32 %0, %%laneid;" : "=r"(l));
    const unsigned* c = &g_hint[(l & 7) * 32 + idx];
    int it = 0;
    while (__any_sync(0xffffffffu, (int)(ld_poll32(c) - target) < 0)) { if (++it > SPIN_LIMIT) TRAP(); }
}
__device__ __forceinline__ void mbar_init(uint32_t bar, uint32_t cnt) { asm volatile("mbarrier.init.shared::cta.b64 [%0], %1;\n" ::"r"(bar), "r"(cnt) : "memory"); }
__device__ __forceinline__ void mbar_expect(uint32_t bar, uint32_t bytes) {
    asm volatile("mbarrier.arrive.expect_tx.shared::cta.b64 _, [%0], %1;\n" ::"r"(bar), "r"(bytes) : "memory");
}
__device__ __forceinline__ void mbar_arrive(uint32_t bar) { asm volatile("mbarrier.arrive.shared::cta.b64 _, [%0];\n" ::"r"(bar) : "memory"); }
__device__ __forceinline__ void mbar_wait(uint32_t bar) {
    asm volatile(
        "{\n.reg .pred p;\n"
        "W_%=:\n"
        "mbarrier.try_wait.parity.shared::cta.b64 p, [%0], 0;\n"
        "@!p bra W_%=;\n}\n" ::"r"(bar) : "memory");
}
__device__ __forceinline__ void bulk_s2g(void* dst, uint32_t src, uint32_t bytes) {
    asm volatile("cp.async.bulk.global.shared::cta.bulk_group [%0], [%1], %2;\ncp.async.bulk.commit_group;\n" ::"l"(dst), "r"(src), "r"(bytes) : "memory");
}
__device__ __forceinline__ void tma_2d(uint32_t dst, const CUtensorMap* tm, int c0, int c1, uint32_t bar) {
    asm volatile("cp.async.bulk.tensor.2d.shared::cluster.global.mbarrier::complete_tx::bytes [%0], [%1, {%3, %4}], [%2];\n"
                 ::"r"(dst), "l"(tm), "r"(bar), "r"(c0), "r"(c1) : "memory");
}
__device__ __forceinline__ void tma_3d(uint32_t dst, const CUtensorMap* tm, int c0, int c1, int c2, uint32_t bar) {
    asm volatile("cp.async.bulk.tensor.3d.shared::cluster.global.mbarrier::complete_tx::bytes [%0], [%1, {%3, %4, %5}], [%2];\n"
                 ::"r"(dst), "l"(tm), "r"(bar), "r"(c0), "r"(c1), "r"(c2) : "memory");
}
__device__ __forceinline__ void tma_st_3d(const CUtensorMap* tm, uint32_t src, int c0, int c1, int c2) {
    asm volatile("cp.async.bulk.tensor.3d.global.shared::cta.bulk_group [%0, {%2, %3, %4}], [%1];\ncp.async.bulk.commit_group;\n"
                 ::"l"(tm), "r"(src), "r"(c0), "r"(c1), "r"(c2) : "memory");
}
__device__ __forceinline__ bool elect_one() {
    uint32_t r;
    asm volatile("{\n.reg .pred p;\nelect.sync _|p, 0xffffffff;\nselp.u32 %0, 1, 0, p;\n}\n" : "=r"(r));
    return r;
}
__device__ __forceinline__ void fence_async() { asm volatile("fence.proxy.async.shared::cta;\n" ::: "memory"); }

__device__ __forceinline__ float2 cmul(float2 a, float2 b) {
    return make_float2(fmaf(a.x, b.x, -a.y * b.y), fmaf(a.x, b.y, a.y * b.x));
}
__device__ __forceinline__ float2 csq(float2 a) {
    float p = a.x * a.y;
    return make_float2(fmaf(a.x, a.x, -a.y * a.y), p + p);
}
__device__ __forceinline__ float2 cexp_e(float lr2, float rh, float rl, float e) {
    float m;
    asm("ex2.approx.ftz.f32 %0, %1;\n" : "=f"(m) : "f"(lr2 * e));
    const float a = rh * e;
    const float r = fmaf(rl, e, a - rintf(a)) * 6.283185307179586f;
    return make_float2(m * __cosf(r), m * __sinf(r));
}
__device__ __forceinline__ float rcp_approx(float x) { float r; asm("rcp.approx.ftz.f32 %0, %1;\n" : "=f"(r) : "f"(x)); return r; }
__device__ __forceinline__ float ex2_approx(float x) { float r; asm("ex2.approx.ftz.f32 %0, %1;\n" : "=f"(r) : "f"(x)); return r; }
__device__ __forceinline__ float sqrt_approx(float x) { float r; asm("sqrt.approx.ftz.f32 %0, %1;\n" : "=f"(r) : "f"(x)); return r; }

__device__ __forceinline__ void wg_fence() { asm volatile("wgmma.fence.sync.aligned;\n" ::: "memory"); }
__device__ __forceinline__ void wg_commit() { asm volatile("wgmma.commit_group.sync.aligned;\n" ::: "memory"); }
__device__ __forceinline__ void wg_wait0() { asm volatile("wgmma.wait_group.sync.aligned 0;\n" ::: "memory"); }
template <int T0, int NT> __device__ __forceinline__ void wg_h(uint32_t (&acc)[32], const uint32_t (&a)[4], uint64_t desc);
template <> __device__ __forceinline__ void wg_h<0, 16>(uint32_t (&acc)[32], const uint32_t (&a)[4], uint64_t desc) {
    asm volatile("wgmma.mma_async.sync.aligned.m64n128k16.f16.f16.f16 {%0,%1,%2,%3,%4,%5,%6,%7,%8,%9,%10,%11,%12,%13,%14,%15,%16,%17,%18,%19,%20,%21,%22,%23,%24,%25,%26,%27,%28,%29,%30,%31}, {%32,%33,%34,%35}, %36, 1, 1, 1, 0;\n"
                 : "+r"(acc[0]), "+r"(acc[1]), "+r"(acc[2]), "+r"(acc[3]), "+r"(acc[4]), "+r"(acc[5]), "+r"(acc[6]), "+r"(acc[7]), "+r"(acc[8]), "+r"(acc[9]), "+r"(acc[10]), "+r"(acc[11]), "+r"(acc[12]), "+r"(acc[13]), "+r"(acc[14]), "+r"(acc[15]), "+r"(acc[16]), "+r"(acc[17]), "+r"(acc[18]), "+r"(acc[19]), "+r"(acc[20]), "+r"(acc[21]), "+r"(acc[22]), "+r"(acc[23]), "+r"(acc[24]), "+r"(acc[25]), "+r"(acc[26]), "+r"(acc[27]), "+r"(acc[28]), "+r"(acc[29]), "+r"(acc[30]), "+r"(acc[31])
                 : "r"(a[0]), "r"(a[1]), "r"(a[2]), "r"(a[3]), "l"(desc));
}
template <> __device__ __forceinline__ void wg_h<4, 4>(uint32_t (&acc)[32], const uint32_t (&a)[4], uint64_t desc) {
    asm volatile("wgmma.mma_async.sync.aligned.m64n32k16.f16.f16.f16 {%0,%1,%2,%3,%4,%5,%6,%7}, {%8,%9,%10,%11}, %12, 1, 1, 1, 0;\n"
                 : "+r"(acc[8]), "+r"(acc[9]), "+r"(acc[10]), "+r"(acc[11]), "+r"(acc[12]), "+r"(acc[13]), "+r"(acc[14]), "+r"(acc[15])
                 : "r"(a[0]), "r"(a[1]), "r"(a[2]), "r"(a[3]), "l"(desc));
}
template <> __device__ __forceinline__ void wg_h<8, 4>(uint32_t (&acc)[32], const uint32_t (&a)[4], uint64_t desc) {
    asm volatile("wgmma.mma_async.sync.aligned.m64n32k16.f16.f16.f16 {%0,%1,%2,%3,%4,%5,%6,%7}, {%8,%9,%10,%11}, %12, 1, 1, 1, 0;\n"
                 : "+r"(acc[16]), "+r"(acc[17]), "+r"(acc[18]), "+r"(acc[19]), "+r"(acc[20]), "+r"(acc[21]), "+r"(acc[22]), "+r"(acc[23])
                 : "r"(a[0]), "r"(a[1]), "r"(a[2]), "r"(a[3]), "l"(desc));
}
template <> __device__ __forceinline__ void wg_h<12, 4>(uint32_t (&acc)[32], const uint32_t (&a)[4], uint64_t desc) {
    asm volatile("wgmma.mma_async.sync.aligned.m64n32k16.f16.f16.f16 {%0,%1,%2,%3,%4,%5,%6,%7}, {%8,%9,%10,%11}, %12, 1, 1, 1, 0;\n"
                 : "+r"(acc[24]), "+r"(acc[25]), "+r"(acc[26]), "+r"(acc[27]), "+r"(acc[28]), "+r"(acc[29]), "+r"(acc[30]), "+r"(acc[31])
                 : "r"(a[0]), "r"(a[1]), "r"(a[2]), "r"(a[3]), "l"(desc));
}
template <> __device__ __forceinline__ void wg_h<0, 8>(uint32_t (&acc)[32], const uint32_t (&a)[4], uint64_t desc) {
    asm volatile("wgmma.mma_async.sync.aligned.m64n64k16.f16.f16.f16 {%0,%1,%2,%3,%4,%5,%6,%7,%8,%9,%10,%11,%12,%13,%14,%15}, {%16,%17,%18,%19}, %20, 1, 1, 1, 0;\n"
                 : "+r"(acc[0]), "+r"(acc[1]), "+r"(acc[2]), "+r"(acc[3]), "+r"(acc[4]), "+r"(acc[5]), "+r"(acc[6]), "+r"(acc[7]), "+r"(acc[8]), "+r"(acc[9]), "+r"(acc[10]), "+r"(acc[11]), "+r"(acc[12]), "+r"(acc[13]), "+r"(acc[14]), "+r"(acc[15])
                 : "r"(a[0]), "r"(a[1]), "r"(a[2]), "r"(a[3]), "l"(desc));
}
template <> __device__ __forceinline__ void wg_h<4, 12>(uint32_t (&acc)[32], const uint32_t (&a)[4], uint64_t desc) {
    asm volatile("wgmma.mma_async.sync.aligned.m64n96k16.f16.f16.f16 {%0,%1,%2,%3,%4,%5,%6,%7,%8,%9,%10,%11,%12,%13,%14,%15,%16,%17,%18,%19,%20,%21,%22,%23}, {%24,%25,%26,%27}, %28, 1, 1, 1, 0;\n"
                 : "+r"(acc[8]), "+r"(acc[9]), "+r"(acc[10]), "+r"(acc[11]), "+r"(acc[12]), "+r"(acc[13]), "+r"(acc[14]), "+r"(acc[15]), "+r"(acc[16]), "+r"(acc[17]), "+r"(acc[18]), "+r"(acc[19]), "+r"(acc[20]), "+r"(acc[21]), "+r"(acc[22]), "+r"(acc[23]), "+r"(acc[24]), "+r"(acc[25]), "+r"(acc[26]), "+r"(acc[27]), "+r"(acc[28]), "+r"(acc[29]), "+r"(acc[30]), "+r"(acc[31])
                 : "r"(a[0]), "r"(a[1]), "r"(a[2]), "r"(a[3]), "l"(desc));
}

#define PBYTES 4608
#define DELAY(n) do { if (n) { const unsigned c0_ = clock32(); while ((int)(clock32() - c0_) < (n)) {} } } while (0)
#define KDEL 300
#define PDEL 300
#define CST(i) do { if ((warp & 3) == 0 && lane_v() == 0) { unsigned t_; asm volatile("mov.u32 %0, %%globaltimer_lo;" : "=r"(t_) :: "memory"); sts32(sb + SMEM_TOTAL - 768 + (warp >> 2) * 128 + (i) * 4, t_); } } while (0)
#define HINTW 10
#define WAS 0x0005
#define WA0 (WAS >> 12)
#define WA1 ((WAS >> 8) & 15)
#define WA2 ((WAS >> 4) & 15)
#define WA3 (WAS & 15)
#define WDAT 1
#define PAUSE 2
#define PCNT (32 + ((PAUSE & 1) ? 288 : 0) + ((PAUSE & 6) ? 320 : 64))
#define LNAT 2
#define UW 8
#define FINAT 3
#define UAT 2
#define TOKEN_OF(g) (16 * ((g) & 1) + ((g) >> 2) + 2 * ((g) & 2))
#define HI2(a, b) (pack_f16_rz(__uint_as_float(a), __uint_as_float(b)) & 0xfff8fff8u)
struct Params {
    const bf16 *x, *lar, *aim, *cre, *cim, *ldt, *dsk;
    Scratch* s;
    const bf16* wr;
    bf16* out;
};

template <int NK>
__device__ __forceinline__ void ln_partial(const uint32_t (&H)[2][NK], const uint32_t (&bw)[NK], uint32_t lp, int warp, int g, int t) {
    float cs[4] = {0.f, 0.f, 0.f, 0.f}, cl[4] = {0.f, 0.f, 0.f, 0.f}, ch[4] = {0.f, 0.f, 0.f, 0.f};
#pragma unroll
    for (int k = 0; k < NK; k += 2) {
        uint32_t a0, a1, a2, a3;
        asm volatile("prmt.b32 %0, %4, %4, %8;\nprmt.b32 %1, %5, %5, %8;\nprmt.b32 %2, %6, %6, %8;\nprmt.b32 %3, %7, %7, %8;\n"
                     : "=r"(a0), "=r"(a1), "=r"(a2), "=r"(a3) : "r"(H[0][k]), "r"(H[1][k]), "r"(H[0][k + 1]), "r"(H[1][k + 1]), "r"(0x3210u + (warp >> 8)));
        mma_bf16(cl, a0, a1, a2, a3, H[0][k], H[0][k + 1]);
        mma_bf16(ch, a0, a1, a2, a3, H[1][k], H[1][k + 1]);
        mma_bf16(cs, a0, a1, a2, a3, bw[k], bw[k + 1]);
    }
    const uint32_t a = lp + (g * 20 + warp) * 4;
    if (t == 0) {
        stsf(a, cs[1]); stsf(a + 8 * 80, cs[3]);
    }
    if (t == (g >> 1)) { stsf(a + 16 * 80, (g & 1) ? cl[1] : cl[0]); stsf(a + 24 * 80, (g & 1) ? ch[3] : ch[2]); }
}
__device__ __forceinline__ float sum18(uint32_t a) {
    const uint4 p = lds128(a), q = lds128(a + 16), r = lds128(a + 32), s = lds128(a + 48);
    const uint2 u = lds64(a + 64);
#define F(x) __uint_as_float(x)
    return (((F(p.x) + F(p.y)) + (F(p.z) + F(p.w))) + ((F(q.x) + F(q.y)) + (F(q.z) + F(q.w)))) +
           (((F(r.x) + F(r.y)) + (F(r.z) + F(r.w))) + ((F(s.x) + F(s.y)) + (F(s.z) + F(s.w))) + (F(u.x) + F(u.y)));
#undef F
}
__device__ __forceinline__ float sum9(uint32_t a) {
    const uint4 p = lds128(a), q = lds128(a + 16);
#define F(x) __uint_as_float(x)
    return (((F(p.x) + F(p.y)) + (F(p.z) + F(p.w))) + ((F(q.x) + F(q.y)) + (F(q.z) + F(q.w)))) + ldsf(a + 32);
#undef F
}
template <int N>
__device__ __forceinline__ void ln_finish(uint32_t lp, int lane, float& mb, float& rc) {
    const float v = N == 9 ? sum9(lp + lane * 80) : sum18(lp + lane * 80);
    const float o = __shfl_xor_sync(0xffffffffu, v, 16);
    const float m0 = v * (1.0f / 576.0f);
    const float mean = fmaf(fmaf(-m0, 576.0f, v), 1.0f / 576.0f, m0);
    const float var = fmaxf(fmaf(-mean, mean, o * (1.0f / 576.0f)), 0.f);
    mb = rbf(mean);
    rc = rcp_approx(rbf(sqrt_approx(rbf(rbf(var) + 1e-5f))));
}
__device__ __forceinline__ uint32_t ln_apply(uint32_t w, const uint2& st) {
    uint32_t r;
    asm("{\n.reg .b16 m, t, h, l;\n.reg .b32 mm, hh, ll, d, e;\nmov.b32 {m, t}, %2;\nmov.b32 {h, l}, %3;\nmov.b32 mm, {m, m};\nmov.b32 hh, {h, h};\nmov.b32 ll, {l, l};\n"
        "sub.rn.bf16x2 d, %1, mm;\nmul.rn.bf16x2 e, d, ll;\nfma.rn.bf16x2 %0, d, hh, e;\n}\n" : "=r"(r) : "r"(w), "r"(st.x), "r"(st.y));
    return r;
}
__device__ __forceinline__ void stat_store(uint32_t a, float mb, float rc, uint32_t extra) {
    const float rh = rbf(rc);
    sts64(a, (__float_as_uint(mb) >> 16) | (extra << 16), pack_bf16(rh, rc - rh));
}

__device__ __forceinline__ void hcmul(uint32_t re, uint32_t im, uint32_t z, uint32_t& ore, uint32_t& oim) {
    asm("{\n.reg .b16 x, y;\n.reg .b32 xx, yy, ny, a, b;\nmov.b32 {x, y}, %4;\nmov.b32 xx, {x, x};\nmov.b32 yy, {y, y};\nneg.f16x2 ny, yy;\n"
        "mul.rn.f16x2 a, %2, xx;\nfma.rn.f16x2 %0, %3, ny, a;\nmul.rn.f16x2 b, %3, xx;\nfma.rn.f16x2 %1, %2, yy, b;\n}\n" : "=&r"(ore), "=r"(oim) : "r"(re), "r"(im), "r"(z));
}
__device__ __forceinline__ void hcmul(uint32_t re, uint32_t im, uint32_t zx, uint32_t zy, uint32_t& ore, uint32_t& oim) {
    asm("{\n.reg .b32 ny, a, b;\nneg.f16x2 ny, %5;\n"
        "mul.rn.f16x2 a, %2, %4;\nfma.rn.f16x2 %0, %3, ny, a;\nmul.rn.f16x2 b, %3, %4;\nfma.rn.f16x2 %1, %2, %5, b;\n}\n" : "=&r"(ore), "=r"(oim) : "r"(re), "r"(im), "r"(zx), "r"(zy));
}

struct KGen {
    uint32_t Af[4][4];
    float2 z1, z8, z64, z128, T[9];
    uint32_t zw;
};
__device__ __forceinline__ void kgen_setup(KGen& k, uint32_t pa, float dt) {
    const float A = rbf(expf(bf_lo(pa)));
    const float lr2 = -(A * dt) * 1.4426950408889634f;
    const float li = bf_hi(pa) * dt;
    const float rh = li * 0.15915494309189535f;
    const float rl = fmaf(li, 6.4206382986e-9f, fmaf(li, 0.15915494309189535f, -rh));
    k.z1 = cexp_e(lr2, rh, rl, 1.0f);
    k.z8 = cexp_e(lr2, rh, rl, 8.0f);
    k.z64 = cexp_e(lr2, rh, rl, 64.0f);
}
__device__ __forceinline__ void kgen_rows(KGen& k, uint32_t tb, int lane) {
    const float2 z8 = k.z8, z64 = k.z64;
    const uint32_t row = tb + lane * TBP;
    k.z128 = csq(z64);
    const float2 z16 = csq(z8), z32 = csq(z16), z48 = cmul(z32, z16), z80 = cmul(z64, z16), z96 = cmul(z64, z32), z112 = cmul(z64, z48);
    uint32_t re[4], im[4], a[4], b[4];
    re[0] = pack_f16(1.0f, z16.x); im[0] = pack_f16(0.0f, z16.y);
    re[1] = pack_f16(z32.x, z48.x); im[1] = pack_f16(z32.y, z48.y);
    re[2] = pack_f16(z64.x, z80.x); im[2] = pack_f16(z64.y, z80.y);
    re[3] = pack_f16(z96.x, z112.x); im[3] = pack_f16(z96.y, z112.y);
    sts128(row, re[0], re[1], re[2], re[3]);
    sts128(row + 32, im[0], im[1], im[2], im[3]);
    const uint32_t zz = pack_f16(z8.x, z8.y);
#pragma unroll
    for (int j = 0; j < 4; j++) hcmul(re[j], im[j], zz, a[j], b[j]);
    sts128(row + 16, a[0], a[1], a[2], a[3]);
    sts128(row + 48, b[0], b[1], b[2], b[3]);
    __syncwarp();
    const int mi = lane >> 3;
    const uint32_t ad = tb + (lane & 7) * TBP + mi * 16;
#pragma unroll
    for (int ks = 0; ks < 4; ks++) ldsm_x4_t(k.Af[ks][0], k.Af[ks][1], k.Af[ks][2], k.Af[ks][3], ad + ks * 8 * TBP);
}
__device__ __forceinline__ void kgen_chain(KGen& k, uint32_t pc, float cs) {
    k.T[0] = make_float2(bf_lo(pc) * cs, -bf_hi(pc) * cs);
    const float2 y1 = make_float2(k.z1.x, -k.z1.y);
#pragma unroll
    for (int c = 1; c < 8; c++) k.T[c] = cmul(k.T[c - 1], y1);
    k.T[8] = cmul(k.T[0], make_float2(k.z8.x, -k.z8.y));
}
__device__ __forceinline__ void kgen_cols(KGen& k, uint32_t tb, int lane) {
    const uint32_t row = tb + lane * TBP;
    const float2 (&T)[9] = k.T;
    const uint32_t zv = pack_f16(k.z128.x, k.z128.y), zo = __shfl_xor_sync(0xffffffffu, zv, 1);
    k.zw = (lane & 1) ? __byte_perm(zo, zv, 0x7632) : __byte_perm(zv, zo, 0x5410);
    const float2 y256 = csq(make_float2(k.z128.x, -k.z128.y)), y512 = csq(y256), y768 = cmul(y512, y256), y1024 = csq(y512);
    const float2 c1032 = cmul(T[8], y1024);
    const uint32_t r04 = pack_f16(T[0].x, T[4].x), i04 = pack_f16(T[0].y, T[4].y), r26 = pack_f16(T[2].x, T[6].x), i26 = pack_f16(T[2].y, T[6].y);
    const uint32_t r48 = pack_f16(T[4].x, T[8].x), i48 = pack_f16(T[4].y, T[8].y);
    __syncwarp();
    sts128(row, r04, pack_f16(T[1].x, T[5].x), r26, pack_f16(T[3].x, T[7].x));
    sts128(row + 16, i04, pack_f16(T[1].y, T[5].y), i26, pack_f16(T[3].y, T[7].y));
    uint32_t a[4], b[4];
    {
        const uint32_t zz = pack_f16(y256.x, y256.y);
        hcmul(r04, i04, zz, a[0], b[0]);
        hcmul(r26, i26, zz, a[2], b[2]);
        hcmul(r48, i48, zz, a[3], b[3]);
    }
    sts128(row + 32, a[0], a[0], a[2], a[3]);
    sts128(row + 48, b[0], b[0], b[2], b[3]);
    {
        hcmul(r48, i48, pack_f16(y512.x, y512.y), a[0], b[0]);
        hcmul(r48, i48, pack_f16(y768.x, y768.y), a[1], b[1]);
        const uint32_t zz = pack_f16(c1032.x, c1032.y);
        hcmul(pack_f16(1.0f, y256.x), pack_f16(0.0f, y256.y), zz, a[2], b[2]);
        hcmul(pack_f16(y512.x, y768.x), pack_f16(y512.y, y768.y), zz, a[3], b[3]);
    }
    sts128(row + 64, a[0], a[1], a[2], a[3]);
    sts128(row + 80, b[0], b[1], b[2], b[3]);
}
__device__ __forceinline__ void kgen_mma(const KGen& k, uint32_t tb, int lane) {
    const int t = lane & 3;
    const uint32_t zw = k.zw;
    uint32_t zx[4], zy[4];
#pragma unroll
    for (int ks = 0; ks < 4; ks++) { zx[ks] = __shfl_sync(0xffffffffu, zw, 8 * ks + 2 * t); zy[ks] = __shfl_sync(0xffffffffu, zw, 8 * ks + 2 * t + 1); }
    __syncwarp();
    float acc[2][3][4];
#pragma unroll
    for (int i = 0; i < 6; i++)
#pragma unroll
        for (int j = 0; j < 4; j++) acc[i / 3][i % 3][j] = 0.f;
    {
        const int mi = lane >> 3;
        const uint32_t bd = tb + ((lane & 7) + 8 * (mi >> 1)) * TBP + (mi & 1) * 16;
#pragma unroll
        for (int kp = 0; kp < 2; kp++) {
            uint32_t b[3][4];
#pragma unroll
            for (int j = 0; j < 3; j++) ldsm_x4_t(b[j][0], b[j][1], b[j][2], b[j][3], bd + kp * 16 * TBP + j * 32);
#pragma unroll
            for (int h = 0; h < 2; h++) {
                const int ks = 2 * kp + h;
                uint32_t d[4];
                hcmul(k.Af[ks][0], k.Af[ks][2], zx[ks], zy[ks], d[0], d[2]);
                hcmul(k.Af[ks][1], k.Af[ks][3], zx[ks], zy[ks], d[1], d[3]);
#pragma unroll
                for (int j = 0; j < 3; j++) {
                    mma_f16(acc[0][j], k.Af[ks][0], k.Af[ks][1], k.Af[ks][2], k.Af[ks][3], b[j][2 * h], b[j][2 * h + 1]);
                    mma_f16(acc[1][j], d[0], d[1], d[2], d[3], b[j][2 * h], b[j][2 * h + 1]);
                }
            }
        }
    }
    __syncwarp();
#pragma unroll
    for (int h = 0; h < 2; h++) {
        sts64(tb + h * 256 + lane * 8, pack_f16(acc[h][0][0], acc[h][0][1]), pack_f16(acc[h][0][2], acc[h][0][3]));
        sts64(tb + 512 + h * 256 + lane * 8, pack_f16(acc[h][1][0], acc[h][1][1]), pack_f16(acc[h][1][2], acc[h][1][3]));
        sts32(tb + 1024 + h * 256 + lane * 4, pack_f16(acc[h][2][0], t < 2 ? acc[h][2][1] : acc[h][2][2]));
        sts32(tb + 1152 + h * 256 + lane * 4, pack_f16(t < 2 ? acc[h][2][2] : acc[h][2][1], acc[h][2][3]));
    }
}
__device__ __forceinline__ uint32_t table_buf(uint32_t sb, int warp) { return sb + SM_TB + warp * TBW; }

__device__ __forceinline__ void kgen_combine(uint32_t sb, int warp, int lane, uint32_t kw, uint32_t ao) {
    const int wq = warp & 3;
    const uint32_t a = table_buf(sb, warp & ~3) + wq * 256 + lane * 8, c = table_buf(sb, warp & ~3) + 1024 + wq * 128 + lane * 4;
    const int t = lane & 3;
    const uint32_t o0 = (t < 2 ? KW_T2 + KW_KH + 16 + t * 256 - (wq & 1) * KW_KH : KW_T3 + 16 - 1024 + t * 512 + (wq & 1) * 256) + (lane >> 2) * 16;
    const uint4 o = make_uint4(o0 + t * 36, o0 + (t ^ 1) * 36, o0 + (t ^ 2) * 36, o0 + (t ^ 3) * 36);
    const uint2 u = lds64(a), v = lds64(a + TBW), w = lds64(a + 2 * TBW), x = lds64(a + 3 * TBW);
    const uint32_t kt = hadd2(hadd2(lds32(c), lds32(c + TBW)), hadd2(lds32(c + 2 * TBW), lds32(c + 3 * TBW)));
    const uint32_t k23 = hadd2(hadd2(u.y, v.y), hadd2(w.y, x.y));
    sts64(kw + wq * 64 + ao, hadd2(hadd2(u.x, v.x), hadd2(w.x, x.x)), k23);
    const uint32_t d = kw + (wq >> 1) * 128;
    const uint32_t kh = hmul2(kt, 0x38003800u);
    sts32(d + o.x, kh); sts32(d + o.y, kh); sts32(d + o.z, kh); sts32(d + o.w, kh);
    if (wq == 3) {
        if (lane == 31) { sts32(kw + 264, k23 >> 16); sts32(kw + 288 + 264, k23 >> 16); sts32(kw + 576 + 264, k23 >> 16); }
        if (lane == 29) { sts32(kw + 864 + 280, kt >> 16); sts32(kw + 280, kt & 0xffff0000u); }
    }
}

__device__ __forceinline__ int c_exponent(const uint2& r, const uint2& i) {
    uint32_t mx = __vmaxu2(__vmaxu2(r.x & 0x7fff7fffu, r.y & 0x7fff7fffu), __vmaxu2(i.x & 0x7fff7fffu, i.y & 0x7fff7fffu));
    mx = __reduce_max_sync(0xffffffffu, max(mx & 0xffffu, mx >> 16));
    return min(max((int)(mx >> 7), 4), 240);
}

__device__ __forceinline__ int warp_v() { int l; asm volatile("mov.u32 %0, %%tid.x;" : "=r"(l)); return __shfl_sync(0xffffffffu, l >> 5, 0); }
__device__ __forceinline__ int lane_v() { int l; asm volatile("mov.u32 %0, %%laneid;" : "=r"(l)); return l; }
__device__ __forceinline__ unsigned clock32() { unsigned c; asm volatile("mov.u32 %0, %%clock;" : "=r"(c)); return c; }
__device__ __forceinline__ uint32_t prmt(uint32_t a, uint32_t b, uint32_t s) { uint32_t d; asm("prmt.b32 %0, %1, %2, %3;\n" : "=r"(d) : "r"(a), "r"(b), "r"(s)); return d; }
__device__ __forceinline__ uint32_t prmt_v(uint32_t a, uint32_t b, uint32_t s) { uint32_t d; asm volatile("prmt.b32 %0, %1, %2, %3;\n" : "=r"(d) : "r"(a), "r"(b), "r"(s)); return d; }
__device__ __forceinline__ void mmah16(uint32_t& d0, uint32_t& d1, uint32_t a0, uint32_t a1, uint32_t a2, uint32_t a3, uint32_t b0, uint32_t b1, uint32_t c0, uint32_t c1) {
    asm volatile("mma.sync.aligned.m16n8k16.row.col.f16.f16.f16.f16 {%0,%1}, {%2,%3,%4,%5}, {%6,%7}, {%8,%9};\n"
                 : "=r"(d0), "=r"(d1) : "r"(a0), "r"(a1), "r"(a2), "r"(a3), "r"(b0), "r"(b1), "r"(c0), "r"(c1));
}
__device__ __forceinline__ void mmah8(uint32_t& d0, uint32_t& d1, uint32_t a0, uint32_t a1, uint32_t b0, uint32_t c0, uint32_t c1) {
    asm volatile("mma.sync.aligned.m16n8k8.row.col.f16.f16.f16.f16 {%0,%1}, {%2,%3}, {%4}, {%5,%6};\n"
                 : "=r"(d0), "=r"(d1) : "r"(a0), "r"(a1), "r"(b0), "r"(c0), "r"(c1));
}
template <int A = 8, int B = 32>
__device__ __forceinline__ void conv_rename(uint32_t (&acc)[32]) {
#pragma unroll
    for (int i = A; i < B; i++) { uint32_t v; asm volatile("mov.b32 %0, %1;\n" : "=r"(v) : "r"(acc[i])); acc[i] = v; }
}
__host__ __device__ constexpr uint32_t band_bits(int hw, int sh) {
    uint32_t c = 0;
    for (int s = 0; s <= 10; s++)
        for (int e = 0; e < 2; e++) {
            const int v = s - 3 + sh - 4 * e;
            if (v <= hw && v >= -hw) c |= 1u << (14 + 16 * e - s);
        }
    return c;
}
template <int HW, int SH, int J> __device__ __forceinline__ uint32_t band(uint32_t p2) {
    uint32_t d;
    asm volatile("{\n.reg .b32 t;\nmul.lo.u32 t, %1, %2;\nand.b32 %0, t, 0x40004000;\n}\n" : "=r"(d) : "r"(p2), "n"(band_bits(HW, SH) | J));
    return d;
}
template <int H0, int SH> __device__ __forceinline__ void band_pair(uint4& l, uint4& u, uint32_t p2) {
    l = make_uint4(band<H0, 8, 1>(p2), band<H0 - 1, SH + 8, 2>(p2), band<H0, 0, 1>(p2), band<H0 - 1, SH, 1>(p2));
    u = make_uint4(band<H0, 0, 2>(p2), band<H0 - 1, SH, 2>(p2), band<H0, -8, 1>(p2), band<H0 - 1, SH - 8, 1>(p2));
}
__device__ __forceinline__ void run_sums(uint32_t (&G)[3][2], const uint32_t (&c)[5], const uint4& l, const uint4& u) {
    mmah8(G[0][0], G[0][1], l.x, l.y, c[0], 0u, 0u);
    mmah8(G[1][0], G[1][1], u.z, u.w, c[3], 0u, 0u);
    mmah8(G[2][0], G[2][1], l.x, l.y, c[2], 0u, 0u);
    mmah16(G[0][0], G[0][1], u.x, u.y, u.z, u.w, c[1], c[2], G[0][0], G[0][1]);
    mmah16(G[1][0], G[1][1], l.x, l.y, l.z, l.w, c[1], c[2], G[1][0], G[1][1]);
    mmah16(G[2][0], G[2][1], u.x, u.y, u.z, u.w, c[3], c[4], G[2][0], G[2][1]);
}
__device__ __forceinline__ float h_lo(uint32_t w) { return __half2float(__ushort_as_half((unsigned short)(w & 0xffffu))); }
__device__ __forceinline__ float h_hi(uint32_t w) { return __half2float(__ushort_as_half((unsigned short)(w >> 16))); }
__device__ __forceinline__ uint64_t smem_desc(uint32_t sb, uint32_t o16, uint32_t lbo) {
    uint64_t d;
    asm("mov.b64 %0, {%1, %2};" : "=l"(d) : "r"(((sb & 0x3FFFF) >> 4) + o16 + (lbo << 12)), "r"(8));
    return d;
}
template <int I> struct IC { static constexpr int value = I; };

struct Conv {
    uint32_t u[3][5];
    uint32_t q2[3][2][4];
    uint32_t q3[2][4];
    uint32_t r[18];
};
struct ConvPre {
    uint32_t a[5], b[5];
    uint32_t t[4];
};
__device__ __forceinline__ void conv_pre(ConvPre& e, uint32_t ka, uint32_t ks, uint32_t sel) {
    const uint4 r = lds128(ka + 256), s = lds128(ka + 272);
    ldsm_x4(e.t[0], e.t[1], e.t[2], e.t[3], ks);
    const uint32_t sw = sel ^ 0x4444u;
    e.a[0] = prmt(r.y, r.z, sel); e.a[1] = prmt(r.w, r.z, sw); e.a[2] = prmt(r.x, r.y, sel); e.a[3] = prmt(r.z, r.y, sw); e.a[4] = prmt(r.z, r.w, sel);
    e.b[0] = prmt(s.y, s.z, sel); e.b[1] = prmt(s.w, s.z, sw); e.b[2] = prmt(s.x, s.y, sel); e.b[3] = prmt(s.z, s.y, sw); e.b[4] = prmt(s.z, s.w, sel);
}
__device__ __forceinline__ void conv_sums(Conv& c, uint32_t (&acc)[32], const ConvPre& e, uint32_t a0, uint32_t a1, const uint4 (&bd)[4], uint32_t ka, uint32_t sel, int wq, uint32_t zr) {
    {
        uint32_t x;
        ldsm_x4(c.u[0][1], c.u[0][2], c.u[0][3], c.u[0][4], a1);
        ldsm_x4(c.u[0][0], c.u[1][0], c.u[2][0], x, a0);
#pragma unroll
        for (int q = 1; q < 3; q++) ldsm_x4(c.u[q][1], c.u[q][2], c.u[q][3], c.u[q][4], a1 + q * 512);
    }
#pragma unroll
    for (int i = 0; i < 32; i++) acc[i] = 0u;
    uint32_t G[3][2];
#pragma unroll
    for (int q = 0; q < 3; q++) {
        mmah8(acc[8 * q + 8], acc[8 * q + 9], e.a[4], 0u, c.u[q][2], acc[8 * q + 8], acc[8 * q + 9]);
        mmah16(acc[8 * q + 8], acc[8 * q + 9], e.a[0], e.a[1], e.a[2], e.a[3], c.u[q][3], c.u[q][4], acc[8 * q + 8], acc[8 * q + 9]);
        if (q < 2) {
            mmah8(acc[8 * q + 16], acc[8 * q + 17], e.b[4], 0u, c.u[q][2], 0u, 0u);
            mmah16(acc[8 * q + 16], acc[8 * q + 17], e.b[0], e.b[1], e.b[2], e.b[3], c.u[q][3], c.u[q][4], acc[8 * q + 16], acc[8 * q + 17]);
            run_sums(G, c.u[q], bd[2], bd[3]);
            c.q3[q][0] = prmt(G[1][1], G[0][0], 0x7632u); c.q3[q][1] = prmt(G[2][1], G[1][0], 0x7632u);
            c.q3[q][2] = prmt(G[1][1], G[0][0], 0x5410u); c.q3[q][3] = prmt(G[2][1], G[1][0], 0x5410u);
        }
    }
    {
        const uint32_t a = (ka + wq * 64) ^ (((acc[8] | acc[16] | acc[24]) | (c.q3[0][0] | c.q3[0][1]) | (c.q3[1][0] | c.q3[1][1])) & zr);
#pragma unroll
        for (int i = 0; i < 4; i++) { const uint4 v = lds128(a + i * 16); c.r[4 * i] = v.x; c.r[4 * i + 1] = v.y; c.r[4 * i + 2] = v.z; c.r[4 * i + 3] = v.w; }
        const uint2 v = lds64(a + 64);
        c.r[16] = v.x; c.r[17] = v.y;
    }
#pragma unroll
    for (int q = 0; q < 3; q++) {
        run_sums(G, c.u[q], bd[0], bd[1]);
#pragma unroll
        for (int h = 0; h < 2; h++) {
            const uint32_t s = h ? 0x7632u : 0x5410u;
            c.q2[q][h][0] = prmt(G[0][1], G[0][0], s); c.q2[q][h][1] = prmt(G[1][1], G[1][0], s);
            c.q2[q][h][2] = prmt(G[1][0], G[1][1], s ^ 0x4444u); c.q2[q][h][3] = prmt(G[2][1], G[2][0], s);
            if (q < 2) mmah16(acc[8 * q + 16], acc[8 * q + 17], c.q2[q][h][0], c.q2[q][h][1], c.q2[q][h][2], c.q2[q][h][3], e.t[2 * h], e.t[2 * h + 1], acc[8 * q + 16], acc[8 * q + 17]);
        }
    }
    if (sel == 0u) {
#pragma unroll
        for (int i = 0; i < 6; i++) sts128(ka + i * 16, c.q2[i >> 1][i & 1][0], c.q2[i >> 1][i & 1][1], c.q2[i >> 1][i & 1][2], c.q2[i >> 1][i & 1][3]);
#pragma unroll
        for (int i = 0; i < 2; i++) sts128(ka + i * 16, c.q3[i][0], c.q3[i][1], c.q3[i][2], c.q3[i][3]);
#pragma unroll
        for (int i = 1; i < 4; i++) sts64(ka + i * 16, acc[8 * i], acc[8 * i + 1]);
    }
    conv_rename(acc);
}
#define SPACE 100
#define SPN 3
#define O4 4
#define B2L 1
#define GATE 2
#define HAND 2
#define GA 6
#define GB 4
template <int TA, int TB, int IA, class FG>
__device__ __forceinline__ void conv_tail(uint32_t (&acc)[32], const uint32_t (&a)[8][4], uint32_t sb, unsigned char* gy0, int warp, size_t ycopy, FG fg) {
    const int wg = warp >> 2, wq = warp & 3, ord = TA == 0 && TB == 16 ? 3 - wg + (3 - wg >= O4) : O4;
    const uint32_t ub = sb + SM_U + wg * USLOT_B + UPAD * 16, turn = sb + SM_MISC + 376 + ord * 8, sfs = sb + SM_MISC + 256 + wg * 8;
    const uint32_t du = wg * (USLOT_B / 16) + (SM_U / 16 + UPAD + TA * 8);
    uint32_t ud[8], fs;
    auto skip = [&]() {
        const int lane = lane_v();
        const uint32_t ua = ub + ((lane >> 3) & 1) * ULO_B + (8 * wq + (lane & 7)) * 16 + (lane >> 4) * 512;
        if (IA == 0) ldsm_x4_t(ud[0], ud[1], ud[2], ud[3], ua);
        if (TB == 16) ldsm_x4_t(ud[4], ud[5], ud[6], ud[7], ua + 1024);
        const uint2 fd = lds64(sfs);
        fs = fd.x;
        const float dsk = __uint_as_float(fd.y);
#pragma unroll
        for (int i = 2 * IA; i < TB / 2; i++) ud[i] = pack_bf16(h_lo(ud[i]) * dsk, h_hi(ud[i]) * dsk);
    };
    conv_rename<2 * TA, 2 * TB>(acc);
    if (__builtin_expect(ord != 0, 0)) {
        skip();
        mbar_wait(turn);
    } else if (B2L) {
        bar_sync(0, NWRK);
    }
    if (O4 < 4 || (TA == 0 && TB == 16)) asm volatile("{\n.reg .pred p;\nelect.sync _|p, 0xffffffff;\n@p mbarrier.arrive.shared::cta.b64 _, [%0];\n}\n" ::"r"(turn + 48) : "memory");
    fg(IC<8>());
    wg_fence();
#pragma unroll
    for (int m = 7; m >= 0; m--) {
        wg_h<TA, TB - TA>(acc, a[m], smem_desc(sb, du - m, ULO_B));
        if (m == GA || m == GB || m == HAND) wg_commit();
        if (m == GB) asm volatile("wgmma.wait_group.sync.aligned 1;\n" ::: "memory");
    }
    wg_commit();
    if (O4 < 4 || (TA == 0 && TB == 16)) {
        asm volatile("wgmma.wait_group.sync.aligned 1;\n" ::: "memory");
        asm volatile("{\n.reg .pred p;\nelect.sync _|p, 0xffffffff;\n@p mbarrier.arrive.shared::cta.b64 _, [%0];\n}\n" ::"r"(turn + 8) : "memory");
    }
    __syncwarp();
    fg(IC<3>());
    if (!ord) skip();
    fg(IC<4>());
    const int lane = lane_v();
    const uint32_t lp = sb + SM_PL + (ord >= 3 ? ord - 3 : ord) * PL_B + lane * 8;
    unsigned char* gy = gy0 + ((4 * wq + (lane & 3)) * DM + (TA == 0 && TB == 16 ? 4 * blockIdx.x + wg : 512 + (blockIdx.x >> 1))) * 64 + (lane >> 2) * 8;
    const uint32_t st = lp + (wq * 12 - ((wq * (wq - 1)) >> 1)) * 256;
    uint32_t ld[3];
#pragma unroll
    for (int s = 1; s < 4; s++) {
        const int w = (wq - s) & 3;
        ld[s - 1] = lp + (w * 12 - ((w * (w - 1)) >> 1) + s - 1 - (wq < s ? 3 : 0)) * 256;
    }
    const uint32_t one = 1u + (warp >> 8);
    if (one == 0u) stg64(gy, ld[0], ld[1]);
    if (ord >= 3) bar_sync(9 + ord, 256);
    wg_wait0();
    fg(IC<6>());
#pragma unroll
    for (int j = TA; j < TB; j++)
        if ((j & 3) && j + 3 >= 4 * IA && (j + 3 < TB || j + wq < TB)) sts64(st + (j - 1 - (j >> 2)) * 256, acc[2 * j], acc[2 * j + 1]);
    bar_sync(1 + wg, 128);
    fg(IC<7>());
    uint2 v[4][3];
#pragma unroll
    for (int i = IA; i < TB / 4; i++)
#pragma unroll
        for (int s = 0; s < 3; s++) {
            if (i == 0) { v[i][s] = make_uint2(0u, 0u); if (wq > s) v[i][s] = lds64(ld[s]); }
            else v[i][s] = lds64(ld[s] + i * 768);
        }
    fg(IC<5>());
#pragma unroll
    for (int i = IA; i < TB / 4; i++) {
        const uint32_t x0 = hadd2(v[i][0].x, acc[8 * i]), x1 = hadd2(v[i][1].x, v[i][2].x), y0 = hadd2(v[i][0].y, acc[8 * i + 1]), y1 = hadd2(v[i][1].y, v[i][2].y);
        const uint32_t x = hadd2(x0, x1), y = hadd2(y0, y1);
        const uint32_t lo = pack_bf16(h_lo(x), h_hi(x)), hi = pack_bf16(h_lo(y), h_hi(y));
        ud[2 * i] = max(hfma2_bf(lo, fs, ud[2 * i]), one); ud[2 * i + 1] = hfma2_bf(hi, fs, ud[2 * i + 1]);
    }
    if (SPACE && TA == 0 && TB == 16 && ord < SPN) {
#pragma unroll
        for (int i = 0; i < 4; i++) {
            stg64(gy + i * 16 * DM * 64, ud[2 * i], ud[2 * i + 1]);
            if (i < 3) { const unsigned c0 = clock32(); while (clock32() - c0 < SPACE) {} }
        }
    } else {
#pragma unroll
        for (int i = IA; i < TB / 4; i++) stg64(gy + i * 16 * DM * 64, ud[2 * i], ud[2 * i + 1]);
    }
    if (ord < 2) bar_arrive(12 + ord, 256);
}
template <int M0, int M1>
__device__ __forceinline__ void conv_frags(uint32_t (&a)[8][4], const uint32_t (&r)[18], uint32_t sel, uint32_t dep, int warp) {
    const uint32_t s = prmt_v(sel, dep, 0x3210u + (warp >> 8)), sw = s ^ 0x4444u;
#pragma unroll
    for (int m = M0; m < M1; m++) {
        a[m][0] = prmt_v(r[2 * m + 1], r[2 * m + 2], s); a[m][1] = prmt_v(r[2 * m + 2], r[2 * m + 3], s);
        a[m][2] = prmt_v(r[2 * m + 1], r[2 * m], sw); a[m][3] = prmt_v(r[2 * m + 2], r[2 * m + 1], sw);
    }
}
template <class FG>
__device__ __forceinline__ void conv_main(const Conv& c, uint32_t (&acc)[32], uint32_t sb, uint32_t sel, unsigned char* gy, int warp, size_t ycopy, FG fg) {
    const uint32_t kw = (warp >> 2) * (KW_B / 16) + SM_KW / 16;
    const uint64_t d2 = smem_desc(sb, kw + KW_T2 / 16, KW_KH), d2b = smem_desc(sb, kw + KW_T2 / 16 + 1, KW_KH), d3 = smem_desc(sb, kw + KW_T3 / 16, 16), d3b = smem_desc(sb, kw + KW_T3 / 16 + 32, 16);
    uint32_t a[8][4];
    {
        const int ord = warp < 16 ? 3 - (warp >> 2) + (3 - (warp >> 2) >= O4) : O4;
        if (__builtin_expect(ord >= GATE, 0)) {
            fg(IC<1>());
            mbar_wait(sb + SM_MISC + 376 + 48 + (ord - GATE) * 8);
        }
    }
    wg_fence();
    wg_h<12, 4>(acc, c.q3[0], d3b); wg_h<8, 4>(acc, c.q3[0], d3); wg_h<4, 4>(acc, c.q2[0][0], d2b);
    wg_h<12, 4>(acc, c.q3[1], d3); wg_h<8, 4>(acc, c.q2[1][0], d2b);
    wg_h<12, 4>(acc, c.q2[2][0], d2b); wg_h<4, 4>(acc, c.q2[0][1], d2); wg_h<8, 4>(acc, c.q2[1][1], d2);
    wg_h<12, 4>(acc, c.q2[2][1], d2);
    wg_commit(); __syncwarp();
    fg(IC<0>());
    wg_wait0();
    conv_frags<0, 8>(a, c.r, sel, acc[16], warp);
    fg(IC<2>());
    if (warp >= 16) {
        if (blockIdx.x & 1) conv_tail<4, 16, 2>(acc, a, sb, gy, warp, ycopy, fg);
        else conv_tail<0, 8, 0>(acc, a, sb, gy, warp, ycopy, fg);
    } else {
        conv_tail<0, 16, 0>(acc, a, sb, gy, warp, ycopy, fg);
    }
}
#define CONV_LT6 const int dd = (lane >> 3) + (lane & 4) - (lane & 3); \
        const uint4 lt6 = make_uint4(prmt_v((dd & 3) * 288, 0u, idn), prmt_v(0x3254u + (dd >> 2) * 0x2222u, 0u, idn), \
            prmt_v(UPAD * 16 + (lane & 7) * 16 + ULO_B - 32 + (lane >> 3) * 512, 0u, idn), prmt_v(UPAD * 16 + (lane & 7) * 16 + ((lane >> 3) & 1) * ULO_B - 16 + (lane & 16), 0u, idn));
#define CONV_PRE \
        CONV_LT6 \
        const uint32_t ka = kw + lt6.x, sel = lt6.y, ks = kw + lt7.x; \
        const uint32_t ca0 = sb + SM_U + wg * USLOT_B + (warp & 3) * 128 + lt6.z, ca1 = sb + SM_U + wg * USLOT_B + (warp & 3) * 128 + lt6.w; \
        uint4 bd[4]; \
        band_pair<2, 4>(bd[0], bd[1], lt7.w); band_pair<4, 0>(bd[2], bd[3], lt7.w);
#define CONV_PRE2 ConvPre ce_; conv_pre(ce_, ka, ks, sel);
#define CONV_BODY \
        Conv c; \
        uint32_t acc[32]; \
        conv_sums(c, acc, ce_, ca0, ca1, bd, ka, sel, warp & 3, warp >> 8);
#define WS a_b_0_1_2_34_xy_56_7__c__r____de__
#define WS_STR2(x) #x
#define WS_STR(x) WS_STR2(x)
__device__ constexpr char wunit(int pt, int k) {
    constexpr char t[] = WS_STR(WS);
    int i = 0;
    for (; pt > 0 && t[i]; i++) pt -= t[i] == '_';
    for (; k > 0 && t[i] && t[i] != '_'; i++) k--;
    return t[i] == '_' ? 0 : t[i];
}
__device__ constexpr bool wsched_ok() {
    int seen = 0;
    for (int p = 0; p < 21; p++)
        for (int k = 0; wunit(p, k); k++) {
            const char c = wunit(p, k);
            const int bit = 1 << (c == 'r' ? 13 : c >= 'x' ? c - 'x' + 14 : c >= 'a' ? c - 'a' + 8 : c - '0');
            if ((seen & bit) || k >= (p < 16 ? 4 : 2) || (p < 5 && c >= '4' && c <= '7') || (p < 6 && (c == 'c' || c == 'd')) || (p < 16 && c == 'e')) return false;
            seen |= bit;
        }
    return seen == 0xffff;
}
struct WMaps { CUtensorMap g, u, gr, ur, d, dr; };
static_assert((PAUSE & 2) && GATE <= 2 && O4 >= 2, "resets");
static_assert(wsched_ok(), "weight schedule");
template <int PT, int K>
__device__ __forceinline__ void weight_units(uint32_t sb, const WMaps& m, int w) {
    constexpr char U = wunit(PT, K);
    if constexpr (U != 0) {
        if (w == K && elect_one()) {
            const int P = blockIdx.x >> 1, odd = blockIdx.x & 1;
            constexpr int bar = SM_MISC + (U == 'e' ? 352 : U >= 'a' && U <= 'r' ? 336 : 328);
            if constexpr (U == 'e') { if (!odd) tma_2d(sb + SM_WD + 4 * 8192, &m.d, 256, 64 * P, sb + bar); }
            else if constexpr (U == 'r') tma_3d(sb + SM_WD + 40960, &m.dr, 0, 4096 + 8 * P, 5 * odd, sb + bar);
            else if constexpr (U >= 'x') tma_3d(sb + SM_WR + (U - 'x') * 4608, U == 'x' ? &m.gr : &m.ur, 4096 + 8 * P, 0, 2 * odd, sb + bar);
            else if constexpr (U >= 'a') tma_2d(sb + SM_WD + (U - 'a') * 8192, &m.d, 320 * odd + 64 * (U - 'a'), 64 * P, sb + bar);
            else tma_2d(sb + (U < '4' ? SM_WG : SM_WU) + (U & 3) * 9216, U < '4' ? &m.g : &m.u, 64 * P, 288 * odd + (U & 3) * 72, sb + bar);
        }
        weight_units<PT, K + 1>(sb, m, w);
    }
}
#define WPOINT(i, w) do { weight_units<i, 0>(sb, wm, w); } while (0)

__global__ void __launch_bounds__(NTHR, 1) __cluster_dims__(2, 1, 1)
fused_kernel(const Params p, const __grid_constant__ WMaps wm, const __grid_constant__ CUtensorMap tm_x,
             const __grid_constant__ CUtensorMap tm_y, const __grid_constant__ CUtensorMap tm_z) {
    extern __shared__ __align__(1024) unsigned char smem[];
    const uint32_t sb = smem_u32(smem);
    const int tid = threadIdx.x, warp = __shfl_sync(0xffffffffu, tid >> 5, 0), lane = tid & 31;
    const int b = blockIdx.x, P = b >> 1, odd = b & 1;
    const int g = lane >> 2, t = lane & 3;
    const int wg = warp >> 2, t128 = tid & 127;
    const uint32_t s_stat = sb + SM_MISC;
    const uint32_t s_key = sb + SM_MISC + 128;
    const uint32_t s_wm = sb + SM_MISC + 256;
    const uint32_t s_k16 = sb + SM_MISC + 192;
    const uint32_t s_fs = sb + SM_MISC + 256;
    const uint32_t s_cnt = sb + SM_MISC + 320;
    const uint32_t bar_w = sb + SM_MISC + 328, bar_d = bar_w + 8, bar_g = bar_w + 16, bar_r = bar_w + 32, bar_h = bar_w + 40, bar_x = bar_w + 48;
    STAMP(0);

    const bool lnw = (unsigned)(warp - 10) < 9u;
    const unsigned pm = tid + (tid < 512 ? 512 * b : 65024 + 128 * P), pq = (pm & ~127u) + 4 * lane;
    uint32_t pl = ldg16(p.lar + pm), ldt = ldg16(p.ldt + (pm >> 7));
    const uint32_t pa2 = ldg16(p.aim + pm), pc = ldg16(p.cre + pm), pi = ldg16(p.cim + pm);
    const uint2 call_re = ldg64(p.cre + pq), call_im = ldg64(p.cim + pq);
    const uint32_t dskl = ldg16(p.dsk + (pm >> 7));
    const uint32_t ep = ld_poll32(p.s->hint + (b & 7) * 32 + 1 + (lane >> 5));
    if ((unsigned)(tid - 320) < 288u) {
        const bf16* xp = p.x + (unsigned)((32 * P + 2 * odd + TOKEN_OF(g)) * DM + ((tid - 320) & ~31) + 8 * t);
        const uint32_t xt = sb + SM_XT + ((tid - 320) & ~31) * 32 + lane * 16;
        asm volatile("cp.async.cg.shared.global [%0], [%1], 16;\ncp.async.cg.shared.global [%0 + 512], [%1 + 9216], 16;\n"
                     "cp.async.cg.shared.global [%0 + 9216], [%1 + 576], 16;\ncp.async.cg.shared.global [%0 + 9728], [%1 + 9792], 16;\n" ::"r"(xt), "l"(xp) : "memory");
    }
    uint32_t* const std_ = p.s->st + ((lane & 12) * 128 + odd * 256 + 4 * P + 2 * (lane & 1) + ((lane >> 1) & 1)) * 2;
    unsigned char* const ud = reinterpret_cast<unsigned char*>(p.s->uT) + (32 * (warp - UW) + 8 * (g >> 1) + (g & 1)) * 4096 + b * 32 + t * 8;
    if (warp == 0) {
        if (lane == 0) {
            mbar_init(bar_x, 1); mbar_init(bar_w, 1); mbar_init(bar_d, 1); mbar_init(bar_d + 16, 1); mbar_init(bar_g, 1); mbar_init(bar_h, 3); mbar_init(bar_r, 1);
            #pragma unroll
            for (int i = 1; i < 11; i++) mbar_init(bar_x + 8 * i, 4);
            asm volatile("fence.mbarrier_init.release.cluster;\n" ::: "memory");
            mbar_expect(bar_x, 16384); mbar_expect(bar_r, 8192);
            mbar_expect(bar_w, 2 * 41472); mbar_expect(bar_d, 32768 + 5120); mbar_expect(bar_d + 16, 8192); mbar_expect(bar_g, 9 * 512);
        }
        __syncwarp();
        bar_arrive(0, NWRK);
    }
    if (warp == 0 && elect_one()) tma_3d(sb + SM_XC, &tm_x, 8 * P, 0, 8 * odd, bar_x);
    asm volatile("barrier.cluster.arrive.relaxed.aligned;\n" ::: "memory");
    const uint32_t kw = sb + SM_KW + wg * KW_B;
    if (t128 < 2 * UPAD) sts128(sb + SM_U + wg * USLOT_B + (t128 & 1) * ULO_B + (t128 >> 1) * 16, 0u, 0u, 0u, 0u);
    sts128(kw + t128 * 16, 0u, 0u, 0u, 0u);
    if (t128 < KW_B / 16 - 128) sts128(kw + 2048 + t128 * 16, 0u, 0u, 0u, 0u);
    if (tid < 128) {
#pragma unroll
        for (int i = 0; i < 4; i++) sts128(sb + SM_ZERO + i * 2048 + tid * 16, 0u, 0u, 0u, 0u);
    }
    if (warp != 0) bar_sync(0, NWRK);
    STAMP(1);
    if (warp == 19 || warp == UW || warp == UW + 1) {
        if (warp == 19) {
            if (lane < 16) stg64(std_, 0u, 0u);
            if (lane < 9) asm volatile("prefetch.global.L2 [%0];\n" ::"l"(p.wr + lane * 64));
        } else {
#pragma unroll
            for (int k = 0; k < 4; k++) stg64(ud + k * 8192, 0u, 0u);
        }
    }
    uint32_t X[2][8];
    auto partial = [&]() {
        const uint32_t xt = sb + SM_XT + (warp - 10) * 1024 + lane * 16;
        asm volatile("cp.async.wait_all;\n" ::: "memory");
        STAMP(23);
        const uint4 a = lds128(xt), c = lds128(xt + 512), d = lds128(xt + 9216), e = lds128(xt + 9728);
        X[0][0] = a.x; X[0][1] = a.y; X[0][2] = a.z; X[0][3] = a.w; X[0][4] = d.x; X[0][5] = d.y; X[0][6] = d.z; X[0][7] = d.w;
        X[1][0] = c.x; X[1][1] = c.y; X[1][2] = c.z; X[1][3] = c.w; X[1][4] = e.x; X[1][5] = e.y; X[1][6] = e.z; X[1][7] = e.w;
        const uint32_t one[8] = {0x3f803f80u, 0x3f803f80u, 0x3f803f80u, 0x3f803f80u, 0x3f803f80u, 0x3f803f80u, 0x3f803f80u, 0x3f803f80u};
        ln_partial<8>(X, one, sb + SM_LNP, warp - 10, g, t);
        bar_arrive(6, 320);
        if (PAUSE & 1) bar_sync(7, PCNT);
    };
    if (LNAT == 0 && lnw) {
        partial();
        pl = prmt_v(pl, X[0][0], 0x3210u + (warp >> 8)); ldt = prmt_v(ldt, X[0][0], 0x3210u + (warp >> 8));
    }
    auto finish = [&]() {
        bar_sync(6, 320);
        float mb, rc;
        ln_finish<9>(sb + SM_LNP, lane, mb, rc);
        const float rh = rbf(rc);
        const uint32_t s0 = (__float_as_uint(mb) >> 16) | (((ep & 0x7fffu) + 1u) << 16), s1 = pack_bf16(rh, rc - rh);
        if (lane < 16) { stg64(std_, s0, s1); sts64(s_stat + lane * 8, s0, s1); }
        if (lane == 16) sts32(s_cnt + 4, ep);
        bar_arrive(7, PCNT);
        STAMP(28);
    };
    auto upub = [&]() {
        if (!(PAUSE & 6)) bar_sync(7, PCNT);
        const uint32_t utag = ((ep & 3u) + 1u) * 0x10001u;
        uint32_t U[2][4];
#pragma unroll
        for (int hf = 0; hf < 2; hf++) {
            const uint2 st = lds64(s_stat + (g + 8 * hf) * 8);
            const uint4 xv = lds128(sb + SM_XT + (16 + warp - UW) * 1024 + hf * 512 + lane * 16);
            const uint32_t xs[4] = {xv.x, xv.y, xv.z, xv.w};
#pragma unroll
            for (int k = 0; k < 4; k++) {
                const uint32_t u = ln_apply(xs[k], st);
                U[hf][k] = movm((pack_f16_rz(bf_lo(u), __uint_as_float(u)) & 0xfff8fff8u) | utag);
            }
        }
#pragma unroll
        for (int k = 0; k < 4; k++) stg64(ud + k * 8192, U[0][k], U[1][k]);
    };
    if (FINAT == 0 && warp == 19) finish();
    const uint32_t tb = table_buf(sb, warp);
    const float dt = rbf(expf(bf_lo(ldt)));
    KGen kg;
    kgen_setup(kg, pl | (pa2 << 16), dt);
    if (LNAT == 1 && lnw) {
        partial();
        kg.z8.x = __uint_as_float(prmt_v(__float_as_uint(kg.z8.x), X[0][0], 0x3210u + (warp >> 8)));
        kg.z1.x = __uint_as_float(prmt_v(__float_as_uint(kg.z1.x), X[0][0], 0x3210u + (warp >> 8)));
    }
    if (FINAT == 1 && warp == 19) finish();
    if (UAT == 0 && (warp == UW || warp == UW + 1)) upub();
    kgen_rows(kg, tb, lane);
    if (wg == 0) fence_async();
    if (LNAT == 2 && lnw) {
        partial();
        kg.z128.x = __uint_as_float(prmt_v(__float_as_uint(kg.z128.x), X[0][0], 0x3210u + (warp >> 8)));
        kg.z1.x = __uint_as_float(prmt_v(__float_as_uint(kg.z1.x), X[0][0], 0x3210u + (warp >> 8)));
    }
    if (FINAT == 2 && warp == 19) finish();
    if (UAT == 1 && (warp == UW || warp == UW + 1)) upub();
    STAMP(2);
    WPOINT(0, warp - 4);
    const int ce = c_exponent(call_re, call_im);
    if (t128 == 0) sts64(s_fs + wg * 8, (uint32_t)min(max(ce + (int)(__float_as_uint(dt) >> 23) - 116, 0), 254) * 0x800080u, dskl << 16);
    kgen_chain(kg, pc | (pi << 16), __uint_as_float(((uint32_t)(244 - ce) << 23) | (__float_as_uint(dt) & 0x7fffffu)));
    if ((PAUSE & 4) && warp < 10) bar_sync(7, PCNT);
    if (UAT == 4 && (warp == UW || warp == UW + 1)) upub();
    STAMP(3);
    WPOINT(1, warp - 6);
    kgen_cols(kg, tb, lane);
    if (LNAT == 3 && lnw) partial();
    if (FINAT == 3 && warp == 19) finish();
    if ((PAUSE & 2) && warp < 10) bar_sync(7, PCNT);
    if (UAT == 2 && (warp == UW || warp == UW + 1)) upub();
    STAMP(4);
    WPOINT(2, warp - 8);
    const uint4* usrc = wg < 4 ? reinterpret_cast<const uint4*>(p.s->st) + odd * 512 + (lane & 1) * 128 + 16 * (warp & 7) + (lane >> 1)
                               : reinterpret_cast<const uint4*>(p.s->uT) + P * 256 + 2 * t128;
    const int ustep = wg < 4 ? 256 : 1;
    uint4 uv0, uv1;
    kgen_mma(kg, tb, lane);
    if (UAT == 3 && (warp == UW || warp == UW + 1)) upub();
    STAMP(26);
    WPOINT(3, warp - 5);
    const uint32_t idn = 0x3210u + (warp >> 8);
    const uint4 lt7 = make_uint4(prmt_v(KW_T2 + ((lane >> 3) & 1) * KW_KH + (33 + (lane & 7)) * 16 - (lane & 16), 0u, idn), t * 288 + g * 8 + 8, (lane & 1) * 4096 + (lane >> 1) * 16,
                                 prmt_v(8u << ((lane >> 3) + (lane & 4)) >> (lane & 3), 0u, idn));
    asm volatile("barrier.cluster.wait.acquire.aligned;\n" ::: "memory");
    bar_sync(1 + wg, 128);
    uv0 = ld_poll(usrc); uv1 = ld_poll(usrc + ustep);
    kgen_combine(sb, warp, lane, kw, lt7.y);
    if (warp < 3 || warp > 6) bar_arrive(14, NWRK);
    CONV_PRE
    STAMP(5);
    WPOINT(4, warp - 7);
    if (wg < 4) {
        mbar_wait(bar_x);
        const bool far = warp < 8;
        const uint32_t xa = sb + SM_XC + (warp & 7) * 256 + (odd ^ far) * 8 + lt7.z;
        uint2 xv[4] = {lds64(xa), lds64(xa + 8192), lds64(xa + 2048), lds64(xa + 10240)};
        const uint32_t tag = ((ep & 0x7fffu) + 1u) << 16;
        int it = 0;
        while (true) {
            const bool bad = (((uv0.x ^ tag) | (uv0.z ^ tag)) | ((uv1.x ^ tag) | (uv1.z ^ tag))) >> 16;
            if (!__any_sync(0xffffffffu, bad)) break;
            if (++it > SPIN_LIMIT) TRAP();
            if (bad) { uv0 = ld_poll(usrc); uv1 = ld_poll(usrc + 256); }
        }
        STAMP(6);
        DBG(wg, it);
        const uint2 st[4] = {make_uint2(uv0.x, uv0.y), make_uint2(uv0.z, uv0.w), make_uint2(uv1.x, uv1.y), make_uint2(uv1.z, uv1.w)};
#pragma unroll
        for (int i = 0; i < 4; i++) {
            xv[i].x = ln_apply(xv[i].x, st[i]);
            xv[i].y = ln_apply(xv[i].y, st[i]);
        }
        const uint32_t ub = sb + SM_U + UPAD * 16 + odd * ULO_B + (warp & 7) * 256 + lane * 8;
        const uint32_t w[4][2] = {{pack_f16(bf_lo(xv[0].x), bf_lo(xv[1].x)), pack_f16(bf_lo(xv[2].x), bf_lo(xv[3].x))}, {HI2(xv[0].x, xv[1].x), HI2(xv[2].x, xv[3].x)},
                                  {pack_f16(bf_lo(xv[0].y), bf_lo(xv[1].y)), pack_f16(bf_lo(xv[2].y), bf_lo(xv[3].y))}, {HI2(xv[0].y, xv[1].y), HI2(xv[2].y, xv[3].y)}};
#pragma unroll
        for (int i = 0; i < 4; i++) {
            if (far) asm volatile("st.async.shared::cluster.mbarrier::complete_tx::bytes.v2.b32 [%0], {%1,%2}, [%3];\n" ::"r"((ub ^ 0x1000000u) + i * USLOT_B), "r"(w[i][0]), "r"(w[i][1]), "r"(bar_r ^ 0x1000000u) : "memory");
            else sts64(ub + i * USLOT_B, w[i][0], w[i][1]);
        }
    } else {
        const uint32_t utag = ((ep & 3u) + 1u) * 0x10001u;
        int it = 0;
        while (true) {
            const bool bad = (((uv0.x ^ utag) | (uv0.y ^ utag) | (uv0.z ^ utag) | (uv0.w ^ utag)) | ((uv1.x ^ utag) | (uv1.y ^ utag) | (uv1.z ^ utag) | (uv1.w ^ utag))) & 0x70007u;
            if (!__any_sync(0xffffffffu, bad)) break;
            if (++it > SPIN_LIMIT) TRAP();
            if (bad) { uv0 = ld_poll(usrc); uv1 = ld_poll(usrc + 1); }
        }
        STAMP(6);
        DBG(4, it);
        const uint32_t ub = sb + SM_U + UPAD * 16 + 4 * USLOT_B + (t128 >> 1) * 32 + (t128 & 1) * 8;
        sts64(ub, prmt(uv0.x, uv0.z, 0x5410u) ^ utag, prmt(uv1.x, uv1.z, 0x5410u) ^ utag);
        sts64(ub + 16, prmt(uv0.x, uv0.z, 0x7632u) ^ utag, prmt(uv1.x, uv1.z, 0x7632u) ^ utag);
        sts64(ub + ULO_B, prmt(uv0.y, uv0.w, 0x5410u) ^ utag, prmt(uv1.y, uv1.w, 0x5410u) ^ utag);
        sts64(ub + ULO_B + 16, prmt(uv0.y, uv0.w, 0x7632u) ^ utag, prmt(uv1.y, uv1.w, 0x7632u) ^ utag);
    }
    if (warp < 3 && elect_one()) tma_st_3d(warp < 2 ? &tm_y : &tm_z, sb + SM_ZERO, warp < 2 ? 128 * b : 32 * (512 + P), 0, 2 * (warp < 2 ? warp : odd));
    if (warp >= 3 && warp <= 6) {
        bar_sync(14, NWRK);
        WPOINT(5, warp - 3);
    }
    bar_sync(1 + wg, 128);
    CONV_PRE2
    mbar_wait(bar_r);
    fence_async();
    bar_sync(0, NWRK);
    STAMP(7);
    uint32_t hv0 = 0;
    {
        WPOINT(6, 19 - warp);
        CONV_BODY
        WPOINT(7, 19 - warp);
        if (!B2L) bar_sync(0, NWRK); else if (wg != 3) bar_arrive(0, NWRK);
        STAMP(8);
        size_t ycopy = 0;
        auto hook = [&](auto gi) {
                     constexpr int G = decltype(gi)::value;
                     if (G == 4 && warp == HINTW) hv0 = ld_poll32(p.s->hint + (lane_v() & 7) * 32);
                     if (G == 4) mbar_wait(bar_h);
                     if (G == 1 || G == 2) WPOINT(7 + G, warp - 16);
                     if (G == 3) { WPOINT(10, warp - 12); WPOINT(12, warp - 8); WPOINT(14, warp - 4); }
                     if (G == 5) { WPOINT(11, warp - 13); WPOINT(13, warp - 9); WPOINT(15, warp - 5); }
                     if (G == 1 && warp >= 17 && elect_one())
                         bulk_s2g(warp == 17 ? p.s->part + b * (PBYTES / 4) : warp == 18 ? p.s->rows + b * 1152 : p.s->sc + b * 32, sb + SM_ZERO, warp == 17 ? PBYTES : warp == 18 ? 4608 : 32);
                     if (G == 4 && warp >= 17 && elect_one()) {
                         asm volatile("cp.async.bulk.wait_group 0;\n" ::: "memory");
                         hint_arrive(p.s->hint, 2, b & 7);
                     }
                     if (G == 1 && warp < 3) {
                         if (elect_one()) {
                             asm volatile("cp.async.bulk.wait_group 0;\n" ::: "memory");
                             mbar_arrive(bar_h);
                             hint_arrive(p.s->hint, 0, b & 7);
                         }
                         __syncwarp();
                         STAMP(17);
                     }
                 };
        conv_main(c, acc, sb, sel, reinterpret_cast<unsigned char*>(p.s->y), warp, ycopy, hook);
        STAMP(10);
    }
    {
    const int warp = warp_v(), lane = lane_v(), tid = 32 * warp + lane, g = lane >> 2, t = lane & 3;
    if (warp == HINTW) {
        const uint32_t target = (lds32(s_cnt + 4) + 1u) * 48u;
        if (__any_sync(0xffffffffu, (int)(hv0 - target) < 0)) hint_wait(p.s->hint, 0, target);
    }
    const unsigned char* ys = reinterpret_cast<const unsigned char*>(p.s->y) + ((size_t)P * DM + 32 * warp + 8 * (g >> 1) + (g & 1)) * 64 + odd * 32 + t * 8;
    STAMP(27);
    bar_sync(0, NWRK);
    STAMP(11);
    const uint32_t zr = warp >> 8;
    auto late_rows = [&](auto pub) {
        const uint32_t k = lds32(s_key + (lane & 7) * 4), ep = lds32(s_cnt + 4);
        const bool late = k & 256u, mine = late && ((k & 255u) >> 1) == (uint32_t)b;
        uint32_t todo = __ballot_sync(0xffffffffu, mine) & 0xffu;
        if (todo) {
#pragma unroll 1
            while (todo) {
                const int s = __ffs(todo) - 1, row = (__shfl_sync(0xffffffffu, k, s) >> 9) & 15;
                todo &= todo - 1;
                if ((row & 7) == g) pub(row & 8, 2 * NCTA + s);
            }
            __threadfence();
            bar_sync(0, NWRK);
            if (tid < NSEL && mine) *reinterpret_cast<volatile unsigned*>(p.s->flag + tid) = ep + 1u;
        }
        int it = 0;
        while (__any_sync(0xffffffffu, late && ld_poll32(p.s->flag + (lane & 7)) != ep + 1u)) { if (++it > SPIN_LIMIT) TRAP(); }
        __threadfence();
        const int gs = tid / 36;
        const uint4* src = reinterpret_cast<const uint4*>(p.s->rows) + __shfl_sync(0xffffffffu, late ? 2 * NCTA + (lane & 7) : (k & 255u), gs & 7) * 144 + 36 * odd + (tid - gs * 36);
        if (tid < 288) {
            uint4 v0;
            do { v0 = ld_poll(src); if (++it > SPIN_LIMIT) TRAP(); } while (!v0.x);
            sts128(sb + SM_XS + gs * XS_PITCH + (tid - gs * 36) * 16, v0.x, v0.y, v0.z, v0.w);
        }
        bar_sync(0, NWRK);
    };
    if (warp >= 18) {
        if (warp == 18) {
            uint32_t* const kp = pin(p.s->sc + 32 * b, zr);
            const uint32_t kid = pin(0x30000000u | ((lane & 15) << 9) | 2 * b, zr), ka = pin(s_k16 + (lane & 15) * 4, zr), kb = pin(s_k16 + (lane & 16) * 2, zr);
            bar_sync(8, 640);
            float mb, rc;
            ln_finish<18>(sb + SM_LNP, lane, mb, rc);
            if (lane < 16) stat_store(s_stat + lane * 8, mb, rc, 0u);
            bar_arrive(13, 608);
            bar_sync(10, 608);
            const float r = sum18(sb + SM_LNP + (32 + (lane & 15)) * 80);
            const uint32_t bits = pack_bf16(0.f, r);
            const uint32_t me = (((bits ^ ((uint32_t)((int)bits >> 31) & 0x7fffffffu)) >> 3) & 0x1fffe000u) ^ kid;
            sts32(ka, me);
            __syncwarp();
            const uint4 v = lds128(kb), w = lds128(kb + 16);
#define GT(x) ((me - (x)) >> 31)
            uint32_t rank = pin(GT(v.x) + GT(v.y) + GT(v.z), zr) + pin(GT(v.w) + GT(w.x) + GT(w.y), zr) + pin(GT(w.z) + GT(w.w), zr);
#undef GT
            rank += __shfl_xor_sync(0xffffffffu, rank, 16);
            if (lane < 16) { if (rank < 8) stg32(kp + rank, me + (rank < 2 ? rank : 256u)); }
            else sts32(ka + (s_wm - s_k16), rank);
            bar_arrive(11, 640);
            weight_units<19, 0>(sb, wm, 0); weight_units<19, 1>(sb, wm, 1);
        }
        const uint4* ksrc = pin(reinterpret_cast<const uint4*>(p.s->sc) + 8 * lane, zr);
        const uint4* rsrc = pin(reinterpret_cast<const uint4*>(p.s->rows) + 36 * odd + t, zr);
        if (warp == 19) {
            weight_units<20, 0>(sb, wm, 0); weight_units<20, 1>(sb, wm, 1);
            bar_sync(8, 640);
            weight_units<16, 0>(sb, wm, 0); weight_units<16, 1>(sb, wm, 1);
            hint_wait(p.s->hint, 2, (lds32(s_cnt + 4) + 1u) * 48u);
            bar_sync(11, 640);
        }
        bool slow = false;
        int it = 0;
        if (warp == 19) {
        uint4 q[4];
        DELAY(KDEL);
#pragma unroll
        for (int i = 0; i < 4; i++) q[i] = ld_poll(ksrc + 256 * i);
        while (true) {
            uint32_t a[4];
#pragma unroll
            for (int i = 0; i < 4; i++) a[i] = q[i].x & q[i].y & q[i].z & q[i].w;
            if (__all_sync(0xffffffffu, a[0] & a[1] & a[2] & a[3])) break;
#pragma unroll
            for (int i = 0; i < 4; i++)
                if (!a[i]) q[i] = ld_poll(ksrc + 256 * i);
            if (++it > SPIN_LIMIT) TRAP();
        }
        bar_arrive(9, 608);
        STAMP(16);
        auto merge = [](const uint4& x, const uint4& y) {
            const uint32_t a = max(x.x, y.w), c = max(x.y, y.z), d = max(x.z, y.y), e = max(x.w, y.x);
            const uint32_t a2 = max(a, d), d2 = min(a, d), c2 = max(c, e), e2 = min(c, e);
            return make_uint4(max(a2, c2), min(a2, c2), max(d2, e2), min(d2, e2));
        };
        uint4 h = merge(merge(q[0], q[1]), merge(q[2], q[3]));
        uint4 v[9];
        uint32_t key = 0;
#pragma unroll
        for (int s = 0; s < 8; s++) {
            const uint32_t m = __reduce_max_sync(0xffffffffu, h.x);
            const bool w = h.x == m;
            h.x = w ? h.y : h.x; h.y = w ? h.z : h.y; h.z = w ? h.w : h.z; h.w = w ? 0u : h.w;
            if (g == s) key = m;
        }
        rsrc += (key & 255u) * 144;
#pragma unroll
        for (int j = 0; j < 9; j++) v[j] = ld_poll(rsrc + 4 * j);
        slow = __any_sync(0xffffffffu, key & 256u);
        STAMP(18);
        if (__any_sync(0xffffffffu, h.x == 0u)) {
            uint4 r[4];
            it = 0;
            while (true) {
#pragma unroll
                for (int i = 0; i < 4; i++) r[i] = ld_poll(ksrc + 256 * i + 1);
                if (__all_sync(0xffffffffu, all_nz(r[0]) && all_nz(r[1]) && all_nz(r[2]) && all_nz(r[3]))) break;
                if (++it > SPIN_LIMIT) TRAP();
            }
            uint32_t m = 1u << 30;
#pragma unroll 1
            for (int s = 0; s < 8; s++) {
                uint32_t x = 0;
#pragma unroll
                for (int i = 0; i < 4; i++) {
                    x = max(max(max(x, q[i].x - m), max(q[i].y - m, q[i].z - m)), q[i].w - m);
                    x = max(max(max(x, r[i].x - m), max(r[i].y - m, r[i].z - m)), r[i].w - m);
                }
                m += __reduce_max_sync(0xffffffffu, x);
                if (g == s) key = m;
            }
            slow = true;
        }
        const uint32_t xsa = sb + SM_XS + g * XS_PITCH + t * 16;
        sts32(s_key + g * 4, key);
        sts32(xsa, 0u);
        bar_arrive(12, 608);
#pragma unroll
        for (int j = 0; j < 9; j++) sts128(xsa + j * 64, v[j].x, v[j].y, v[j].z, v[j].w);
        slow = slow || min(min(min(min(v[0].x, v[1].x), v[2].x), min(min(v[3].x, v[4].x), v[5].x)), min(min(v[6].x, v[7].x), v[8].x)) == 0u;
        }
        if (bar_or(0, NWRK, slow)) late_rows([](bool, int) {});
        STAMP(19);
        const int fl = 16 * (b & 1) + ((tid >> 2) & 15), fc = 16 * (b >> 1) + (fl >> 2) + 8 * ((tid >> 1) & 1), fsl = 2 * (fl & 3) + (tid & 1);
        const uint32_t kk = lds32(s_key + fsl * 4);
        const uint32_t* fsrc = p.s->rows + ((kk & 256u) ? 2 * NCTA + fsl : (kk & 255u)) * DM + (fc >> 1);
        uint32_t hw = 1u, uw = 1u;
        if (b < 72) { uw = ld_poll32(fsrc); hw = ld_poll32(fsrc + 288); }
        if (b < 72) {
            it = 0;
            while (!hw || !uw) { uw = ld_poll32(fsrc); hw = ld_poll32(fsrc + 288); if (++it > SPIN_LIMIT) TRAP(); }
            const int row = (kk >> 9) & 15, ftok = 8 * (kk & 252u) + (kk & 2u) + TOKEN_OF(row & 7) + (row & 8);
            const unsigned k16 = (kk >> 13) & 0xffffu;
            const unsigned bits = (k16 & 0x8000u) ? (k16 & 0x7fffu) : (~k16 & 0xffffu);
            const float rs = 512.0f * rbf(__fdividef(1.0f, 1.0f + __expf(-__uint_as_float(bits << 16))));
            bf16* const op = p.out + (unsigned)(ftok * DM + fc);
            const float uv = (fc & 1) ? bf_hi(uw) : bf_lo(uw), hv = (fc & 1) ? bf_hi(hw) : bf_lo(hw);
            const uint32_t a = sb + SM_FIN + (tid - 576) * 80;
            sts128(a + 64, __float_as_uint(rs), __float_as_uint(uv), __float_as_uint(hv), (uint32_t)(size_t)op ^ (uint32_t)((size_t)op >> 32));
            bar_sync(14, 576);
            const uint4 p0 = lds128(a), p1 = lds128(a + 16), p2 = lds128(a + 32), p3 = lds128(a + 48);
#define F4(p) ((__uint_as_float(p.x) + __uint_as_float(p.y)) + (__uint_as_float(p.z) + __uint_as_float(p.w)))
            const float v0 = F4(p0), v1 = F4(p1), v2 = F4(p2), v3 = F4(p3);
#undef F4
            const float y3 = rbf(rbf((v0 + v1) + (v2 + v3)) * rs);
            asm volatile("st.global.u16 [%0], %1;\n" ::"l"(op), "h"((unsigned short)pack_bf16(hv + rbf(uv + y3), 0.f)) : "memory");
        }
        if (b == 0 && tid >= 632) *reinterpret_cast<volatile unsigned*>(p.s->hint + (tid & 7) * 32 + 1) = lds32(s_cnt + 4) + 1u;
    } else {
        uint32_t H[2][4], U2[2][4], WA[9][4], WD[18], WE[18];
        const int fkh = warp >= 9, fmt = warp - 9 * fkh;
        auto load_wa = [&](auto k0, auto k1) {
            if (k0.value >= k1.value) return;
            if (k0.value == 0) mbar_wait(bar_w);
            const int mi = lane >> 3, rr = lane & 7;
            const int row = fkh * 144 + rr + 8 * (mi >> 1);
            const uint32_t aad = sb + (fmt < 8 ? SM_WG + (mi & 1) * (SM_WU - SM_WG) + row * 128 + (fmt ^ rr) * 16 : SM_WR + (mi & 1) * 4608 + row * 16), ks = fmt < 8 ? 2048 : 256;
#pragma unroll
            for (int k = k0.value; k < k1.value; k++) ldsm_x4_t(WA[k][0], WA[k][1], WA[k][2], WA[k][3], aad + k * ks);
        };
        auto load_wd = [&](uint32_t (&WD)[18], int tile) {
            mbar_wait(bar_d);
            if (tile & 16) mbar_wait(bar_d + 16);
            const int mi = lane >> 3, rr = lane & 7;
            const uint32_t base = sb + SM_WD + rr * 128 + (((2 * tile + (mi & 1)) & 7) ^ rr) * 16;
#pragma unroll
            for (int k = 0; k < 4; k++) ldsm_x4_t(WD[4 * k], WD[4 * k + 1], WD[4 * k + 2], WD[4 * k + 3], base + (tile >> 2) * 8192 + (k * 16 + 8 * (mi >> 1)) * 128);
            ldsm_x2_t(WD[16], WD[17], base + 40960 + (tile >> 2) * 1024);
        };
        auto publish = [&](bool hi, int slot) {
            uint4* rowp = reinterpret_cast<uint4*>(p.s->rows) + slot * 144 + warp * 4 + t;
            stg128(rowp, nzw(hi ? U2[1][0] : U2[0][0]), nzw(hi ? U2[1][1] : U2[0][1]), nzw(hi ? U2[1][2] : U2[0][2]), nzw(hi ? U2[1][3] : U2[0][3]));
            stg128(rowp + 72, nzw(hi ? H[1][0] : H[0][0]), nzw(hi ? H[1][1] : H[0][1]), nzw(hi ? H[1][2] : H[0][2]), nzw(hi ? H[1][3] : H[0][3]));
        };
        uint4 wr = make_uint4(0x3f803f80u, 0x3f803f80u, 0x3f803f80u, 0x3f803f80u);
        {
            uint2 yv[4];
#pragma unroll
            for (int k = 0; k < 4; k++) yv[k] = ld_poll64(ys + k * 128);
            if (g == 0) wr = ldg128(p.wr + 32 * warp + 8 * t);
            const uint4 x0 = lds128(sb + SM_XT + warp * 1024 + lane * 16), x1 = lds128(sb + SM_XT + warp * 1024 + 512 + lane * 16);
            load_wa(IC<0>(), IC<WA0>());
            int it = 0;
            while (!__all_sync(0xffffffffu, yv[0].x && yv[1].x && yv[2].x && yv[3].x)) {
#pragma unroll
                for (int k = 0; k < 4; k++) yv[k] = ld_poll64(ys + k * 128);
                if (++it > SPIN_LIMIT) TRAP();
            }
            STAMP(12);
            const uint32_t Z[2][4] = {{x0.x, x0.y, x0.z, x0.w}, {x1.x, x1.y, x1.z, x1.w}};
#pragma unroll
            for (int k = 0; k < 4; k++) {
                H[0][k] = hadd2_bf(Z[0][k], movm(yv[k].x));
                H[1][k] = hadd2_bf(Z[1][k], movm(yv[k].y));
            }
            const uint32_t bw[4] = {wr.x, wr.y, wr.z, wr.w};
            ln_partial<4>(H, bw, sb + SM_LNP, warp, g, t);
        }
        bar_arrive(8, 640);
        load_wa(IC<WA0>(), IC<WA1>());
        STAMP(13);
        bar_sync(13, 608);
        STAMP(14);
#pragma unroll
        for (int hf = 0; hf < 2; hf++) {
            const uint2 st = lds64(s_stat + (g + 8 * hf) * 8);
#pragma unroll
            for (int k = 0; k < 4; k++) U2[hf][k] = ln_apply(H[hf][k], st);
        }
        {
            float cs[4] = {0.f, 0.f, 0.f, 0.f};
            mma_bf16(cs, U2[0][0], U2[1][0], U2[0][1], U2[1][1], wr.x, wr.y);
            mma_bf16(cs, U2[0][2], U2[1][2], U2[0][3], U2[1][3], wr.z, wr.w);
            if (t == 0) { stsf(sb + SM_LNP + ((32 + g) * 20 + warp) * 4, cs[0]); stsf(sb + SM_LNP + ((40 + g) * 20 + warp) * 4, cs[2]); }
            bar_arrive(10, 608);
        }
        load_wa(IC<WA1>(), IC<WA2>());
        bar_sync(11, 640);
        {
            const uint32_t rk[2] = {lds32(s_wm + g * 4), lds32(s_wm + 32 + g * 4)};
            uint32_t lo = min(rk[0], rk[1]), hi = max(rk[0], rk[1]);
#pragma unroll 1
            while (lo < 2) { publish(lo == rk[1], 2 * b + lo); lo = hi; hi = 16; }
        }
        load_wa(IC<WA2>(), IC<WA3>());
        bar_sync(9, 608);
        load_wa(IC<WA3>(), IC<9>());
#pragma unroll
        for (int hf = 0; hf < 2; hf++)
            sts128(sb + SM_OUT + (g + 8 * hf) * OUT_PITCH + warp * 64 + t * 16,
                   hadd2_bf(H[hf][0], U2[hf][0]), hadd2_bf(H[hf][1], U2[hf][1]), hadd2_bf(H[hf][2], U2[hf][2]), hadd2_bf(H[hf][3], U2[hf][3]));
        fence_async();
        WPOINT(17, warp - 16);
        if ((WDAT == 0 || (WDAT == 2 && fkh)) && (warp < 16 || !odd)) load_wd(WD, warp);
        const uint32_t bad = pin(sb + SM_XS + (lane & 7) * XS_PITCH + (fkh * 144 + 8 * (lane >> 3)) * 2, zr), ex = pin(sb + SM_EX + warp * 512 + lane * 16, zr);
        uint32_t* pp = pin(p.s->part + ((size_t)(2 * (20 * odd + warp) + (lane >> 4)) * 64 + P) * 32 + (lane & 15) * 2, zr);
        bar_sync(12, 608);
        if (warp < 16 && !__any_sync(0xffffffffu, (lds32(s_key + (lane & 7) * 4) & 0x1efeu) == (uint32_t)((warp << 9) | 2 * b)) && elect_one())
            bulk_s2g(p.out + (size_t)(32 * P + 2 * odd + TOKEN_OF(warp & 7) + (warp & 8)) * DM, sb + SM_OUT + warp * OUT_PITCH, DM * 2);
        WPOINT(18, warp - 16);
        STAMP(15);
        if (bar_or(0, NWRK, false)) late_rows(publish);
        STAMP(19);
        float gp[4];
        {
            float c4[3][4];
#pragma unroll
            for (int i = 0; i < 3; i++)
#pragma unroll
                for (int j = 0; j < 4; j++) c4[i][j] = 0.f;
#pragma unroll
            for (int k = 0; k < 10; k += 2) {
                uint32_t b0, b1, b2, b3;
                ldsm_x4(b0, b1, b2, b3, bad + k * 32);
                mma_bf16(c4[k % 3], WA[k][0], WA[k][1], WA[k][2], WA[k][3], b0, b1);
                if (k < 8) mma_bf16(c4[(k + 1) % 3], WA[k + 1][0], WA[k + 1][1], WA[k + 1][2], WA[k + 1][3], b2, b3);
            }
#pragma unroll
            for (int j = 0; j < 4; j++) gp[j] = c4[0][j] + (c4[1][j] + c4[2][j]);
            if (warp >= 9) {
                sts128f(ex, gp);
                bar_arrive(6, 576);
            } else {
                bar_sync(6, 576);
                const uint4 o = lds128(ex + 4608);
                gp[0] += __uint_as_float(o.x); gp[1] += __uint_as_float(o.y); gp[2] += __uint_as_float(o.z); gp[3] += __uint_as_float(o.w);
                asm volatile("st.async.shared::cluster.mbarrier::complete_tx::bytes.v4.b32 [%0], {%1,%2,%3,%4}, [%5];\n"
                             ::"r"(ex ^ 0x1000000u), "r"(__float_as_uint(gp[0])), "r"(__float_as_uint(gp[1])), "r"(__float_as_uint(gp[2])), "r"(__float_as_uint(gp[3])), "r"(bar_g ^ 0x1000000u) : "memory");
                if (WDAT == 2) load_wd(WD, warp);
            }
            if (WDAT == 1 && (warp < 16 || !odd)) load_wd(WD, warp);
            if (warp >= 16 && !odd) load_wd(WE, warp + 2);
        }
        STAMP(20);
        if (warp < 9) {
            mbar_wait(bar_g);
            const uint4 u = lds128(ex);
            const uint32_t G = pack_bf16(gp[0] + __uint_as_float(u.x), gp[1] + __uint_as_float(u.y)), U = pack_bf16(gp[2] + __uint_as_float(u.z), gp[3] + __uint_as_float(u.w));
            const float G0 = bf_lo(G), G1 = bf_hi(G);
            sts32(sb + SM_GU + tid * 4, hmul2_bf(pack_bf16(G0 * rcp_approx(1.0f + ex2_approx(G0 * -1.4426950408889634f)), G1 * rcp_approx(1.0f + ex2_approx(G1 * -1.4426950408889634f))), U));
        }
        bar_sync(7, 576);
        STAMP(21);
        if (warp < 16 || !odd) {
            uint32_t gb[9];
            ldsm_x4_t(gb[0], gb[1], gb[2], gb[3], sb + SM_GU + lane * 16);
            ldsm_x4_t(gb[4], gb[5], gb[6], gb[7], sb + SM_GU + 512 + lane * 16);
            ldsm_x1_t(gb[8], sb + SM_GU + 1024 + (lane & 7) * 16);
            auto down = [&](const uint32_t (&W)[18], uint32_t* dst) {
                float c4[4] = {0.f, 0.f, 0.f, 0.f}, d4[4] = {0.f, 0.f, 0.f, 0.f}, e4[4] = {0.f, 0.f, 0.f, 0.f};
                mma_bf16(c4, W[0], W[1], W[2], W[3], gb[0], gb[1]);
                mma_bf16(d4, W[4], W[5], W[6], W[7], gb[2], gb[3]);
                mma_bf16(e4, W[8], W[9], W[10], W[11], gb[4], gb[5]);
                mma_bf16_k8(c4, W[16], W[17], gb[8]);
                mma_bf16(d4, W[12], W[13], W[14], W[15], gb[6], gb[7]);
                const float v0 = (c4[0] + e4[0]) + d4[0], v1 = (c4[1] + e4[1]) + d4[1], v2 = (c4[2] + e4[2]) + d4[2], v3 = (c4[3] + e4[3]) + d4[3];
                const uint32_t e = max(max(__float_as_uint(fmaxf(fabsf(v0), fabsf(v1))), __float_as_uint(fmaxf(fabsf(v2), fabsf(v3)))), 16u << 23) >> 23;
                const float sc = __uint_as_float((245u - e) << 23);
                stg64(dst, pack_f16(v0 * sc, v1 * sc) | ((e * 0x8002000u) & 0x60006000u), pack_f16(v2 * sc, v3 * sc) | ((e * 0x800200u) & 0x60006000u));
            };
            if (warp >= 16) { down(WE, pp + 4 * 64 * 32); down(WD, pp); }
            else down(WD, pp);
        }
        asm volatile("cp.async.bulk.wait_group.read 0;\n" ::: "memory");
        STAMP(22);
        if (b < 72 && warp < 16) {
            const uint2* src = reinterpret_cast<const uint2*>(p.s->part) + (unsigned)(b * 1024 + tid);
            uint2 a, c;
            int it = 0;
            DELAY(PDEL);
            a = ld_poll64(src); c = ld_poll64(src + 512);
            while (!__all_sync(0xffffffffu, a.y && c.y)) {
                a = ld_poll64(src); c = ld_poll64(src + 512);
                if (++it > SPIN_LIMIT) TRAP();
            }
            STAMP(24);
            const float ea = __uint_as_float((((a.y & 0x60006000u) | ((a.x >> 4) & 0x06000600u)) * 0x4001u) & 0x7f800000u);
            const float ec = __uint_as_float((((c.y & 0x60006000u) | ((c.x >> 4) & 0x06000600u)) * 0x4001u) & 0x7f800000u);
            a.x &= 0x9fff9fffu; a.y &= 0x9fff9fffu; c.x &= 0x9fff9fffu; c.y &= 0x9fff9fffu;
            const float s0 = fmaf(h_lo(a.x), ea, h_lo(c.x) * ec), s1 = fmaf(h_hi(a.x), ea, h_hi(c.x) * ec), s2 = fmaf(h_lo(a.y), ea, h_lo(c.y) * ec), s3 = fmaf(h_hi(a.y), ea, h_hi(c.y) * ec);
            const bool up = lane & 16;
            const float r0 = __shfl_xor_sync(0xffffffffu, up ? s0 : s2, 16), r1 = __shfl_xor_sync(0xffffffffu, up ? s1 : s3, 16);
            const uint32_t fa = sb + SM_FIN + ((lane & 15) * 4 + (up ? 2 : 0)) * 80 + warp * 4;
            stsf(fa, (up ? s2 : s0) + r0); stsf(fa + 80, (up ? s3 : s1) + r1);
            bar_arrive(14, 576);
        }
    }
    STAMP(25);
    }
}

typedef CUresult (*PFN_tmEncode)(CUtensorMap*, CUtensorMapDataType, cuuint32_t, void*, const cuuint64_t*, const cuuint64_t*, const cuuint32_t*,
                                 const cuuint32_t*, CUtensorMapInterleave, CUtensorMapSwizzle, CUtensorMapL2promotion, CUtensorMapFloatOOBfill);

extern "C" void kernel_launch(void* const* d_in, const int* in_sizes, int n_in, void* d_out, int out_size) {
    Params p;
    p.x = (const bf16*)d_in[0];
    p.lar = (const bf16*)d_in[1];
    p.aim = (const bf16*)d_in[2];
    p.cre = (const bf16*)d_in[3];
    p.cim = (const bf16*)d_in[4];
    p.ldt = (const bf16*)d_in[5];
    p.dsk = (const bf16*)d_in[6];
    p.wr = (const bf16*)d_in[8];
    p.out = (bf16*)d_out;
    static PFN_tmEncode enc = nullptr;
    static void* scratch = nullptr;
    if (!enc) {
        cudaFuncSetAttribute(fused_kernel, cudaFuncAttributeMaxDynamicSharedMemorySize, SMEM_TOTAL);
        void* fn = nullptr;
        cudaDriverEntryPointQueryResult qr;
        cudaGetDriverEntryPoint("cuTensorMapEncodeTiled", &fn, cudaEnableDefault, &qr);
        enc = (PFN_tmEncode)fn;
        cudaGetSymbolAddress(&scratch, g_scratch);
    }
    p.s = (Scratch*)scratch;
    WMaps wm;
    CUtensorMap tm_x, tm_y, tm_z;
    const cuuint64_t dims[2] = {FF, DM}, strides[1] = {FF * 2}, rdims[3] = {FF, 144, 4}, rstrides[2] = {FF * 2, 144 * FF * 2};
    const cuuint32_t box[2] = {64, 72}, rbox[3] = {8, 144, 2}, es3[3] = {1, 1, 1};
    for (int i = 0; i < 2; i++) {
        enc(i ? &wm.u : &wm.g, CU_TENSOR_MAP_DATA_TYPE_BFLOAT16, 2, d_in[9 + i], dims, strides, box, es3, CU_TENSOR_MAP_INTERLEAVE_NONE, CU_TENSOR_MAP_SWIZZLE_128B,
            CU_TENSOR_MAP_L2_PROMOTION_NONE, CU_TENSOR_MAP_FLOAT_OOB_FILL_NONE);
        enc(i ? &wm.ur : &wm.gr, CU_TENSOR_MAP_DATA_TYPE_BFLOAT16, 3, d_in[9 + i], rdims, rstrides, rbox, es3, CU_TENSOR_MAP_INTERLEAVE_NONE, CU_TENSOR_MAP_SWIZZLE_NONE,
            CU_TENSOR_MAP_L2_PROMOTION_NONE, CU_TENSOR_MAP_FLOAT_OOB_FILL_NONE);
    }
    const cuuint64_t ddims[2] = {DM, FF}, dstrides[1] = {DM * 2}, edims[3] = {64, FF, 9}, estrides[2] = {DM * 2, 128};
    const cuuint32_t dbox[2] = {64, 64}, ebox[3] = {64, 8, 5};
    enc(&wm.d, CU_TENSOR_MAP_DATA_TYPE_BFLOAT16, 2, d_in[11], ddims, dstrides, dbox, es3, CU_TENSOR_MAP_INTERLEAVE_NONE, CU_TENSOR_MAP_SWIZZLE_128B,
        CU_TENSOR_MAP_L2_PROMOTION_NONE, CU_TENSOR_MAP_FLOAT_OOB_FILL_NONE);
    enc(&wm.dr, CU_TENSOR_MAP_DATA_TYPE_BFLOAT16, 3, d_in[11], edims, estrides, ebox, es3, CU_TENSOR_MAP_INTERLEAVE_NONE, CU_TENSOR_MAP_SWIZZLE_128B,
        CU_TENSOR_MAP_L2_PROMOTION_NONE, CU_TENSOR_MAP_FLOAT_OOB_FILL_NONE);
    const cuuint64_t xdims[3] = {DM, LSEQ / 16, 16}, xstrides[2] = {16 * DM * 2, DM * 2};
    const cuuint32_t xbox[3] = {8, LSEQ / 16, 8};
    enc(&tm_x, CU_TENSOR_MAP_DATA_TYPE_BFLOAT16, 3, d_in[0], xdims, xstrides, xbox, es3, CU_TENSOR_MAP_INTERLEAVE_NONE, CU_TENSOR_MAP_SWIZZLE_NONE,
        CU_TENSOR_MAP_L2_PROMOTION_NONE, CU_TENSOR_MAP_FLOAT_OOB_FILL_NONE);
    const cuuint64_t ydims[3] = {DM * 32, 16, 4}, ystrides[2] = {DM * 64, 16 * DM * 64};
    const cuuint32_t ybox[3] = {128, 16, 2}, zbox[3] = {32, 16, 2};
    enc(&tm_y, CU_TENSOR_MAP_DATA_TYPE_BFLOAT16, 3, p.s->y, ydims, ystrides, ybox, es3, CU_TENSOR_MAP_INTERLEAVE_NONE, CU_TENSOR_MAP_SWIZZLE_NONE,
        CU_TENSOR_MAP_L2_PROMOTION_NONE, CU_TENSOR_MAP_FLOAT_OOB_FILL_NONE);
    enc(&tm_z, CU_TENSOR_MAP_DATA_TYPE_BFLOAT16, 3, p.s->y, ydims, ystrides, zbox, es3, CU_TENSOR_MAP_INTERLEAVE_NONE, CU_TENSOR_MAP_SWIZZLE_NONE,
        CU_TENSOR_MAP_L2_PROMOTION_NONE, CU_TENSOR_MAP_FLOAT_OOB_FILL_NONE);
    fused_kernel<<<NCTA, NTHR, SMEM_TOTAL>>>(p, wm, tm_x, tm_y, tm_z);
}
```

```cpp
#include <cuda_runtime.h>
#include <cuda.h>
#include <cuda_fp16.h>
#include <cuda_bf16.h>
#include <stdint.h>

#define LSEQ 2048
#define DM 576
#define NST 128
#define FF 4608
#define NSEL 8
#define NCTA 128
#define NTHR 640
#define NWRK 640

typedef __nv_bfloat16 bf16;

#define SM_WD 0
#define SM_WG 46080
#define SM_WR 82944
#define SM_WU 92160
#define SM_ZERO 32768
#define SM_XC 16384
#define SM_TB 96000
#define SM_PL 129024
#define PL_B 10752
#define SM_XT (SM_TB + 20 * TBW)
#define SM_U (SM_XT + 18432)
#define UPAD 8
#define ULO_B ((UPAD + 128) * 16)
#define USLOT_B (2 * ULO_B)
#define SM_KW (SM_U + 5 * USLOT_B)
#define KW_B 3600
#define KW_T2 1152
#define KW_KH 656
#define KW_T3 2464
#define SM_MISC (SM_KW + 5 * KW_B)
#define SM_LNP (SM_MISC + 576)
#define SMEM_TOTAL (SM_LNP + 3840)
#define TBP 112
#define TBW (32 * TBP)
#define SM_OUT SM_PL
#define OUT_PITCH 1216
#define SM_XS (SM_PL + 19456)
#define XS_PITCH 592
#define SM_EX (SM_PL + 24320)
#define SM_FIN SM_KW
#define SM_GU (SM_PL + 33536)

struct __align__(128) Scratch {
    unsigned hint[8 * 32];
    unsigned flag[32];
    uint32_t sc[NCTA * 32];
    uint32_t st[LSEQ * 2];
    uint32_t uT[64 * (LSEQ / 2)];
    uint32_t y[NCTA * DM * 8];
    uint32_t part[72 * 64 * 32];
    uint32_t rows[(2 * NCTA + NSEL) * DM];
};
__device__ Scratch g_scratch;
#define STAMP(i)
#define DBG(i, v)

__device__ __forceinline__ float rbf(float x) {
    uint32_t r;
    asm("cvt.rn.bf16x2.f32 %0, %1, %2;\n" : "=r"(r) : "f"(x), "f"(0.f));
    return __uint_as_float(r & 0xffff0000u);
}
__device__ __forceinline__ uint32_t pack_bf16(float lo, float hi) {
    uint32_t r;
    asm("cvt.rn.bf16x2.f32 %0, %1, %2;\n" : "=r"(r) : "f"(hi), "f"(lo));
    return r;
}
__device__ __forceinline__ uint32_t pack_f16(float lo, float hi) {
    uint32_t r;
    asm("cvt.rn.f16x2.f32 %0, %1, %2;\n" : "=r"(r) : "f"(hi), "f"(lo));
    return r;
}
__device__ __forceinline__ uint32_t pack_f16_rz(float lo, float hi) {
    uint32_t r;
    asm("cvt.rz.f16x2.f32 %0, %1, %2;\n" : "=r"(r) : "f"(hi), "f"(lo));
    return r;
}
__device__ __forceinline__ float bf_lo(uint32_t w) { return __uint_as_float(w << 16); }
__device__ __forceinline__ float bf_hi(uint32_t w) { return __uint_as_float(w & 0xffff0000u); }
__device__ __forceinline__ uint32_t hadd2_bf(uint32_t a, uint32_t b) {
    __nv_bfloat162 r = __hadd2_rn(*reinterpret_cast<__nv_bfloat162*>(&a), *reinterpret_cast<__nv_bfloat162*>(&b));
    return *reinterpret_cast<uint32_t*>(&r);
}
__device__ __forceinline__ uint32_t hmul2_bf(uint32_t a, uint32_t b) {
    __nv_bfloat162 r = __hmul2_rn(*reinterpret_cast<__nv_bfloat162*>(&a), *reinterpret_cast<__nv_bfloat162*>(&b));
    return *reinterpret_cast<uint32_t*>(&r);
}
__device__ __forceinline__ uint32_t hfma2_bf(uint32_t a, uint32_t b, uint32_t c) { uint32_t r; asm("fma.rn.bf16x2 %0, %1, %2, %3;\n" : "=r"(r) : "r"(a), "r"(b), "r"(c)); return r; }
__device__ __forceinline__ uint32_t hmul2(uint32_t a, uint32_t b) { uint32_t r; asm("mul.rn.f16x2 %0, %1, %2;\n" : "=r"(r) : "r"(a), "r"(b)); return r; }
__device__ __forceinline__ uint32_t hadd2(uint32_t a, uint32_t b) { uint32_t r; asm("add.rn.f16x2 %0, %1, %2;\n" : "=r"(r) : "r"(a), "r"(b)); return r; }
__device__ __forceinline__ uint32_t nzw(uint32_t w) { return w ? w : 0x8000u; }
__device__ __forceinline__ uint32_t smem_u32(const void* p) { return (uint32_t)__cvta_generic_to_shared(p); }
__device__ __forceinline__ uint32_t lds32(uint32_t addr) {
    uint32_t v;
    asm volatile("ld.shared.u32 %0, [%1];\n" : "=r"(v) : "r"(addr) : "memory");
    return v;
}
__device__ __forceinline__ uint2 lds64(uint32_t addr) {
    uint2 v;
    asm volatile("ld.shared.v2.u32 {%0,%1}, [%2];\n" : "=r"(v.x), "=r"(v.y) : "r"(addr) : "memory");
    return v;
}
__device__ __forceinline__ uint4 lds128(uint32_t addr) {
    uint4 v;
    asm volatile("ld.shared.v4.u32 {%0,%1,%2,%3}, [%4];\n" : "=r"(v.x), "=r"(v.y), "=r"(v.z), "=r"(v.w) : "r"(addr) : "memory");
    return v;
}
__device__ __forceinline__ float ldsf(uint32_t addr) { return __uint_as_float(lds32(addr)); }
__device__ __forceinline__ void sts32(uint32_t addr, uint32_t v) { asm volatile("st.shared.u32 [%0], %1;\n" ::"r"(addr), "r"(v) : "memory"); }
__device__ __forceinline__ void stsf(uint32_t addr, float v) { sts32(addr, __float_as_uint(v)); }
__device__ __forceinline__ void sts64(uint32_t addr, uint32_t a, uint32_t b) { asm volatile("st.shared.v2.u32 [%0], {%1,%2};\n" ::"r"(addr), "r"(a), "r"(b) : "memory"); }
__device__ __forceinline__ void sts128(uint32_t addr, uint32_t a, uint32_t b, uint32_t c, uint32_t d) {
    asm volatile("st.shared.v4.u32 [%0], {%1,%2,%3,%4};\n" ::"r"(addr), "r"(a), "r"(b), "r"(c), "r"(d) : "memory");
}
__device__ __forceinline__ void sts128f(uint32_t addr, const float (&v)[4]) {
    sts128(addr, __float_as_uint(v[0]), __float_as_uint(v[1]), __float_as_uint(v[2]), __float_as_uint(v[3]));
}
__device__ __forceinline__ void ldsm_x4(uint32_t& r0, uint32_t& r1, uint32_t& r2, uint32_t& r3, uint32_t addr) {
    asm volatile("ldmatrix.sync.aligned.m8n8.x4.shared.b16 {%0,%1,%2,%3}, [%4];\n"
                 : "=r"(r0), "=r"(r1), "=r"(r2), "=r"(r3) : "r"(addr) : "memory");
}
__device__ __forceinline__ void ldsm_x4_t(uint32_t& r0, uint32_t& r1, uint32_t& r2, uint32_t& r3, uint32_t addr) {
    asm volatile("ldmatrix.sync.aligned.m8n8.x4.trans.shared.b16 {%0,%1,%2,%3}, [%4];\n"
                 : "=r"(r0), "=r"(r1), "=r"(r2), "=r"(r3) : "r"(addr) : "memory");
}
__device__ __forceinline__ void ldsm_x2_t(uint32_t& r0, uint32_t& r1, uint32_t addr) {
    asm volatile("ldmatrix.sync.aligned.m8n8.x2.trans.shared.b16 {%0,%1}, [%2];\n" : "=r"(r0), "=r"(r1) : "r"(addr) : "memory");
}
__device__ __forceinline__ void ldsm_x1_t(uint32_t& r0, uint32_t addr) {
    asm volatile("ldmatrix.sync.aligned.m8n8.x1.trans.shared.b16 {%0}, [%1];\n" : "=r"(r0) : "r"(addr) : "memory");
}
__device__ __forceinline__ uint32_t movm(uint32_t a) {
    uint32_t d;
    asm volatile("movmatrix.sync.aligned.m8n8.trans.b16 %0, %1;\n" : "=r"(d) : "r"(a));
    return d;
}
__device__ __forceinline__ void mma_f16(float (&c)[4], uint32_t a0, uint32_t a1, uint32_t a2, uint32_t a3, uint32_t b0, uint32_t b1) {
    asm volatile(
        "mma.sync.aligned.m16n8k16.row.col.f32.f16.f16.f32 {%0,%1,%2,%3}, {%4,%5,%6,%7}, {%8,%9}, {%0,%1,%2,%3};\n"
        : "+f"(c[0]), "+f"(c[1]), "+f"(c[2]), "+f"(c[3])
        : "r"(a0), "r"(a1), "r"(a2), "r"(a3), "r"(b0), "r"(b1));
}
__device__ __forceinline__ void mma_bf16(float (&c)[4], uint32_t a0, uint32_t a1, uint32_t a2, uint32_t a3, uint32_t b0, uint32_t b1) {
    asm volatile(
        "mma.sync.aligned.m16n8k16.row.col.f32.bf16.bf16.f32 {%0,%1,%2,%3}, {%4,%5,%6,%7}, {%8,%9}, {%0,%1,%2,%3};\n"
        : "+f"(c[0]), "+f"(c[1]), "+f"(c[2]), "+f"(c[3])
        : "r"(a0), "r"(a1), "r"(a2), "r"(a3), "r"(b0), "r"(b1));
}
__device__ __forceinline__ void mma_bf16_k8(float (&c)[4], uint32_t a0, uint32_t a1, uint32_t b0) {
    asm volatile("mma.sync.aligned.m16n8k8.row.col.f32.bf16.bf16.f32 {%0,%1,%2,%3}, {%4,%5}, {%6}, {%0,%1,%2,%3};\n"
        : "+f"(c[0]), "+f"(c[1]), "+f"(c[2]), "+f"(c[3]) : "r"(a0), "r"(a1), "r"(b0));
}
__device__ __forceinline__ void bar_sync(int id, int n) { asm volatile("bar.sync %0, %1;\n" ::"r"(id), "r"(n) : "memory"); }
__device__ __forceinline__ void bar_arrive(int id, int n) { asm volatile("bar.arrive %0, %1;\n" ::"r"(id), "r"(n) : "memory"); }
__device__ __forceinline__ bool bar_or(int id, int n, bool v) {
    uint32_t r;
    asm volatile("{\n.reg .pred p, q;\nsetp.ne.u32 p, %3, 0;\nbar.red.or.pred q, %1, %2, p;\nselp.u32 %0, 1, 0, q;\n}\n" : "=r"(r) : "r"(id), "r"(n), "r"((uint32_t)v) : "memory");
    return r;
}
__device__ __forceinline__ uint4 ld_poll(const void* p) {
    uint4 v;
    asm volatile("ld.relaxed.gpu.global.v4.u32 {%0,%1,%2,%3}, [%4];\n" : "=r"(v.x), "=r"(v.y), "=r"(v.z), "=r"(v.w) : "l"(p) : "memory");
    return v;
}
template <class T> __device__ __forceinline__ T* pin(T* p, uint32_t z) {
    uint32_t lo, hi;
    asm volatile("mov.b64 {%0, %1}, %2;\n" : "=r"(lo), "=r"(hi) : "l"(p));
    asm volatile("xor.b32 %0, %0, %1;\n" : "+r"(lo) : "r"(z));
    asm volatile("xor.b32 %0, %0, %1;\n" : "+r"(hi) : "r"(z));
    asm volatile("mov.b64 %0, {%1, %2};\n" : "=l"(p) : "r"(lo), "r"(hi));
    return p;
}
__device__ __forceinline__ uint32_t pin(uint32_t a, uint32_t z) { asm volatile("xor.b32 %0, %0, %1;\n" : "+r"(a) : "r"(z)); return a; }
__device__ __forceinline__ uint2 ld_poll64(const void* p) {
    uint2 v;
    asm volatile("ld.relaxed.gpu.global.v2.u32 {%0,%1}, [%2];\n" : "=r"(v.x), "=r"(v.y) : "l"(p) : "memory");
    return v;
}
__device__ __forceinline__ uint32_t ld_poll32(const void* p) {
    uint32_t v;
    asm volatile("ld.relaxed.gpu.global.u32 %0, [%1];\n" : "=r"(v) : "l"(p) : "memory");
    return v;
}
__device__ __forceinline__ uint4 ldg128(const void* p) {
    uint4 v;
    asm volatile("ld.global.nc.v4.u32 {%0,%1,%2,%3}, [%4];\n" : "=r"(v.x), "=r"(v.y), "=r"(v.z), "=r"(v.w) : "l"(p));
    return v;
}
__device__ __forceinline__ uint2 ldg64(const void* p) {
    uint2 v;
    asm volatile("ld.global.nc.v2.u32 {%0,%1}, [%2];\n" : "=r"(v.x), "=r"(v.y) : "l"(p));
    return v;
}
__device__ __forceinline__ uint32_t ldg16(const void* p) {
    uint32_t v;
    asm volatile("ld.global.nc.u16 %0, [%1];\n" : "=r"(v) : "l"(p));
    return v;
}
__device__ __forceinline__ void stg128(void* p, uint32_t a, uint32_t b, uint32_t c, uint32_t d) {
    asm volatile("st.global.v4.u32 [%0], {%1,%2,%3,%4};\n" ::"l"(p), "r"(a), "r"(b), "r"(c), "r"(d) : "memory");
}
__device__ __forceinline__ void stg64(void* p, uint32_t a, uint32_t b) { asm volatile("st.global.v2.u32 [%0], {%1,%2};\n" ::"l"(p), "r"(a), "r"(b) : "memory"); }
__device__ __forceinline__ void stg32(void* p, uint32_t a) { asm volatile("st.global.u32 [%0], %1;\n" ::"l"(p), "r"(a) : "memory"); }
__device__ __forceinline__ bool all_nz(const uint4& v) { return v.x && v.y && v.z && v.w; }
#define SPIN_LIMIT (1 << 21)
#define TRAP() __trap()
__device__ __forceinline__ void hint_arrive(unsigned* g_hint, int idx, int sub) {
    asm volatile("red.relaxed.gpu.global.add.u32 [%0], 1;\n" ::"l"(&g_hint[sub * 32 + idx]) : "memory");
}
__device__ __forceinline__ void hint_wait(const unsigned* g_hint, int idx, unsigned target) {
    unsigned l;
    asm volatile("mov.u32 %0, %%laneid;" : "=r"(l));
    const unsigned* c = &g_hint[(l & 7) * 32 + idx];
    int it = 0;
    while (__any_sync(0xffffffffu, (int)(ld_poll32(c) - target) < 0)) { if (++it > SPIN_LIMIT) TRAP(); }
}
__device__ __forceinline__ void mbar_init(uint32_t bar, uint32_t cnt) { asm volatile("mbarrier.init.shared::cta.b64 [%0], %1;\n" ::"r"(bar), "r"(cnt) : "memory"); }
__device__ __forceinline__ void mbar_expect(uint32_t bar, uint32_t bytes) {
    asm volatile("mbarrier.arrive.expect_tx.shared::cta.b64 _, [%0], %1;\n" ::"r"(bar), "r"(bytes) : "memory");
}
__device__ __forceinline__ void mbar_arrive(uint32_t bar) { asm volatile("mbarrier.arrive.shared::cta.b64 _, [%0];\n" ::"r"(bar) : "memory"); }
__device__ __forceinline__ void mbar_wait(uint32_t bar) {
    asm volatile(
        "{\n.reg .pred p;\n"
        "W_%=:\n"
        "mbarrier.try_wait.parity.shared::cta.b64 p, [%0], 0;\n"
        "@!p bra W_%=;\n}\n" ::"r"(bar) : "memory");
}
__device__ __forceinline__ void bulk_s2g(void* dst, uint32_t src, uint32_t bytes) {
    asm volatile("cp.async.bulk.global.shared::cta.bulk_group [%0], [%1], %2;\ncp.async.bulk.commit_group;\n" ::"l"(dst), "r"(src), "r"(bytes) : "memory");
}
__device__ __forceinline__ void tma_2d(uint32_t dst, const CUtensorMap* tm, int c0, int c1, uint32_t bar) {
    asm volatile("cp.async.bulk.tensor.2d.shared::cluster.global.mbarrier::complete_tx::bytes [%0], [%1, {%3, %4}], [%2];\n"
                 ::"r"(dst), "l"(tm), "r"(bar), "r"(c0), "r"(c1) : "memory");
}
__device__ __forceinline__ void tma_3d(uint32_t dst, const CUtensorMap* tm, int c0, int c1, int c2, uint32_t bar) {
    asm volatile("cp.async.bulk.tensor.3d.shared::cluster.global.mbarrier::complete_tx::bytes [%0], [%1, {%3, %4, %5}], [%2];\n"
                 ::"r"(dst), "l"(tm), "r"(bar), "r"(c0), "r"(c1), "r"(c2) : "memory");
}
__device__ __forceinline__ void tma_st_3d(const CUtensorMap* tm, uint32_t src, int c0, int c1, int c2) {
    asm volatile("cp.async.bulk.tensor.3d.global.shared::cta.bulk_group [%0, {%2, %3, %4}], [%1];\ncp.async.bulk.commit_group;\n"
                 ::"l"(tm), "r"(src), "r"(c0), "r"(c1), "r"(c2) : "memory");
}
__device__ __forceinline__ bool elect_one() {
    uint32_t r;
    asm volatile("{\n.reg .pred p;\nelect.sync _|p, 0xffffffff;\nselp.u32 %0, 1, 0, p;\n}\n" : "=r"(r));
    return r;
}
__device__ __forceinline__ void fence_async() { asm volatile("fence.proxy.async.shared::cta;\n" ::: "memory"); }

__device__ __forceinline__ float2 cmul(float2 a, float2 b) {
    return make_float2(fmaf(a.x, b.x, -a.y * b.y), fmaf(a.x, b.y, a.y * b.x));
}
__device__ __forceinline__ float2 csq(float2 a) {
    float p = a.x * a.y;
    return make_float2(fmaf(a.x, a.x, -a.y * a.y), p + p);
}
__device__ __forceinline__ float2 cexp_e(float lr2, float rh, float rl, float e) {
    float m;
    asm("ex2.approx.ftz.f32 %0, %1;\n" : "=f"(m) : "f"(lr2 * e));
    const float a = rh * e;
    const float r = fmaf(rl, e, a - rintf(a)) * 6.283185307179586f;
    return make_float2(m * __cosf(r), m * __sinf(r));
}
__device__ __forceinline__ float rcp_approx(float x) { float r; asm("rcp.approx.ftz.f32 %0, %1;\n" : "=f"(r) : "f"(x)); return r; }
__device__ __forceinline__ float ex2_approx(float x) { float r; asm("ex2.approx.ftz.f32 %0, %1;\n" : "=f"(r) : "f"(x)); return r; }
__device__ __forceinline__ float sqrt_approx(float x) { float r; asm("sqrt.approx.ftz.f32 %0, %1;\n" : "=f"(r) : "f"(x)); return r; }

__device__ __forceinline__ void wg_fence() { asm volatile("wgmma.fence.sync.aligned;\n" ::: "memory"); }
__device__ __forceinline__ void wg_commit() { asm volatile("wgmma.commit_group.sync.aligned;\n" ::: "memory"); }
__device__ __forceinline__ void wg_wait0() { asm volatile("wgmma.wait_group.sync.aligned 0;\n" ::: "memory"); }
template <int T0, int NT> __device__ __forceinline__ void wg_h(uint32_t (&acc)[32], const uint32_t (&a)[4], uint64_t desc);
template <> __device__ __forceinline__ void wg_h<0, 16>(uint32_t (&acc)[32], const uint32_t (&a)[4], uint64_t desc) {
    asm volatile("wgmma.mma_async.sync.aligned.m64n128k16.f16.f16.f16 {%0,%1,%2,%3,%4,%5,%6,%7,%8,%9,%10,%11,%12,%13,%14,%15,%16,%17,%18,%19,%20,%21,%22,%23,%24,%25,%26,%27,%28,%29,%30,%31}, {%32,%33,%34,%35}, %36, 1, 1, 1, 0;\n"
                 : "+r"(acc[0]), "+r"(acc[1]), "+r"(acc[2]), "+r"(acc[3]), "+r"(acc[4]), "+r"(acc[5]), "+r"(acc[6]), "+r"(acc[7]), "+r"(acc[8]), "+r"(acc[9]), "+r"(acc[10]), "+r"(acc[11]), "+r"(acc[12]), "+r"(acc[13]), "+r"(acc[14]), "+r"(acc[15]), "+r"(acc[16]), "+r"(acc[17]), "+r"(acc[18]), "+r"(acc[19]), "+r"(acc[20]), "+r"(acc[21]), "+r"(acc[22]), "+r"(acc[23]), "+r"(acc[24]), "+r"(acc[25]), "+r"(acc[26]), "+r"(acc[27]), "+r"(acc[28]), "+r"(acc[29]), "+r"(acc[30]), "+r"(acc[31])
                 : "r"(a[0]), "r"(a[1]), "r"(a[2]), "r"(a[3]), "l"(desc));
}
template <> __device__ __forceinline__ void wg_h<4, 4>(uint32_t (&acc)[32], const uint32_t (&a)[4], uint64_t desc) {
    asm volatile("wgmma.mma_async.sync.aligned.m64n32k16.f16.f16.f16 {%0,%1,%2,%3,%4,%5,%6,%7}, {%8,%9,%10,%11}, %12, 1, 1, 1, 0;\n"
                 : "+r"(acc[8]), "+r"(acc[9]), "+r"(acc[10]), "+r"(acc[11]), "+r"(acc[12]), "+r"(acc[13]), "+r"(acc[14]), "+r"(acc[15])
                 : "r"(a[0]), "r"(a[1]), "r"(a[2]), "r"(a[3]), "l"(desc));
}
template <> __device__ __forceinline__ void wg_h<8, 4>(uint32_t (&acc)[32], const uint32_t (&a)[4], uint64_t desc) {
    asm volatile("wgmma.mma_async.sync.aligned.m64n32k16.f16.f16.f16 {%0,%1,%2,%3,%4,%5,%6,%7}, {%8,%9,%10,%11}, %12, 1, 1, 1, 0;\n"
                 : "+r"(acc[16]), "+r"(acc[17]), "+r"(acc[18]), "+r"(acc[19]), "+r"(acc[20]), "+r"(acc[21]), "+r"(acc[22]), "+r"(acc[23])
                 : "r"(a[0]), "r"(a[1]), "r"(a[2]), "r"(a[3]), "l"(desc));
}
template <> __device__ __forceinline__ void wg_h<12, 4>(uint32_t (&acc)[32], const uint32_t (&a)[4], uint64_t desc) {
    asm volatile("wgmma.mma_async.sync.aligned.m64n32k16.f16.f16.f16 {%0,%1,%2,%3,%4,%5,%6,%7}, {%8,%9,%10,%11}, %12, 1, 1, 1, 0;\n"
                 : "+r"(acc[24]), "+r"(acc[25]), "+r"(acc[26]), "+r"(acc[27]), "+r"(acc[28]), "+r"(acc[29]), "+r"(acc[30]), "+r"(acc[31])
                 : "r"(a[0]), "r"(a[1]), "r"(a[2]), "r"(a[3]), "l"(desc));
}
template <> __device__ __forceinline__ void wg_h<0, 8>(uint32_t (&acc)[32], const uint32_t (&a)[4], uint64_t desc) {
    asm volatile("wgmma.mma_async.sync.aligned.m64n64k16.f16.f16.f16 {%0,%1,%2,%3,%4,%5,%6,%7,%8,%9,%10,%11,%12,%13,%14,%15}, {%16,%17,%18,%19}, %20, 1, 1, 1, 0;\n"
                 : "+r"(acc[0]), "+r"(acc[1]), "+r"(acc[2]), "+r"(acc[3]), "+r"(acc[4]), "+r"(acc[5]), "+r"(acc[6]), "+r"(acc[7]), "+r"(acc[8]), "+r"(acc[9]), "+r"(acc[10]), "+r"(acc[11]), "+r"(acc[12]), "+r"(acc[13]), "+r"(acc[14]), "+r"(acc[15])
                 : "r"(a[0]), "r"(a[1]), "r"(a[2]), "r"(a[3]), "l"(desc));
}
template <> __device__ __forceinline__ void wg_h<4, 12>(uint32_t (&acc)[32], const uint32_t (&a)[4], uint64_t desc) {
    asm volatile("wgmma.mma_async.sync.aligned.m64n96k16.f16.f16.f16 {%0,%1,%2,%3,%4,%5,%6,%7,%8,%9,%10,%11,%12,%13,%14,%15,%16,%17,%18,%19,%20,%21,%22,%23}, {%24,%25,%26,%27}, %28, 1, 1, 1, 0;\n"
                 : "+r"(acc[8]), "+r"(acc[9]), "+r"(acc[10]), "+r"(acc[11]), "+r"(acc[12]), "+r"(acc[13]), "+r"(acc[14]), "+r"(acc[15]), "+r"(acc[16]), "+r"(acc[17]), "+r"(acc[18]), "+r"(acc[19]), "+r"(acc[20]), "+r"(acc[21]), "+r"(acc[22]), "+r"(acc[23]), "+r"(acc[24]), "+r"(acc[25]), "+r"(acc[26]), "+r"(acc[27]), "+r"(acc[28]), "+r"(acc[29]), "+r"(acc[30]), "+r"(acc[31])
                 : "r"(a[0]), "r"(a[1]), "r"(a[2]), "r"(a[3]), "l"(desc));
}

#define PBYTES 4608
#define DELAY(n) do { if (n) { const unsigned c0_ = clock32(); while ((int)(clock32() - c0_) < (n)) {} } } while (0)
#define KDEL 300
#define PDEL 300
#define CST(i) do { if ((warp & 3) == 0 && lane_v() == 0) { unsigned t_; asm volatile("mov.u32 %0, %%globaltimer_lo;" : "=r"(t_) :: "memory"); sts32(sb + SMEM_TOTAL - 768 + (warp >> 2) * 128 + (i) * 4, t_); } } while (0)
#define TP0 5000
#define TP4 5800
#define HINTW 10
#define WAS 0x0005
#define WA0 (WAS >> 12)
#define WA1 ((WAS >> 8) & 15)
#define WA2 ((WAS >> 4) & 15)
#define WA3 (WAS & 15)
#define WDAT 1
#define PAUSE 2
#define PCNT (32 + ((PAUSE & 1) ? 288 : 0) + ((PAUSE & 6) ? 320 : 64))
#define LNAT 2
#define UW 8
#define FINAT 3
#define UAT 2
#define TOKEN_OF(g) (16 * ((g) & 1) + ((g) >> 2) + 2 * ((g) & 2))
#define HI2(a, b) (pack_f16_rz(__uint_as_float(a), __uint_as_float(b)) & 0xfff8fff8u)
struct Params {
    const bf16 *x, *lar, *aim, *cre, *cim, *ldt, *dsk;
    Scratch* s;
    const bf16* wr;
    bf16* out;
};

template <int NK>
__device__ __forceinline__ void ln_partial(const uint32_t (&H)[2][NK], const uint32_t (&bw)[NK], uint32_t lp, int warp, int g, int t) {
    float cs[4] = {0.f, 0.f, 0.f, 0.f}, cl[4] = {0.f, 0.f, 0.f, 0.f}, ch[4] = {0.f, 0.f, 0.f, 0.f};
#pragma unroll
    for (int k = 0; k < NK; k += 2) {
        uint32_t a0, a1, a2, a3;
        asm volatile("prmt.b32 %0, %4, %4, %8;\nprmt.b32 %1, %5, %5, %8;\nprmt.b32 %2, %6, %6, %8;\nprmt.b32 %3, %7, %7, %8;\n"
                     : "=r"(a0), "=r"(a1), "=r"(a2), "=r"(a3) : "r"(H[0][k]), "r"(H[1][k]), "r"(H[0][k + 1]), "r"(H[1][k + 1]), "r"(0x3210u + (warp >> 8)));
        mma_bf16(cl, a0, a1, a2, a3, H[0][k], H[0][k + 1]);
        mma_bf16(ch, a0, a1, a2, a3, H[1][k], H[1][k + 1]);
        mma_bf16(cs, a0, a1, a2, a3, bw[k], bw[k + 1]);
    }
    const uint32_t a = lp + (g * 20 + warp) * 4;
    if (t == 0) {
        stsf(a, cs[1]); stsf(a + 8 * 80, cs[3]);
    }
    if (t == (g >> 1)) { stsf(a + 16 * 80, (g & 1) ? cl[1] : cl[0]); stsf(a + 24 * 80, (g & 1) ? ch[3] : ch[2]); }
}
__device__ __forceinline__ float sum18(uint32_t a) {
    const uint4 p = lds128(a), q = lds128(a + 16), r = lds128(a + 32), s = lds128(a + 48);
    const uint2 u = lds64(a + 64);
#define F(x) __uint_as_float(x)
    return (((F(p.x) + F(p.y)) + (F(p.z) + F(p.w))) + ((F(q.x) + F(q.y)) + (F(q.z) + F(q.w)))) +
           (((F(r.x) + F(r.y)) + (F(r.z) + F(r.w))) + ((F(s.x) + F(s.y)) + (F(s.z) + F(s.w))) + (F(u.x) + F(u.y)));
#undef F
}
__device__ __forceinline__ float sum9(uint32_t a) {
    const uint4 p = lds128(a), q = lds128(a + 16);
#define F(x) __uint_as_float(x)
    return (((F(p.x) + F(p.y)) + (F(p.z) + F(p.w))) + ((F(q.x) + F(q.y)) + (F(q.z) + F(q.w)))) + ldsf(a + 32);
#undef F
}
template <int N>
__device__ __forceinline__ void ln_finish(uint32_t lp, int lane, float& mb, float& rc) {
    const float v = N == 9 ? sum9(lp + lane * 80) : sum18(lp + lane * 80);
    const float o = __shfl_xor_sync(0xffffffffu, v, 16);
    const float m0 = v * (1.0f / 576.0f);
    const float mean = fmaf(fmaf(-m0, 576.0f, v), 1.0f / 576.0f, m0);
    const float var = fmaxf(fmaf(-mean, mean, o * (1.0f / 576.0f)), 0.f);
    mb = rbf(mean);
    rc = rcp_approx(rbf(sqrt_approx(rbf(rbf(var) + 1e-5f))));
}
__device__ __forceinline__ uint32_t ln_apply(uint32_t w, const uint2& st) {
    uint32_t r;
    asm("{\n.reg .b16 m, t, h, l;\n.reg .b32 mm, hh, ll, d, e;\nmov.b32 {m, t}, %2;\nmov.b32 {h, l}, %3;\nmov.b32 mm, {m, m};\nmov.b32 hh, {h, h};\nmov.b32 ll, {l, l};\n"
        "sub.rn.bf16x2 d, %1, mm;\nmul.rn.bf16x2 e, d, ll;\nfma.rn.bf16x2 %0, d, hh, e;\n}\n" : "=r"(r) : "r"(w), "r"(st.x), "r"(st.y));
    return r;
}
__device__ __forceinline__ void stat_store(uint32_t a, float mb, float rc, uint32_t extra) {
    const float rh = rbf(rc);
    sts64(a, (__float_as_uint(mb) >> 16) | (extra << 16), pack_bf16(rh, rc - rh));
}

__device__ __forceinline__ void hcmul(uint32_t re, uint32_t im, uint32_t z, uint32_t& ore, uint32_t& oim) {
    asm("{\n.reg .b16 x, y;\n.reg .b32 xx, yy, ny, a, b;\nmov.b32 {x, y}, %4;\nmov.b32 xx, {x, x};\nmov.b32 yy, {y, y};\nneg.f16x2 ny, yy;\n"
        "mul.rn.f16x2 a, %2, xx;\nfma.rn.f16x2 %0, %3, ny, a;\nmul.rn.f16x2 b, %3, xx;\nfma.rn.f16x2 %1, %2, yy, b;\n}\n" : "=&r"(ore), "=r"(oim) : "r"(re), "r"(im), "r"(z));
}
__device__ __forceinline__ void hcmul(uint32_t re, uint32_t im, uint32_t zx, uint32_t zy, uint32_t& ore, uint32_t& oim) {
    asm("{\n.reg .b32 ny, a, b;\nneg.f16x2 ny, %5;\n"
        "mul.rn.f16x2 a, %2, %4;\nfma.rn.f16x2 %0, %3, ny, a;\nmul.rn.f16x2 b, %3, %4;\nfma.rn.f16x2 %1, %2, %5, b;\n}\n" : "=&r"(ore), "=r"(oim) : "r"(re), "r"(im), "r"(zx), "r"(zy));
}

struct KGen {
    uint32_t Af[4][4];
    float2 z1, z8, z64, z128, T[9];
    uint32_t zw;
};
__device__ __forceinline__ void kgen_setup(KGen& k, uint32_t pa, float dt) {
    const float A = rbf(expf(bf_lo(pa)));
    const float lr2 = -(A * dt) * 1.4426950408889634f;
    const float li = bf_hi(pa) * dt;
    const float rh = li * 0.15915494309189535f;
    const float rl = fmaf(li, 6.4206382986e-9f, fmaf(li, 0.15915494309189535f, -rh));
    k.z1 = cexp_e(lr2, rh, rl, 1.0f);
    k.z8 = cexp_e(lr2, rh, rl, 8.0f);
    k.z64 = cexp_e(lr2, rh, rl, 64.0f);
}
__device__ __forceinline__ void kgen_rows(KGen& k, uint32_t tb, int lane) {
    const float2 z8 = k.z8, z64 = k.z64;
    const uint32_t row = tb + lane * TBP;
    k.z128 = csq(z64);
    const float2 z16 = csq(z8), z32 = csq(z16), z48 = cmul(z32, z16), z80 = cmul(z64, z16), z96 = cmul(z64, z32), z112 = cmul(z64, z48);
    uint32_t re[4], im[4], a[4], b[4];
    re[0] = pack_f16(1.0f, z16.x); im[0] = pack_f16(0.0f, z16.y);
    re[1] = pack_f16(z32.x, z48.x); im[1] = pack_f16(z32.y, z48.y);
    re[2] = pack_f16(z64.x, z80.x); im[2] = pack_f16(z64.y, z80.y);
    re[3] = pack_f16(z96.x, z112.x); im[3] = pack_f16(z96.y, z112.y);
    sts128(row, re[0], re[1], re[2], re[3]);
    sts128(row + 32, im[0], im[1], im[2], im[3]);
    const uint32_t zz = pack_f16(z8.x, z8.y);
#pragma unroll
    for (int j = 0; j < 4; j++) hcmul(re[j], im[j], zz, a[j], b[j]);
    sts128(row + 16, a[0], a[1], a[2], a[3]);
    sts128(row + 48, b[0], b[1], b[2], b[3]);
    __syncwarp();
    const int mi = lane >> 3;
    const uint32_t ad = tb + (lane & 7) * TBP + mi * 16;
#pragma unroll
    for (int ks = 0; ks < 4; ks++) ldsm_x4_t(k.Af[ks][0], k.Af[ks][1], k.Af[ks][2], k.Af[ks][3], ad + ks * 8 * TBP);
}
__device__ __forceinline__ void kgen_chain(KGen& k, uint32_t pc, float cs) {
    k.T[0] = make_float2(bf_lo(pc) * cs, -bf_hi(pc) * cs);
    const float2 y1 = make_float2(k.z1.x, -k.z1.y);
#pragma unroll
    for (int c = 1; c < 8; c++) k.T[c] = cmul(k.T[c - 1], y1);
    k.T[8] = cmul(k.T[0], make_float2(k.z8.x, -k.z8.y));
}
__device__ __forceinline__ void kgen_cols(KGen& k, uint32_t tb, int lane) {
    const uint32_t row = tb + lane * TBP;
    const float2 (&T)[9] = k.T;
    const uint32_t zv = pack_f16(k.z128.x, k.z128.y), zo = __shfl_xor_sync(0xffffffffu, zv, 1);
    k.zw = (lane & 1) ? __byte_perm(zo, zv, 0x7632) : __byte_perm(zv, zo, 0x5410);
    const float2 y256 = csq(make_float2(k.z128.x, -k.z128.y)), y512 = csq(y256), y768 = cmul(y512, y256), y1024 = csq(y512);
    const float2 c1032 = cmul(T[8], y1024);
    const uint32_t r04 = pack_f16(T[0].x, T[4].x), i04 = pack_f16(T[0].y, T[4].y), r26 = pack_f16(T[2].x, T[6].x), i26 = pack_f16(T[2].y, T[6].y);
    const uint32_t r48 = pack_f16(T[4].x, T[8].x), i48 = pack_f16(T[4].y, T[8].y);
    __syncwarp();
    sts128(row, r04, pack_f16(T[1].x, T[5].x), r26, pack_f16(T[3].x, T[7].x));
    sts128(row + 16, i04, pack_f16(T[1].y, T[5].y), i26, pack_f16(T[3].y, T[7].y));
    uint32_t a[4], b[4];
    {
        const uint32_t zz = pack_f16(y256.x, y256.y);
        hcmul(r04, i04, zz, a[0], b[0]);
        hcmul(r26, i26, zz, a[2], b[2]);
        hcmul(r48, i48, zz, a[3], b[3]);
    }
    sts128(row + 32, a[0], a[0], a[2], a[3]);
    sts128(row + 48, b[0], b[0], b[2], b[3]);
    {
        hcmul(r48, i48, pack_f16(y512.x, y512.y), a[0], b[0]);
        hcmul(r48, i48, pack_f16(y768.x, y768.y), a[1], b[1]);
        const uint32_t zz = pack_f16(c1032.x, c1032.y);
        hcmul(pack_f16(1.0f, y256.x), pack_f16(0.0f, y256.y), zz, a[2], b[2]);
        hcmul(pack_f16(y512.x, y768.x), pack_f16(y512.y, y768.y), zz, a[3], b[3]);
    }
    sts128(row + 64, a[0], a[1], a[2], a[3]);
    sts128(row + 80, b[0], b[1], b[2], b[3]);
}
__device__ __forceinline__ void kgen_mma(const KGen& k, uint32_t tb, int lane) {
    const int t = lane & 3;
    const uint32_t zw = k.zw;
    uint32_t zx[4], zy[4];
#pragma unroll
    for (int ks = 0; ks < 4; ks++) { zx[ks] = __shfl_sync(0xffffffffu, zw, 8 * ks + 2 * t); zy[ks] = __shfl_sync(0xffffffffu, zw, 8 * ks + 2 * t + 1); }
    __syncwarp();
    float acc[2][3][4];
#pragma unroll
    for (int i = 0; i < 6; i++)
#pragma unroll
        for (int j = 0; j < 4; j++) acc[i / 3][i % 3][j] = 0.f;
    {
        const int mi = lane >> 3;
        const uint32_t bd = tb + ((lane & 7) + 8 * (mi >> 1)) * TBP + (mi & 1) * 16;
#pragma unroll
        for (int kp = 0; kp < 2; kp++) {
            uint32_t b[3][4];
#pragma unroll
            for (int j = 0; j < 3; j++) ldsm_x4_t(b[j][0], b[j][1], b[j][2], b[j][3], bd + kp * 16 * TBP + j * 32);
#pragma unroll
            for (int h = 0; h < 2; h++) {
                const int ks = 2 * kp + h;
                uint32_t d[4];
                hcmul(k.Af[ks][0], k.Af[ks][2], zx[ks], zy[ks], d[0], d[2]);
                hcmul(k.Af[ks][1], k.Af[ks][3], zx[ks], zy[ks], d[1], d[3]);
#pragma unroll
                for (int j = 0; j < 3; j++) {
                    mma_f16(acc[0][j], k.Af[ks][0], k.Af[ks][1], k.Af[ks][2], k.Af[ks][3], b[j][2 * h], b[j][2 * h + 1]);
                    mma_f16(acc[1][j], d[0], d[1], d[2], d[3], b[j][2 * h], b[j][2 * h + 1]);
                }
            }
        }
    }
    __syncwarp();
#pragma unroll
    for (int h = 0; h < 2; h++) {
        sts64(tb + h * 256 + lane * 8, pack_f16(acc[h][0][0], acc[h][0][1]), pack_f16(acc[h][0][2], acc[h][0][3]));
        sts64(tb + 512 + h * 256 + lane * 8, pack_f16(acc[h][1][0], acc[h][1][1]), pack_f16(acc[h][1][2], acc[h][1][3]));
        sts32(tb + 1024 + h * 256 + lane * 4, pack_f16(acc[h][2][0], t < 2 ? acc[h][2][1] : acc[h][2][2]));
        sts32(tb + 1152 + h * 256 + lane * 4, pack_f16(t < 2 ? acc[h][2][2] : acc[h][2][1], acc[h][2][3]));
    }
}
__device__ __forceinline__ uint32_t table_buf(uint32_t sb, int warp) { return sb + SM_TB + warp * TBW; }

__device__ __forceinline__ void kgen_combine(uint32_t sb, int warp, int lane, uint32_t kw, uint32_t ao) {
    const int wq = warp & 3;
    const uint32_t a = table_buf(sb, warp & ~3) + wq * 256 + lane * 8, c = table_buf(sb, warp & ~3) + 1024 + wq * 128 + lane * 4;
    const int t = lane & 3;
    const uint32_t o0 = (t < 2 ? KW_T2 + KW_KH + 16 + t * 256 - (wq & 1) * KW_KH : KW_T3 + 16 - 1024 + t * 512 + (wq & 1) * 256) + (lane >> 2) * 16;
    const uint4 o = make_uint4(o0 + t * 36, o0 + (t ^ 1) * 36, o0 + (t ^ 2) * 36, o0 + (t ^ 3) * 36);
    const uint2 u = lds64(a), v = lds64(a + TBW), w = lds64(a + 2 * TBW), x = lds64(a + 3 * TBW);
    const uint32_t kt = hadd2(hadd2(lds32(c), lds32(c + TBW)), hadd2(lds32(c + 2 * TBW), lds32(c + 3 * TBW)));
    const uint32_t k23 = hadd2(hadd2(u.y, v.y), hadd2(w.y, x.y));
    sts64(kw + wq * 64 + ao, hadd2(hadd2(u.x, v.x), hadd2(w.x, x.x)), k23);
    const uint32_t d = kw + (wq >> 1) * 128;
    const uint32_t kh = hmul2(kt, 0x38003800u);
    sts32(d + o.x, kh); sts32(d + o.y, kh); sts32(d + o.z, kh); sts32(d + o.w, kh);
    if (wq == 3) {
        if (lane == 31) { sts32(kw + 264, k23 >> 16); sts32(kw + 288 + 264, k23 >> 16); sts32(kw + 576 + 264, k23 >> 16); }
        if (lane == 29) { sts32(kw + 864 + 280, kt >> 16); sts32(kw + 280, kt & 0xffff0000u); }
    }
}

__device__ __forceinline__ int c_exponent(const uint2& r, const uint2& i) {
    uint32_t mx = __vmaxu2(__vmaxu2(r.x & 0x7fff7fffu, r.y & 0x7fff7fffu), __vmaxu2(i.x & 0x7fff7fffu, i.y & 0x7fff7fffu));
    mx = __reduce_max_sync(0xffffffffu, max(mx & 0xffffu, mx >> 16));
    return min(max((int)(mx >> 7), 4), 240);
}

__device__ __forceinline__ int warp_v() { int l; asm volatile("mov.u32 %0, %%tid.x;" : "=r"(l)); return __shfl_sync(0xffffffffu, l >> 5, 0); }
__device__ __forceinline__ int lane_v() { int l; asm volatile("mov.u32 %0, %%laneid;" : "=r"(l)); return l; }
__device__ __forceinline__ unsigned clock32() { unsigned c; asm volatile("mov.u32 %0, %%clock;" : "=r"(c)); return c; }
__device__ __forceinline__ uint32_t prmt(uint32_t a, uint32_t b, uint32_t s) { uint32_t d; asm("prmt.b32 %0, %1, %2, %3;\n" : "=r"(d) : "r"(a), "r"(b), "r"(s)); return d; }
__device__ __forceinline__ uint32_t prmt_v(uint32_t a, uint32_t b, uint32_t s) { uint32_t d; asm volatile("prmt.b32 %0, %1, %2, %3;\n" : "=r"(d) : "r"(a), "r"(b), "r"(s)); return d; }
__device__ __forceinline__ void mmah16(uint32_t& d0, uint32_t& d1, uint32_t a0, uint32_t a1, uint32_t a2, uint32_t a3, uint32_t b0, uint32_t b1, uint32_t c0, uint32_t c1) {
    asm volatile("mma.sync.aligned.m16n8k16.row.col.f16.f16.f16.f16 {%0,%1}, {%2,%3,%4,%5}, {%6,%7}, {%8,%9};\n"
                 : "=r"(d0), "=r"(d1) : "r"(a0), "r"(a1), "r"(a2), "r"(a3), "r"(b0), "r"(b1), "r"(c0), "r"(c1));
}
__device__ __forceinline__ void mmah8(uint32_t& d0, uint32_t& d1, uint32_t a0, uint32_t a1, uint32_t b0, uint32_t c0, uint32_t c1) {
    asm volatile("mma.sync.aligned.m16n8k8.row.col.f16.f16.f16.f16 {%0,%1}, {%2,%3}, {%4}, {%5,%6};\n"
                 : "=r"(d0), "=r"(d1) : "r"(a0), "r"(a1), "r"(b0), "r"(c0), "r"(c1));
}
template <int A = 8, int B = 32>
__device__ __forceinline__ void conv_rename(uint32_t (&acc)[32]) {
#pragma unroll
    for (int i = A; i < B; i++) { uint32_t v; asm volatile("mov.b32 %0, %1;\n" : "=r"(v) : "r"(acc[i])); acc[i] = v; }
}
__host__ __device__ constexpr uint32_t band_bits(int hw, int sh) {
    uint32_t c = 0;
    for (int s = 0; s <= 10; s++)
        for (int e = 0; e < 2; e++) {
            const int v = s - 3 + sh - 4 * e;
            if (v <= hw && v >= -hw) c |= 1u << (14 + 16 * e - s);
        }
    return c;
}
template <int HW, int SH, int J> __device__ __forceinline__ uint32_t band(uint32_t p2) {
    uint32_t d;
    asm volatile("{\n.reg .b32 t;\nmul.lo.u32 t, %1, %2;\nand.b32 %0, t, 0x40004000;\n}\n" : "=r"(d) : "r"(p2), "n"(band_bits(HW, SH) | J));
    return d;
}
template <int H0, int SH> __device__ __forceinline__ void band_pair(uint4& l, uint4& u, uint32_t p2) {
    l = make_uint4(band<H0, 8, 1>(p2), band<H0 - 1, SH + 8, 2>(p2), band<H0, 0, 1>(p2), band<H0 - 1, SH, 1>(p2));
    u = make_uint4(band<H0, 0, 2>(p2), band<H0 - 1, SH, 2>(p2), band<H0, -8, 1>(p2), band<H0 - 1, SH - 8, 1>(p2));
}
__device__ __forceinline__ void run_sums(uint32_t (&G)[3][2], const uint32_t (&c)[5], const uint4& l, const uint4& u) {
    mmah8(G[0][0], G[0][1], l.x, l.y, c[0], 0u, 0u);
    mmah8(G[1][0], G[1][1], u.z, u.w, c[3], 0u, 0u);
    mmah8(G[2][0], G[2][1], l.x, l.y, c[2], 0u, 0u);
    mmah16(G[0][0], G[0][1], u.x, u.y, u.z, u.w, c[1], c[2], G[0][0], G[0][1]);
    mmah16(G[1][0], G[1][1], l.x, l.y, l.z, l.w, c[1], c[2], G[1][0], G[1][1]);
    mmah16(G[2][0], G[2][1], u.x, u.y, u.z, u.w, c[3], c[4], G[2][0], G[2][1]);
}
__device__ __forceinline__ float h_lo(uint32_t w) { return __half2float(__ushort_as_half((unsigned short)(w & 0xffffu))); }
__device__ __forceinline__ float h_hi(uint32_t w) { return __half2float(__ushort_as_half((unsigned short)(w >> 16))); }
__device__ __forceinline__ uint64_t smem_desc(uint32_t sb, uint32_t o16, uint32_t lbo) {
    uint64_t d;
    asm("mov.b64 %0, {%1, %2};" : "=l"(d) : "r"(((sb & 0x3FFFF) >> 4) + o16 + (lbo << 12)), "r"(8));
    return d;
}
template <int I> struct IC { static constexpr int value = I; };

struct Conv {
    uint32_t u[3][5];
    uint32_t q2[3][2][4];
    uint32_t q3[2][4];
    uint32_t r[18];
};
struct ConvPre {
    uint32_t a[5], b[5];
    uint32_t t[4];
};
__device__ __forceinline__ void conv_pre(ConvPre& e, uint32_t ka, uint32_t ks, uint32_t sel) {
    const uint4 r = lds128(ka + 256), s = lds128(ka + 272);
    ldsm_x4(e.t[0], e.t[1], e.t[2], e.t[3], ks);
    const uint32_t sw = sel ^ 0x4444u;
    e.a[0] = prmt(r.y, r.z, sel); e.a[1] = prmt(r.w, r.z, sw); e.a[2] = prmt(r.x, r.y, sel); e.a[3] = prmt(r.z, r.y, sw); e.a[4] = prmt(r.z, r.w, sel);
    e.b[0] = prmt(s.y, s.z, sel); e.b[1] = prmt(s.w, s.z, sw); e.b[2] = prmt(s.x, s.y, sel); e.b[3] = prmt(s.z, s.y, sw); e.b[4] = prmt(s.z, s.w, sel);
}
__device__ __forceinline__ void conv_sums(Conv& c, uint32_t (&acc)[32], const ConvPre& e, uint32_t a0, uint32_t a1, const uint4 (&bd)[4], uint32_t ka, uint32_t sel, int wq, uint32_t zr) {
    {
        uint32_t x;
        ldsm_x4(c.u[0][1], c.u[0][2], c.u[0][3], c.u[0][4], a1);
        ldsm_x4(c.u[0][0], c.u[1][0], c.u[2][0], x, a0);
#pragma unroll
        for (int q = 1; q < 3; q++) ldsm_x4(c.u[q][1], c.u[q][2], c.u[q][3], c.u[q][4], a1 + q * 512);
    }
#pragma unroll
    for (int i = 0; i < 32; i++) acc[i] = 0u;
    uint32_t G[3][2];
#pragma unroll
    for (int q = 0; q < 3; q++) {
        mmah8(acc[8 * q + 8], acc[8 * q + 9], e.a[4], 0u, c.u[q][2], acc[8 * q + 8], acc[8 * q + 9]);
        mmah16(acc[8 * q + 8], acc[8 * q + 9], e.a[0], e.a[1], e.a[2], e.a[3], c.u[q][3], c.u[q][4], acc[8 * q + 8], acc[8 * q + 9]);
        if (q < 2) {
            mmah8(acc[8 * q + 16], acc[8 * q + 17], e.b[4], 0u, c.u[q][2], 0u, 0u);
            mmah16(acc[8 * q + 16], acc[8 * q + 17], e.b[0], e.b[1], e.b[2], e.b[3], c.u[q][3], c.u[q][4], acc[8 * q + 16], acc[8 * q + 17]);
            run_sums(G, c.u[q], bd[2], bd[3]);
            c.q3[q][0] = prmt(G[1][1], G[0][0], 0x7632u); c.q3[q][1] = prmt(G[2][1], G[1][0], 0x7632u);
            c.q3[q][2] = prmt(G[1][1], G[0][0], 0x5410u); c.q3[q][3] = prmt(G[2][1], G[1][0], 0x5410u);
        }
    }
    {
        const uint32_t a = (ka + wq * 64) ^ (((acc[8] | acc[16] | acc[24]) | (c.q3[0][0] | c.q3[0][1]) | (c.q3[1][0] | c.q3[1][1])) & zr);
#pragma unroll
        for (int i = 0; i < 4; i++) { const uint4 v = lds128(a + i * 16); c.r[4 * i] = v.x; c.r[4 * i + 1] = v.y; c.r[4 * i + 2] = v.z; c.r[4 * i + 3] = v.w; }
        const uint2 v = lds64(a + 64);
        c.r[16] = v.x; c.r[17] = v.y;
    }
#pragma unroll
    for (int q = 0; q < 3; q++) {
        run_sums(G, c.u[q], bd[0], bd[1]);
#pragma unroll
        for (int h = 0; h < 2; h++) {
            const uint32_t s = h ? 0x7632u : 0x5410u;
            c.q2[q][h][0] = prmt(G[0][1], G[0][0], s); c.q2[q][h][1] = prmt(G[1][1], G[1][0], s);
            c.q2[q][h][2] = prmt(G[1][0], G[1][1], s ^ 0x4444u); c.q2[q][h][3] = prmt(G[2][1], G[2][0], s);
            if (q < 2) mmah16(acc[8 * q + 16], acc[8 * q + 17], c.q2[q][h][0], c.q2[q][h][1], c.q2[q][h][2], c.q2[q][h][3], e.t[2 * h], e.t[2 * h + 1], acc[8 * q + 16], acc[8 * q + 17]);
        }
    }
    if (sel == 0u) {
#pragma unroll
        for (int i = 0; i < 6; i++) sts128(ka + i * 16, c.q2[i >> 1][i & 1][0], c.q2[i >> 1][i & 1][1], c.q2[i >> 1][i & 1][2], c.q2[i >> 1][i & 1][3]);
#pragma unroll
        for (int i = 0; i < 2; i++) sts128(ka + i * 16, c.q3[i][0], c.q3[i][1], c.q3[i][2], c.q3[i][3]);
#pragma unroll
        for (int i = 1; i < 4; i++) sts64(ka + i * 16, acc[8 * i], acc[8 * i + 1]);
    }
    conv_rename(acc);
}
#define SPACE 100
#define SPN 3
#define O4 4
#define B2L 1
#define GATE 2
#define HAND 2
#define GA 6
#define GB 4
template <int TA, int TB, int IA, class FG>
__device__ __forceinline__ void conv_tail(uint32_t (&acc)[32], const uint32_t (&a)[8][4], uint32_t sb, unsigned char* gy0, int warp, size_t ycopy, FG fg) {
    const int wg = warp >> 2, wq = warp & 3, ord = TA == 0 && TB == 16 ? 3 - wg + (3 - wg >= O4) : O4;
    const uint32_t ub = sb + SM_U + wg * USLOT_B + UPAD * 16, turn = sb + SM_MISC + 376 + ord * 8, sfs = sb + SM_MISC + 256 + wg * 8;
    const uint32_t du = wg * (USLOT_B / 16) + (SM_U / 16 + UPAD + TA * 8);
    uint32_t ud[8], fs;
    auto skip = [&]() {
        const int lane = lane_v();
        const uint32_t ua = ub + ((lane >> 3) & 1) * ULO_B + (8 * wq + (lane & 7)) * 16 + (lane >> 4) * 512;
        if (IA == 0) ldsm_x4_t(ud[0], ud[1], ud[2], ud[3], ua);
        if (TB == 16) ldsm_x4_t(ud[4], ud[5], ud[6], ud[7], ua + 1024);
        const uint2 fd = lds64(sfs);
        fs = fd.x;
        const float dsk = __uint_as_float(fd.y);
#pragma unroll
        for (int i = 2 * IA; i < TB / 2; i++) ud[i] = pack_bf16(h_lo(ud[i]) * dsk, h_hi(ud[i]) * dsk);
    };
    conv_rename<2 * TA, 2 * TB>(acc);
    if (__builtin_expect(ord != 0, 0)) {
        skip();
        mbar_wait(turn);
    } else if (B2L) {
        bar_sync(0, NWRK);
    }
    if (O4 < 4 || (TA == 0 && TB == 16)) asm volatile("{\n.reg .pred p;\nelect.sync _|p, 0xffffffff;\n@p mbarrier.arrive.shared::cta.b64 _, [%0];\n}\n" ::"r"(turn + 48) : "memory");
    fg(IC<8>());
    wg_fence();
#pragma unroll
    for (int m = 7; m >= 0; m--) {
        wg_h<TA, TB - TA>(acc, a[m], smem_desc(sb, du - m, ULO_B));
        if (m == GA || m == GB || m == HAND) wg_commit();
        if (m == GB) asm volatile("wgmma.wait_group.sync.aligned 1;\n" ::: "memory");
    }
    wg_commit();
    if (O4 < 4 || (TA == 0 && TB == 16)) {
        asm volatile("wgmma.wait_group.sync.aligned 1;\n" ::: "memory");
        asm volatile("{\n.reg .pred p;\nelect.sync _|p, 0xffffffff;\n@p mbarrier.arrive.shared::cta.b64 _, [%0];\n}\n" ::"r"(turn + 8) : "memory");
    }
    __syncwarp();
    fg(IC<3>());
    if (!ord) skip();
    fg(IC<4>());
    const int lane = lane_v();
    const uint32_t lp = sb + SM_PL + (ord >= 3 ? ord - 3 : ord) * PL_B + lane * 8;
    unsigned char* gy = gy0 + ((4 * wq + (lane & 3)) * DM + (TA == 0 && TB == 16 ? 4 * blockIdx.x + wg : 512 + (blockIdx.x >> 1))) * 64 + (lane >> 2) * 8;
    const uint32_t st = lp + (wq * 12 - ((wq * (wq - 1)) >> 1)) * 256;
    uint32_t ld[3];
#pragma unroll
    for (int s = 1; s < 4; s++) {
        const int w = (wq - s) & 3;
        ld[s - 1] = lp + (w * 12 - ((w * (w - 1)) >> 1) + s - 1 - (wq < s ? 3 : 0)) * 256;
    }
    const uint32_t one = 1u + (warp >> 8);
    if (one == 0u) stg64(gy, ld[0], ld[1]);
    if (ord >= 3) bar_sync(9 + ord, 256);
    wg_wait0();
    fg(IC<6>());
#pragma unroll
    for (int j = TA; j < TB; j++)
        if ((j & 3) && j + 3 >= 4 * IA && (j + 3 < TB || j + wq < TB)) sts64(st + (j - 1 - (j >> 2)) * 256, acc[2 * j], acc[2 * j + 1]);
    bar_sync(1 + wg, 128);
    fg(IC<7>());
    uint2 v[4][3];
#pragma unroll
    for (int i = IA; i < TB / 4; i++)
#pragma unroll
        for (int s = 0; s < 3; s++) {
            if (i == 0) { v[i][s] = make_uint2(0u, 0u); if (wq > s) v[i][s] = lds64(ld[s]); }
            else v[i][s] = lds64(ld[s] + i * 768);
        }
    fg(IC<5>());
#pragma unroll
    for (int i = IA; i < TB / 4; i++) {
        const uint32_t x0 = hadd2(v[i][0].x, acc[8 * i]), x1 = hadd2(v[i][1].x, v[i][2].x), y0 = hadd2(v[i][0].y, acc[8 * i + 1]), y1 = hadd2(v[i][1].y, v[i][2].y);
        const uint32_t x = hadd2(x0, x1), y = hadd2(y0, y1);
        const uint32_t lo = pack_bf16(h_lo(x), h_hi(x)), hi = pack_bf16(h_lo(y), h_hi(y));
        ud[2 * i] = max(hfma2_bf(lo, fs, ud[2 * i]), one); ud[2 * i + 1] = hfma2_bf(hi, fs, ud[2 * i + 1]);
    }
    if (SPACE && TA == 0 && TB == 16 && ord < SPN) {
#pragma unroll
        for (int i = 0; i < 4; i++) {
            stg64(gy + i * 16 * DM * 64, ud[2 * i], ud[2 * i + 1]);
            if (i < 3) { const unsigned c0 = clock32(); while (clock32() - c0 < SPACE) {} }
        }
    } else {
#pragma unroll
        for (int i = IA; i < TB / 4; i++) stg64(gy + i * 16 * DM * 64, ud[2 * i], ud[2 * i + 1]);
    }
    if (ord < 2) bar_arrive(12 + ord, 256);
}
template <int M0, int M1>
__device__ __forceinline__ void conv_frags(uint32_t (&a)[8][4], const uint32_t (&r)[18], uint32_t sel, uint32_t dep, int warp) {
    const uint32_t s = prmt_v(sel, dep, 0x3210u + (warp >> 8)), sw = s ^ 0x4444u;
#pragma unroll
    for (int m = M0; m < M1; m++) {
        a[m][0] = prmt_v(r[2 * m + 1], r[2 * m + 2], s); a[m][1] = prmt_v(r[2 * m + 2], r[2 * m + 3], s);
        a[m][2] = prmt_v(r[2 * m + 1], r[2 * m], sw); a[m][3] = prmt_v(r[2 * m + 2], r[2 * m + 1], sw);
    }
}
template <class FG>
__device__ __forceinline__ void conv_main(const Conv& c, uint32_t (&acc)[32], uint32_t sb, uint32_t sel, unsigned char* gy, int warp, size_t ycopy, FG fg) {
    const uint32_t kw = (warp >> 2) * (KW_B / 16) + SM_KW / 16;
    const uint64_t d2 = smem_desc(sb, kw + KW_T2 / 16, KW_KH), d2b = smem_desc(sb, kw + KW_T2 / 16 + 1, KW_KH), d3 = smem_desc(sb, kw + KW_T3 / 16, 16), d3b = smem_desc(sb, kw + KW_T3 / 16 + 32, 16);
    uint32_t a[8][4];
    {
        const int ord = warp < 16 ? 3 - (warp >> 2) + (3 - (warp >> 2) >= O4) : O4;
        if (__builtin_expect(ord >= GATE, 0)) {
            fg(IC<1>());
            mbar_wait(sb + SM_MISC + 376 + 48 + (ord - GATE) * 8);
        }
    }
    wg_fence();
    wg_h<12, 4>(acc, c.q3[0], d3b); wg_h<8, 4>(acc, c.q3[0], d3); wg_h<4, 4>(acc, c.q2[0][0], d2b);
    wg_h<12, 4>(acc, c.q3[1], d3); wg_h<8, 4>(acc, c.q2[1][0], d2b);
    wg_h<12, 4>(acc, c.q2[2][0], d2b); wg_h<4, 4>(acc, c.q2[0][1], d2); wg_h<8, 4>(acc, c.q2[1][1], d2);
    wg_h<12, 4>(acc, c.q2[2][1], d2);
    wg_commit(); __syncwarp();
    fg(IC<0>());
    wg_wait0();
    conv_frags<0, 8>(a, c.r, sel, acc[16], warp);
    fg(IC<2>());
    if (warp >= 16) {
        if (blockIdx.x & 1) conv_tail<4, 16, 2>(acc, a, sb, gy, warp, ycopy, fg);
        else conv_tail<0, 8, 0>(acc, a, sb, gy, warp, ycopy, fg);
    } else {
        conv_tail<0, 16, 0>(acc, a, sb, gy, warp, ycopy, fg);
    }
}
#define CONV_LT6 const int dd = (lane >> 3) + (lane & 4) - (lane & 3); \
        const uint4 lt6 = make_uint4(prmt_v((dd & 3) * 288, 0u, idn), prmt_v(0x3254u + (dd >> 2) * 0x2222u, 0u, idn), \
            prmt_v(UPAD * 16 + (lane & 7) * 16 + ULO_B - 32 + (lane >> 3) * 512, 0u, idn), prmt_v(UPAD * 16 + (lane & 7) * 16 + ((lane >> 3) & 1) * ULO_B - 16 + (lane & 16), 0u, idn));
#define CONV_PRE \
        CONV_LT6 \
        const uint32_t ka = kw + lt6.x, sel = lt6.y, ks = kw + lt7.x; \
        const uint32_t ca0 = sb + SM_U + wg * USLOT_B + (warp & 3) * 128 + lt6.z, ca1 = sb + SM_U + wg * USLOT_B + (warp & 3) * 128 + lt6.w; \
        uint4 bd[4]; \
        band_pair<2, 4>(bd[0], bd[1], lt7.w); band_pair<4, 0>(bd[2], bd[3], lt7.w);
#define CONV_PRE2 ConvPre ce_; conv_pre(ce_, ka, ks, sel);
#define CONV_BODY \
        Conv c; \
        uint32_t acc[32]; \
        conv_sums(c, acc, ce_, ca0, ca1, bd, ka, sel, warp & 3, warp >> 8);
#define WS a_b_0_1_2_34_xy_56_7__c__r____de__
#define WS_STR2(x) #x
#define WS_STR(x) WS_STR2(x)
__device__ constexpr char wunit(int pt, int k) {
    constexpr char t[] = WS_STR(WS);
    int i = 0;
    for (; pt > 0 && t[i]; i++) pt -= t[i] == '_';
    for (; k > 0 && t[i] && t[i] != '_'; i++) k--;
    return t[i] == '_' ? 0 : t[i];
}
__device__ constexpr bool wsched_ok() {
    int seen = 0;
    for (int p = 0; p < 21; p++)
        for (int k = 0; wunit(p, k); k++) {
            const char c = wunit(p, k);
            const int bit = 1 << (c == 'r' ? 13 : c >= 'x' ? c - 'x' + 14 : c >= 'a' ? c - 'a' + 8 : c - '0');
            if ((seen & bit) || k >= (p < 16 ? 4 : 2) || (p < 5 && c >= '4' && c <= '7') || (p < 6 && (c == 'c' || c == 'd')) || (p < 16 && c == 'e')) return false;
            seen |= bit;
        }
    return seen == 0xffff;
}
struct WMaps { CUtensorMap g, u, gr, ur, d, dr; };
static_assert(GATE <= 2 && O4 >= 2, "resets");
static_assert(wsched_ok(), "weight schedule");
template <int PT, int K>
__device__ __forceinline__ void weight_units(uint32_t sb, const WMaps& m, int w) {
    constexpr char U = wunit(PT, K);
    if constexpr (U != 0) {
        if (w == K && elect_one()) {
            const int P = blockIdx.x >> 1, odd = blockIdx.x & 1;
            constexpr int bar = SM_MISC + (U == 'e' ? 352 : U >= 'a' && U <= 'r' ? 336 : 328);
            if constexpr (U == 'e') { if (!odd) tma_2d(sb + SM_WD + 4 * 8192, &m.d, 256, 64 * P, sb + bar); }
            else if constexpr (U == 'r') tma_3d(sb + SM_WD + 40960, &m.dr, 0, 4096 + 8 * P, 5 * odd, sb + bar);
            else if constexpr (U >= 'x') tma_3d(sb + SM_WR + (U - 'x') * 4608, U == 'x' ? &m.gr : &m.ur, 4096 + 8 * P, 0, 2 * odd, sb + bar);
            else if constexpr (U >= 'a') tma_2d(sb + SM_WD + (U - 'a') * 8192, &m.d, 320 * odd + 64 * (U - 'a'), 64 * P, sb + bar);
            else tma_2d(sb + (U < '4' ? SM_WG : SM_WU) + (U & 3) * 9216, U < '4' ? &m.g : &m.u, 64 * P, 288 * odd + (U & 3) * 72, sb + bar);
        }
        weight_units<PT, K + 1>(sb, m, w);
    }
}
#define WPOINT(i, w) do { weight_units<i, 0>(sb, wm, w); } while (0)

__global__ void __launch_bounds__(NTHR, 1) __cluster_dims__(2, 1, 1)
fused_kernel(const Params p, const __grid_constant__ WMaps wm, const __grid_constant__ CUtensorMap tm_x,
             const __grid_constant__ CUtensorMap tm_y, const __grid_constant__ CUtensorMap tm_z) {
    extern __shared__ __align__(1024) unsigned char smem[];
    const uint32_t sb = smem_u32(smem);
    const int tid = threadIdx.x, warp = __shfl_sync(0xffffffffu, tid >> 5, 0), lane = tid & 31;
    const int b = blockIdx.x, P = b >> 1, odd = b & 1;
    const int g = lane >> 2, t = lane & 3;
    const int wg = warp >> 2, t128 = tid & 127;
    const uint32_t s_stat = sb + SM_MISC;
    const uint32_t s_key = sb + SM_MISC + 128;
    const uint32_t s_wm = sb + SM_MISC + 256;
    const uint32_t s_k16 = sb + SM_MISC + 192;
    const uint32_t s_fs = sb + SM_MISC + 256;
    const uint32_t s_cnt = sb + SM_MISC + 320;
    const uint32_t bar_w = sb + SM_MISC + 328, bar_d = bar_w + 8, bar_g = bar_w + 16, bar_r = bar_w + 32, bar_h = bar_w + 40, bar_x = bar_w + 48;
    STAMP(0);

    const unsigned tk0 = clock32();
    const bool lnw = (unsigned)(warp - 10) < 9u;
    const unsigned pm = tid + (tid < 512 ? 512 * b : 65024 + 128 * P), pq = (pm & ~127u) + 4 * lane;
    uint32_t pl = ldg16(p.lar + pm), ldt = ldg16(p.ldt + (pm >> 7));
    const uint32_t pa2 = ldg16(p.aim + pm), pc = ldg16(p.cre + pm), pi = ldg16(p.cim + pm);
    const uint2 call_re = ldg64(p.cre + pq), call_im = ldg64(p.cim + pq);
    const uint32_t dskl = ldg16(p.dsk + (pm >> 7));
    const uint32_t ep = ld_poll32(p.s->hint + (b & 7) * 32 + 1 + (lane >> 5));
    if ((unsigned)(tid - 320) < 288u) {
        const bf16* xp = p.x + (unsigned)((32 * P + 2 * odd + TOKEN_OF(g)) * DM + ((tid - 320) & ~31) + 8 * t);
        const uint32_t xt = sb + SM_XT + ((tid - 320) & ~31) * 32 + lane * 16;
        asm volatile("cp.async.cg.shared.global [%0], [%1], 16;\ncp.async.cg.shared.global [%0 + 512], [%1 + 9216], 16;\n"
                     "cp.async.cg.shared.global [%0 + 9216], [%1 + 576], 16;\ncp.async.cg.shared.global [%0 + 9728], [%1 + 9792], 16;\n" ::"r"(xt), "l"(xp) : "memory");
    }
    uint32_t* const std_ = p.s->st + ((lane & 12) * 128 + odd * 256 + 4 * P + 2 * (lane & 1) + ((lane >> 1) & 1)) * 2;
    unsigned char* const ud = reinterpret_cast<unsigned char*>(p.s->uT) + (32 * (warp - UW) + 8 * (g >> 1) + (g & 1)) * 4096 + b * 32 + t * 8;
    if (warp == 0) {
        if (lane == 0) {
            mbar_init(bar_x, 1); mbar_init(bar_w, 1); mbar_init(bar_d, 1); mbar_init(bar_d + 16, 1); mbar_init(bar_g, 1); mbar_init(bar_h, 3); mbar_init(bar_r, 1);
            #pragma unroll
            for (int i = 1; i < 11; i++) mbar_init(bar_x + 8 * i, 4);
            asm volatile("fence.mbarrier_init.release.cluster;\n" ::: "memory");
            mbar_expect(bar_x, 16384); mbar_expect(bar_r, 8192);
            mbar_expect(bar_w, 2 * 41472); mbar_expect(bar_d, 32768 + 5120); mbar_expect(bar_d + 16, 8192); mbar_expect(bar_g, 9 * 512);
        }
        __syncwarp();
        bar_arrive(0, NWRK);
    }
    if (warp == 0 && elect_one()) tma_3d(sb + SM_XC, &tm_x, 8 * P, 0, 8 * odd, bar_x);
    asm volatile("barrier.cluster.arrive.relaxed.aligned;\n" ::: "memory");
    const uint32_t kw = sb + SM_KW + wg * KW_B;
    if (t128 < 2 * UPAD) sts128(sb + SM_U + wg * USLOT_B + (t128 & 1) * ULO_B + (t128 >> 1) * 16, 0u, 0u, 0u, 0u);
    sts128(kw + t128 * 16, 0u, 0u, 0u, 0u);
    if (t128 < KW_B / 16 - 128) sts128(kw + 2048 + t128 * 16, 0u, 0u, 0u, 0u);
    if (tid < 128) {
#pragma unroll
        for (int i = 0; i < 4; i++) sts128(sb + SM_ZERO + i * 2048 + tid * 16, 0u, 0u, 0u, 0u);
    }
    if (warp != 0) bar_sync(0, NWRK);
    STAMP(1);
    if (warp == 19 || warp == UW || warp == UW + 1) {
        if (warp == 19) {
            if (lane < 16) stg64(std_, 0u, 0u);
            if (lane < 9) asm volatile("prefetch.global.L2 [%0];\n" ::"l"(p.wr + lane * 64));
        } else {
#pragma unroll
            for (int k = 0; k < 4; k++) stg64(ud + k * 8192, 0u, 0u);
        }
    }
    uint32_t X[2][8];
    auto partial = [&]() {
        const uint32_t xt = sb + SM_XT + (warp - 10) * 1024 + lane * 16;
        asm volatile("cp.async.wait_all;\n" ::: "memory");
        STAMP(23);
        const uint4 a = lds128(xt), c = lds128(xt + 512), d = lds128(xt + 9216), e = lds128(xt + 9728);
        X[0][0] = a.x; X[0][1] = a.y; X[0][2] = a.z; X[0][3] = a.w; X[0][4] = d.x; X[0][5] = d.y; X[0][6] = d.z; X[0][7] = d.w;
        X[1][0] = c.x; X[1][1] = c.y; X[1][2] = c.z; X[1][3] = c.w; X[1][4] = e.x; X[1][5] = e.y; X[1][6] = e.z; X[1][7] = e.w;
        const uint32_t one[8] = {0x3f803f80u, 0x3f803f80u, 0x3f803f80u, 0x3f803f80u, 0x3f803f80u, 0x3f803f80u, 0x3f803f80u, 0x3f803f80u};
        ln_partial<8>(X, one, sb + SM_LNP, warp - 10, g, t);
        bar_arrive(6, 320);
        if (PAUSE & 1) bar_sync(7, PCNT);
    };
    if (LNAT == 0 && lnw) {
        partial();
        pl = prmt_v(pl, X[0][0], 0x3210u + (warp >> 8)); ldt = prmt_v(ldt, X[0][0], 0x3210u + (warp >> 8));
    }
    auto finish = [&]() {
        bar_sync(6, 320);
        float mb, rc;
        ln_finish<9>(sb + SM_LNP, lane, mb, rc);
        const float rh = rbf(rc);
        const uint32_t s0 = (__float_as_uint(mb) >> 16) | (((ep & 0x7fffu) + 1u) << 16), s1 = pack_bf16(rh, rc - rh);
        if (lane < 16) { stg64(std_, s0, s1); sts64(s_stat + lane * 8, s0, s1); }
        if (lane == 16) sts32(s_cnt + 4, ep);
        bar_arrive(7, PCNT);
        STAMP(28);
    };
    auto upub = [&]() {
        if (!(PAUSE & 6)) bar_sync(7, PCNT);
        const uint32_t utag = ((ep & 3u) + 1u) * 0x10001u;
        uint32_t U[2][4];
#pragma unroll
        for (int hf = 0; hf < 2; hf++) {
            const uint2 st = lds64(s_stat + (g + 8 * hf) * 8);
            const uint4 xv = lds128(sb + SM_XT + (16 + warp - UW) * 1024 + hf * 512 + lane * 16);
            const uint32_t xs[4] = {xv.x, xv.y, xv.z, xv.w};
#pragma unroll
            for (int k = 0; k < 4; k++) {
                const uint32_t u = ln_apply(xs[k], st);
                U[hf][k] = movm((pack_f16_rz(bf_lo(u), __uint_as_float(u)) & 0xfff8fff8u) | utag);
            }
        }
#pragma unroll
        for (int k = 0; k < 4; k++) stg64(ud + k * 8192, U[0][k], U[1][k]);
    };
    if (FINAT == 0 && warp == 19) finish();
    const uint32_t tb = table_buf(sb, warp);
    const float dt = rbf(expf(bf_lo(ldt)));
    KGen kg;
    kgen_setup(kg, pl | (pa2 << 16), dt);
    if (LNAT == 1 && lnw) {
        partial();
        kg.z8.x = __uint_as_float(prmt_v(__float_as_uint(kg.z8.x), X[0][0], 0x3210u + (warp >> 8)));
        kg.z1.x = __uint_as_float(prmt_v(__float_as_uint(kg.z1.x), X[0][0], 0x3210u + (warp >> 8)));
    }
    if (FINAT == 1 && warp == 19) finish();
    if (UAT == 0 && (warp == UW || warp == UW + 1)) upub();
    kgen_rows(kg, tb, lane);
    if (wg == 0) fence_async();
    if (LNAT == 2 && lnw) {
        partial();
        kg.z128.x = __uint_as_float(prmt_v(__float_as_uint(kg.z128.x), X[0][0], 0x3210u + (warp >> 8)));
        kg.z1.x = __uint_as_float(prmt_v(__float_as_uint(kg.z1.x), X[0][0], 0x3210u + (warp >> 8)));
    }
    if (FINAT == 2 && warp == 19) finish();
    if (UAT == 1 && (warp == UW || warp == UW + 1)) upub();
    STAMP(2);
    WPOINT(0, warp - 4);
    const int ce = c_exponent(call_re, call_im);
    if (t128 == 0) sts64(s_fs + wg * 8, (uint32_t)min(max(ce + (int)(__float_as_uint(dt) >> 23) - 116, 0), 254) * 0x800080u, dskl << 16);
    kgen_chain(kg, pc | (pi << 16), __uint_as_float(((uint32_t)(244 - ce) << 23) | (__float_as_uint(dt) & 0x7fffffu)));
    if ((PAUSE & 4) && warp < 10) bar_sync(7, PCNT);
    if (UAT == 4 && (warp == UW || warp == UW + 1)) upub();
    STAMP(3);
    WPOINT(1, warp - 6);
    kgen_cols(kg, tb, lane);
    if (LNAT == 3 && lnw) partial();
    if (FINAT == 3 && warp == 19) finish();
    if ((PAUSE & 2) && warp < 10) bar_sync(7, PCNT);
    if (UAT == 2 && (warp == UW || warp == UW + 1)) upub();
    STAMP(4);
    WPOINT(2, warp - 8);
    const uint4* usrc = wg < 4 ? reinterpret_cast<const uint4*>(p.s->st) + odd * 512 + (lane & 1) * 128 + 16 * (warp & 7) + (lane >> 1)
                               : reinterpret_cast<const uint4*>(p.s->uT) + P * 256 + 2 * t128;
    const int ustep = wg < 4 ? 256 : 1;
    uint4 uv0, uv1;
    kgen_mma(kg, tb, lane);
    if (UAT == 3 && (warp == UW || warp == UW + 1)) upub();
    STAMP(26);
    WPOINT(3, warp - 5);
    const uint32_t idn = 0x3210u + (warp >> 8);
    uint4 lt7 = make_uint4(prmt_v(KW_T2 + ((lane >> 3) & 1) * KW_KH + (33 + (lane & 7)) * 16 - (lane & 16), 0u, idn), t * 288 + g * 8 + 8, (lane & 1) * 4096 + (lane >> 1) * 16,
                                 prmt_v(8u << ((lane >> 3) + (lane & 4)) >> (lane & 3), 0u, idn));
    asm volatile("barrier.cluster.wait.acquire.aligned;\n" ::: "memory");
    const bool pe = (int)(clock32() - tk0) >= (wg < 4 ? TP0 : TP4);
    if (pe) { uv0 = ld_poll(usrc); uv1 = ld_poll(usrc + ustep); }
    bar_sync(1 + wg, 128);
    kgen_combine(sb, warp, lane, kw, lt7.y);
    if (warp < 3 || warp > 6) bar_arrive(14, NWRK);
    STAMP(5);
    WPOINT(4, warp - 7);
    if (!pe) {
        while ((int)(clock32() - tk0) < (wg < 4 ? TP0 : TP4)) {}
        uv0 = ld_poll(usrc); uv1 = ld_poll(usrc + ustep);
    }
    if (wg < 4) {
        mbar_wait(bar_x);
        const bool far = warp < 8;
        const uint32_t xa = sb + SM_XC + (warp & 7) * 256 + (odd ^ far) * 8 + lt7.z;
        uint2 xv[4] = {lds64(xa), lds64(xa + 8192), lds64(xa + 2048), lds64(xa + 10240)};
        const uint32_t tag = ((ep & 0x7fffu) + 1u) << 16;
        int it = 0;
        while (true) {
            const bool bad = (((uv0.x ^ tag) | (uv0.z ^ tag)) | ((uv1.x ^ tag) | (uv1.z ^ tag))) >> 16;
            if (!__any_sync(0xffffffffu, bad)) break;
            if (++it > SPIN_LIMIT) TRAP();
            if (bad) { uv0 = ld_poll(usrc); uv1 = ld_poll(usrc + 256); }
        }
        STAMP(6);
        DBG(wg, it);
        const uint2 st[4] = {make_uint2(uv0.x, uv0.y), make_uint2(uv0.z, uv0.w), make_uint2(uv1.x, uv1.y), make_uint2(uv1.z, uv1.w)};
#pragma unroll
        for (int i = 0; i < 4; i++) {
            xv[i].x = ln_apply(xv[i].x, st[i]);
            xv[i].y = ln_apply(xv[i].y, st[i]);
        }
        const uint32_t ub = sb + SM_U + UPAD * 16 + odd * ULO_B + (warp & 7) * 256 + lane * 8;
        const uint32_t w[4][2] = {{pack_f16(bf_lo(xv[0].x), bf_lo(xv[1].x)), pack_f16(bf_lo(xv[2].x), bf_lo(xv[3].x))}, {HI2(xv[0].x, xv[1].x), HI2(xv[2].x, xv[3].x)},
                                  {pack_f16(bf_lo(xv[0].y), bf_lo(xv[1].y)), pack_f16(bf_lo(xv[2].y), bf_lo(xv[3].y))}, {HI2(xv[0].y, xv[1].y), HI2(xv[2].y, xv[3].y)}};
#pragma unroll
        for (int i = 0; i < 4; i++) {
            if (far) asm volatile("st.async.shared::cluster.mbarrier::complete_tx::bytes.v2.b32 [%0], {%1,%2}, [%3];\n" ::"r"((ub ^ 0x1000000u) + i * USLOT_B), "r"(w[i][0]), "r"(w[i][1]), "r"(bar_r ^ 0x1000000u) : "memory");
            else sts64(ub + i * USLOT_B, w[i][0], w[i][1]);
        }
    } else {
        const uint32_t utag = ((ep & 3u) + 1u) * 0x10001u;
        int it = 0;
        while (true) {
            const bool bad = (((uv0.x ^ utag) | (uv0.y ^ utag) | (uv0.z ^ utag) | (uv0.w ^ utag)) | ((uv1.x ^ utag) | (uv1.y ^ utag) | (uv1.z ^ utag) | (uv1.w ^ utag))) & 0x70007u;
            if (!__any_sync(0xffffffffu, bad)) break;
            if (++it > SPIN_LIMIT) TRAP();
            if (bad) { uv0 = ld_poll(usrc); uv1 = ld_poll(usrc + 1); }
        }
        STAMP(6);
        DBG(4, it);
        const uint32_t ub = sb + SM_U + UPAD * 16 + 4 * USLOT_B + (t128 >> 1) * 32 + (t128 & 1) * 8;
        sts64(ub, prmt(uv0.x, uv0.z, 0x5410u) ^ utag, prmt(uv1.x, uv1.z, 0x5410u) ^ utag);
        sts64(ub + 16, prmt(uv0.x, uv0.z, 0x7632u) ^ utag, prmt(uv1.x, uv1.z, 0x7632u) ^ utag);
        sts64(ub + ULO_B, prmt(uv0.y, uv0.w, 0x5410u) ^ utag, prmt(uv1.y, uv1.w, 0x5410u) ^ utag);
        sts64(ub + ULO_B + 16, prmt(uv0.y, uv0.w, 0x7632u) ^ utag, prmt(uv1.y, uv1.w, 0x7632u) ^ utag);
    }
    lt7.w = prmt_v(lt7.w, uv0.x, idn);
    CONV_PRE
    if (warp < 3 && elect_one()) tma_st_3d(warp < 2 ? &tm_y : &tm_z, sb + SM_ZERO, warp < 2 ? 128 * b : 32 * (512 + P), 0, 2 * (warp < 2 ? warp : odd));
    if (warp >= 3 && warp <= 6) {
        bar_sync(14, NWRK);
        WPOINT(5, warp - 3);
    }
    bar_sync(1 + wg, 128);
    CONV_PRE2
    mbar_wait(bar_r);
    fence_async();
    bar_sync(0, NWRK);
    STAMP(7);
    uint32_t hv0 = 0;
    {
        WPOINT(6, 19 - warp);
        CONV_BODY
        WPOINT(7, 19 - warp);
        if (!B2L) bar_sync(0, NWRK); else if (wg != 3) bar_arrive(0, NWRK);
        STAMP(8);
        size_t ycopy = 0;
        auto hook = [&](auto gi) {
                     constexpr int G = decltype(gi)::value;
                     if (G == 4 && warp == HINTW) hv0 = ld_poll32(p.s->hint + (lane_v() & 7) * 32);
                     if (G == 4) mbar_wait(bar_h);
                     if (G == 1 || G == 2) WPOINT(7 + G, warp - 16);
                     if (G == 3) { WPOINT(10, warp - 12); WPOINT(12, warp - 8); WPOINT(14, warp - 4); }
                     if (G == 5) { WPOINT(11, warp - 13); WPOINT(13, warp - 9); WPOINT(15, warp - 5); }
                     if (G == 1 && warp >= 17 && elect_one())
                         bulk_s2g(warp == 17 ? p.s->part + b * (PBYTES / 4) : warp == 18 ? p.s->rows + b * 1152 : p.s->sc + b * 32, sb + SM_ZERO, warp == 17 ? PBYTES : warp == 18 ? 4608 : 32);
                     if (G == 4 && warp >= 17 && elect_one()) {
                         asm volatile("cp.async.bulk.wait_group 0;\n" ::: "memory");
                         hint_arrive(p.s->hint, 2, b & 7);
                     }
                     if (G == 1 && warp < 3) {
                         if (elect_one()) {
                             asm volatile("cp.async.bulk.wait_group 0;\n" ::: "memory");
                             mbar_arrive(bar_h);
                             hint_arrive(p.s->hint, 0, b & 7);
                         }
                         __syncwarp();
                         STAMP(17);
                     }
                 };
        conv_main(c, acc, sb, sel, reinterpret_cast<unsigned char*>(p.s->y), warp, ycopy, hook);
        STAMP(10);
    }
    {
    const int warp = warp_v(), lane = lane_v(), tid = 32 * warp + lane, g = lane >> 2, t = lane & 3;
    if (warp == HINTW) {
        const uint32_t target = (lds32(s_cnt + 4) + 1u) * 48u;
        if (__any_sync(0xffffffffu, (int)(hv0 - target) < 0)) hint_wait(p.s->hint, 0, target);
    }
    const unsigned char* ys = reinterpret_cast<const unsigned char*>(p.s->y) + ((size_t)P * DM + 32 * warp + 8 * (g >> 1) + (g & 1)) * 64 + odd * 32 + t * 8;
    STAMP(27);
    bar_sync(0, NWRK);
    STAMP(11);
    const uint32_t zr = warp >> 8;
    auto late_rows = [&](auto pub) {
        const uint32_t k = lds32(s_key + (lane & 7) * 4), ep = lds32(s_cnt + 4);
        const bool late = k & 256u, mine = late && ((k & 255u) >> 1) == (uint32_t)b;
        uint32_t todo = __ballot_sync(0xffffffffu, mine) & 0xffu;
        if (todo) {
#pragma unroll 1
            while (todo) {
                const int s = __ffs(todo) - 1, row = (__shfl_sync(0xffffffffu, k, s) >> 9) & 15;
                todo &= todo - 1;
                if ((row & 7) == g) pub(row & 8, 2 * NCTA + s);
            }
            __threadfence();
            bar_sync(0, NWRK);
            if (tid < NSEL && mine) *reinterpret_cast<volatile unsigned*>(p.s->flag + tid) = ep + 1u;
        }
        int it = 0;
        while (__any_sync(0xffffffffu, late && ld_poll32(p.s->flag + (lane & 7)) != ep + 1u)) { if (++it > SPIN_LIMIT) TRAP(); }
        __threadfence();
        const int gs = tid / 36;
        const uint4* src = reinterpret_cast<const uint4*>(p.s->rows) + __shfl_sync(0xffffffffu, late ? 2 * NCTA + (lane & 7) : (k & 255u), gs & 7) * 144 + 36 * odd + (tid - gs * 36);
        if (tid < 288) {
            uint4 v0;
            do { v0 = ld_poll(src); if (++it > SPIN_LIMIT) TRAP(); } while (!v0.x);
            sts128(sb + SM_XS + gs * XS_PITCH + (tid - gs * 36) * 16, v0.x, v0.y, v0.z, v0.w);
        }
        bar_sync(0, NWRK);
    };
    if (warp >= 18) {
        if (warp == 18) {
            uint32_t* const kp = pin(p.s->sc + 32 * b, zr);
            const uint32_t kid = pin(0x30000000u | ((lane & 15) << 9) | 2 * b, zr), ka = pin(s_k16 + (lane & 15) * 4, zr), kb = pin(s_k16 + (lane & 16) * 2, zr);
            bar_sync(8, 640);
            float mb, rc;
            ln_finish<18>(sb + SM_LNP, lane, mb, rc);
            if (lane < 16) stat_store(s_stat + lane * 8, mb, rc, 0u);
            bar_arrive(13, 608);
            bar_sync(10, 608);
            const float r = sum18(sb + SM_LNP + (32 + (lane & 15)) * 80);
            const uint32_t bits = pack_bf16(0.f, r);
            const uint32_t me = (((bits ^ ((uint32_t)((int)bits >> 31) & 0x7fffffffu)) >> 3) & 0x1fffe000u) ^ kid;
            sts32(ka, me);
            __syncwarp();
            const uint4 v = lds128(kb), w = lds128(kb + 16);
#define GT(x) ((me - (x)) >> 31)
            uint32_t rank = pin(GT(v.x) + GT(v.y) + GT(v.z), zr) + pin(GT(v.w) + GT(w.x) + GT(w.y), zr) + pin(GT(w.z) + GT(w.w), zr);
#undef GT
            rank += __shfl_xor_sync(0xffffffffu, rank, 16);
            if (lane < 16) { if (rank < 8) stg32(kp + rank, me + (rank < 2 ? rank : 256u)); }
            else sts32(ka + (s_wm - s_k16), rank);
            bar_arrive(11, 640);
            weight_units<19, 0>(sb, wm, 0); weight_units<19, 1>(sb, wm, 1);
        }
        const uint4* ksrc = pin(reinterpret_cast<const uint4*>(p.s->sc) + 8 * lane, zr);
        const uint4* rsrc = pin(reinterpret_cast<const uint4*>(p.s->rows) + 36 * odd + t, zr);
        if (warp == 19) {
            weight_units<20, 0>(sb, wm, 0); weight_units<20, 1>(sb, wm, 1);
            bar_sync(8, 640);
            weight_units<16, 0>(sb, wm, 0); weight_units<16, 1>(sb, wm, 1);
            hint_wait(p.s->hint, 2, (lds32(s_cnt + 4) + 1u) * 48u);
            bar_sync(11, 640);
        }
        bool slow = false;
        int it = 0;
        if (warp == 19) {
        uint4 q[4];
        DELAY(KDEL);
#pragma unroll
        for (int i = 0; i < 4; i++) q[i] = ld_poll(ksrc + 256 * i);
        while (true) {
            uint32_t a[4];
#pragma unroll
            for (int i = 0; i < 4; i++) a[i] = q[i].x & q[i].y & q[i].z & q[i].w;
            if (__all_sync(0xffffffffu, a[0] & a[1] & a[2] & a[3])) break;
#pragma unroll
            for (int i = 0; i < 4; i++)
                if (!a[i]) q[i] = ld_poll(ksrc + 256 * i);
            if (++it > SPIN_LIMIT) TRAP();
        }
        bar_arrive(9, 608);
        STAMP(16);
        auto merge = [](const uint4& x, const uint4& y) {
            const uint32_t a = max(x.x, y.w), c = max(x.y, y.z), d = max(x.z, y.y), e = max(x.w, y.x);
            const uint32_t a2 = max(a, d), d2 = min(a, d), c2 = max(c, e), e2 = min(c, e);
            return make_uint4(max(a2, c2), min(a2, c2), max(d2, e2), min(d2, e2));
        };
        uint4 h = merge(merge(q[0], q[1]), merge(q[2], q[3]));
        uint4 v[9];
        uint32_t key = 0;
#pragma unroll
        for (int s = 0; s < 8; s++) {
            const uint32_t m = __reduce_max_sync(0xffffffffu, h.x);
            const bool w = h.x == m;
            h.x = w ? h.y : h.x; h.y = w ? h.z : h.y; h.z = w ? h.w : h.z; h.w = w ? 0u : h.w;
            if (g == s) key = m;
        }
        rsrc += (key & 255u) * 144;
#pragma unroll
        for (int j = 0; j < 9; j++) v[j] = ld_poll(rsrc + 4 * j);
        slow = __any_sync(0xffffffffu, key & 256u);
        STAMP(18);
        if (__any_sync(0xffffffffu, h.x == 0u)) {
            uint4 r[4];
            it = 0;
            while (true) {
#pragma unroll
                for (int i = 0; i < 4; i++) r[i] = ld_poll(ksrc + 256 * i + 1);
                if (__all_sync(0xffffffffu, all_nz(r[0]) && all_nz(r[1]) && all_nz(r[2]) && all_nz(r[3]))) break;
                if (++it > SPIN_LIMIT) TRAP();
            }
            uint32_t m = 1u << 30;
#pragma unroll 1
            for (int s = 0; s < 8; s++) {
                uint32_t x = 0;
#pragma unroll
                for (int i = 0; i < 4; i++) {
                    x = max(max(max(x, q[i].x - m), max(q[i].y - m, q[i].z - m)), q[i].w - m);
                    x = max(max(max(x, r[i].x - m), max(r[i].y - m, r[i].z - m)), r[i].w - m);
                }
                m += __reduce_max_sync(0xffffffffu, x);
                if (g == s) key = m;
            }
            slow = true;
        }
        const uint32_t xsa = sb + SM_XS + g * XS_PITCH + t * 16;
        sts32(s_key + g * 4, key);
        sts32(xsa, 0u);
        bar_arrive(12, 608);
#pragma unroll
        for (int j = 0; j < 9; j++) sts128(xsa + j * 64, v[j].x, v[j].y, v[j].z, v[j].w);
        slow = slow || min(min(min(min(v[0].x, v[1].x), v[2].x), min(min(v[3].x, v[4].x), v[5].x)), min(min(v[6].x, v[7].x), v[8].x)) == 0u;
        }
        if (bar_or(0, NWRK, slow)) late_rows([](bool, int) {});
        STAMP(19);
        const int fl = 16 * (b & 1) + ((tid >> 2) & 15), fc = 16 * (b >> 1) + (fl >> 2) + 8 * ((tid >> 1) & 1), fsl = 2 * (fl & 3) + (tid & 1);
        const uint32_t kk = lds32(s_key + fsl * 4);
        const uint32_t* fsrc = p.s->rows + ((kk & 256u) ? 2 * NCTA + fsl : (kk & 255u)) * DM + (fc >> 1);
        uint32_t hw = 1u, uw = 1u;
        if (b < 72) { uw = ld_poll32(fsrc); hw = ld_poll32(fsrc + 288); }
        if (b < 72) {
            it = 0;
            while (!hw || !uw) { uw = ld_poll32(fsrc); hw = ld_poll32(fsrc + 288); if (++it > SPIN_LIMIT) TRAP(); }
            const int row = (kk >> 9) & 15, ftok = 8 * (kk & 252u) + (kk & 2u) + TOKEN_OF(row & 7) + (row & 8);
            const unsigned k16 = (kk >> 13) & 0xffffu;
            const unsigned bits = (k16 & 0x8000u) ? (k16 & 0x7fffu) : (~k16 & 0xffffu);
            const float rs = 512.0f * rbf(__fdividef(1.0f, 1.0f + __expf(-__uint_as_float(bits << 16))));
            bf16* const op = p.out + (unsigned)(ftok * DM + fc);
            const float uv = (fc & 1) ? bf_hi(uw) : bf_lo(uw), hv = (fc & 1) ? bf_hi(hw) : bf_lo(hw);
            const uint32_t a = sb + SM_FIN + (tid - 576) * 80;
            sts128(a + 64, __float_as_uint(rs), __float_as_uint(uv), __float_as_uint(hv), (uint32_t)(size_t)op ^ (uint32_t)((size_t)op >> 32));
            bar_sync(14, 576);
            const uint4 p0 = lds128(a), p1 = lds128(a + 16), p2 = lds128(a + 32), p3 = lds128(a + 48);
#define F4(p) ((__uint_as_float(p.x) + __uint_as_float(p.y)) + (__uint_as_float(p.z) + __uint_as_float(p.w)))
            const float v0 = F4(p0), v1 = F4(p1), v2 = F4(p2), v3 = F4(p3);
#undef F4
            const float y3 = rbf(rbf((v0 + v1) + (v2 + v3)) * rs);
            asm volatile("st.global.u16 [%0], %1;\n" ::"l"(op), "h"((unsigned short)pack_bf16(hv + rbf(uv + y3), 0.f)) : "memory");
        }
        if (b == 0 && tid >= 632) *reinterpret_cast<volatile unsigned*>(p.s->hint + (tid & 7) * 32 + 1) = lds32(s_cnt + 4) + 1u;
    } else {
        uint32_t H[2][4], U2[2][4], WA[9][4], WD[18], WE[18];
        const int fkh = warp >= 9, fmt = warp - 9 * fkh;
        auto load_wa = [&](auto k0, auto k1) {
            if (k0.value >= k1.value) return;
            if (k0.value == 0) mbar_wait(bar_w);
            const int mi = lane >> 3, rr = lane & 7;
            const int row = fkh * 144 + rr + 8 * (mi >> 1);
            const uint32_t aad = sb + (fmt < 8 ? SM_WG + (mi & 1) * (SM_WU - SM_WG) + row * 128 + (fmt ^ rr) * 16 : SM_WR + (mi & 1) * 4608 + row * 16), ks = fmt < 8 ? 2048 : 256;
#pragma unroll
            for (int k = k0.value; k < k1.value; k++) ldsm_x4_t(WA[k][0], WA[k][1], WA[k][2], WA[k][3], aad + k * ks);
        };
        auto load_wd = [&](uint32_t (&WD)[18], int tile) {
            mbar_wait(bar_d);
            if (tile & 16) mbar_wait(bar_d + 16);
            const int mi = lane >> 3, rr = lane & 7;
            const uint32_t base = sb + SM_WD + rr * 128 + (((2 * tile + (mi & 1)) & 7) ^ rr) * 16;
#pragma unroll
            for (int k = 0; k < 4; k++) ldsm_x4_t(WD[4 * k], WD[4 * k + 1], WD[4 * k + 2], WD[4 * k + 3], base + (tile >> 2) * 8192 + (k * 16 + 8 * (mi >> 1)) * 128);
            ldsm_x2_t(WD[16], WD[17], base + 40960 + (tile >> 2) * 1024);
        };
        auto publish = [&](bool hi, int slot) {
            uint4* rowp = reinterpret_cast<uint4*>(p.s->rows) + slot * 144 + warp * 4 + t;
            stg128(rowp, nzw(hi ? U2[1][0] : U2[0][0]), nzw(hi ? U2[1][1] : U2[0][1]), nzw(hi ? U2[1][2] : U2[0][2]), nzw(hi ? U2[1][3] : U2[0][3]));
            stg128(rowp + 72, nzw(hi ? H[1][0] : H[0][0]), nzw(hi ? H[1][1] : H[0][1]), nzw(hi ? H[1][2] : H[0][2]), nzw(hi ? H[1][3] : H[0][3]));
        };
        uint4 wr = make_uint4(0x3f803f80u, 0x3f803f80u, 0x3f803f80u, 0x3f803f80u);
        {
            uint2 yv[4];
#pragma unroll
            for (int k = 0; k < 4; k++) yv[k] = ld_poll64(ys + k * 128);
            if (g == 0) wr = ldg128(p.wr + 32 * warp + 8 * t);
            const uint4 x0 = lds128(sb + SM_XT + warp * 1024 + lane * 16), x1 = lds128(sb + SM_XT + warp * 1024 + 512 + lane * 16);
            load_wa(IC<0>(), IC<WA0>());
            int it = 0;
            while (!__all_sync(0xffffffffu, yv[0].x && yv[1].x && yv[2].x && yv[3].x)) {
#pragma unroll
                for (int k = 0; k < 4; k++) yv[k] = ld_poll64(ys + k * 128);
                if (++it > SPIN_LIMIT) TRAP();
            }
            STAMP(12);
            const uint32_t Z[2][4] = {{x0.x, x0.y, x0.z, x0.w}, {x1.x, x1.y, x1.z, x1.w}};
#pragma unroll
            for (int k = 0; k < 4; k++) {
                H[0][k] = hadd2_bf(Z[0][k], movm(yv[k].x));
                H[1][k] = hadd2_bf(Z[1][k], movm(yv[k].y));
            }
            const uint32_t bw[4] = {wr.x, wr.y, wr.z, wr.w};
            ln_partial<4>(H, bw, sb + SM_LNP, warp, g, t);
        }
        bar_arrive(8, 640);
        load_wa(IC<WA0>(), IC<WA1>());
        STAMP(13);
        bar_sync(13, 608);
        STAMP(14);
#pragma unroll
        for (int hf = 0; hf < 2; hf++) {
            const uint2 st = lds64(s_stat + (g + 8 * hf) * 8);
#pragma unroll
            for (int k = 0; k < 4; k++) U2[hf][k] = ln_apply(H[hf][k], st);
        }
        {
            float cs[4] = {0.f, 0.f, 0.f, 0.f};
            mma_bf16(cs, U2[0][0], U2[1][0], U2[0][1], U2[1][1], wr.x, wr.y);
            mma_bf16(cs, U2[0][2], U2[1][2], U2[0][3], U2[1][3], wr.z, wr.w);
            if (t == 0) { stsf(sb + SM_LNP + ((32 + g) * 20 + warp) * 4, cs[0]); stsf(sb + SM_LNP + ((40 + g) * 20 + warp) * 4, cs[2]); }
            bar_arrive(10, 608);
        }
        load_wa(IC<WA1>(), IC<WA2>());
        bar_sync(11, 640);
        {
            const uint32_t rk[2] = {lds32(s_wm + g * 4), lds32(s_wm + 32 + g * 4)};
            uint32_t lo = min(rk[0], rk[1]), hi = max(rk[0], rk[1]);
#pragma unroll 1
            while (lo < 2) { publish(lo == rk[1], 2 * b + lo); lo = hi; hi = 16; }
        }
        load_wa(IC<WA2>(), IC<WA3>());
        bar_sync(9, 608);
        load_wa(IC<WA3>(), IC<9>());
#pragma unroll
        for (int hf = 0; hf < 2; hf++)
            sts128(sb + SM_OUT + (g + 8 * hf) * OUT_PITCH + warp * 64 + t * 16,
                   hadd2_bf(H[hf][0], U2[hf][0]), hadd2_bf(H[hf][1], U2[hf][1]), hadd2_bf(H[hf][2], U2[hf][2]), hadd2_bf(H[hf][3], U2[hf][3]));
        fence_async();
        WPOINT(17, warp - 16);
        if ((WDAT == 0 || (WDAT == 2 && fkh)) && (warp < 16 || !odd)) load_wd(WD, warp);
        const uint32_t bad = pin(sb + SM_XS + (lane & 7) * XS_PITCH + (fkh * 144 + 8 * (lane >> 3)) * 2, zr), ex = pin(sb + SM_EX + warp * 512 + lane * 16, zr);
        uint32_t* pp = pin(p.s->part + ((size_t)(2 * (20 * odd + warp) + (lane >> 4)) * 64 + P) * 32 + (lane & 15) * 2, zr);
        bar_sync(12, 608);
        if (warp < 16 && !__any_sync(0xffffffffu, (lds32(s_key + (lane & 7) * 4) & 0x1efeu) == (uint32_t)((warp << 9) | 2 * b)) && elect_one())
            bulk_s2g(p.out + (size_t)(32 * P + 2 * odd + TOKEN_OF(warp & 7) + (warp & 8)) * DM, sb + SM_OUT + warp * OUT_PITCH, DM * 2);
        WPOINT(18, warp - 16);
        STAMP(15);
        if (bar_or(0, NWRK, false)) late_rows(publish);
        STAMP(19);
        float gp[4];
        {
            float c4[3][4];
#pragma unroll
            for (int i = 0; i < 3; i++)
#pragma unroll
                for (int j = 0; j < 4; j++) c4[i][j] = 0.f;
#pragma unroll
            for (int k = 0; k < 10; k += 2) {
                uint32_t b0, b1, b2, b3;
                ldsm_x4(b0, b1, b2, b3, bad + k * 32);
                mma_bf16(c4[k % 3], WA[k][0], WA[k][1], WA[k][2], WA[k][3], b0, b1);
                if (k < 8) mma_bf16(c4[(k + 1) % 3], WA[k + 1][0], WA[k + 1][1], WA[k + 1][2], WA[k + 1][3], b2, b3);
            }
#pragma unroll
            for (int j = 0; j < 4; j++) gp[j] = c4[0][j] + (c4[1][j] + c4[2][j]);
            if (warp >= 9) {
                sts128f(ex, gp);
                bar_arrive(6, 576);
            } else {
                bar_sync(6, 576);
                const uint4 o = lds128(ex + 4608);
                gp[0] += __uint_as_float(o.x); gp[1] += __uint_as_float(o.y); gp[2] += __uint_as_float(o.z); gp[3] += __uint_as_float(o.w);
                asm volatile("st.async.shared::cluster.mbarrier::complete_tx::bytes.v4.b32 [%0], {%1,%2,%3,%4}, [%5];\n"
                             ::"r"(ex ^ 0x1000000u), "r"(__float_as_uint(gp[0])), "r"(__float_as_uint(gp[1])), "r"(__float_as_uint(gp[2])), "r"(__float_as_uint(gp[3])), "r"(bar_g ^ 0x1000000u) : "memory");
                if (WDAT == 2) load_wd(WD, warp);
            }
            if (WDAT == 1 && (warp < 16 || !odd)) load_wd(WD, warp);
            if (warp >= 16 && !odd) load_wd(WE, warp + 2);
        }
        STAMP(20);
        if (warp < 9) {
            mbar_wait(bar_g);
            const uint4 u = lds128(ex);
            const uint32_t G = pack_bf16(gp[0] + __uint_as_float(u.x), gp[1] + __uint_as_float(u.y)), U = pack_bf16(gp[2] + __uint_as_float(u.z), gp[3] + __uint_as_float(u.w));
            const float G0 = bf_lo(G), G1 = bf_hi(G);
            sts32(sb + SM_GU + tid * 4, hmul2_bf(pack_bf16(G0 * rcp_approx(1.0f + ex2_approx(G0 * -1.4426950408889634f)), G1 * rcp_approx(1.0f + ex2_approx(G1 * -1.4426950408889634f))), U));
        }
        bar_sync(7, 576);
        STAMP(21);
        if (warp < 16 || !odd) {
            uint32_t gb[9];
            ldsm_x4_t(gb[0], gb[1], gb[2], gb[3], sb + SM_GU + lane * 16);
            ldsm_x4_t(gb[4], gb[5], gb[6], gb[7], sb + SM_GU + 512 + lane * 16);
            ldsm_x1_t(gb[8], sb + SM_GU + 1024 + (lane & 7) * 16);
            auto down = [&](const uint32_t (&W)[18], uint32_t* dst) {
                float c4[4] = {0.f, 0.f, 0.f, 0.f}, d4[4] = {0.f, 0.f, 0.f, 0.f}, e4[4] = {0.f, 0.f, 0.f, 0.f};
                mma_bf16(c4, W[0], W[1], W[2], W[3], gb[0], gb[1]);
                mma_bf16(d4, W[4], W[5], W[6], W[7], gb[2], gb[3]);
                mma_bf16(e4, W[8], W[9], W[10], W[11], gb[4], gb[5]);
                mma_bf16_k8(c4, W[16], W[17], gb[8]);
                mma_bf16(d4, W[12], W[13], W[14], W[15], gb[6], gb[7]);
                const float v0 = (c4[0] + e4[0]) + d4[0], v1 = (c4[1] + e4[1]) + d4[1], v2 = (c4[2] + e4[2]) + d4[2], v3 = (c4[3] + e4[3]) + d4[3];
                const uint32_t e = max(max(__float_as_uint(fmaxf(fabsf(v0), fabsf(v1))), __float_as_uint(fmaxf(fabsf(v2), fabsf(v3)))), 16u << 23) >> 23;
                const float sc = __uint_as_float((245u - e) << 23);
                stg64(dst, pack_f16(v0 * sc, v1 * sc) | ((e * 0x8002000u) & 0x60006000u), pack_f16(v2 * sc, v3 * sc) | ((e * 0x800200u) & 0x60006000u));
            };
            if (warp >= 16) { down(WE, pp + 4 * 64 * 32); down(WD, pp); }
            else down(WD, pp);
        }
        asm volatile("cp.async.bulk.wait_group.read 0;\n" ::: "memory");
        STAMP(22);
        if (b < 72 && warp < 16) {
            const uint2* src = reinterpret_cast<const uint2*>(p.s->part) + (unsigned)(b * 1024 + tid);
            uint2 a, c;
            int it = 0;
            DELAY(PDEL);
            a = ld_poll64(src); c = ld_poll64(src + 512);
            while (!__all_sync(0xffffffffu, a.y && c.y)) {
                a = ld_poll64(src); c = ld_poll64(src + 512);
                if (++it > SPIN_LIMIT) TRAP();
            }
            STAMP(24);
            const float ea = __uint_as_float((((a.y & 0x60006000u) | ((a.x >> 4) & 0x06000600u)) * 0x4001u) & 0x7f800000u);
            const float ec = __uint_as_float((((c.y & 0x60006000u) | ((c.x >> 4) & 0x06000600u)) * 0x4001u) & 0x7f800000u);
            a.x &= 0x9fff9fffu; a.y &= 0x9fff9fffu; c.x &= 0x9fff9fffu; c.y &= 0x9fff9fffu;
            const float s0 = fmaf(h_lo(a.x), ea, h_lo(c.x) * ec), s1 = fmaf(h_hi(a.x), ea, h_hi(c.x) * ec), s2 = fmaf(h_lo(a.y), ea, h_lo(c.y) * ec), s3 = fmaf(h_hi(a.y), ea, h_hi(c.y) * ec);
            const bool up = lane & 16;
            const float r0 = __shfl_xor_sync(0xffffffffu, up ? s0 : s2, 16), r1 = __shfl_xor_sync(0xffffffffu, up ? s1 : s3, 16);
            const uint32_t fa = sb + SM_FIN + ((lane & 15) * 4 + (up ? 2 : 0)) * 80 + warp * 4;
            stsf(fa, (up ? s2 : s0) + r0); stsf(fa + 80, (up ? s3 : s1) + r1);
            bar_arrive(14, 576);
        }
    }
    STAMP(25);
    }
}

typedef CUresult (*PFN_tmEncode)(CUtensorMap*, CUtensorMapDataType, cuuint32_t, void*, const cuuint64_t*, const cuuint64_t*, const cuuint32_t*,
                                 const cuuint32_t*, CUtensorMapInterleave, CUtensorMapSwizzle, CUtensorMapL2promotion, CUtensorMapFloatOOBfill);

extern "C" void kernel_launch(void* const* d_in, const int* in_sizes, int n_in, void* d_out, int out_size) {
    Params p;
    p.x = (const bf16*)d_in[0];
    p.lar = (const bf16*)d_in[1];
    p.aim = (const bf16*)d_in[2];
    p.cre = (const bf16*)d_in[3];
    p.cim = (const bf16*)d_in[4];
    p.ldt = (const bf16*)d_in[5];
    p.dsk = (const bf16*)d_in[6];
    p.wr = (const bf16*)d_in[8];
    p.out = (bf16*)d_out;
    static PFN_tmEncode enc = nullptr;
    static void* scratch = nullptr;
    if (!enc) {
        cudaFuncSetAttribute(fused_kernel, cudaFuncAttributeMaxDynamicSharedMemorySize, SMEM_TOTAL);
        void* fn = nullptr;
        cudaDriverEntryPointQueryResult qr;
        cudaGetDriverEntryPoint("cuTensorMapEncodeTiled", &fn, cudaEnableDefault, &qr);
        enc = (PFN_tmEncode)fn;
        cudaGetSymbolAddress(&scratch, g_scratch);
    }
    p.s = (Scratch*)scratch;
    WMaps wm;
    CUtensorMap tm_x, tm_y, tm_z;
    const cuuint64_t dims[2] = {FF, DM}, strides[1] = {FF * 2}, rdims[3] = {FF, 144, 4}, rstrides[2] = {FF * 2, 144 * FF * 2};
    const cuuint32_t box[2] = {64, 72}, rbox[3] = {8, 144, 2}, es3[3] = {1, 1, 1};
    for (int i = 0; i < 2; i++) {
        enc(i ? &wm.u : &wm.g, CU_TENSOR_MAP_DATA_TYPE_BFLOAT16, 2, d_in[9 + i], dims, strides, box, es3, CU_TENSOR_MAP_INTERLEAVE_NONE, CU_TENSOR_MAP_SWIZZLE_128B,
            CU_TENSOR_MAP_L2_PROMOTION_NONE, CU_TENSOR_MAP_FLOAT_OOB_FILL_NONE);
        enc(i ? &wm.ur : &wm.gr, CU_TENSOR_MAP_DATA_TYPE_BFLOAT16, 3, d_in[9 + i], rdims, rstrides, rbox, es3, CU_TENSOR_MAP_INTERLEAVE_NONE, CU_TENSOR_MAP_SWIZZLE_NONE,
            CU_TENSOR_MAP_L2_PROMOTION_NONE, CU_TENSOR_MAP_FLOAT_OOB_FILL_NONE);
    }
    const cuuint64_t ddims[2] = {DM, FF}, dstrides[1] = {DM * 2}, edims[3] = {64, FF, 9}, estrides[2] = {DM * 2, 128};
    const cuuint32_t dbox[2] = {64, 64}, ebox[3] = {64, 8, 5};
    enc(&wm.d, CU_TENSOR_MAP_DATA_TYPE_BFLOAT16, 2, d_in[11], ddims, dstrides, dbox, es3, CU_TENSOR_MAP_INTERLEAVE_NONE, CU_TENSOR_MAP_SWIZZLE_128B,
        CU_TENSOR_MAP_L2_PROMOTION_NONE, CU_TENSOR_MAP_FLOAT_OOB_FILL_NONE);
    enc(&wm.dr, CU_TENSOR_MAP_DATA_TYPE_BFLOAT16, 3, d_in[11], edims, estrides, ebox, es3, CU_TENSOR_MAP_INTERLEAVE_NONE, CU_TENSOR_MAP_SWIZZLE_128B,
        CU_TENSOR_MAP_L2_PROMOTION_NONE, CU_TENSOR_MAP_FLOAT_OOB_FILL_NONE);
    const cuuint64_t xdims[3] = {DM, LSEQ / 16, 16}, xstrides[2] = {16 * DM * 2, DM * 2};
    const cuuint32_t xbox[3] = {8, LSEQ / 16, 8};
    enc(&tm_x, CU_TENSOR_MAP_DATA_TYPE_BFLOAT16, 3, d_in[0], xdims, xstrides, xbox, es3, CU_TENSOR_MAP_INTERLEAVE_NONE, CU_TENSOR_MAP_SWIZZLE_NONE,
        CU_TENSOR_MAP_L2_PROMOTION_NONE, CU_TENSOR_MAP_FLOAT_OOB_FILL_NONE);
    const cuuint64_t ydims[3] = {DM * 32, 16, 4}, ystrides[2] = {DM * 64, 16 * DM * 64};
    const cuuint32_t ybox[3] = {128, 16, 2}, zbox[3] = {32, 16, 2};
    enc(&tm_y, CU_TENSOR_MAP_DATA_TYPE_BFLOAT16, 3, p.s->y, ydims, ystrides, ybox, es3, CU_TENSOR_MAP_INTERLEAVE_NONE, CU_TENSOR_MAP_SWIZZLE_NONE,
        CU_TENSOR_MAP_L2_PROMOTION_NONE, CU_TENSOR_MAP_FLOAT_OOB_FILL_NONE);
    enc(&tm_z, CU_TENSOR_MAP_DATA_TYPE_BFLOAT16, 3, p.s->y, ydims, ystrides, zbox, es3, CU_TENSOR_MAP_INTERLEAVE_NONE, CU_TENSOR_MAP_SWIZZLE_NONE,
        CU_TENSOR_MAP_L2_PROMOTION_NONE, CU_TENSOR_MAP_FLOAT_OOB_FILL_NONE);
    fused_kernel<<<NCTA, NTHR, SMEM_TOTAL>>>(p, wm, tm_x, tm_y, tm_z);
}
```

```cpp
#include <cuda_runtime.h>
#include <cuda.h>
#include <cuda_fp16.h>
#include <cuda_bf16.h>
#include <stdint.h>

#define LSEQ 2048
#define DM 576
#define NST 128
#define FF 4608
#define NSEL 8
#define NCTA 128
#define NTHR 640
#define NWRK 640

typedef __nv_bfloat16 bf16;

#define SM_WD 0
#define SM_WG 46080
#define SM_WR 82944
#define SM_WU 92160
#define SM_ZERO 32768
#define SM_XC 16384
#define SM_TB 96000
#define SM_PL 129024
#define PL_B 10752
#define SM_XT (SM_TB + 20 * TBW)
#define SM_U (SM_XT + 18432)
#define UPAD 8
#define ULO_B ((UPAD + 128) * 16)
#define USLOT_B (2 * ULO_B)
#define SM_KW (SM_U + 5 * USLOT_B)
#define KW_B 3600
#define KW_T2 1152
#define KW_KH 656
#define KW_T3 2464
#define SM_MISC (SM_KW + 5 * KW_B)
#define SM_LNP (SM_MISC + 576)
#define SMEM_TOTAL (SM_LNP + 3840)
#define TBP 112
#define TBW (32 * TBP)
#define SM_OUT SM_PL
#define OUT_PITCH 1216
#define SM_XS (SM_PL + 19456)
#define XS_PITCH 592
#define SM_EX (SM_PL + 24320)
#define SM_FIN SM_KW
#define SM_GU (SM_PL + 33536)

struct __align__(128) Scratch {
    unsigned hint[8 * 32];
    unsigned flag[32];
    uint32_t sc[NCTA * 32];
    uint32_t st[LSEQ * 2];
    uint32_t uT[64 * (LSEQ / 2)];
    uint32_t y[NCTA * DM * 8];
    uint32_t part[72 * 64 * 32];
    uint32_t rows[(2 * NCTA + NSEL) * DM];
};
__device__ Scratch g_scratch;
#define STAMP(i)
#define DBG(i, v)

__device__ __forceinline__ float rbf(float x) {
    uint32_t r;
    asm("cvt.rn.bf16x2.f32 %0, %1, %2;\n" : "=r"(r) : "f"(x), "f"(0.f));
    return __uint_as_float(r);
}
__device__ __forceinline__ uint32_t pack_bf16(float lo, float hi) {
    uint32_t r;
    asm("cvt.rn.bf16x2.f32 %0, %1, %2;\n" : "=r"(r) : "f"(hi), "f"(lo));
    return r;
}
__device__ __forceinline__ uint32_t pack_f16(float lo, float hi) {
    uint32_t r;
    asm("cvt.rn.f16x2.f32 %0, %1, %2;\n" : "=r"(r) : "f"(hi), "f"(lo));
    return r;
}
__device__ __forceinline__ uint32_t pack_f16_rz(float lo, float hi) {
    uint32_t r;
    asm("cvt.rz.f16x2.f32 %0, %1, %2;\n" : "=r"(r) : "f"(hi), "f"(lo));
    return r;
}
__device__ __forceinline__ float bf_lo(uint32_t w) { return __uint_as_float(w << 16); }
__device__ __forceinline__ float bf_hi(uint32_t w) { return __uint_as_float(w & 0xffff0000u); }
__device__ __forceinline__ uint32_t hadd2_bf(uint32_t a, uint32_t b) {
    __nv_bfloat162 r = __hadd2_rn(*reinterpret_cast<__nv_bfloat162*>(&a), *reinterpret_cast<__nv_bfloat162*>(&b));
    return *reinterpret_cast<uint32_t*>(&r);
}
__device__ __forceinline__ uint32_t hmul2_bf(uint32_t a, uint32_t b) {
    __nv_bfloat162 r = __hmul2_rn(*reinterpret_cast<__nv_bfloat162*>(&a), *reinterpret_cast<__nv_bfloat162*>(&b));
    return *reinterpret_cast<uint32_t*>(&r);
}
__device__ __forceinline__ uint32_t hfma2_bf(uint32_t a, uint32_t b, uint32_t c) { uint32_t r; asm("fma.rn.bf16x2 %0, %1, %2, %3;\n" : "=r"(r) : "r"(a), "r"(b), "r"(c)); return r; }
__device__ __forceinline__ uint32_t hmul2(uint32_t a, uint32_t b) { uint32_t r; asm("mul.rn.f16x2 %0, %1, %2;\n" : "=r"(r) : "r"(a), "r"(b)); return r; }
__device__ __forceinline__ uint32_t hadd2(uint32_t a, uint32_t b) { uint32_t r; asm("add.rn.f16x2 %0, %1, %2;\n" : "=r"(r) : "r"(a), "r"(b)); return r; }
__device__ __forceinline__ uint32_t nzw(uint32_t w) { return w ? w : 0x8000u; }
__device__ __forceinline__ uint32_t smem_u32(const void* p) { return (uint32_t)__cvta_generic_to_shared(p); }
__device__ __forceinline__ uint32_t lds32(uint32_t addr) {
    uint32_t v;
    asm volatile("ld.shared.u32 %0, [%1];\n" : "=r"(v) : "r"(addr) : "memory");
    return v;
}
__device__ __forceinline__ uint2 lds64(uint32_t addr) {
    uint2 v;
    asm volatile("ld.shared.v2.u32 {%0,%1}, [%2];\n" : "=r"(v.x), "=r"(v.y) : "r"(addr) : "memory");
    return v;
}
__device__ __forceinline__ uint4 lds128(uint32_t addr) {
    uint4 v;
    asm volatile("ld.shared.v4.u32 {%0,%1,%2,%3}, [%4];\n" : "=r"(v.x), "=r"(v.y), "=r"(v.z), "=r"(v.w) : "r"(addr) : "memory");
    return v;
}
__device__ __forceinline__ float ldsf(uint32_t addr) { return __uint_as_float(lds32(addr)); }
__device__ __forceinline__ void sts32(uint32_t addr, uint32_t v) { asm volatile("st.shared.u32 [%0], %1;\n" ::"r"(addr), "r"(v) : "memory"); }
__device__ __forceinline__ void stsf(uint32_t addr, float v) { sts32(addr, __float_as_uint(v)); }
__device__ __forceinline__ void sts64(uint32_t addr, uint32_t a, uint32_t b) { asm volatile("st.shared.v2.u32 [%0], {%1,%2};\n" ::"r"(addr), "r"(a), "r"(b) : "memory"); }
__device__ __forceinline__ void sts128(uint32_t addr, uint32_t a, uint32_t b, uint32_t c, uint32_t d) {
    asm volatile("st.shared.v4.u32 [%0], {%1,%2,%3,%4};\n" ::"r"(addr), "r"(a), "r"(b), "r"(c), "r"(d) : "memory");
}
__device__ __forceinline__ void sts128f(uint32_t addr, const float (&v)[4]) {
    sts128(addr, __float_as_uint(v[0]), __float_as_uint(v[1]), __float_as_uint(v[2]), __float_as_uint(v[3]));
}
__device__ __forceinline__ void ldsm_x4(uint32_t& r0, uint32_t& r1, uint32_t& r2, uint32_t& r3, uint32_t addr) {
    asm volatile("ldmatrix.sync.aligned.m8n8.x4.shared.b16 {%0,%1,%2,%3}, [%4];\n"
                 : "=r"(r0), "=r"(r1), "=r"(r2), "=r"(r3) : "r"(addr) : "memory");
}
__device__ __forceinline__ void ldsm_x4_t(uint32_t& r0, uint32_t& r1, uint32_t& r2, uint32_t& r3, uint32_t addr) {
    asm volatile("ldmatrix.sync.aligned.m8n8.x4.trans.shared.b16 {%0,%1,%2,%3}, [%4];\n"
                 : "=r"(r0), "=r"(r1), "=r"(r2), "=r"(r3) : "r"(addr) : "memory");
}
__device__ __forceinline__ void ldsm_x2_t(uint32_t& r0, uint32_t& r1, uint32_t addr) {
    asm volatile("ldmatrix.sync.aligned.m8n8.x2.trans.shared.b16 {%0,%1}, [%2];\n" : "=r"(r0), "=r"(r1) : "r"(addr) : "memory");
}
__device__ __forceinline__ void ldsm_x1_t(uint32_t& r0, uint32_t addr) {
    asm volatile("ldmatrix.sync.aligned.m8n8.x1.trans.shared.b16 {%0}, [%1];\n" : "=r"(r0) : "r"(addr) : "memory");
}
__device__ __forceinline__ uint32_t movm(uint32_t a) {
    uint32_t d;
    asm volatile("movmatrix.sync.aligned.m8n8.trans.b16 %0, %1;\n" : "=r"(d) : "r"(a));
    return d;
}
__device__ __forceinline__ void mma_f16(float (&c)[4], uint32_t a0, uint32_t a1, uint32_t a2, uint32_t a3, uint32_t b0, uint32_t b1) {
    asm volatile(
        "mma.sync.aligned.m16n8k16.row.col.f32.f16.f16.f32 {%0,%1,%2,%3}, {%4,%5,%6,%7}, {%8,%9}, {%0,%1,%2,%3};\n"
        : "+f"(c[0]), "+f"(c[1]), "+f"(c[2]), "+f"(c[3])
        : "r"(a0), "r"(a1), "r"(a2), "r"(a3), "r"(b0), "r"(b1));
}
__device__ __forceinline__ void mma_bf16(float (&c)[4], uint32_t a0, uint32_t a1, uint32_t a2, uint32_t a3, uint32_t b0, uint32_t b1) {
    asm volatile(
        "mma.sync.aligned.m16n8k16.row.col.f32.bf16.bf16.f32 {%0,%1,%2,%3}, {%4,%5,%6,%7}, {%8,%9}, {%0,%1,%2,%3};\n"
        : "+f"(c[0]), "+f"(c[1]), "+f"(c[2]), "+f"(c[3])
        : "r"(a0), "r"(a1), "r"(a2), "r"(a3), "r"(b0), "r"(b1));
}
__device__ __forceinline__ void mma_bf16_k8(float (&c)[4], uint32_t a0, uint32_t a1, uint32_t b0) {
    asm volatile("mma.sync.aligned.m16n8k8.row.col.f32.bf16.bf16.f32 {%0,%1,%2,%3}, {%4,%5}, {%6}, {%0,%1,%2,%3};\n"
        : "+f"(c[0]), "+f"(c[1]), "+f"(c[2]), "+f"(c[3]) : "r"(a0), "r"(a1), "r"(b0));
}
__device__ __forceinline__ void bar_sync(int id, int n) { asm volatile("bar.sync %0, %1;\n" ::"r"(id), "r"(n) : "memory"); }
__device__ __forceinline__ void bar_arrive(int id, int n) { asm volatile("bar.arrive %0, %1;\n" ::"r"(id), "r"(n) : "memory"); }
__device__ __forceinline__ bool bar_or(int id, int n, bool v) {
    uint32_t r;
    asm volatile("{\n.reg .pred p, q;\nsetp.ne.u32 p, %3, 0;\nbar.red.or.pred q, %1, %2, p;\nselp.u32 %0, 1, 0, q;\n}\n" : "=r"(r) : "r"(id), "r"(n), "r"((uint32_t)v) : "memory");
    return r;
}
__device__ __forceinline__ uint4 ld_poll(const void* p) {
    uint4 v;
    asm volatile("ld.relaxed.gpu.global.v4.u32 {%0,%1,%2,%3}, [%4];\n" : "=r"(v.x), "=r"(v.y), "=r"(v.z), "=r"(v.w) : "l"(p) : "memory");
    return v;
}
template <class T> __device__ __forceinline__ T* pin(T* p, uint32_t z) {
    uint32_t lo, hi;
    asm volatile("mov.b64 {%0, %1}, %2;\n" : "=r"(lo), "=r"(hi) : "l"(p));
    asm volatile("xor.b32 %0, %0, %1;\n" : "+r"(lo) : "r"(z));
    asm volatile("xor.b32 %0, %0, %1;\n" : "+r"(hi) : "r"(z));
    asm volatile("mov.b64 %0, {%1, %2};\n" : "=l"(p) : "r"(lo), "r"(hi));
    return p;
}
__device__ __forceinline__ uint32_t pin(uint32_t a, uint32_t z) { asm volatile("xor.b32 %0, %0, %1;\n" : "+r"(a) : "r"(z)); return a; }
__device__ __forceinline__ uint2 ld_poll64(const void* p) {
    uint2 v;
    asm volatile("ld.relaxed.gpu.global.v2.u32 {%0,%1}, [%2];\n" : "=r"(v.x), "=r"(v.y) : "l"(p) : "memory");
    return v;
}
__device__ __forceinline__ uint32_t ld_poll32(const void* p) {
    uint32_t v;
    asm volatile("ld.relaxed.gpu.global.u32 %0, [%1];\n" : "=r"(v) : "l"(p) : "memory");
    return v;
}
__device__ __forceinline__ uint4 ldg128(const void* p) {
    uint4 v;
    asm volatile("ld.global.nc.v4.u32 {%0,%1,%2,%3}, [%4];\n" : "=r"(v.x), "=r"(v.y), "=r"(v.z), "=r"(v.w) : "l"(p));
    return v;
}
__device__ __forceinline__ uint2 ldg64(const void* p) {
    uint2 v;
    asm volatile("ld.global.nc.v2.u32 {%0,%1}, [%2];\n" : "=r"(v.x), "=r"(v.y) : "l"(p));
    return v;
}
__device__ __forceinline__ uint32_t ldg16(const void* p) {
    uint32_t v;
    asm volatile("ld.global.nc.u16 %0, [%1];\n" : "=r"(v) : "l"(p));
    return v;
}
__device__ __forceinline__ void stg128(void* p, uint32_t a, uint32_t b, uint32_t c, uint32_t d) {
    asm volatile("st.global.v4.u32 [%0], {%1,%2,%3,%4};\n" ::"l"(p), "r"(a), "r"(b), "r"(c), "r"(d) : "memory");
}
__device__ __forceinline__ void stg64(void* p, uint32_t a, uint32_t b) { asm volatile("st.global.v2.u32 [%0], {%1,%2};\n" ::"l"(p), "r"(a), "r"(b) : "memory"); }
__device__ __forceinline__ void stg32(void* p, uint32_t a) { asm volatile("st.global.u32 [%0], %1;\n" ::"l"(p), "r"(a) : "memory"); }
__device__ __forceinline__ bool all_nz(const uint4& v) { return v.x && v.y && v.z && v.w; }
#define SPIN_LIMIT (1 << 21)
#define TRAP() __trap()
__device__ __forceinline__ void hint_arrive(unsigned* g_hint, int idx, int sub) {
    asm volatile("red.relaxed.gpu.global.add.u32 [%0], 1;\n" ::"l"(&g_hint[sub * 32 + idx]) : "memory");
}
__device__ __forceinline__ void hint_wait(const unsigned* g_hint, int idx, unsigned target) {
    unsigned l;
    asm volatile("mov.u32 %0, %%laneid;" : "=r"(l));
    const unsigned* c = &g_hint[(l & 7) * 32 + idx];
    int it = 0;
    while (__any_sync(0xffffffffu, (int)(ld_poll32(c) - target) < 0)) { if (++it > SPIN_LIMIT) TRAP(); }
}
__device__ __forceinline__ void mbar_init(uint32_t bar, uint32_t cnt) { asm volatile("mbarrier.init.shared::cta.b64 [%0], %1;\n" ::"r"(bar), "r"(cnt) : "memory"); }
__device__ __forceinline__ void mbar_expect(uint32_t bar, uint32_t bytes) {
    asm volatile("mbarrier.arrive.expect_tx.shared::cta.b64 _, [%0], %1;\n" ::"r"(bar), "r"(bytes) : "memory");
}
__device__ __forceinline__ void mbar_arrive(uint32_t bar) { asm volatile("mbarrier.arrive.shared::cta.b64 _, [%0];\n" ::"r"(bar) : "memory"); }
__device__ __forceinline__ void mbar_wait(uint32_t bar) {
    asm volatile(
        "{\n.reg .pred p;\n"
        "W_%=:\n"
        "mbarrier.try_wait.parity.shared::cta.b64 p, [%0], 0;\n"
        "@!p bra W_%=;\n}\n" ::"r"(bar) : "memory");
}
__device__ __forceinline__ void bulk_s2g(void* dst, uint32_t src, uint32_t bytes) {
    asm volatile("cp.async.bulk.global.shared::cta.bulk_group [%0], [%1], %2;\ncp.async.bulk.commit_group;\n" ::"l"(dst), "r"(src), "r"(bytes) : "memory");
}
__device__ __forceinline__ void tma_2d(uint32_t dst, const CUtensorMap* tm, int c0, int c1, uint32_t bar) {
    asm volatile("cp.async.bulk.tensor.2d.shared::cluster.global.mbarrier::complete_tx::bytes [%0], [%1, {%3, %4}], [%2];\n"
                 ::"r"(dst), "l"(tm), "r"(bar), "r"(c0), "r"(c1) : "memory");
}
__device__ __forceinline__ void tma_3d(uint32_t dst, const CUtensorMap* tm, int c0, int c1, int c2, uint32_t bar) {
    asm volatile("cp.async.bulk.tensor.3d.shared::cluster.global.mbarrier::complete_tx::bytes [%0], [%1, {%3, %4, %5}], [%2];\n"
                 ::"r"(dst), "l"(tm), "r"(bar), "r"(c0), "r"(c1), "r"(c2) : "memory");
}
__device__ __forceinline__ void tma_st_3d(const CUtensorMap* tm, uint32_t src, int c0, int c1, int c2) {
    asm volatile("cp.async.bulk.tensor.3d.global.shared::cta.bulk_group [%0, {%2, %3, %4}], [%1];\ncp.async.bulk.commit_group;\n"
                 ::"l"(tm), "r"(src), "r"(c0), "r"(c1), "r"(c2) : "memory");
}
__device__ __forceinline__ bool elect_one() {
    uint32_t r;
    asm volatile("{\n.reg .pred p;\nelect.sync _|p, 0xffffffff;\nselp.u32 %0, 1, 0, p;\n}\n" : "=r"(r));
    return r;
}
__device__ __forceinline__ void fence_async() { asm volatile("fence.proxy.async.shared::cta;\n" ::: "memory"); }

__device__ __forceinline__ float2 cmul(float2 a, float2 b) {
    return make_float2(fmaf(a.x, b.x, -a.y * b.y), fmaf(a.x, b.y, a.y * b.x));
}
__device__ __forceinline__ float2 csq(float2 a) {
    float p = a.x * a.y;
    return make_float2(fmaf(a.x, a.x, -a.y * a.y), p + p);
}
__device__ __forceinline__ float2 cexp_e(float lr2, float rh, float rl, float e) {
    float m;
    asm("ex2.approx.ftz.f32 %0, %1;\n" : "=f"(m) : "f"(lr2 * e));
    const float a = rh * e;
    const float r = fmaf(rl, e, a - rintf(a)) * 6.283185307179586f;
    return make_float2(m * __cosf(r), m * __sinf(r));
}
__device__ __forceinline__ float rcp_approx(float x) { float r; asm("rcp.approx.ftz.f32 %0, %1;\n" : "=f"(r) : "f"(x)); return r; }
__device__ __forceinline__ float ex2_approx(float x) { float r; asm("ex2.approx.ftz.f32 %0, %1;\n" : "=f"(r) : "f"(x)); return r; }
__device__ __forceinline__ float sqrt_approx(float x) { float r; asm("sqrt.approx.ftz.f32 %0, %1;\n" : "=f"(r) : "f"(x)); return r; }

__device__ __forceinline__ void wg_fence() { asm volatile("wgmma.fence.sync.aligned;\n" ::: "memory"); }
__device__ __forceinline__ void wg_commit() { asm volatile("wgmma.commit_group.sync.aligned;\n" ::: "memory"); }
__device__ __forceinline__ void wg_wait0() { asm volatile("wgmma.wait_group.sync.aligned 0;\n" ::: "memory"); }
template <int T0, int NT> __device__ __forceinline__ void wg_h(uint32_t (&acc)[32], const uint32_t (&a)[4], uint64_t desc);
template <> __device__ __forceinline__ void wg_h<0, 16>(uint32_t (&acc)[32], const uint32_t (&a)[4], uint64_t desc) {
    asm volatile("wgmma.mma_async.sync.aligned.m64n128k16.f16.f16.f16 {%0,%1,%2,%3,%4,%5,%6,%7,%8,%9,%10,%11,%12,%13,%14,%15,%16,%17,%18,%19,%20,%21,%22,%23,%24,%25,%26,%27,%28,%29,%30,%31}, {%32,%33,%34,%35}, %36, 1, 1, 1, 0;\n"
                 : "+r"(acc[0]), "+r"(acc[1]), "+r"(acc[2]), "+r"(acc[3]), "+r"(acc[4]), "+r"(acc[5]), "+r"(acc[6]), "+r"(acc[7]), "+r"(acc[8]), "+r"(acc[9]), "+r"(acc[10]), "+r"(acc[11]), "+r"(acc[12]), "+r"(acc[13]), "+r"(acc[14]), "+r"(acc[15]), "+r"(acc[16]), "+r"(acc[17]), "+r"(acc[18]), "+r"(acc[19]), "+r"(acc[20]), "+r"(acc[21]), "+r"(acc[22]), "+r"(acc[23]), "+r"(acc[24]), "+r"(acc[25]), "+r"(acc[26]), "+r"(acc[27]), "+r"(acc[28]), "+r"(acc[29]), "+r"(acc[30]), "+r"(acc[31])
                 : "r"(a[0]), "r"(a[1]), "r"(a[2]), "r"(a[3]), "l"(desc));
}
template <> __device__ __forceinline__ void wg_h<4, 4>(uint32_t (&acc)[32], const uint32_t (&a)[4], uint64_t desc) {
    asm volatile("wgmma.mma_async.sync.aligned.m64n32k16.f16.f16.f16 {%0,%1,%2,%3,%4,%5,%6,%7}, {%8,%9,%10,%11}, %12, 1, 1, 1, 0;\n"
                 : "+r"(acc[8]), "+r"(acc[9]), "+r"(acc[10]), "+r"(acc[11]), "+r"(acc[12]), "+r"(acc[13]), "+r"(acc[14]), "+r"(acc[15])
                 : "r"(a[0]), "r"(a[1]), "r"(a[2]), "r"(a[3]), "l"(desc));
}
template <> __device__ __forceinline__ void wg_h<8, 4>(uint32_t (&acc)[32], const uint32_t (&a)[4], uint64_t desc) {
    asm volatile("wgmma.mma_async.sync.aligned.m64n32k16.f16.f16.f16 {%0,%1,%2,%3,%4,%5,%6,%7}, {%8,%9,%10,%11}, %12, 1, 1, 1, 0;\n"
                 : "+r"(acc[16]), "+r"(acc[17]), "+r"(acc[18]), "+r"(acc[19]), "+r"(acc[20]), "+r"(acc[21]), "+r"(acc[22]), "+r"(acc[23])
                 : "r"(a[0]), "r"(a[1]), "r"(a[2]), "r"(a[3]), "l"(desc));
}
template <> __device__ __forceinline__ void wg_h<12, 4>(uint32_t (&acc)[32], const uint32_t (&a)[4], uint64_t desc) {
    asm volatile("wgmma.mma_async.sync.aligned.m64n32k16.f16.f16.f16 {%0,%1,%2,%3,%4,%5,%6,%7}, {%8,%9,%10,%11}, %12, 1, 1, 1, 0;\n"
                 : "+r"(acc[24]), "+r"(acc[25]), "+r"(acc[26]), "+r"(acc[27]), "+r"(acc[28]), "+r"(acc[29]), "+r"(acc[30]), "+r"(acc[31])
                 : "r"(a[0]), "r"(a[1]), "r"(a[2]), "r"(a[3]), "l"(desc));
}
template <> __device__ __forceinline__ void wg_h<0, 8>(uint32_t (&acc)[32], const uint32_t (&a)[4], uint64_t desc) {
    asm volatile("wgmma.mma_async.sync.aligned.m64n64k16.f16.f16.f16 {%0,%1,%2,%3,%4,%5,%6,%7,%8,%9,%10,%11,%12,%13,%14,%15}, {%16,%17,%18,%19}, %20, 1, 1, 1, 0;\n"
                 : "+r"(acc[0]), "+r"(acc[1]), "+r"(acc[2]), "+r"(acc[3]), "+r"(acc[4]), "+r"(acc[5]), "+r"(acc[6]), "+r"(acc[7]), "+r"(acc[8]), "+r"(acc[9]), "+r"(acc[10]), "+r"(acc[11]), "+r"(acc[12]), "+r"(acc[13]), "+r"(acc[14]), "+r"(acc[15])
                 : "r"(a[0]), "r"(a[1]), "r"(a[2]), "r"(a[3]), "l"(desc));
}
template <> __device__ __forceinline__ void wg_h<4, 12>(uint32_t (&acc)[32], const uint32_t (&a)[4], uint64_t desc) {
    asm volatile("wgmma.mma_async.sync.aligned.m64n96k16.f16.f16.f16 {%0,%1,%2,%3,%4,%5,%6,%7,%8,%9,%10,%11,%12,%13,%14,%15,%16,%17,%18,%19,%20,%21,%22,%23}, {%24,%25,%26,%27}, %28, 1, 1, 1, 0;\n"
                 : "+r"(acc[8]), "+r"(acc[9]), "+r"(acc[10]), "+r"(acc[11]), "+r"(acc[12]), "+r"(acc[13]), "+r"(acc[14]), "+r"(acc[15]), "+r"(acc[16]), "+r"(acc[17]), "+r"(acc[18]), "+r"(acc[19]), "+r"(acc[20]), "+r"(acc[21]), "+r"(acc[22]), "+r"(acc[23]), "+r"(acc[24]), "+r"(acc[25]), "+r"(acc[26]), "+r"(acc[27]), "+r"(acc[28]), "+r"(acc[29]), "+r"(acc[30]), "+r"(acc[31])
                 : "r"(a[0]), "r"(a[1]), "r"(a[2]), "r"(a[3]), "l"(desc));
}

#define PBYTES 4608
#define DELAY(n) do { if (n) { const unsigned c0_ = clock32(); while ((int)(clock32() - c0_) < (n)) {} } } while (0)
#define KDEL 300
#define PDEL 300
#define CST(i) do { if ((warp & 3) == 0 && lane_v() == 0) { unsigned t_; asm volatile("mov.u32 %0, %%globaltimer_lo;" : "=r"(t_) :: "memory"); sts32(sb + SMEM_TOTAL - 768 + (warp >> 2) * 128 + (i) * 4, t_); } } while (0)
#define TP0 5000
#define TP4 5800
#define HINTW 10
#define WAS 0x0005
#define WA0 (WAS >> 12)
#define WA1 ((WAS >> 8) & 15)
#define WA2 ((WAS >> 4) & 15)
#define WA3 (WAS & 15)
#define WDAT 1
#define PAUSE 2
#define PCNT (32 + ((PAUSE & 1) ? 288 : 0) + ((PAUSE & 6) ? 320 : 64))
#define LNAT 2
#define UW 8
#define FINAT 3
#define UAT 2
#define TOKEN_OF(g) (16 * ((g) & 1) + ((g) >> 2) + 2 * ((g) & 2))
#define HI2(a, b) (pack_f16_rz(__uint_as_float(a), __uint_as_float(b)) & 0xfff8fff8u)
struct Params {
    const bf16 *x, *lar, *aim, *cre, *cim, *ldt, *dsk;
    Scratch* s;
    const bf16* wr;
    bf16* out;
};

template <int NK>
__device__ __forceinline__ void ln_partial(const uint32_t (&H)[2][NK], const uint32_t (&bw)[NK], uint32_t lp, int warp, int g, int t) {
    float cs[4] = {0.f, 0.f, 0.f, 0.f}, cl[4] = {0.f, 0.f, 0.f, 0.f}, ch[4] = {0.f, 0.f, 0.f, 0.f};
#pragma unroll
    for (int k = 0; k < NK; k += 2) {
        uint32_t a0, a1, a2, a3;
        asm volatile("prmt.b32 %0, %4, %4, %8;\nprmt.b32 %1, %5, %5, %8;\nprmt.b32 %2, %6, %6, %8;\nprmt.b32 %3, %7, %7, %8;\n"
                     : "=r"(a0), "=r"(a1), "=r"(a2), "=r"(a3) : "r"(H[0][k]), "r"(H[1][k]), "r"(H[0][k + 1]), "r"(H[1][k + 1]), "r"(0x3210u + (warp >> 8)));
        mma_bf16(cl, a0, a1, a2, a3, H[0][k], H[0][k + 1]);
        mma_bf16(ch, a0, a1, a2, a3, H[1][k], H[1][k + 1]);
        mma_bf16(cs, a0, a1, a2, a3, bw[k], bw[k + 1]);
    }
    const uint32_t a = lp + (g * 20 + warp) * 4;
    if (t == 0) {
        stsf(a, cs[1]); stsf(a + 8 * 80, cs[3]);
    }
    if (t == (g >> 1)) { stsf(a + 16 * 80, (g & 1) ? cl[1] : cl[0]); stsf(a + 24 * 80, (g & 1) ? ch[3] : ch[2]); }
}
__device__ __forceinline__ float sum18(uint32_t a) {
    const uint4 p = lds128(a), q = lds128(a + 16), r = lds128(a + 32), s = lds128(a + 48);
    const uint2 u = lds64(a + 64);
#define F(x) __uint_as_float(x)
    return (((F(p.x) + F(p.y)) + (F(p.z) + F(p.w))) + ((F(q.x) + F(q.y)) + (F(q.z) + F(q.w)))) +
           (((F(r.x) + F(r.y)) + (F(r.z) + F(r.w))) + ((F(s.x) + F(s.y)) + (F(s.z) + F(s.w))) + (F(u.x) + F(u.y)));
#undef F
}
__device__ __forceinline__ float sum9(uint32_t a) {
    const uint4 p = lds128(a), q = lds128(a + 16);
#define F(x) __uint_as_float(x)
    return (((F(p.x) + F(p.y)) + (F(p.z) + F(p.w))) + ((F(q.x) + F(q.y)) + (F(q.z) + F(q.w)))) + ldsf(a + 32);
#undef F
}
template <int N>
__device__ __forceinline__ void ln_finish(uint32_t lp, int lane, float& mb, float& rc) {
    const float v = N == 9 ? sum9(lp + lane * 80) : sum18(lp + lane * 80);
    const float o = __shfl_xor_sync(0xffffffffu, v, 16);
    const float m0 = v * (1.0f / 576.0f);
    const float mean = fmaf(fmaf(-m0, 576.0f, v), 1.0f / 576.0f, m0);
    const float var = fmaxf(fmaf(o, 1.0f / 576.0f, -(mean * mean)), 0.f);
    mb = rbf(mean);
    rc = rcp_approx(rbf(sqrt_approx(rbf(rbf(var) + 1e-5f))));
}
__device__ __forceinline__ uint32_t ln_apply(uint32_t w, const uint2& st) {
    uint32_t r;
    asm("{\n.reg .b16 m, t, h, l;\n.reg .b32 mm, hh, ll, d, e;\nmov.b32 {m, t}, %2;\nmov.b32 {h, l}, %3;\nmov.b32 mm, {m, m};\nmov.b32 hh, {h, h};\nmov.b32 ll, {l, l};\n"
        "sub.rn.bf16x2 d, %1, mm;\nmul.rn.bf16x2 e, d, ll;\nfma.rn.bf16x2 %0, d, hh, e;\n}\n" : "=r"(r) : "r"(w), "r"(st.x), "r"(st.y));
    return r;
}
__device__ __forceinline__ void stat_store(uint32_t a, float mb, float rc, uint32_t extra) {
    const float rh = rbf(rc);
    sts64(a, (__float_as_uint(mb) >> 16) | (extra << 16), pack_bf16(rh, rc - rh));
}

__device__ __forceinline__ void hcmul(uint32_t re, uint32_t im, uint32_t z, uint32_t& ore, uint32_t& oim) {
    asm("{\n.reg .b16 x, y;\n.reg .b32 xx, yy, ny, a, b;\nmov.b32 {x, y}, %4;\nmov.b32 xx, {x, x};\nmov.b32 yy, {y, y};\nneg.f16x2 ny, yy;\n"
        "mul.rn.f16x2 a, %2, xx;\nfma.rn.f16x2 %0, %3, ny, a;\nmul.rn.f16x2 b, %3, xx;\nfma.rn.f16x2 %1, %2, yy, b;\n}\n" : "=&r"(ore), "=r"(oim) : "r"(re), "r"(im), "r"(z));
}
__device__ __forceinline__ void hcmul(uint32_t re, uint32_t im, uint32_t zx, uint32_t zy, uint32_t& ore, uint32_t& oim) {
    asm("{\n.reg .b32 ny, a, b;\nneg.f16x2 ny, %5;\n"
        "mul.rn.f16x2 a, %2, %4;\nfma.rn.f16x2 %0, %3, ny, a;\nmul.rn.f16x2 b, %3, %4;\nfma.rn.f16x2 %1, %2, %5, b;\n}\n" : "=&r"(ore), "=r"(oim) : "r"(re), "r"(im), "r"(zx), "r"(zy));
}

struct KGen {
    uint32_t Af[4][4];
    float2 z1, z8, z64, z128, T[9];
    uint32_t zw;
};
__device__ __forceinline__ void kgen_setup(KGen& k, uint32_t pa, float dt) {
    const float A = rbf(expf(bf_lo(pa)));
    const float lr2 = -(A * dt) * 1.4426950408889634f;
    const float li = bf_hi(pa) * dt;
    const float rh = li * 0.15915494309189535f;
    const float rl = fmaf(li, 6.4206382986e-9f, fmaf(li, 0.15915494309189535f, -rh));
    k.z1 = cexp_e(lr2, rh, rl, 1.0f);
    k.z8 = cexp_e(lr2, rh, rl, 8.0f);
    k.z64 = cexp_e(lr2, rh, rl, 64.0f);
}
__device__ __forceinline__ void kgen_rows(KGen& k, uint32_t tb, int lane) {
    const float2 z8 = k.z8, z64 = k.z64;
    const uint32_t row = tb + lane * TBP;
    k.z128 = csq(z64);
    const float2 z16 = csq(z8), z32 = csq(z16), z48 = cmul(z32, z16), z80 = cmul(z64, z16), z96 = cmul(z64, z32), z112 = cmul(z64, z48);
    uint32_t re[4], im[4], a[4], b[4];
    re[0] = pack_f16(1.0f, z16.x); im[0] = pack_f16(0.0f, z16.y);
    re[1] = pack_f16(z32.x, z48.x); im[1] = pack_f16(z32.y, z48.y);
    re[2] = pack_f16(z64.x, z80.x); im[2] = pack_f16(z64.y, z80.y);
    re[3] = pack_f16(z96.x, z112.x); im[3] = pack_f16(z96.y, z112.y);
    sts128(row, re[0], re[1], re[2], re[3]);
    sts128(row + 32, im[0], im[1], im[2], im[3]);
    const uint32_t zz = pack_f16(z8.x, z8.y);
#pragma unroll
    for (int j = 0; j < 4; j++) hcmul(re[j], im[j], zz, a[j], b[j]);
    sts128(row + 16, a[0], a[1], a[2], a[3]);
    sts128(row + 48, b[0], b[1], b[2], b[3]);
    __syncwarp();
    const int mi = lane >> 3;
    const uint32_t ad = tb + (lane & 7) * TBP + mi * 16;
#pragma unroll
    for (int ks = 0; ks < 4; ks++) ldsm_x4_t(k.Af[ks][0], k.Af[ks][1], k.Af[ks][2], k.Af[ks][3], ad + ks * 8 * TBP);
}
__device__ __forceinline__ void kgen_chain(KGen& k, uint32_t pc, float cs) {
    k.T[0] = make_float2(bf_lo(pc) * cs, -bf_hi(pc) * cs);
    const float2 y1 = make_float2(k.z1.x, -k.z1.y);
#pragma unroll
    for (int c = 1; c < 8; c++) k.T[c] = cmul(k.T[c - 1], y1);
    k.T[8] = cmul(k.T[0], make_float2(k.z8.x, -k.z8.y));
}
__device__ __forceinline__ void kgen_cols(KGen& k, uint32_t tb, int lane) {
    const uint32_t row = tb + lane * TBP;
    const float2 (&T)[9] = k.T;
    const uint32_t zv = pack_f16(k.z128.x, k.z128.y), zo = __shfl_xor_sync(0xffffffffu, zv, 1);
    k.zw = (lane & 1) ? __byte_perm(zo, zv, 0x7632) : __byte_perm(zv, zo, 0x5410);
    const float2 y256 = csq(make_float2(k.z128.x, -k.z128.y)), y512 = csq(y256), y768 = cmul(y512, y256), y1024 = csq(y512);
    const float2 c1032 = cmul(T[8], y1024);
    const uint32_t r04 = pack_f16(T[0].x, T[4].x), i04 = pack_f16(T[0].y, T[4].y), r26 = pack_f16(T[2].x, T[6].x), i26 = pack_f16(T[2].y, T[6].y);
    const uint32_t r48 = pack_f16(T[4].x, T[8].x), i48 = pack_f16(T[4].y, T[8].y);
    __syncwarp();
    sts128(row, r04, pack_f16(T[1].x, T[5].x), r26, pack_f16(T[3].x, T[7].x));
    sts128(row + 16, i04, pack_f16(T[1].y, T[5].y), i26, pack_f16(T[3].y, T[7].y));
    uint32_t a[4], b[4];
    {
        const uint32_t zz = pack_f16(y256.x, y256.y);
        hcmul(r04, i04, zz, a[0], b[0]);
        hcmul(r26, i26, zz, a[2], b[2]);
        hcmul(r48, i48, zz, a[3], b[3]);
    }
    sts128(row + 32, a[0], a[0], a[2], a[3]);
    sts128(row + 48, b[0], b[0], b[2], b[3]);
    {
        hcmul(r48, i48, pack_f16(y512.x, y512.y), a[0], b[0]);
        hcmul(r48, i48, pack_f16(y768.x, y768.y), a[1], b[1]);
        const uint32_t zz = pack_f16(c1032.x, c1032.y);
        hcmul(pack_f16(1.0f, y256.x), pack_f16(0.0f, y256.y), zz, a[2], b[2]);
        hcmul(pack_f16(y512.x, y768.x), pack_f16(y512.y, y768.y), zz, a[3], b[3]);
    }
    sts128(row + 64, a[0], a[1], a[2], a[3]);
    sts128(row + 80, b[0], b[1], b[2], b[3]);
}
__device__ __forceinline__ void kgen_mma(const KGen& k, uint32_t tb, int lane) {
    const int t = lane & 3;
    const uint32_t zw = k.zw;
    uint32_t zx[4], zy[4];
#pragma unroll
    for (int ks = 0; ks < 4; ks++) { zx[ks] = __shfl_sync(0xffffffffu, zw, 8 * ks + 2 * t); zy[ks] = __shfl_sync(0xffffffffu, zw, 8 * ks + 2 * t + 1); }
    __syncwarp();
    float acc[2][3][4];
#pragma unroll
    for (int i = 0; i < 6; i++)
#pragma unroll
        for (int j = 0; j < 4; j++) acc[i / 3][i % 3][j] = 0.f;
    {
        const int mi = lane >> 3;
        const uint32_t bd = tb + ((lane & 7) + 8 * (mi >> 1)) * TBP + (mi & 1) * 16;
#pragma unroll
        for (int kp = 0; kp < 2; kp++) {
            uint32_t b[3][4];
#pragma unroll
            for (int j = 0; j < 3; j++) ldsm_x4_t(b[j][0], b[j][1], b[j][2], b[j][3], bd + kp * 16 * TBP + j * 32);
#pragma unroll
            for (int h = 0; h < 2; h++) {
                const int ks = 2 * kp + h;
                uint32_t d[4];
                hcmul(k.Af[ks][0], k.Af[ks][2], zx[ks], zy[ks], d[0], d[2]);
                hcmul(k.Af[ks][1], k.Af[ks][3], zx[ks], zy[ks], d[1], d[3]);
#pragma unroll
                for (int j = 0; j < 3; j++) {
                    mma_f16(acc[0][j], k.Af[ks][0], k.Af[ks][1], k.Af[ks][2], k.Af[ks][3], b[j][2 * h], b[j][2 * h + 1]);
                    mma_f16(acc[1][j], d[0], d[1], d[2], d[3], b[j][2 * h], b[j][2 * h + 1]);
                }
            }
        }
    }
    __syncwarp();
#pragma unroll
    for (int h = 0; h < 2; h++) {
        sts64(tb + h * 256 + lane * 8, pack_f16(acc[h][0][0], acc[h][0][1]), pack_f16(acc[h][0][2], acc[h][0][3]));
        sts64(tb + 512 + h * 256 + lane * 8, pack_f16(acc[h][1][0], acc[h][1][1]), pack_f16(acc[h][1][2], acc[h][1][3]));
        sts32(tb + 1024 + h * 256 + lane * 4, pack_f16(acc[h][2][0], t < 2 ? acc[h][2][1] : acc[h][2][2]));
        sts32(tb + 1152 + h * 256 + lane * 4, pack_f16(t < 2 ? acc[h][2][2] : acc[h][2][1], acc[h][2][3]));
    }
}
__device__ __forceinline__ uint32_t table_buf(uint32_t sb, int warp) { return sb + SM_TB + warp * TBW; }

__device__ __forceinline__ void kgen_combine(uint32_t sb, int warp, int lane, uint32_t kw, uint32_t ao) {
    const int wq = warp & 3;
    const uint32_t a = table_buf(sb, warp & ~3) + wq * 256 + lane * 8, c = table_buf(sb, warp & ~3) + 1024 + wq * 128 + lane * 4;
    const int t = lane & 3;
    const uint32_t o0 = (t < 2 ? KW_T2 + KW_KH + 16 + t * 256 - (wq & 1) * KW_KH : KW_T3 + 16 - 1024 + t * 512 + (wq & 1) * 256) + (lane >> 2) * 16;
    const uint4 o = make_uint4(o0 + t * 36, o0 + (t ^ 1) * 36, o0 + (t ^ 2) * 36, o0 + (t ^ 3) * 36);
    const uint2 u = lds64(a), v = lds64(a + TBW), w = lds64(a + 2 * TBW), x = lds64(a + 3 * TBW);
    const uint32_t kt = hadd2(hadd2(lds32(c), lds32(c + TBW)), hadd2(lds32(c + 2 * TBW), lds32(c + 3 * TBW)));
    const uint32_t k23 = hadd2(hadd2(u.y, v.y), hadd2(w.y, x.y));
    sts64(kw + wq * 64 + ao, hadd2(hadd2(u.x, v.x), hadd2(w.x, x.x)), k23);
    const uint32_t d = kw + (wq >> 1) * 128;
    const uint32_t kh = hmul2(kt, 0x38003800u);
    sts32(d + o.x, kh); sts32(d + o.y, kh); sts32(d + o.z, kh); sts32(d + o.w, kh);
    if (wq == 3) {
        if (lane == 31) { sts32(kw + 264, k23 >> 16); sts32(kw + 288 + 264, k23 >> 16); sts32(kw + 576 + 264, k23 >> 16); }
        if (lane == 29) { sts32(kw + 864 + 280, kt >> 16); sts32(kw + 280, kt & 0xffff0000u); }
    }
}

__device__ __forceinline__ int c_exponent(const uint2& r, const uint2& i) {
    uint32_t mx = __vmaxu2(__vmaxu2(r.x & 0x7fff7fffu, r.y & 0x7fff7fffu), __vmaxu2(i.x & 0x7fff7fffu, i.y & 0x7fff7fffu));
    mx = __reduce_max_sync(0xffffffffu, max(mx & 0xffffu, mx >> 16));
    return min(max((int)(mx >> 7), 4), 240);
}

__device__ __forceinline__ int warp_v() { int l; asm volatile("mov.u32 %0, %%tid.x;" : "=r"(l)); return __shfl_sync(0xffffffffu, l >> 5, 0); }
__device__ __forceinline__ int lane_v() { int l; asm volatile("mov.u32 %0, %%laneid;" : "=r"(l)); return l; }
__device__ __forceinline__ unsigned clock32() { unsigned c; asm volatile("mov.u32 %0, %%clock;" : "=r"(c)); return c; }
__device__ __forceinline__ uint32_t prmt(uint32_t a, uint32_t b, uint32_t s) { uint32_t d; asm("prmt.b32 %0, %1, %2, %3;\n" : "=r"(d) : "r"(a), "r"(b), "r"(s)); return d; }
__device__ __forceinline__ uint32_t prmt_v(uint32_t a, uint32_t b, uint32_t s) { uint32_t d; asm volatile("prmt.b32 %0, %1, %2, %3;\n" : "=r"(d) : "r"(a), "r"(b), "r"(s)); return d; }
__device__ __forceinline__ void mmah16(uint32_t& d0, uint32_t& d1, uint32_t a0, uint32_t a1, uint32_t a2, uint32_t a3, uint32_t b0, uint32_t b1, uint32_t c0, uint32_t c1) {
    asm volatile("mma.sync.aligned.m16n8k16.row.col.f16.f16.f16.f16 {%0,%1}, {%2,%3,%4,%5}, {%6,%7}, {%8,%9};\n"
                 : "=r"(d0), "=r"(d1) : "r"(a0), "r"(a1), "r"(a2), "r"(a3), "r"(b0), "r"(b1), "r"(c0), "r"(c1));
}
__device__ __forceinline__ void mmah8(uint32_t& d0, uint32_t& d1, uint32_t a0, uint32_t a1, uint32_t b0, uint32_t c0, uint32_t c1) {
    asm volatile("mma.sync.aligned.m16n8k8.row.col.f16.f16.f16.f16 {%0,%1}, {%2,%3}, {%4}, {%5,%6};\n"
                 : "=r"(d0), "=r"(d1) : "r"(a0), "r"(a1), "r"(b0), "r"(c0), "r"(c1));
}
template <int A = 8, int B = 32>
__device__ __forceinline__ void conv_rename(uint32_t (&acc)[32]) {
#pragma unroll
    for (int i = A; i < B; i++) { uint32_t v; asm volatile("mov.b32 %0, %1;\n" : "=r"(v) : "r"(acc[i])); acc[i] = v; }
}
__host__ __device__ constexpr uint32_t band_bits(int hw, int sh) {
    uint32_t c = 0;
    for (int s = 0; s <= 10; s++)
        for (int e = 0; e < 2; e++) {
            const int v = s - 3 + sh - 4 * e;
            if (v <= hw && v >= -hw) c |= 1u << (14 + 16 * e - s);
        }
    return c;
}
template <int HW, int SH, int J> __device__ __forceinline__ uint32_t band(uint32_t p2) {
    uint32_t d;
    asm volatile("{\n.reg .b32 t;\nmul.lo.u32 t, %1, %2;\nand.b32 %0, t, 0x40004000;\n}\n" : "=r"(d) : "r"(p2), "n"(band_bits(HW, SH) | J));
    return d;
}
template <int H0, int SH> __device__ __forceinline__ void band_pair(uint4& l, uint4& u, uint32_t p2) {
    l = make_uint4(band<H0, 8, 1>(p2), band<H0 - 1, SH + 8, 2>(p2), band<H0, 0, 1>(p2), band<H0 - 1, SH, 1>(p2));
    u = make_uint4(band<H0, 0, 2>(p2), band<H0 - 1, SH, 2>(p2), band<H0, -8, 1>(p2), band<H0 - 1, SH - 8, 1>(p2));
}
__device__ __forceinline__ void run_sums(uint32_t (&G)[3][2], const uint32_t (&c)[5], const uint4& l, const uint4& u) {
    mmah8(G[0][0], G[0][1], l.x, l.y, c[0], 0u, 0u);
    mmah8(G[1][0], G[1][1], u.z, u.w, c[3], 0u, 0u);
    mmah8(G[2][0], G[2][1], l.x, l.y, c[2], 0u, 0u);
    mmah16(G[0][0], G[0][1], u.x, u.y, u.z, u.w, c[1], c[2], G[0][0], G[0][1]);
    mmah16(G[1][0], G[1][1], l.x, l.y, l.z, l.w, c[1], c[2], G[1][0], G[1][1]);
    mmah16(G[2][0], G[2][1], u.x, u.y, u.z, u.w, c[3], c[4], G[2][0], G[2][1]);
}
__device__ __forceinline__ float h_lo(uint32_t w) { return __half2float(__ushort_as_half((unsigned short)(w & 0xffffu))); }
__device__ __forceinline__ float h_hi(uint32_t w) { return __half2float(__ushort_as_half((unsigned short)(w >> 16))); }
__device__ __forceinline__ uint64_t smem_desc(uint32_t sb, uint32_t o16, uint32_t lbo) {
    uint64_t d;
    asm("mov.b64 %0, {%1, %2};" : "=l"(d) : "r"(((sb & 0x3FFFF) >> 4) + o16 + (lbo << 12)), "r"(8));
    return d;
}
template <int I> struct IC { static constexpr int value = I; };

struct Conv {
    uint32_t u[3][5];
    uint32_t q2[3][2][4];
    uint32_t q3[2][4];
    uint32_t r[18];
};
struct ConvPre {
    uint32_t a[5], b[5];
    uint32_t t[4];
};
__device__ __forceinline__ void conv_pre(ConvPre& e, uint32_t ka, uint32_t ks, uint32_t sel) {
    const uint4 r = lds128(ka + 256), s = lds128(ka + 272);
    ldsm_x4(e.t[0], e.t[1], e.t[2], e.t[3], ks);
    const uint32_t sw = sel ^ 0x4444u;
    e.a[0] = prmt(r.y, r.z, sel); e.a[1] = prmt(r.w, r.z, sw); e.a[2] = prmt(r.x, r.y, sel); e.a[3] = prmt(r.z, r.y, sw); e.a[4] = prmt(r.z, r.w, sel);
    e.b[0] = prmt(s.y, s.z, sel); e.b[1] = prmt(s.w, s.z, sw); e.b[2] = prmt(s.x, s.y, sel); e.b[3] = prmt(s.z, s.y, sw); e.b[4] = prmt(s.z, s.w, sel);
}
__device__ __forceinline__ void conv_sums(Conv& c, uint32_t (&acc)[32], const ConvPre& e, uint32_t a0, uint32_t a1, const uint4 (&bd)[4], uint32_t ka, uint32_t sel, int wq, uint32_t zr) {
    {
        uint32_t x;
        ldsm_x4(c.u[0][1], c.u[0][2], c.u[0][3], c.u[0][4], a1);
        ldsm_x4(c.u[0][0], c.u[1][0], c.u[2][0], x, a0);
#pragma unroll
        for (int q = 1; q < 3; q++) ldsm_x4(c.u[q][1], c.u[q][2], c.u[q][3], c.u[q][4], a1 + q * 512);
    }
#pragma unroll
    for (int i = 0; i < 32; i++) acc[i] = 0u;
    uint32_t G[3][2];
#pragma unroll
    for (int q = 0; q < 3; q++) {
        mmah8(acc[8 * q + 8], acc[8 * q + 9], e.a[4], 0u, c.u[q][2], acc[8 * q + 8], acc[8 * q + 9]);
        mmah16(acc[8 * q + 8], acc[8 * q + 9], e.a[0], e.a[1], e.a[2], e.a[3], c.u[q][3], c.u[q][4], acc[8 * q + 8], acc[8 * q + 9]);
        if (q < 2) {
            mmah8(acc[8 * q + 16], acc[8 * q + 17], e.b[4], 0u, c.u[q][2], 0u, 0u);
            mmah16(acc[8 * q + 16], acc[8 * q + 17], e.b[0], e.b[1], e.b[2], e.b[3], c.u[q][3], c.u[q][4], acc[8 * q + 16], acc[8 * q + 17]);
            run_sums(G, c.u[q], bd[2], bd[3]);
            c.q3[q][0] = prmt(G[1][1], G[0][0], 0x7632u); c.q3[q][1] = prmt(G[2][1], G[1][0], 0x7632u);
            c.q3[q][2] = prmt(G[1][1], G[0][0], 0x5410u); c.q3[q][3] = prmt(G[2][1], G[1][0], 0x5410u);
        }
    }
    {
        const uint32_t a = (ka + wq * 64) ^ (((acc[8] | acc[16] | acc[24]) | (c.q3[0][0] | c.q3[0][1]) | (c.q3[1][0] | c.q3[1][1])) & zr);
#pragma unroll
        for (int i = 0; i < 4; i++) { const uint4 v = lds128(a + i * 16); c.r[4 * i] = v.x; c.r[4 * i + 1] = v.y; c.r[4 * i + 2] = v.z; c.r[4 * i + 3] = v.w; }
        const uint2 v = lds64(a + 64);
        c.r[16] = v.x; c.r[17] = v.y;
    }
#pragma unroll
    for (int q = 0; q < 3; q++) {
        run_sums(G, c.u[q], bd[0], bd[1]);
#pragma unroll
        for (int h = 0; h < 2; h++) {
            const uint32_t s = h ? 0x7632u : 0x5410u;
            c.q2[q][h][0] = prmt(G[0][1], G[0][0], s); c.q2[q][h][1] = prmt(G[1][1], G[1][0], s);
            c.q2[q][h][2] = prmt(G[1][0], G[1][1], s ^ 0x4444u); c.q2[q][h][3] = prmt(G[2][1], G[2][0], s);
            if (q < 2) mmah16(acc[8 * q + 16], acc[8 * q + 17], c.q2[q][h][0], c.q2[q][h][1], c.q2[q][h][2], c.q2[q][h][3], e.t[2 * h], e.t[2 * h + 1], acc[8 * q + 16], acc[8 * q + 17]);
        }
    }
    if (sel == 0u) {
#pragma unroll
        for (int i = 0; i < 6; i++) sts128(ka + i * 16, c.q2[i >> 1][i & 1][0], c.q2[i >> 1][i & 1][1], c.q2[i >> 1][i & 1][2], c.q2[i >> 1][i & 1][3]);
#pragma unroll
        for (int i = 0; i < 2; i++) sts128(ka + i * 16, c.q3[i][0], c.q3[i][1], c.q3[i][2], c.q3[i][3]);
#pragma unroll
        for (int i = 1; i < 4; i++) sts64(ka + i * 16, acc[8 * i], acc[8 * i + 1]);
    }
    conv_rename(acc);
}
#define SPACE 100
#define SPN 3
#define O4 4
#define B2L 1
#define GATE 2
#define HAND 2
#define GA 6
#define GB 4
template <int TA, int TB, int IA, class FG>
__device__ __forceinline__ void conv_tail(uint32_t (&acc)[32], const uint32_t (&a)[8][4], uint32_t sb, unsigned char* gy0, int warp, size_t ycopy, FG fg) {
    const int wg = warp >> 2, wq = warp & 3, ord = TA == 0 && TB == 16 ? 3 - wg + (3 - wg >= O4) : O4;
    const uint32_t ub = sb + SM_U + wg * USLOT_B + UPAD * 16, turn = sb + SM_MISC + 376 + ord * 8, sfs = sb + SM_MISC + 256 + wg * 8;
    const uint32_t du = wg * (USLOT_B / 16) + (SM_U / 16 + UPAD + TA * 8);
    uint32_t ud[8], fs;
    auto skip = [&]() {
        const int lane = lane_v();
        const uint32_t ua = ub + ((lane >> 3) & 1) * ULO_B + (8 * wq + (lane & 7)) * 16 + (lane >> 4) * 512;
        if (IA == 0) ldsm_x4_t(ud[0], ud[1], ud[2], ud[3], ua);
        if (TB == 16) ldsm_x4_t(ud[4], ud[5], ud[6], ud[7], ua + 1024);
        const uint2 fd = lds64(sfs);
        fs = fd.x;
        const float dsk = __uint_as_float(fd.y);
#pragma unroll
        for (int i = 2 * IA; i < TB / 2; i++) ud[i] = pack_bf16(h_lo(ud[i]) * dsk, h_hi(ud[i]) * dsk);
    };
    conv_rename<2 * TA, 2 * TB>(acc);
    if (__builtin_expect(ord != 0, 0)) {
        skip();
        mbar_wait(turn);
    } else if (B2L) {
        bar_sync(0, NWRK);
    }
    if (O4 < 4 || (TA == 0 && TB == 16)) asm volatile("{\n.reg .pred p;\nelect.sync _|p, 0xffffffff;\n@p mbarrier.arrive.shared::cta.b64 _, [%0];\n}\n" ::"r"(turn + 48) : "memory");
    fg(IC<8>());
    wg_fence();
#pragma unroll
    for (int m = 7; m >= 0; m--) {
        wg_h<TA, TB - TA>(acc, a[m], smem_desc(sb, du - m, ULO_B));
        if (m == GA || m == GB || m == HAND) wg_commit();
        if (m == GB) asm volatile("wgmma.wait_group.sync.aligned 1;\n" ::: "memory");
    }
    wg_commit();
    if (O4 < 4 || (TA == 0 && TB == 16)) {
        asm volatile("wgmma.wait_group.sync.aligned 1;\n" ::: "memory");
        asm volatile("{\n.reg .pred p;\nelect.sync _|p, 0xffffffff;\n@p mbarrier.arrive.shared::cta.b64 _, [%0];\n}\n" ::"r"(turn + 8) : "memory");
    }
    __syncwarp();
    fg(IC<3>());
    if (!ord) skip();
    fg(IC<4>());
    const int lane = lane_v();
    const uint32_t lp = sb + SM_PL + (ord >= 3 ? ord - 3 : ord) * PL_B + lane * 8;
    unsigned char* gy = gy0 + ((4 * wq + (lane & 3)) * DM + (TA == 0 && TB == 16 ? 4 * blockIdx.x + wg : 512 + (blockIdx.x >> 1))) * 64 + (lane >> 2) * 8;
    const uint32_t st = lp + (wq * 12 - ((wq * (wq - 1)) >> 1)) * 256;
    uint32_t ld[3];
#pragma unroll
    for (int s = 1; s < 4; s++) {
        const int w = (wq - s) & 3;
        ld[s - 1] = lp + (w * 12 - ((w * (w - 1)) >> 1) + s - 1 - (wq < s ? 3 : 0)) * 256;
    }
    const uint32_t one = 1u + (warp >> 8);
    if (one == 0u) stg64(gy, ld[0], ld[1]);
    if (ord >= 3) bar_sync(9 + ord, 256);
    wg_wait0();
    fg(IC<6>());
#pragma unroll
    for (int j = TA; j < TB; j++)
        if ((j & 3) && j + 3 >= 4 * IA && (j + 3 < TB || j + wq < TB)) sts64(st + (j - 1 - (j >> 2)) * 256, acc[2 * j], acc[2 * j + 1]);
    bar_sync(1 + wg, 128);
    fg(IC<7>());
    uint2 v[4][3];
#pragma unroll
    for (int i = IA; i < TB / 4; i++)
#pragma unroll
        for (int s = 0; s < 3; s++) {
            if (i == 0) { v[i][s] = make_uint2(0u, 0u); if (wq > s) v[i][s] = lds64(ld[s]); }
            else v[i][s] = lds64(ld[s] + i * 768);
        }
    fg(IC<5>());
#pragma unroll
    for (int i = IA; i < TB / 4; i++) {
        const uint32_t x0 = hadd2(v[i][0].x, acc[8 * i]), x1 = hadd2(v[i][1].x, v[i][2].x), y0 = hadd2(v[i][0].y, acc[8 * i + 1]), y1 = hadd2(v[i][1].y, v[i][2].y);
        const uint32_t x = hadd2(x0, x1), y = hadd2(y0, y1);
        const uint32_t lo = pack_bf16(h_lo(x), h_hi(x)), hi = pack_bf16(h_lo(y), h_hi(y));
        ud[2 * i] = max(hfma2_bf(lo, fs, ud[2 * i]), one); ud[2 * i + 1] = hfma2_bf(hi, fs, ud[2 * i + 1]);
    }
    if (SPACE && TA == 0 && TB == 16 && ord < SPN) {
#pragma unroll
        for (int i = 0; i < 4; i++) {
            stg64(gy + i * 16 * DM * 64, ud[2 * i], ud[2 * i + 1]);
            if (i < 3) { const unsigned c0 = clock32(); while (clock32() - c0 < SPACE) {} }
        }
    } else {
#pragma unroll
        for (int i = IA; i < TB / 4; i++) stg64(gy + i * 16 * DM * 64, ud[2 * i], ud[2 * i + 1]);
    }
    if (ord < 2) bar_arrive(12 + ord, 256);
}
template <int M0, int M1>
__device__ __forceinline__ void conv_frags(uint32_t (&a)[8][4], const uint32_t (&r)[18], uint32_t sel, uint32_t dep, int warp) {
    const uint32_t s = prmt_v(sel, dep, 0x3210u + (warp >> 8)), sw = s ^ 0x4444u;
#pragma unroll
    for (int m = M0; m < M1; m++) {
        a[m][0] = prmt_v(r[2 * m + 1], r[2 * m + 2], s); a[m][1] = prmt_v(r[2 * m + 2], r[2 * m + 3], s);
        a[m][2] = prmt_v(r[2 * m + 1], r[2 * m], sw); a[m][3] = prmt_v(r[2 * m + 2], r[2 * m + 1], sw);
    }
}
template <class FG>
__device__ __forceinline__ void conv_main(const Conv& c, uint32_t (&acc)[32], uint32_t sb, uint32_t sel, unsigned char* gy, int warp, size_t ycopy, FG fg) {
    const uint32_t kw = (warp >> 2) * (KW_B / 16) + SM_KW / 16;
    const uint64_t d2 = smem_desc(sb, kw + KW_T2 / 16, KW_KH), d2b = smem_desc(sb, kw + KW_T2 / 16 + 1, KW_KH), d3 = smem_desc(sb, kw + KW_T3 / 16, 16), d3b = smem_desc(sb, kw + KW_T3 / 16 + 32, 16);
    uint32_t a[8][4];
    {
        const int ord = warp < 16 ? 3 - (warp >> 2) + (3 - (warp >> 2) >= O4) : O4;
        if (__builtin_expect(ord >= GATE, 0)) {
            fg(IC<1>());
            mbar_wait(sb + SM_MISC + 376 + 48 + (ord - GATE) * 8);
        }
    }
    wg_fence();
    wg_h<12, 4>(acc, c.q3[0], d3b); wg_h<8, 4>(acc, c.q3[0], d3); wg_h<4, 4>(acc, c.q2[0][0], d2b);
    wg_h<12, 4>(acc, c.q3[1], d3); wg_h<8, 4>(acc, c.q2[1][0], d2b);
    wg_h<12, 4>(acc, c.q2[2][0], d2b); wg_h<4, 4>(acc, c.q2[0][1], d2); wg_h<8, 4>(acc, c.q2[1][1], d2);
    wg_h<12, 4>(acc, c.q2[2][1], d2);
    wg_commit(); __syncwarp();
    fg(IC<0>());
    wg_wait0();
    conv_frags<0, 8>(a, c.r, sel, acc[16], warp);
    fg(IC<2>());
    if (warp >= 16) {
        if (blockIdx.x & 1) conv_tail<4, 16, 2>(acc, a, sb, gy, warp, ycopy, fg);
        else conv_tail<0, 8, 0>(acc, a, sb, gy, warp, ycopy, fg);
    } else {
        conv_tail<0, 16, 0>(acc, a, sb, gy, warp, ycopy, fg);
    }
}
#define CONV_LT6 const int dd = (lane >> 3) + (lane & 4) - (lane & 3); \
        const uint4 lt6 = make_uint4(prmt_v((dd & 3) * 288, 0u, idn), prmt_v(0x3254u + (dd >> 2) * 0x2222u, 0u, idn), \
            prmt_v(UPAD * 16 + (lane & 7) * 16 + ULO_B - 32 + (lane >> 3) * 512, 0u, idn), prmt_v(UPAD * 16 + (lane & 7) * 16 + ((lane >> 3) & 1) * ULO_B - 16 + (lane & 16), 0u, idn));
#define CONV_PRE \
        CONV_LT6 \
        const uint32_t ka = kw + lt6.x, sel = lt6.y, ks = kw + lt7.x; \
        const uint32_t ca0 = sb + SM_U + wg * USLOT_B + (warp & 3) * 128 + lt6.z, ca1 = sb + SM_U + wg * USLOT_B + (warp & 3) * 128 + lt6.w; \
        uint4 bd[4]; \
        band_pair<2, 4>(bd[0], bd[1], lt7.w); band_pair<4, 0>(bd[2], bd[3], lt7.w);
#define CONV_PRE2 ConvPre ce_; conv_pre(ce_, ka, ks, sel);
#define CONV_BODY \
        Conv c; \
        uint32_t acc[32]; \
        conv_sums(c, acc, ce_, ca0, ca1, bd, ka, sel, warp & 3, warp >> 8);
#define WS a_b_0_1_2_34_xy_56_7__c__r____de__
#define WS_STR2(x) #x
#define WS_STR(x) WS_STR2(x)
__device__ constexpr char wunit(int pt, int k) {
    constexpr char t[] = WS_STR(WS);
    int i = 0;
    for (; pt > 0 && t[i]; i++) pt -= t[i] == '_';
    for (; k > 0 && t[i] && t[i] != '_'; i++) k--;
    return t[i] == '_' ? 0 : t[i];
}
__device__ constexpr bool wsched_ok() {
    int seen = 0;
    for (int p = 0; p < 21; p++)
        for (int k = 0; wunit(p, k); k++) {
            const char c = wunit(p, k);
            const int bit = 1 << (c == 'r' ? 13 : c >= 'x' ? c - 'x' + 14 : c >= 'a' ? c - 'a' + 8 : c - '0');
            if ((seen & bit) || k >= (p < 16 ? 4 : 2) || (p < 5 && c >= '4' && c <= '7') || (p < 6 && (c == 'c' || c == 'd')) || (p < 16 && c == 'e')) return false;
            seen |= bit;
        }
    return seen == 0xffff;
}
struct WMaps { CUtensorMap g, u, gr, ur, d, dr; };
static_assert(GATE <= 2 && O4 >= 2, "resets");
static_assert(wsched_ok(), "weight schedule");
template <int PT, int K>
__device__ __forceinline__ void weight_units(uint32_t sb, const WMaps& m, int w) {
    constexpr char U = wunit(PT, K);
    if constexpr (U != 0) {
        if (w == K && elect_one()) {
            const int P = blockIdx.x >> 1, odd = blockIdx.x & 1;
            constexpr int bar = SM_MISC + (U == 'e' ? 352 : U >= 'a' && U <= 'r' ? 336 : 328);
            if constexpr (U == 'e') { if (!odd) tma_2d(sb + SM_WD + 4 * 8192, &m.d, 256, 64 * P, sb + bar); }
            else if constexpr (U == 'r') tma_3d(sb + SM_WD + 40960, &m.dr, 0, 4096 + 8 * P, 5 * odd, sb + bar);
            else if constexpr (U >= 'x') tma_3d(sb + SM_WR + (U - 'x') * 4608, U == 'x' ? &m.gr : &m.ur, 4096 + 8 * P, 0, 2 * odd, sb + bar);
            else if constexpr (U >= 'a') tma_2d(sb + SM_WD + (U - 'a') * 8192, &m.d, 320 * odd + 64 * (U - 'a'), 64 * P, sb + bar);
            else tma_2d(sb + (U < '4' ? SM_WG : SM_WU) + (U & 3) * 9216, U < '4' ? &m.g : &m.u, 64 * P, 288 * odd + (U & 3) * 72, sb + bar);
        }
        weight_units<PT, K + 1>(sb, m, w);
    }
}
#define WPOINT(i, w) do { weight_units<i, 0>(sb, wm, w); } while (0)

__global__ void __launch_bounds__(NTHR, 1) __cluster_dims__(2, 1, 1)
fused_kernel(const Params p, const __grid_constant__ WMaps wm, const __grid_constant__ CUtensorMap tm_x,
             const __grid_constant__ CUtensorMap tm_y, const __grid_constant__ CUtensorMap tm_z) {
    extern __shared__ __align__(1024) unsigned char smem[];
    const uint32_t sb = smem_u32(smem);
    const int tid = threadIdx.x, warp = __shfl_sync(0xffffffffu, tid >> 5, 0), lane = tid & 31;
    const int b = blockIdx.x, P = b >> 1, odd = b & 1;
    const int g = lane >> 2, t = lane & 3;
    const int wg = warp >> 2, t128 = tid & 127;
    const uint32_t s_stat = sb + SM_MISC;
    const uint32_t s_key = sb + SM_MISC + 128;
    const uint32_t s_wm = sb + SM_MISC + 256;
    const uint32_t s_k16 = sb + SM_MISC + 192;
    const uint32_t s_fs = sb + SM_MISC + 256;
    const uint32_t s_cnt = sb + SM_MISC + 320;
    const uint32_t bar_w = sb + SM_MISC + 328, bar_d = bar_w + 8, bar_g = bar_w + 16, bar_r = bar_w + 32, bar_h = bar_w + 40, bar_x = bar_w + 48;
    STAMP(0);

    const unsigned tk0 = clock32();
    const bool lnw = (unsigned)(warp - 10) < 9u;
    const unsigned pm = tid + (tid < 512 ? 512 * b : 65024 + 128 * P), pq = (pm & ~127u) + 4 * lane;
    uint32_t pl = ldg16(p.lar + pm), ldt = ldg16(p.ldt + (pm >> 7));
    const uint32_t pa2 = ldg16(p.aim + pm), pc = ldg16(p.cre + pm), pi = ldg16(p.cim + pm);
    const uint2 call_re = ldg64(p.cre + pq), call_im = ldg64(p.cim + pq);
    const uint32_t dskl = ldg16(p.dsk + (pm >> 7));
    const uint32_t ep = ld_poll32(p.s->hint + (b & 7) * 32 + 1 + (lane >> 5));
    if ((unsigned)(tid - 320) < 288u) {
        const bf16* xp = p.x + (unsigned)((32 * P + 2 * odd + TOKEN_OF(g)) * DM + ((tid - 320) & ~31) + 8 * t);
        const uint32_t xt = sb + SM_XT + ((tid - 320) & ~31) * 32 + lane * 16;
        asm volatile("cp.async.cg.shared.global [%0], [%1], 16;\ncp.async.cg.shared.global [%0 + 512], [%1 + 9216], 16;\n"
                     "cp.async.cg.shared.global [%0 + 9216], [%1 + 576], 16;\ncp.async.cg.shared.global [%0 + 9728], [%1 + 9792], 16;\n" ::"r"(xt), "l"(xp) : "memory");
    }
    uint32_t* const std_ = p.s->st + ((lane & 12) * 128 + odd * 256 + 4 * P + 2 * (lane & 1) + ((lane >> 1) & 1)) * 2;
    unsigned char* const ud = reinterpret_cast<unsigned char*>(p.s->uT) + (32 * (warp - UW) + 8 * (g >> 1) + (g & 1)) * 4096 + b * 32 + t * 8;
    if (warp == 0) {
        if (lane == 0) {
            mbar_init(bar_x, 1); mbar_init(bar_w, 1); mbar_init(bar_d, 1); mbar_init(bar_d + 16, 1); mbar_init(bar_g, 1); mbar_init(bar_h, 3); mbar_init(bar_r, 1);
            #pragma unroll
            for (int i = 1; i < 11; i++) mbar_init(bar_x + 8 * i, 4);
            asm volatile("fence.mbarrier_init.release.cluster;\n" ::: "memory");
            mbar_expect(bar_x, 16384); mbar_expect(bar_r, 8192);
            mbar_expect(bar_w, 2 * 41472); mbar_expect(bar_d, 32768 + 5120); mbar_expect(bar_d + 16, 8192); mbar_expect(bar_g, 9 * 512);
        }
        __syncwarp();
        bar_arrive(0, NWRK);
    }
    if (warp == 0 && elect_one()) tma_3d(sb + SM_XC, &tm_x, 8 * P, 0, 8 * odd, bar_x);
    asm volatile("barrier.cluster.arrive.relaxed.aligned;\n" ::: "memory");
    const uint32_t kw = sb + SM_KW + wg * KW_B;
    if (t128 < 2 * UPAD) sts128(sb + SM_U + wg * USLOT_B + (t128 & 1) * ULO_B + (t128 >> 1) * 16, 0u, 0u, 0u, 0u);
    sts128(kw + t128 * 16, 0u, 0u, 0u, 0u);
    if (t128 < KW_B / 16 - 128) sts128(kw + 2048 + t128 * 16, 0u, 0u, 0u, 0u);
    if (tid < 128) {
#pragma unroll
        for (int i = 0; i < 4; i++) sts128(sb + SM_ZERO + i * 2048 + tid * 16, 0u, 0u, 0u, 0u);
    }
    if (warp != 0) bar_sync(0, NWRK);
    STAMP(1);
    if (warp == 19 || warp == UW || warp == UW + 1) {
        if (warp == 19) {
            if (lane < 16) stg64(std_, 0u, 0u);
            if (lane < 9) asm volatile("prefetch.global.L2 [%0];\n" ::"l"(p.wr + lane * 64));
        } else {
#pragma unroll
            for (int k = 0; k < 4; k++) stg64(ud + k * 8192, 0u, 0u);
        }
    }
    uint32_t X[2][8];
    auto partial = [&]() {
        const uint32_t xt = sb + SM_XT + (warp - 10) * 1024 + lane * 16;
        asm volatile("cp.async.wait_all;\n" ::: "memory");
        STAMP(23);
        const uint4 a = lds128(xt), c = lds128(xt + 512), d = lds128(xt + 9216), e = lds128(xt + 9728);
        X[0][0] = a.x; X[0][1] = a.y; X[0][2] = a.z; X[0][3] = a.w; X[0][4] = d.x; X[0][5] = d.y; X[0][6] = d.z; X[0][7] = d.w;
        X[1][0] = c.x; X[1][1] = c.y; X[1][2] = c.z; X[1][3] = c.w; X[1][4] = e.x; X[1][5] = e.y; X[1][6] = e.z; X[1][7] = e.w;
        const uint32_t one[8] = {0x3f803f80u, 0x3f803f80u, 0x3f803f80u, 0x3f803f80u, 0x3f803f80u, 0x3f803f80u, 0x3f803f80u, 0x3f803f80u};
        ln_partial<8>(X, one, sb + SM_LNP, warp - 10, g, t);
        bar_arrive(6, 320);
        if (PAUSE & 1) bar_sync(7, PCNT);
    };
    if (LNAT == 0 && lnw) {
        partial();
        pl = prmt_v(pl, X[0][0], 0x3210u + (warp >> 8)); ldt = prmt_v(ldt, X[0][0], 0x3210u + (warp >> 8));
    }
    auto finish = [&]() {
        bar_sync(6, 320);
        float mb, rc;
        ln_finish<9>(sb + SM_LNP, lane, mb, rc);
        const float rh = rbf(rc);
        const uint32_t s0 = (__float_as_uint(mb) >> 16) | (((ep & 0x7fffu) + 1u) << 16), s1 = pack_bf16(rh, rc - rh);
        if (lane < 16) { stg64(std_, s0, s1); sts64(s_stat + lane * 8, s0, s1); }
        if (lane == 16) sts32(s_cnt + 4, ep);
        bar_arrive(7, PCNT);
        STAMP(28);
    };
    auto upub = [&]() {
        if (!(PAUSE & 6)) bar_sync(7, PCNT);
        const uint32_t utag = ((ep & 3u) + 1u) * 0x10001u;
        uint32_t U[2][4];
#pragma unroll
        for (int hf = 0; hf < 2; hf++) {
            const uint2 st = lds64(s_stat + (g + 8 * hf) * 8);
            const uint4 xv = lds128(sb + SM_XT + (16 + warp - UW) * 1024 + hf * 512 + lane * 16);
            const uint32_t xs[4] = {xv.x, xv.y, xv.z, xv.w};
#pragma unroll
            for (int k = 0; k < 4; k++) {
                const uint32_t u = ln_apply(xs[k], st);
                U[hf][k] = movm((pack_f16_rz(bf_lo(u), __uint_as_float(u)) & 0xfff8fff8u) | utag);
            }
        }
#pragma unroll
        for (int k = 0; k < 4; k++) stg64(ud + k * 8192, U[0][k], U[1][k]);
    };
    if (FINAT == 0 && warp == 19) finish();
    const uint32_t tb = table_buf(sb, warp);
    const float dt = rbf(expf(bf_lo(ldt)));
    KGen kg;
    kgen_setup(kg, pl | (pa2 << 16), dt);
    if (LNAT == 1 && lnw) {
        partial();
        kg.z8.x = __uint_as_float(prmt_v(__float_as_uint(kg.z8.x), X[0][0], 0x3210u + (warp >> 8)));
        kg.z1.x = __uint_as_float(prmt_v(__float_as_uint(kg.z1.x), X[0][0], 0x3210u + (warp >> 8)));
    }
    if (FINAT == 1 && warp == 19) finish();
    if (UAT == 0 && (warp == UW || warp == UW + 1)) upub();
    kgen_rows(kg, tb, lane);
    if (wg == 0) fence_async();
    if (LNAT == 2 && lnw) {
        partial();
        kg.z128.x = __uint_as_float(prmt_v(__float_as_uint(kg.z128.x), X[0][0], 0x3210u + (warp >> 8)));
        kg.z1.x = __uint_as_float(prmt_v(__float_as_uint(kg.z1.x), X[0][0], 0x3210u + (warp >> 8)));
    }
    if (FINAT == 2 && warp == 19) finish();
    if (UAT == 1 && (warp == UW || warp == UW + 1)) upub();
    STAMP(2);
    WPOINT(0, warp - 4);
    const int ce = c_exponent(call_re, call_im);
    if (t128 == 0) sts64(s_fs + wg * 8, (uint32_t)min(max(ce + (int)(__float_as_uint(dt) >> 23) - 116, 0), 254) * 0x800080u, dskl << 16);
    kgen_chain(kg, pc | (pi << 16), __uint_as_float(((uint32_t)(244 - ce) << 23) | (__float_as_uint(dt) & 0x7fffffu)));
    if ((PAUSE & 4) && warp < 10) bar_sync(7, PCNT);
    if (UAT == 4 && (warp == UW || warp == UW + 1)) upub();
    STAMP(3);
    WPOINT(1, warp - 6);
    kgen_cols(kg, tb, lane);
    if (LNAT == 3 && lnw) partial();
    if (FINAT == 3 && warp == 19) finish();
    if ((PAUSE & 2) && warp < 10) bar_sync(7, PCNT);
    if (UAT == 2 && (warp == UW || warp == UW + 1)) upub();
    STAMP(4);
    WPOINT(2, warp - 8);
    const uint4* usrc = wg < 4 ? reinterpret_cast<const uint4*>(p.s->st) + odd * 512 + (lane & 1) * 128 + 16 * (warp & 7) + (lane >> 1)
                               : reinterpret_cast<const uint4*>(p.s->uT) + P * 256 + 2 * t128;
    const int ustep = wg < 4 ? 256 : 1;
    uint4 uv0, uv1;
    kgen_mma(kg, tb, lane);
    if (UAT == 3 && (warp == UW || warp == UW + 1)) upub();
    STAMP(26);
    WPOINT(3, warp - 5);
    const uint32_t idn = 0x3210u + (warp >> 8);
    uint4 lt7 = make_uint4(prmt_v(KW_T2 + ((lane >> 3) & 1) * KW_KH + (33 + (lane & 7)) * 16 - (lane & 16), 0u, idn), t * 288 + g * 8 + 8, (lane & 1) * 4096 + (lane >> 1) * 16,
                                 prmt_v(8u << ((lane >> 3) + (lane & 4)) >> (lane & 3), 0u, idn));
    asm volatile("barrier.cluster.wait.acquire.aligned;\n" ::: "memory");
    const bool pe = (int)(clock32() - tk0) >= (wg < 4 ? TP0 : TP4);
    if (pe) { uv0 = ld_poll(usrc); uv1 = ld_poll(usrc + ustep); }
    bar_sync(1 + wg, 128);
    kgen_combine(sb, warp, lane, kw, lt7.y);
    if (warp < 3 || warp > 6) bar_arrive(14, NWRK);
    STAMP(5);
    WPOINT(4, warp - 7);
    if (!pe) {
        while ((int)(clock32() - tk0) < (wg < 4 ? TP0 : TP4)) {}
        uv0 = ld_poll(usrc); uv1 = ld_poll(usrc + ustep);
    }
    if (wg < 4) {
        mbar_wait(bar_x);
        const bool far = warp < 8;
        const uint32_t xa = sb + SM_XC + (warp & 7) * 256 + (odd ^ far) * 8 + lt7.z;
        uint2 xv[4] = {lds64(xa), lds64(xa + 8192), lds64(xa + 2048), lds64(xa + 10240)};
        const uint32_t tag = ((ep & 0x7fffu) + 1u) << 16;
        int it = 0;
        while (true) {
            const bool bad = (((uv0.x ^ tag) | (uv0.z ^ tag)) | ((uv1.x ^ tag) | (uv1.z ^ tag))) >> 16;
            if (!__any_sync(0xffffffffu, bad)) break;
            if (++it > SPIN_LIMIT) TRAP();
            if (bad) { uv0 = ld_poll(usrc); uv1 = ld_poll(usrc + 256); }
        }
        STAMP(6);
        DBG(wg, it);
        const uint2 st[4] = {make_uint2(uv0.x, uv0.y), make_uint2(uv0.z, uv0.w), make_uint2(uv1.x, uv1.y), make_uint2(uv1.z, uv1.w)};
#pragma unroll
        for (int i = 0; i < 4; i++) {
            xv[i].x = ln_apply(xv[i].x, st[i]);
            xv[i].y = ln_apply(xv[i].y, st[i]);
        }
        const uint32_t ub = sb + SM_U + UPAD * 16 + odd * ULO_B + (warp & 7) * 256 + lane * 8;
        const uint32_t w[4][2] = {{pack_f16(bf_lo(xv[0].x), bf_lo(xv[1].x)), pack_f16(bf_lo(xv[2].x), bf_lo(xv[3].x))}, {HI2(xv[0].x, xv[1].x), HI2(xv[2].x, xv[3].x)},
                                  {pack_f16(bf_lo(xv[0].y), bf_lo(xv[1].y)), pack_f16(bf_lo(xv[2].y), bf_lo(xv[3].y))}, {HI2(xv[0].y, xv[1].y), HI2(xv[2].y, xv[3].y)}};
#pragma unroll
        for (int i = 0; i < 4; i++) {
            if (far) asm volatile("st.async.shared::cluster.mbarrier::complete_tx::bytes.v2.b32 [%0], {%1,%2}, [%3];\n" ::"r"((ub ^ 0x1000000u) + i * USLOT_B), "r"(w[i][0]), "r"(w[i][1]), "r"(bar_r ^ 0x1000000u) : "memory");
            else sts64(ub + i * USLOT_B, w[i][0], w[i][1]);
        }
    } else {
        const uint32_t utag = ((ep & 3u) + 1u) * 0x10001u;
        int it = 0;
        while (true) {
            const bool bad = (((uv0.x ^ utag) | (uv0.y ^ utag) | (uv0.z ^ utag) | (uv0.w ^ utag)) | ((uv1.x ^ utag) | (uv1.y ^ utag) | (uv1.z ^ utag) | (uv1.w ^ utag))) & 0x70007u;
            if (!__any_sync(0xffffffffu, bad)) break;
            if (++it > SPIN_LIMIT) TRAP();
            if (bad) { uv0 = ld_poll(usrc); uv1 = ld_poll(usrc + 1); }
        }
        STAMP(6);
        DBG(4, it);
        const uint32_t ub = sb + SM_U + UPAD * 16 + 4 * USLOT_B + (t128 >> 1) * 32 + (t128 & 1) * 8;
        sts64(ub, prmt(uv0.x, uv0.z, 0x5410u) ^ utag, prmt(uv1.x, uv1.z, 0x5410u) ^ utag);
        sts64(ub + 16, prmt(uv0.x, uv0.z, 0x7632u) ^ utag, prmt(uv1.x, uv1.z, 0x7632u) ^ utag);
        sts64(ub + ULO_B, prmt(uv0.y, uv0.w, 0x5410u) ^ utag, prmt(uv1.y, uv1.w, 0x5410u) ^ utag);
        sts64(ub + ULO_B + 16, prmt(uv0.y, uv0.w, 0x7632u) ^ utag, prmt(uv1.y, uv1.w, 0x7632u) ^ utag);
    }
    lt7.w = prmt_v(lt7.w, uv0.x, idn);
    CONV_PRE
    if (warp < 3 && elect_one()) tma_st_3d(warp < 2 ? &tm_y : &tm_z, sb + SM_ZERO, warp < 2 ? 128 * b : 32 * (512 + P), 0, 2 * (warp < 2 ? warp : odd));
    if (warp >= 3 && warp <= 6) {
        bar_sync(14, NWRK);
        WPOINT(5, warp - 3);
    }
    bar_sync(1 + wg, 128);
    CONV_PRE2
    mbar_wait(bar_r);
    fence_async();
    bar_sync(0, NWRK);
    STAMP(7);
    uint32_t hv0 = 0;
    {
        WPOINT(6, 19 - warp);
        CONV_BODY
        WPOINT(7, 19 - warp);
        if (!B2L) bar_sync(0, NWRK); else if (wg != 3) bar_arrive(0, NWRK);
        STAMP(8);
        size_t ycopy = 0;
        auto hook = [&](auto gi) {
                     constexpr int G = decltype(gi)::value;
                     if (G == 4 && warp == HINTW) hv0 = ld_poll32(p.s->hint + (lane_v() & 7) * 32);
                     if (G == 4) mbar_wait(bar_h);
                     if (G == 1 || G == 2) WPOINT(7 + G, warp - 16);
                     if (G == 3) { WPOINT(10, warp - 12); WPOINT(12, warp - 8); WPOINT(14, warp - 4); }
                     if (G == 5) { WPOINT(11, warp - 13); WPOINT(13, warp - 9); WPOINT(15, warp - 5); }
                     if (G == 1 && warp >= 17 && elect_one())
                         bulk_s2g(warp == 17 ? p.s->part + b * (PBYTES / 4) : warp == 18 ? p.s->rows + b * 1152 : p.s->sc + b * 32, sb + SM_ZERO, warp == 17 ? PBYTES : warp == 18 ? 4608 : 32);
                     if (G == 4 && warp >= 17 && elect_one()) {
                         asm volatile("cp.async.bulk.wait_group 0;\n" ::: "memory");
                         hint_arrive(p.s->hint, 2, b & 7);
                     }
                     if (G == 1 && warp < 3) {
                         if (elect_one()) {
                             asm volatile("cp.async.bulk.wait_group 0;\n" ::: "memory");
                             mbar_arrive(bar_h);
                             hint_arrive(p.s->hint, 0, b & 7);
                         }
                         __syncwarp();
                         STAMP(17);
                     }
                 };
        conv_main(c, acc, sb, sel, reinterpret_cast<unsigned char*>(p.s->y), warp, ycopy, hook);
        STAMP(10);
    }
    {
    const int warp = warp_v(), lane = lane_v(), tid = 32 * warp + lane, g = lane >> 2, t = lane & 3;
    if (warp == HINTW) {
        const uint32_t target = (lds32(s_cnt + 4) + 1u) * 48u;
        if (__any_sync(0xffffffffu, (int)(hv0 - target) < 0)) hint_wait(p.s->hint, 0, target);
    }
    const unsigned char* ys = reinterpret_cast<const unsigned char*>(p.s->y) + ((size_t)P * DM + 32 * warp + 8 * (g >> 1) + (g & 1)) * 64 + odd * 32 + t * 8;
    STAMP(27);
    bar_sync(0, NWRK);
    STAMP(11);
    const uint32_t zr = warp >> 8;
    auto late_rows = [&](auto pub) {
        const uint32_t k = lds32(s_key + (lane & 7) * 4), ep = lds32(s_cnt + 4);
        const bool late = k & 256u, mine = late && ((k & 255u) >> 1) == (uint32_t)b;
        uint32_t todo = __ballot_sync(0xffffffffu, mine) & 0xffu;
        if (todo) {
#pragma unroll 1
            while (todo) {
                const int s = __ffs(todo) - 1, row = (__shfl_sync(0xffffffffu, k, s) >> 9) & 15;
                todo &= todo - 1;
                if ((row & 7) == g) pub(row & 8, 2 * NCTA + s);
            }
            __threadfence();
            bar_sync(0, NWRK);
            if (tid < NSEL && mine) *reinterpret_cast<volatile unsigned*>(p.s->flag + tid) = ep + 1u;
        }
        int it = 0;
        while (__any_sync(0xffffffffu, late && ld_poll32(p.s->flag + (lane & 7)) != ep + 1u)) { if (++it > SPIN_LIMIT) TRAP(); }
        __threadfence();
        const int gs = tid / 36;
        const uint4* src = reinterpret_cast<const uint4*>(p.s->rows) + __shfl_sync(0xffffffffu, late ? 2 * NCTA + (lane & 7) : (k & 255u), gs & 7) * 144 + 36 * odd + (tid - gs * 36);
        if (tid < 288) {
            uint4 v0;
            do { v0 = ld_poll(src); if (++it > SPIN_LIMIT) TRAP(); } while (!v0.x);
            sts128(sb + SM_XS + gs * XS_PITCH + (tid - gs * 36) * 16, v0.x, v0.y, v0.z, v0.w);
        }
        bar_sync(0, NWRK);
    };
    if (warp >= 18) {
        if (warp == 18) {
            uint32_t* const kp = pin(p.s->sc + 32 * b, zr);
            const uint32_t kid = pin(0x30000000u | ((lane & 15) << 9) | 2 * b, zr), ka = pin(s_k16 + (lane & 15) * 4, zr), kb = pin(s_k16 + (lane & 16) * 2, zr);
            bar_sync(8, 640);
            float mb, rc;
            ln_finish<18>(sb + SM_LNP, lane, mb, rc);
            if (lane < 16) stat_store(s_stat + lane * 8, mb, rc, 0u);
            bar_arrive(13, 608);
            bar_sync(10, 608);
            const float r = sum18(sb + SM_LNP + (32 + (lane & 15)) * 80);
            const uint32_t bits = pack_bf16(0.f, r);
            const uint32_t me = (((bits ^ ((uint32_t)((int)bits >> 31) & 0x7fffffffu)) >> 3) & 0x1fffe000u) ^ kid;
            sts32(ka, me);
            __syncwarp();
            const uint4 v = lds128(kb), w = lds128(kb + 16);
#define GT(x) ((me - (x)) >> 31)
            uint32_t rank = pin(GT(v.x) + GT(v.y) + GT(v.z), zr) + pin(GT(v.w) + GT(w.x) + GT(w.y), zr) + pin(GT(w.z) + GT(w.w), zr);
#undef GT
            rank += __shfl_xor_sync(0xffffffffu, rank, 16);
            if (lane < 16) { if (rank < 8) stg32(kp + rank, me + (rank < 2 ? rank : 256u)); }
            else sts32(ka + (s_wm - s_k16), rank);
            bar_arrive(11, 640);
            weight_units<19, 0>(sb, wm, 0); weight_units<19, 1>(sb, wm, 1);
        }
        const uint4* ksrc = pin(reinterpret_cast<const uint4*>(p.s->sc) + 8 * lane, zr);
        const uint4* rsrc = pin(reinterpret_cast<const uint4*>(p.s->rows) + 36 * odd + t, zr);
        if (warp == 19) {
            weight_units<20, 0>(sb, wm, 0); weight_units<20, 1>(sb, wm, 1);
            bar_sync(8, 640);
            weight_units<16, 0>(sb, wm, 0); weight_units<16, 1>(sb, wm, 1);
            hint_wait(p.s->hint, 2, (lds32(s_cnt + 4) + 1u) * 48u);
            bar_sync(11, 640);
        }
        bool slow = false;
        int it = 0;
        if (warp == 19) {
        uint4 q[4];
        DELAY(KDEL);
#pragma unroll
        for (int i = 0; i < 4; i++) q[i] = ld_poll(ksrc + 256 * i);
        while (true) {
            uint32_t a[4];
#pragma unroll
            for (int i = 0; i < 4; i++) a[i] = q[i].x & q[i].y & q[i].z & q[i].w;
            if (__all_sync(0xffffffffu, a[0] & a[1] & a[2] & a[3])) break;
#pragma unroll
            for (int i = 0; i < 4; i++)
                if (!a[i]) q[i] = ld_poll(ksrc + 256 * i);
            if (++it > SPIN_LIMIT) TRAP();
        }
        bar_arrive(9, 608);
        STAMP(16);
        auto merge = [](const uint4& x, const uint4& y) {
            const uint32_t a = max(x.x, y.w), c = max(x.y, y.z), d = max(x.z, y.y), e = max(x.w, y.x);
            const uint32_t a2 = max(a, d), d2 = min(a, d), c2 = max(c, e), e2 = min(c, e);
            return make_uint4(max(a2, c2), min(a2, c2), max(d2, e2), min(d2, e2));
        };
        uint4 h = merge(merge(q[0], q[1]), merge(q[2], q[3]));
        uint4 v[9];
        uint32_t key = 0;
#pragma unroll
        for (int s = 0; s < 8; s++) {
            const uint32_t m = __reduce_max_sync(0xffffffffu, h.x);
            const bool w = h.x == m;
            h.x = w ? h.y : h.x; h.y = w ? h.z : h.y; h.z = w ? h.w : h.z; h.w = w ? 0u : h.w;
            if (g == s) key = m;
        }
        rsrc += (key & 255u) * 144;
#pragma unroll
        for (int j = 0; j < 9; j++) v[j] = ld_poll(rsrc + 4 * j);
        slow = __any_sync(0xffffffffu, key & 256u);
        STAMP(18);
        if (__any_sync(0xffffffffu, h.x == 0u)) {
            uint4 r[4];
            it = 0;
            while (true) {
#pragma unroll
                for (int i = 0; i < 4; i++) r[i] = ld_poll(ksrc + 256 * i + 1);
                if (__all_sync(0xffffffffu, all_nz(r[0]) && all_nz(r[1]) && all_nz(r[2]) && all_nz(r[3]))) break;
                if (++it > SPIN_LIMIT) TRAP();
            }
            uint32_t m = 1u << 30;
#pragma unroll 1
            for (int s = 0; s < 8; s++) {
                uint32_t x = 0;
#pragma unroll
                for (int i = 0; i < 4; i++) {
                    x = max(max(max(x, q[i].x - m), max(q[i].y - m, q[i].z - m)), q[i].w - m);
                    x = max(max(max(x, r[i].x - m), max(r[i].y - m, r[i].z - m)), r[i].w - m);
                }
                m += __reduce_max_sync(0xffffffffu, x);
                if (g == s) key = m;
            }
            slow = true;
        }
        const uint32_t xsa = sb + SM_XS + g * XS_PITCH + t * 16;
        sts32(s_key + g * 4, key);
        sts32(xsa, 0u);
        bar_arrive(12, 608);
#pragma unroll
        for (int j = 0; j < 9; j++) sts128(xsa + j * 64, v[j].x, v[j].y, v[j].z, v[j].w);
        slow = slow || min(min(min(min(v[0].x, v[1].x), v[2].x), min(min(v[3].x, v[4].x), v[5].x)), min(min(v[6].x, v[7].x), v[8].x)) == 0u;
        }
        if (bar_or(0, NWRK, slow)) late_rows([](bool, int) {});
        STAMP(19);
        const int fl = 16 * (b & 1) + ((tid >> 2) & 15), fc = 16 * (b >> 1) + (fl >> 2) + 8 * ((tid >> 1) & 1), fsl = 2 * (fl & 3) + (tid & 1);
        const uint32_t kk = lds32(s_key + fsl * 4);
        const uint32_t* fsrc = p.s->rows + ((kk & 256u) ? 2 * NCTA + fsl : (kk & 255u)) * DM + (fc >> 1);
        uint32_t hw = 1u, uw = 1u;
        if (b < 72) { uw = ld_poll32(fsrc); hw = ld_poll32(fsrc + 288); }
        if (b < 72) {
            it = 0;
            while (!hw || !uw) { uw = ld_poll32(fsrc); hw = ld_poll32(fsrc + 288); if (++it > SPIN_LIMIT) TRAP(); }
            const int row = (kk >> 9) & 15, ftok = 8 * (kk & 252u) + (kk & 2u) + TOKEN_OF(row & 7) + (row & 8);
            const unsigned k16 = (kk >> 13) & 0xffffu;
            const unsigned bits = (k16 & 0x8000u) ? (k16 & 0x7fffu) : (~k16 & 0xffffu);
            const float rs = 512.0f * rbf(__fdividef(1.0f, 1.0f + __expf(-__uint_as_float(bits << 16))));
            bf16* const op = p.out + (unsigned)(ftok * DM + fc);
            const float uv = (fc & 1) ? bf_hi(uw) : bf_lo(uw), hv = (fc & 1) ? bf_hi(hw) : bf_lo(hw);
            const uint32_t a = sb + SM_FIN + (tid - 576) * 80;
            sts128(a + 64, __float_as_uint(rs), __float_as_uint(uv), __float_as_uint(hv), (uint32_t)(size_t)op ^ (uint32_t)((size_t)op >> 32));
            bar_sync(14, 576);
            const uint4 p0 = lds128(a), p1 = lds128(a + 16), p2 = lds128(a + 32), p3 = lds128(a + 48);
#define F4(p) ((__uint_as_float(p.x) + __uint_as_float(p.y)) + (__uint_as_float(p.z) + __uint_as_float(p.w)))
            const float v0 = F4(p0), v1 = F4(p1), v2 = F4(p2), v3 = F4(p3);
#undef F4
            const float y3 = rbf(rbf((v0 + v1) + (v2 + v3)) * rs);
            asm volatile("st.global.u16 [%0], %1;\n" ::"l"(op), "h"((unsigned short)pack_bf16(hv + rbf(uv + y3), 0.f)) : "memory");
        }
        if (b == 0 && tid >= 632) *reinterpret_cast<volatile unsigned*>(p.s->hint + (tid & 7) * 32 + 1) = lds32(s_cnt + 4) + 1u;
    } else {
        uint32_t H[2][4], U2[2][4], WA[9][4], WD[18], WE[18];
        const int fkh = warp >= 9, fmt = warp - 9 * fkh;
        auto load_wa = [&](auto k0, auto k1) {
            if (k0.value >= k1.value) return;
            if (k0.value == 0) mbar_wait(bar_w);
            const int mi = lane >> 3, rr = lane & 7;
            const int row = fkh * 144 + rr + 8 * (mi >> 1);
            const uint32_t aad = sb + (fmt < 8 ? SM_WG + (mi & 1) * (SM_WU - SM_WG) + row * 128 + (fmt ^ rr) * 16 : SM_WR + (mi & 1) * 4608 + row * 16), ks = fmt < 8 ? 2048 : 256;
#pragma unroll
            for (int k = k0.value; k < k1.value; k++) ldsm_x4_t(WA[k][0], WA[k][1], WA[k][2], WA[k][3], aad + k * ks);
        };
        auto load_wd = [&](uint32_t (&WD)[18], int tile) {
            mbar_wait(bar_d);
            if (tile & 16) mbar_wait(bar_d + 16);
            const int mi = lane >> 3, rr = lane & 7;
            const uint32_t base = sb + SM_WD + rr * 128 + (((2 * tile + (mi & 1)) & 7) ^ rr) * 16;
#pragma unroll
            for (int k = 0; k < 4; k++) ldsm_x4_t(WD[4 * k], WD[4 * k + 1], WD[4 * k + 2], WD[4 * k + 3], base + (tile >> 2) * 8192 + (k * 16 + 8 * (mi >> 1)) * 128);
            ldsm_x2_t(WD[16], WD[17], base + 40960 + (tile >> 2) * 1024);
        };
        auto publish = [&](bool hi, int slot) {
            uint4* rowp = reinterpret_cast<uint4*>(p.s->rows) + slot * 144 + warp * 4 + t;
            stg128(rowp, nzw(hi ? U2[1][0] : U2[0][0]), nzw(hi ? U2[1][1] : U2[0][1]), nzw(hi ? U2[1][2] : U2[0][2]), nzw(hi ? U2[1][3] : U2[0][3]));
            stg128(rowp + 72, nzw(hi ? H[1][0] : H[0][0]), nzw(hi ? H[1][1] : H[0][1]), nzw(hi ? H[1][2] : H[0][2]), nzw(hi ? H[1][3] : H[0][3]));
        };
        uint4 wr = make_uint4(0x3f803f80u, 0x3f803f80u, 0x3f803f80u, 0x3f803f80u);
        {
            uint2 yv[4];
#pragma unroll
            for (int k = 0; k < 4; k++) yv[k] = ld_poll64(ys + k * 128);
            if (g == 0) wr = ldg128(p.wr + 32 * warp + 8 * t);
            const uint4 x0 = lds128(sb + SM_XT + warp * 1024 + lane * 16), x1 = lds128(sb + SM_XT + warp * 1024 + 512 + lane * 16);
            load_wa(IC<0>(), IC<WA0>());
            int it = 0;
            while (!__all_sync(0xffffffffu, yv[0].x && yv[1].x && yv[2].x && yv[3].x)) {
#pragma unroll
                for (int k = 0; k < 4; k++) yv[k] = ld_poll64(ys + k * 128);
                if (++it > SPIN_LIMIT) TRAP();
            }
            STAMP(12);
            const uint32_t Z[2][4] = {{x0.x, x0.y, x0.z, x0.w}, {x1.x, x1.y, x1.z, x1.w}};
#pragma unroll
            for (int k = 0; k < 4; k++) {
                H[0][k] = hadd2_bf(Z[0][k], movm(yv[k].x));
                H[1][k] = hadd2_bf(Z[1][k], movm(yv[k].y));
            }
            const uint32_t bw[4] = {wr.x, wr.y, wr.z, wr.w};
            ln_partial<4>(H, bw, sb + SM_LNP, warp, g, t);
        }
        bar_arrive(8, 640);
        load_wa(IC<WA0>(), IC<WA1>());
        STAMP(13);
        bar_sync(13, 608);
        STAMP(14);
#pragma unroll
        for (int hf = 0; hf < 2; hf++) {
            const uint2 st = lds64(s_stat + (g + 8 * hf) * 8);
#pragma unroll
            for (int k = 0; k < 4; k++) U2[hf][k] = ln_apply(H[hf][k], st);
        }
        {
            float cs[4] = {0.f, 0.f, 0.f, 0.f}, ct[4] = {0.f, 0.f, 0.f, 0.f};
            mma_bf16(cs, U2[0][0], U2[1][0], U2[0][1], U2[1][1], wr.x, wr.y);
            mma_bf16(ct, U2[0][2], U2[1][2], U2[0][3], U2[1][3], wr.z, wr.w);
            if (t == 0) { stsf(sb + SM_LNP + ((32 + g) * 20 + warp) * 4, cs[0] + ct[0]); stsf(sb + SM_LNP + ((40 + g) * 20 + warp) * 4, cs[2] + ct[2]); }
            bar_arrive(10, 608);
        }
        load_wa(IC<WA1>(), IC<WA2>());
        bar_sync(11, 640);
        {
            const uint32_t rk[2] = {lds32(s_wm + g * 4), lds32(s_wm + 32 + g * 4)};
            uint32_t lo = min(rk[0], rk[1]), hi = max(rk[0], rk[1]);
#pragma unroll 1
            while (lo < 2) { publish(lo == rk[1], 2 * b + lo); lo = hi; hi = 16; }
        }
        load_wa(IC<WA2>(), IC<WA3>());
        bar_sync(9, 608);
        load_wa(IC<WA3>(), IC<9>());
#pragma unroll
        for (int hf = 0; hf < 2; hf++)
            sts128(sb + SM_OUT + (g + 8 * hf) * OUT_PITCH + warp * 64 + t * 16,
                   hadd2_bf(H[hf][0], U2[hf][0]), hadd2_bf(H[hf][1], U2[hf][1]), hadd2_bf(H[hf][2], U2[hf][2]), hadd2_bf(H[hf][3], U2[hf][3]));
        fence_async();
        WPOINT(17, warp - 16);
        if ((WDAT == 0 || (WDAT == 2 && fkh)) && (warp < 16 || !odd)) load_wd(WD, warp);
        const uint32_t bad = pin(sb + SM_XS + (lane & 7) * XS_PITCH + (fkh * 144 + 8 * (lane >> 3)) * 2, zr), ex = pin(sb + SM_EX + warp * 512 + lane * 16, zr);
        uint32_t* pp = pin(p.s->part + ((size_t)(2 * (20 * odd + warp) + (lane >> 4)) * 64 + P) * 32 + (lane & 15) * 2, zr);
        bar_sync(12, 608);
        if (warp < 16 && !__any_sync(0xffffffffu, (lds32(s_key + (lane & 7) * 4) & 0x1efeu) == (uint32_t)((warp << 9) | 2 * b)) && elect_one())
            bulk_s2g(p.out + (size_t)(32 * P + 2 * odd + TOKEN_OF(warp & 7) + (warp & 8)) * DM, sb + SM_OUT + warp * OUT_PITCH, DM * 2);
        WPOINT(18, warp - 16);
        STAMP(15);
        if (bar_or(0, NWRK, false)) late_rows(publish);
        STAMP(19);
        float gp[4];
        {
            float c4[3][4];
#pragma unroll
            for (int i = 0; i < 3; i++)
#pragma unroll
                for (int j = 0; j < 4; j++) c4[i][j] = 0.f;
#pragma unroll
            for (int k = 0; k < 10; k += 2) {
                uint32_t b0, b1, b2, b3;
                ldsm_x4(b0, b1, b2, b3, bad + k * 32);
                mma_bf16(c4[k % 3], WA[k][0], WA[k][1], WA[k][2], WA[k][3], b0, b1);
                if (k < 8) mma_bf16(c4[(k + 1) % 3], WA[k + 1][0], WA[k + 1][1], WA[k + 1][2], WA[k + 1][3], b2, b3);
            }
#pragma unroll
            for (int j = 0; j < 4; j++) gp[j] = c4[0][j] + (c4[1][j] + c4[2][j]);
            if (warp >= 9) {
                sts128f(ex, gp);
                bar_arrive(6, 576);
            } else {
                bar_sync(6, 576);
                const uint4 o = lds128(ex + 4608);
                gp[0] += __uint_as_float(o.x); gp[1] += __uint_as_float(o.y); gp[2] += __uint_as_float(o.z); gp[3] += __uint_as_float(o.w);
                asm volatile("st.async.shared::cluster.mbarrier::complete_tx::bytes.v4.b32 [%0], {%1,%2,%3,%4}, [%5];\n"
                             ::"r"(ex ^ 0x1000000u), "r"(__float_as_uint(gp[0])), "r"(__float_as_uint(gp[1])), "r"(__float_as_uint(gp[2])), "r"(__float_as_uint(gp[3])), "r"(bar_g ^ 0x1000000u) : "memory");
                if (WDAT == 2) load_wd(WD, warp);
            }
            if (WDAT == 1 && (warp < 16 || !odd)) load_wd(WD, warp);
            if (warp >= 16 && !odd) load_wd(WE, warp + 2);
        }
        STAMP(20);
        if (warp < 9) {
            mbar_wait(bar_g);
            const uint4 u = lds128(ex);
            const uint32_t G = pack_bf16(gp[0] + __uint_as_float(u.x), gp[1] + __uint_as_float(u.y)), U = pack_bf16(gp[2] + __uint_as_float(u.z), gp[3] + __uint_as_float(u.w));
            const float G0 = bf_lo(G), G1 = bf_hi(G);
            sts32(sb + SM_GU + tid * 4, hmul2_bf(pack_bf16(G0 * rcp_approx(1.0f + ex2_approx(G0 * -1.4426950408889634f)), G1 * rcp_approx(1.0f + ex2_approx(G1 * -1.4426950408889634f))), U));
        }
        bar_sync(7, 576);
        STAMP(21);
        if (warp < 16 || !odd) {
            uint32_t gb[9];
            ldsm_x4_t(gb[0], gb[1], gb[2], gb[3], sb + SM_GU + lane * 16);
            ldsm_x4_t(gb[4], gb[5], gb[6], gb[7], sb + SM_GU + 512 + lane * 16);
            ldsm_x1_t(gb[8], sb + SM_GU + 1024 + (lane & 7) * 16);
            auto down = [&](const uint32_t (&W)[18], uint32_t* dst) {
                float c4[4] = {0.f, 0.f, 0.f, 0.f}, d4[4] = {0.f, 0.f, 0.f, 0.f}, e4[4] = {0.f, 0.f, 0.f, 0.f};
                mma_bf16(c4, W[0], W[1], W[2], W[3], gb[0], gb[1]);
                mma_bf16(d4, W[4], W[5], W[6], W[7], gb[2], gb[3]);
                mma_bf16(e4, W[8], W[9], W[10], W[11], gb[4], gb[5]);
                mma_bf16_k8(c4, W[16], W[17], gb[8]);
                mma_bf16(d4, W[12], W[13], W[14], W[15], gb[6], gb[7]);
                const float v0 = (c4[0] + e4[0]) + d4[0], v1 = (c4[1] + e4[1]) + d4[1], v2 = (c4[2] + e4[2]) + d4[2], v3 = (c4[3] + e4[3]) + d4[3];
                const uint32_t e = max(max(__float_as_uint(fmaxf(fabsf(v0), fabsf(v1))), __float_as_uint(fmaxf(fabsf(v2), fabsf(v3)))), 16u << 23) >> 23;
                const float sc = __uint_as_float((245u - e) << 23);
                stg64(dst, pack_f16(v0 * sc, v1 * sc) | ((e * 0x8002000u) & 0x60006000u), pack_f16(v2 * sc, v3 * sc) | ((e * 0x800200u) & 0x60006000u));
            };
            if (warp >= 16) { down(WE, pp + 4 * 64 * 32); down(WD, pp); }
            else down(WD, pp);
        }
        asm volatile("cp.async.bulk.wait_group.read 0;\n" ::: "memory");
        STAMP(22);
        if (b < 72 && warp < 16) {
            const uint2* src = reinterpret_cast<const uint2*>(p.s->part) + (unsigned)(b * 1024 + tid);
            uint2 a, c;
            int it = 0;
            DELAY(PDEL);
            a = ld_poll64(src); c = ld_poll64(src + 512);
            while (!__all_sync(0xffffffffu, a.y && c.y)) {
                a = ld_poll64(src); c = ld_poll64(src + 512);
                if (++it > SPIN_LIMIT) TRAP();
            }
            STAMP(24);
            const float ea = __uint_as_float((((a.y & 0x60006000u) | ((a.x >> 4) & 0x06000600u)) * 0x4001u) & 0x7f800000u);
            const float ec = __uint_as_float((((c.y & 0x60006000u) | ((c.x >> 4) & 0x06000600u)) * 0x4001u) & 0x7f800000u);
            a.x &= 0x9fff9fffu; a.y &= 0x9fff9fffu; c.x &= 0x9fff9fffu; c.y &= 0x9fff9fffu;
            const float s0 = fmaf(h_lo(a.x), ea, h_lo(c.x) * ec), s1 = fmaf(h_hi(a.x), ea, h_hi(c.x) * ec), s2 = fmaf(h_lo(a.y), ea, h_lo(c.y) * ec), s3 = fmaf(h_hi(a.y), ea, h_hi(c.y) * ec);
            const bool up = lane & 16;
            const float r0 = __shfl_xor_sync(0xffffffffu, up ? s0 : s2, 16), r1 = __shfl_xor_sync(0xffffffffu, up ? s1 : s3, 16);
            const uint32_t fa = sb + SM_FIN + ((lane & 15) * 4 + (up ? 2 : 0)) * 80 + warp * 4;
            stsf(fa, (up ? s2 : s0) + r0); stsf(fa + 80, (up ? s3 : s1) + r1);
            bar_arrive(14, 576);
        }
    }
    STAMP(25);
    }
}

typedef CUresult (*PFN_tmEncode)(CUtensorMap*, CUtensorMapDataType, cuuint32_t, void*, const cuuint64_t*, const cuuint64_t*, const cuuint32_t*,
                                 const cuuint32_t*, CUtensorMapInterleave, CUtensorMapSwizzle, CUtensorMapL2promotion, CUtensorMapFloatOOBfill);

extern "C" void kernel_launch(void* const* d_in, const int* in_sizes, int n_in, void* d_out, int out_size) {
    Params p;
    p.x = (const bf16*)d_in[0];
    p.lar = (const bf16*)d_in[1];
    p.aim = (const bf16*)d_in[2];
    p.cre = (const bf16*)d_in[3];
    p.cim = (const bf16*)d_in[4];
    p.ldt = (const bf16*)d_in[5];
    p.dsk = (const bf16*)d_in[6];
    p.wr = (const bf16*)d_in[8];
    p.out = (bf16*)d_out;
    static PFN_tmEncode enc = nullptr;
    static void* scratch = nullptr;
    if (!enc) {
        cudaFuncSetAttribute(fused_kernel, cudaFuncAttributeMaxDynamicSharedMemorySize, SMEM_TOTAL);
        void* fn = nullptr;
        cudaDriverEntryPointQueryResult qr;
        cudaGetDriverEntryPoint("cuTensorMapEncodeTiled", &fn, cudaEnableDefault, &qr);
        enc = (PFN_tmEncode)fn;
        cudaGetSymbolAddress(&scratch, g_scratch);
    }
    p.s = (Scratch*)scratch;
    WMaps wm;
    CUtensorMap tm_x, tm_y, tm_z;
    const cuuint64_t dims[2] = {FF, DM}, strides[1] = {FF * 2}, rdims[3] = {FF, 144, 4}, rstrides[2] = {FF * 2, 144 * FF * 2};
    const cuuint32_t box[2] = {64, 72}, rbox[3] = {8, 144, 2}, es3[3] = {1, 1, 1};
    for (int i = 0; i < 2; i++) {
        enc(i ? &wm.u : &wm.g, CU_TENSOR_MAP_DATA_TYPE_BFLOAT16, 2, d_in[9 + i], dims, strides, box, es3, CU_TENSOR_MAP_INTERLEAVE_NONE, CU_TENSOR_MAP_SWIZZLE_128B,
            CU_TENSOR_MAP_L2_PROMOTION_NONE, CU_TENSOR_MAP_FLOAT_OOB_FILL_NONE);
        enc(i ? &wm.ur : &wm.gr, CU_TENSOR_MAP_DATA_TYPE_BFLOAT16, 3, d_in[9 + i], rdims, rstrides, rbox, es3, CU_TENSOR_MAP_INTERLEAVE_NONE, CU_TENSOR_MAP_SWIZZLE_NONE,
            CU_TENSOR_MAP_L2_PROMOTION_NONE, CU_TENSOR_MAP_FLOAT_OOB_FILL_NONE);
    }
    const cuuint64_t ddims[2] = {DM, FF}, dstrides[1] = {DM * 2}, edims[3] = {64, FF, 9}, estrides[2] = {DM * 2, 128};
    const cuuint32_t dbox[2] = {64, 64}, ebox[3] = {64, 8, 5};
    enc(&wm.d, CU_TENSOR_MAP_DATA_TYPE_BFLOAT16, 2, d_in[11], ddims, dstrides, dbox, es3, CU_TENSOR_MAP_INTERLEAVE_NONE, CU_TENSOR_MAP_SWIZZLE_128B,
        CU_TENSOR_MAP_L2_PROMOTION_NONE, CU_TENSOR_MAP_FLOAT_OOB_FILL_NONE);
    enc(&wm.dr, CU_TENSOR_MAP_DATA_TYPE_BFLOAT16, 3, d_in[11], edims, estrides, ebox, es3, CU_TENSOR_MAP_INTERLEAVE_NONE, CU_TENSOR_MAP_SWIZZLE_128B,
        CU_TENSOR_MAP_L2_PROMOTION_NONE, CU_TENSOR_MAP_FLOAT_OOB_FILL_NONE);
    const cuuint64_t xdims[3] = {DM, LSEQ / 16, 16}, xstrides[2] = {16 * DM * 2, DM * 2};
    const cuuint32_t xbox[3] = {8, LSEQ / 16, 8};
    enc(&tm_x, CU_TENSOR_MAP_DATA_TYPE_BFLOAT16, 3, d_in[0], xdims, xstrides, xbox, es3, CU_TENSOR_MAP_INTERLEAVE_NONE, CU_TENSOR_MAP_SWIZZLE_NONE,
        CU_TENSOR_MAP_L2_PROMOTION_NONE, CU_TENSOR_MAP_FLOAT_OOB_FILL_NONE);
    const cuuint64_t ydims[3] = {DM * 32, 16, 4}, ystrides[2] = {DM * 64, 16 * DM * 64};
    const cuuint32_t ybox[3] = {128, 16, 2}, zbox[3] = {32, 16, 2};
    enc(&tm_y, CU_TENSOR_MAP_DATA_TYPE_BFLOAT16, 3, p.s->y, ydims, ystrides, ybox, es3, CU_TENSOR_MAP_INTERLEAVE_NONE, CU_TENSOR_MAP_SWIZZLE_NONE,
        CU_TENSOR_MAP_L2_PROMOTION_NONE, CU_TENSOR_MAP_FLOAT_OOB_FILL_NONE);
    enc(&tm_z, CU_TENSOR_MAP_DATA_TYPE_BFLOAT16, 3, p.s->y, ydims, ystrides, zbox, es3, CU_TENSOR_MAP_INTERLEAVE_NONE, CU_TENSOR_MAP_SWIZZLE_NONE,
        CU_TENSOR_MAP_L2_PROMOTION_NONE, CU_TENSOR_MAP_FLOAT_OOB_FILL_NONE);
    fused_kernel<<<NCTA, NTHR, SMEM_TOTAL>>>(p, wm, tm_x, tm_y, tm_z);
}
```

```cpp
#include <cuda_runtime.h>
#include <cuda.h>
#include <cuda_fp16.h>
#include <cuda_bf16.h>
#include <stdint.h>

#define LSEQ 2048
#define DM 576
#define NST 128
#define FF 4608
#define NSEL 8
#define NCTA 128
#define NTHR 640
#define NWRK 640

typedef __nv_bfloat16 bf16;

#define SM_WD 0
#define SM_WG 46080
#define SM_WR 82944
#define SM_WU 92160
#define SM_ZERO 32768
#define SM_XC 16384
#define SM_TB 96000
#define SM_PL 129024
#define PL_B 10752
#define SM_XT (SM_TB + 20 * TBW)
#define SM_U (SM_XT + 18432)
#define UPAD 8
#define ULO_B ((UPAD + 128) * 16)
#define USLOT_B (2 * ULO_B)
#define SM_KW (SM_U + 5 * USLOT_B)
#define KW_B 3600
#define KW_T2 1152
#define KW_KH 656
#define KW_T3 2464
#define SM_MISC (SM_KW + 5 * KW_B)
#define SM_LNP (SM_MISC + 576)
#define SMEM_TOTAL (SM_LNP + 5120)
#define TBP 112
#define TBW (32 * TBP)
#define SM_OUT SM_PL
#define OUT_PITCH 1216
#define SM_XS (SM_PL + 19456)
#define XS_PITCH 592
#define SM_EX (SM_PL + 24320)
#define SM_KEYS (SM_KW + 5120)
#define SM_FIN SM_KW
#define SM_GU (SM_PL + 33536)

struct __align__(128) Scratch {
    unsigned hint[8 * 32];
    unsigned flag[32];
    uint32_t sc[NCTA * 64];
    uint32_t st[LSEQ * 2];
    uint32_t uT[64 * (LSEQ / 2)];
    uint32_t y[NCTA * DM * 8];
    uint32_t part[72 * 64 * 32];
    uint32_t rows[(2 * NCTA + NSEL) * DM];
};
__device__ Scratch g_scratch;
#define STAMP(i)
#define DBG(i, v)

__device__ __forceinline__ float rbf(float x) {
    uint32_t r;
    asm("cvt.rn.bf16x2.f32 %0, %1, %2;\n" : "=r"(r) : "f"(x), "f"(0.f));
    return __uint_as_float(r);
}
__device__ __forceinline__ uint32_t pack_bf16(float lo, float hi) {
    uint32_t r;
    asm("cvt.rn.bf16x2.f32 %0, %1, %2;\n" : "=r"(r) : "f"(hi), "f"(lo));
    return r;
}
__device__ __forceinline__ uint32_t pack_f16(float lo, float hi) {
    uint32_t r;
    asm("cvt.rn.f16x2.f32 %0, %1, %2;\n" : "=r"(r) : "f"(hi), "f"(lo));
    return r;
}
__device__ __forceinline__ uint32_t pack_f16_rz(float lo, float hi) {
    uint32_t r;
    asm("cvt.rz.f16x2.f32 %0, %1, %2;\n" : "=r"(r) : "f"(hi), "f"(lo));
    return r;
}
__device__ __forceinline__ float bf_lo(uint32_t w) { return __uint_as_float(w << 16); }
__device__ __forceinline__ float bf_hi(uint32_t w) { return __uint_as_float(w & 0xffff0000u); }
__device__ __forceinline__ uint32_t hadd2_bf(uint32_t a, uint32_t b) {
    __nv_bfloat162 r = __hadd2_rn(*reinterpret_cast<__nv_bfloat162*>(&a), *reinterpret_cast<__nv_bfloat162*>(&b));
    return *reinterpret_cast<uint32_t*>(&r);
}
__device__ __forceinline__ uint32_t hmul2_bf(uint32_t a, uint32_t b) {
    __nv_bfloat162 r = __hmul2_rn(*reinterpret_cast<__nv_bfloat162*>(&a), *reinterpret_cast<__nv_bfloat162*>(&b));
    return *reinterpret_cast<uint32_t*>(&r);
}
__device__ __forceinline__ uint32_t hfma2_bf(uint32_t a, uint32_t b, uint32_t c) { uint32_t r; asm("fma.rn.bf16x2 %0, %1, %2, %3;\n" : "=r"(r) : "r"(a), "r"(b), "r"(c)); return r; }
__device__ __forceinline__ uint32_t hmul2(uint32_t a, uint32_t b) { uint32_t r; asm("mul.rn.f16x2 %0, %1, %2;\n" : "=r"(r) : "r"(a), "r"(b)); return r; }
__device__ __forceinline__ uint32_t hadd2(uint32_t a, uint32_t b) { uint32_t r; asm("add.rn.f16x2 %0, %1, %2;\n" : "=r"(r) : "r"(a), "r"(b)); return r; }
__device__ __forceinline__ uint32_t nzw(uint32_t w) { return w ? w : 0x8000u; }
__device__ __forceinline__ uint32_t smem_u32(const void* p) { return (uint32_t)__cvta_generic_to_shared(p); }
__device__ __forceinline__ uint32_t lds32(uint32_t addr) {
    uint32_t v;
    asm volatile("ld.shared.u32 %0, [%1];\n" : "=r"(v) : "r"(addr) : "memory");
    return v;
}
__device__ __forceinline__ uint2 lds64(uint32_t addr) {
    uint2 v;
    asm volatile("ld.shared.v2.u32 {%0,%1}, [%2];\n" : "=r"(v.x), "=r"(v.y) : "r"(addr) : "memory");
    return v;
}
__device__ __forceinline__ uint4 lds128(uint32_t addr) {
    uint4 v;
    asm volatile("ld.shared.v4.u32 {%0,%1,%2,%3}, [%4];\n" : "=r"(v.x), "=r"(v.y), "=r"(v.z), "=r"(v.w) : "r"(addr) : "memory");
    return v;
}
__device__ __forceinline__ float ldsf(uint32_t addr) { return __uint_as_float(lds32(addr)); }
__device__ __forceinline__ void sts32(uint32_t addr, uint32_t v) { asm volatile("st.shared.u32 [%0], %1;\n" ::"r"(addr), "r"(v) : "memory"); }
__device__ __forceinline__ void stsf(uint32_t addr, float v) { sts32(addr, __float_as_uint(v)); }
__device__ __forceinline__ void sts64(uint32_t addr, uint32_t a, uint32_t b) { asm volatile("st.shared.v2.u32 [%0], {%1,%2};\n" ::"r"(addr), "r"(a), "r"(b) : "memory"); }
__device__ __forceinline__ void sts128(uint32_t addr, uint32_t a, uint32_t b, uint32_t c, uint32_t d) {
    asm volatile("st.shared.v4.u32 [%0], {%1,%2,%3,%4};\n" ::"r"(addr), "r"(a), "r"(b), "r"(c), "r"(d) : "memory");
}
__device__ __forceinline__ void sts128f(uint32_t addr, const float (&v)[4]) {
    sts128(addr, __float_as_uint(v[0]), __float_as_uint(v[1]), __float_as_uint(v[2]), __float_as_uint(v[3]));
}
__device__ __forceinline__ void ldsm_x4(uint32_t& r0, uint32_t& r1, uint32_t& r2, uint32_t& r3, uint32_t addr) {
    asm volatile("ldmatrix.sync.aligned.m8n8.x4.shared.b16 {%0,%1,%2,%3}, [%4];\n"
                 : "=r"(r0), "=r"(r1), "=r"(r2), "=r"(r3) : "r"(addr) : "memory");
}
__device__ __forceinline__ void ldsm_x4_t(uint32_t& r0, uint32_t& r1, uint32_t& r2, uint32_t& r3, uint32_t addr) {
    asm volatile("ldmatrix.sync.aligned.m8n8.x4.trans.shared.b16 {%0,%1,%2,%3}, [%4];\n"
                 : "=r"(r0), "=r"(r1), "=r"(r2), "=r"(r3) : "r"(addr) : "memory");
}
__device__ __forceinline__ void ldsm_x2_t(uint32_t& r0, uint32_t& r1, uint32_t addr) {
    asm volatile("ldmatrix.sync.aligned.m8n8.x2.trans.shared.b16 {%0,%1}, [%2];\n" : "=r"(r0), "=r"(r1) : "r"(addr) : "memory");
}
__device__ __forceinline__ void ldsm_x1_t(uint32_t& r0, uint32_t addr) {
    asm volatile("ldmatrix.sync.aligned.m8n8.x1.trans.shared.b16 {%0}, [%1];\n" : "=r"(r0) : "r"(addr) : "memory");
}
__device__ __forceinline__ uint32_t movm(uint32_t a) {
    uint32_t d;
    asm volatile("movmatrix.sync.aligned.m8n8.trans.b16 %0, %1;\n" : "=r"(d) : "r"(a));
    return d;
}
__device__ __forceinline__ void mma_f16(float (&c)[4], uint32_t a0, uint32_t a1, uint32_t a2, uint32_t a3, uint32_t b0, uint32_t b1) {
    asm volatile(
        "mma.sync.aligned.m16n8k16.row.col.f32.f16.f16.f32 {%0,%1,%2,%3}, {%4,%5,%6,%7}, {%8,%9}, {%0,%1,%2,%3};\n"
        : "+f"(c[0]), "+f"(c[1]), "+f"(c[2]), "+f"(c[3])
        : "r"(a0), "r"(a1), "r"(a2), "r"(a3), "r"(b0), "r"(b1));
}
__device__ __forceinline__ void mma_bf16(float (&c)[4], uint32_t a0, uint32_t a1, uint32_t a2, uint32_t a3, uint32_t b0, uint32_t b1) {
    asm volatile(
        "mma.sync.aligned.m16n8k16.row.col.f32.bf16.bf16.f32 {%0,%1,%2,%3}, {%4,%5,%6,%7}, {%8,%9}, {%0,%1,%2,%3};\n"
        : "+f"(c[0]), "+f"(c[1]), "+f"(c[2]), "+f"(c[3])
        : "r"(a0), "r"(a1), "r"(a2), "r"(a3), "r"(b0), "r"(b1));
}
__device__ __forceinline__ void mma_bf16_k8(float (&c)[4], uint32_t a0, uint32_t a1, uint32_t b0) {
    asm volatile("mma.sync.aligned.m16n8k8.row.col.f32.bf16.bf16.f32 {%0,%1,%2,%3}, {%4,%5}, {%6}, {%0,%1,%2,%3};\n"
        : "+f"(c[0]), "+f"(c[1]), "+f"(c[2]), "+f"(c[3]) : "r"(a0), "r"(a1), "r"(b0));
}
__device__ __forceinline__ void bar_sync(int id, int n) { asm volatile("bar.sync %0, %1;\n" ::"r"(id), "r"(n) : "memory"); }
__device__ __forceinline__ void bar_arrive(int id, int n) { asm volatile("bar.arrive %0, %1;\n" ::"r"(id), "r"(n) : "memory"); }
__device__ __forceinline__ bool bar_or(int id, int n, bool v) {
    uint32_t r;
    asm volatile("{\n.reg .pred p, q;\nsetp.ne.u32 p, %3, 0;\nbar.red.or.pred q, %1, %2, p;\nselp.u32 %0, 1, 0, q;\n}\n" : "=r"(r) : "r"(id), "r"(n), "r"((uint32_t)v) : "memory");
    return r;
}
__device__ __forceinline__ uint4 ld_poll(const void* p) {
    uint4 v;
    asm volatile("ld.relaxed.gpu.global.v4.u32 {%0,%1,%2,%3}, [%4];\n" : "=r"(v.x), "=r"(v.y), "=r"(v.z), "=r"(v.w) : "l"(p) : "memory");
    return v;
}
template <class T> __device__ __forceinline__ T* pin(T* p, uint32_t z) {
    uint32_t lo, hi;
    asm volatile("mov.b64 {%0, %1}, %2;\n" : "=r"(lo), "=r"(hi) : "l"(p));
    asm volatile("xor.b32 %0, %0, %1;\n" : "+r"(lo) : "r"(z));
    asm volatile("xor.b32 %0, %0, %1;\n" : "+r"(hi) : "r"(z));
    asm volatile("mov.b64 %0, {%1, %2};\n" : "=l"(p) : "r"(lo), "r"(hi));
    return p;
}
__device__ __forceinline__ uint32_t pin(uint32_t a, uint32_t z) { asm volatile("xor.b32 %0, %0, %1;\n" : "+r"(a) : "r"(z)); return a; }
__device__ __forceinline__ uint2 ld_poll64(const void* p) {
    uint2 v;
    asm volatile("ld.relaxed.gpu.global.v2.u32 {%0,%1}, [%2];\n" : "=r"(v.x), "=r"(v.y) : "l"(p) : "memory");
    return v;
}
__device__ __forceinline__ uint32_t ld_poll32(const void* p) {
    uint32_t v;
    asm volatile("ld.relaxed.gpu.global.u32 %0, [%1];\n" : "=r"(v) : "l"(p) : "memory");
    return v;
}
__device__ __forceinline__ uint4 ldg128(const void* p) {
    uint4 v;
    asm volatile("ld.global.nc.v4.u32 {%0,%1,%2,%3}, [%4];\n" : "=r"(v.x), "=r"(v.y), "=r"(v.z), "=r"(v.w) : "l"(p));
    return v;
}
__device__ __forceinline__ uint2 ldg64(const void* p) {
    uint2 v;
    asm volatile("ld.global.nc.v2.u32 {%0,%1}, [%2];\n" : "=r"(v.x), "=r"(v.y) : "l"(p));
    return v;
}
__device__ __forceinline__ uint32_t ldg16(const void* p) {
    uint32_t v;
    asm volatile("ld.global.nc.u16 %0, [%1];\n" : "=r"(v) : "l"(p));
    return v;
}
__device__ __forceinline__ void stg128(void* p, uint32_t a, uint32_t b, uint32_t c, uint32_t d) {
    asm volatile("st.global.v4.u32 [%0], {%1,%2,%3,%4};\n" ::"l"(p), "r"(a), "r"(b), "r"(c), "r"(d) : "memory");
}
__device__ __forceinline__ void stg64(void* p, uint32_t a, uint32_t b) { asm volatile("st.global.v2.u32 [%0], {%1,%2};\n" ::"l"(p), "r"(a), "r"(b) : "memory"); }
__device__ __forceinline__ void stg32(void* p, uint32_t a) { asm volatile("st.global.u32 [%0], %1;\n" ::"l"(p), "r"(a) : "memory"); }
__device__ __forceinline__ bool all_nz(const uint4& v) { return v.x && v.y && v.z && v.w; }
#define SPIN_LIMIT (1 << 21)
#define TRAP() __trap()
__device__ __forceinline__ void hint_arrive(unsigned* g_hint, int idx, int sub) {
    asm volatile("red.relaxed.gpu.global.add.u32 [%0], 1;\n" ::"l"(&g_hint[sub * 32 + idx]) : "memory");
}
__device__ __forceinline__ void hint_wait(const unsigned* g_hint, int idx, unsigned target) {
    unsigned l;
    asm volatile("mov.u32 %0, %%laneid;" : "=r"(l));
    const unsigned* c = &g_hint[(l & 7) * 32 + idx];
    int it = 0;
    while (__any_sync(0xffffffffu, (int)(ld_poll32(c) - target) < 0)) { if (++it > SPIN_LIMIT) TRAP(); }
}
__device__ __forceinline__ void mbar_init(uint32_t bar, uint32_t cnt) { asm volatile("mbarrier.init.shared::cta.b64 [%0], %1;\n" ::"r"(bar), "r"(cnt) : "memory"); }
__device__ __forceinline__ void mbar_expect(uint32_t bar, uint32_t bytes) {
    asm volatile("mbarrier.arrive.expect_tx.shared::cta.b64 _, [%0], %1;\n" ::"r"(bar), "r"(bytes) : "memory");
}
__device__ __forceinline__ void mbar_arrive(uint32_t bar) { asm volatile("mbarrier.arrive.shared::cta.b64 _, [%0];\n" ::"r"(bar) : "memory"); }
__device__ __forceinline__ void mbar_wait(uint32_t bar) {
    asm volatile(
        "{\n.reg .pred p;\n"
        "W_%=:\n"
        "mbarrier.try_wait.parity.shared::cta.b64 p, [%0], 0;\n"
        "@!p bra W_%=;\n}\n" ::"r"(bar) : "memory");
}
__device__ __forceinline__ void bulk_s2g(void* dst, uint32_t src, uint32_t bytes) {
    asm volatile("cp.async.bulk.global.shared::cta.bulk_group [%0], [%1], %2;\ncp.async.bulk.commit_group;\n" ::"l"(dst), "r"(src), "r"(bytes) : "memory");
}
__device__ __forceinline__ void tma_2d(uint32_t dst, const CUtensorMap* tm, int c0, int c1, uint32_t bar) {
    asm volatile("cp.async.bulk.tensor.2d.shared::cluster.global.mbarrier::complete_tx::bytes [%0], [%1, {%3, %4}], [%2];\n"
                 ::"r"(dst), "l"(tm), "r"(bar), "r"(c0), "r"(c1) : "memory");
}
__device__ __forceinline__ void tma_3d(uint32_t dst, const CUtensorMap* tm, int c0, int c1, int c2, uint32_t bar) {
    asm volatile("cp.async.bulk.tensor.3d.shared::cluster.global.mbarrier::complete_tx::bytes [%0], [%1, {%3, %4, %5}], [%2];\n"
                 ::"r"(dst), "l"(tm), "r"(bar), "r"(c0), "r"(c1), "r"(c2) : "memory");
}
__device__ __forceinline__ void tma_st_3d(const CUtensorMap* tm, uint32_t src, int c0, int c1, int c2) {
    asm volatile("cp.async.bulk.tensor.3d.global.shared::cta.bulk_group [%0, {%2, %3, %4}], [%1];\ncp.async.bulk.commit_group;\n"
                 ::"l"(tm), "r"(src), "r"(c0), "r"(c1), "r"(c2) : "memory");
}
__device__ __forceinline__ bool elect_one() {
    uint32_t r;
    asm volatile("{\n.reg .pred p;\nelect.sync _|p, 0xffffffff;\nselp.u32 %0, 1, 0, p;\n}\n" : "=r"(r));
    return r;
}
__device__ __forceinline__ void fence_async() { asm volatile("fence.proxy.async.shared::cta;\n" ::: "memory"); }

__device__ __forceinline__ float2 cmul(float2 a, float2 b) {
    return make_float2(fmaf(a.x, b.x, -a.y * b.y), fmaf(a.x, b.y, a.y * b.x));
}
__device__ __forceinline__ float2 csq(float2 a) {
    float p = a.x * a.y;
    return make_float2(fmaf(a.x, a.x, -a.y * a.y), p + p);
}
__device__ __forceinline__ float2 cexp_e(float lr2, float rh, float rl, float e) {
    float m;
    asm("ex2.approx.ftz.f32 %0, %1;\n" : "=f"(m) : "f"(lr2 * e));
    const float a = rh * e;
    const float r = fmaf(rl, e, a - rintf(a)) * 6.283185307179586f;
    return make_float2(m * __cosf(r), m * __sinf(r));
}
__device__ __forceinline__ float rcp_approx(float x) { float r; asm("rcp.approx.ftz.f32 %0, %1;\n" : "=f"(r) : "f"(x)); return r; }
__device__ __forceinline__ float ex2_approx(float x) { float r; asm("ex2.approx.ftz.f32 %0, %1;\n" : "=f"(r) : "f"(x)); return r; }
__device__ __forceinline__ float sqrt_approx(float x) { float r; asm("sqrt.approx.ftz.f32 %0, %1;\n" : "=f"(r) : "f"(x)); return r; }

__device__ __forceinline__ void wg_fence() { asm volatile("wgmma.fence.sync.aligned;\n" ::: "memory"); }
__device__ __forceinline__ void wg_commit() { asm volatile("wgmma.commit_group.sync.aligned;\n" ::: "memory"); }
__device__ __forceinline__ void wg_wait0() { asm volatile("wgmma.wait_group.sync.aligned 0;\n" ::: "memory"); }
template <int T0, int NT> __device__ __forceinline__ void wg_h(uint32_t (&acc)[32], const uint32_t (&a)[4], uint64_t desc);
template <> __device__ __forceinline__ void wg_h<0, 16>(uint32_t (&acc)[32], const uint32_t (&a)[4], uint64_t desc) {
    asm volatile("wgmma.mma_async.sync.aligned.m64n128k16.f16.f16.f16 {%0,%1,%2,%3,%4,%5,%6,%7,%8,%9,%10,%11,%12,%13,%14,%15,%16,%17,%18,%19,%20,%21,%22,%23,%24,%25,%26,%27,%28,%29,%30,%31}, {%32,%33,%34,%35}, %36, 1, 1, 1, 0;\n"
                 : "+r"(acc[0]), "+r"(acc[1]), "+r"(acc[2]), "+r"(acc[3]), "+r"(acc[4]), "+r"(acc[5]), "+r"(acc[6]), "+r"(acc[7]), "+r"(acc[8]), "+r"(acc[9]), "+r"(acc[10]), "+r"(acc[11]), "+r"(acc[12]), "+r"(acc[13]), "+r"(acc[14]), "+r"(acc[15]), "+r"(acc[16]), "+r"(acc[17]), "+r"(acc[18]), "+r"(acc[19]), "+r"(acc[20]), "+r"(acc[21]), "+r"(acc[22]), "+r"(acc[23]), "+r"(acc[24]), "+r"(acc[25]), "+r"(acc[26]), "+r"(acc[27]), "+r"(acc[28]), "+r"(acc[29]), "+r"(acc[30]), "+r"(acc[31])
                 : "r"(a[0]), "r"(a[1]), "r"(a[2]), "r"(a[3]), "l"(desc));
}
template <> __device__ __forceinline__ void wg_h<4, 4>(uint32_t (&acc)[32], const uint32_t (&a)[4], uint64_t desc) {
    asm volatile("wgmma.mma_async.sync.aligned.m64n32k16.f16.f16.f16 {%0,%1,%2,%3,%4,%5,%6,%7}, {%8,%9,%10,%11}, %12, 1, 1, 1, 0;\n"
                 : "+r"(acc[8]), "+r"(acc[9]), "+r"(acc[10]), "+r"(acc[11]), "+r"(acc[12]), "+r"(acc[13]), "+r"(acc[14]), "+r"(acc[15])
                 : "r"(a[0]), "r"(a[1]), "r"(a[2]), "r"(a[3]), "l"(desc));
}
template <> __device__ __forceinline__ void wg_h<8, 4>(uint32_t (&acc)[32], const uint32_t (&a)[4], uint64_t desc) {
    asm volatile("wgmma.mma_async.sync.aligned.m64n32k16.f16.f16.f16 {%0,%1,%2,%3,%4,%5,%6,%7}, {%8,%9,%10,%11}, %12, 1, 1, 1, 0;\n"
                 : "+r"(acc[16]), "+r"(acc[17]), "+r"(acc[18]), "+r"(acc[19]), "+r"(acc[20]), "+r"(acc[21]), "+r"(acc[22]), "+r"(acc[23])
                 : "r"(a[0]), "r"(a[1]), "r"(a[2]), "r"(a[3]), "l"(desc));
}
template <> __device__ __forceinline__ void wg_h<12, 4>(uint32_t (&acc)[32], const uint32_t (&a)[4], uint64_t desc) {
    asm volatile("wgmma.mma_async.sync.aligned.m64n32k16.f16.f16.f16 {%0,%1,%2,%3,%4,%5,%6,%7}, {%8,%9,%10,%11}, %12, 1, 1, 1, 0;\n"
                 : "+r"(acc[24]), "+r"(acc[25]), "+r"(acc[26]), "+r"(acc[27]), "+r"(acc[28]), "+r"(acc[29]), "+r"(acc[30]), "+r"(acc[31])
                 : "r"(a[0]), "r"(a[1]), "r"(a[2]), "r"(a[3]), "l"(desc));
}
template <> __device__ __forceinline__ void wg_h<0, 8>(uint32_t (&acc)[32], const uint32_t (&a)[4], uint64_t desc) {
    asm volatile("wgmma.mma_async.sync.aligned.m64n64k16.f16.f16.f16 {%0,%1,%2,%3,%4,%5,%6,%7,%8,%9,%10,%11,%12,%13,%14,%15}, {%16,%17,%18,%19}, %20, 1, 1, 1, 0;\n"
                 : "+r"(acc[0]), "+r"(acc[1]), "+r"(acc[2]), "+r"(acc[3]), "+r"(acc[4]), "+r"(acc[5]), "+r"(acc[6]), "+r"(acc[7]), "+r"(acc[8]), "+r"(acc[9]), "+r"(acc[10]), "+r"(acc[11]), "+r"(acc[12]), "+r"(acc[13]), "+r"(acc[14]), "+r"(acc[15])
                 : "r"(a[0]), "r"(a[1]), "r"(a[2]), "r"(a[3]), "l"(desc));
}
template <> __device__ __forceinline__ void wg_h<4, 12>(uint32_t (&acc)[32], const uint32_t (&a)[4], uint64_t desc) {
    asm volatile("wgmma.mma_async.sync.aligned.m64n96k16.f16.f16.f16 {%0,%1,%2,%3,%4,%5,%6,%7,%8,%9,%10,%11,%12,%13,%14,%15,%16,%17,%18,%19,%20,%21,%22,%23}, {%24,%25,%26,%27}, %28, 1, 1, 1, 0;\n"
                 : "+r"(acc[8]), "+r"(acc[9]), "+r"(acc[10]), "+r"(acc[11]), "+r"(acc[12]), "+r"(acc[13]), "+r"(acc[14]), "+r"(acc[15]), "+r"(acc[16]), "+r"(acc[17]), "+r"(acc[18]), "+r"(acc[19]), "+r"(acc[20]), "+r"(acc[21]), "+r"(acc[22]), "+r"(acc[23]), "+r"(acc[24]), "+r"(acc[25]), "+r"(acc[26]), "+r"(acc[27]), "+r"(acc[28]), "+r"(acc[29]), "+r"(acc[30]), "+r"(acc[31])
                 : "r"(a[0]), "r"(a[1]), "r"(a[2]), "r"(a[3]), "l"(desc));
}

#define PBYTES 4608
#define DELAY(n) do { if (n) { const unsigned c0_ = clock32(); while ((int)(clock32() - c0_) < (n)) {} } } while (0)
#define KDEL 300
#define PDEL 300
#define CST(i) do { if ((warp & 3) == 0 && lane_v() == 0) { unsigned t_; asm volatile("mov.u32 %0, %%globaltimer_lo;" : "=r"(t_) :: "memory"); sts32(sb + SMEM_TOTAL - 768 + (warp >> 2) * 128 + (i) * 4, t_); } } while (0)
#define TP0 5000
#define TP4 5800
#define KDEL2 300
#define HINTW 10
#define WAS 0x0005
#define WA0 (WAS >> 12)
#define WA1 ((WAS >> 8) & 15)
#define WA2 ((WAS >> 4) & 15)
#define WA3 (WAS & 15)
#define WDAT 1
#define PAUSE 2
#define PCNT (32 + ((PAUSE & 1) ? 288 : 0) + ((PAUSE & 6) ? 320 : 64))
#define LNAT 2
#define UW 8
#define FINAT 3
#define UAT 2
#define TOKEN_OF(g) (16 * ((g) & 1) + ((g) >> 2) + 2 * ((g) & 2))
#define HI2(a, b) (pack_f16_rz(__uint_as_float(a), __uint_as_float(b)) & 0xfff8fff8u)
struct Params {
    const bf16 *x, *lar, *aim, *cre, *cim, *ldt, *dsk;
    Scratch* s;
    const bf16* wr;
    bf16* out;
};

template <int NK>
__device__ __forceinline__ void ln_partial(const uint32_t (&H)[2][NK], const uint32_t (&bw)[NK], uint32_t lp, int warp, int g, int t) {
    float cs[4] = {0.f, 0.f, 0.f, 0.f}, cl[4] = {0.f, 0.f, 0.f, 0.f}, ch[4] = {0.f, 0.f, 0.f, 0.f};
#pragma unroll
    for (int k = 0; k < NK; k += 2) {
        uint32_t a0, a1, a2, a3;
        asm volatile("prmt.b32 %0, %4, %4, %8;\nprmt.b32 %1, %5, %5, %8;\nprmt.b32 %2, %6, %6, %8;\nprmt.b32 %3, %7, %7, %8;\n"
                     : "=r"(a0), "=r"(a1), "=r"(a2), "=r"(a3) : "r"(H[0][k]), "r"(H[1][k]), "r"(H[0][k + 1]), "r"(H[1][k + 1]), "r"(0x3210u + (warp >> 8)));
        mma_bf16(cl, a0, a1, a2, a3, H[0][k], H[0][k + 1]);
        mma_bf16(ch, a0, a1, a2, a3, H[1][k], H[1][k + 1]);
        mma_bf16(cs, a0, a1, a2, a3, bw[k], bw[k + 1]);
    }
    const uint32_t a = lp + (g * 20 + warp) * 4;
    if (t == 0) {
        stsf(a, cs[1]); stsf(a + 8 * 80, cs[3]);
        if (NK == 4) { stsf(a + 48 * 80, cs[0]); stsf(a + 56 * 80, cs[2]); }
    }
    if (t == (g >> 1)) { stsf(a + 16 * 80, (g & 1) ? cl[1] : cl[0]); stsf(a + 24 * 80, (g & 1) ? ch[3] : ch[2]); }
}
__device__ __forceinline__ float sum18(uint32_t a) {
    const uint4 p = lds128(a), q = lds128(a + 16), r = lds128(a + 32), s = lds128(a + 48);
    const uint2 u = lds64(a + 64);
#define F(x) __uint_as_float(x)
    return (((F(p.x) + F(p.y)) + (F(p.z) + F(p.w))) + ((F(q.x) + F(q.y)) + (F(q.z) + F(q.w)))) +
           (((F(r.x) + F(r.y)) + (F(r.z) + F(r.w))) + ((F(s.x) + F(s.y)) + (F(s.z) + F(s.w))) + (F(u.x) + F(u.y)));
#undef F
}
__device__ __forceinline__ float sum9(uint32_t a) {
    const uint4 p = lds128(a), q = lds128(a + 16);
#define F(x) __uint_as_float(x)
    return (((F(p.x) + F(p.y)) + (F(p.z) + F(p.w))) + ((F(q.x) + F(q.y)) + (F(q.z) + F(q.w)))) + ldsf(a + 32);
#undef F
}
template <int N>
__device__ __forceinline__ void ln_finish(uint32_t lp, int lane, float& mb, float& rc) {
    const float v = N == 9 ? sum9(lp + lane * 80) : sum18(lp + lane * 80);
    const float o = __shfl_xor_sync(0xffffffffu, v, 16);
    const float m0 = v * (1.0f / 576.0f);
    const float mean = fmaf(fmaf(-m0, 576.0f, v), 1.0f / 576.0f, m0);
    const float var = fmaxf(fmaf(o, 1.0f / 576.0f, -(mean * mean)), 0.f);
    mb = rbf(mean);
    rc = rcp_approx(rbf(sqrt_approx(rbf(rbf(var) + 1e-5f))));
}
__device__ __forceinline__ uint32_t ln_apply(uint32_t w, const uint2& st) {
    uint32_t r;
    asm("{\n.reg .b16 m, t, h, l;\n.reg .b32 mm, hh, ll, d, e;\nmov.b32 {m, t}, %2;\nmov.b32 {h, l}, %3;\nmov.b32 mm, {m, m};\nmov.b32 hh, {h, h};\nmov.b32 ll, {l, l};\n"
        "sub.rn.bf16x2 d, %1, mm;\nmul.rn.bf16x2 e, d, ll;\nfma.rn.bf16x2 %0, d, hh, e;\n}\n" : "=r"(r) : "r"(w), "r"(st.x), "r"(st.y));
    return r;
}
__device__ __forceinline__ void stat_store(uint32_t a, float mb, float rc, uint32_t extra) {
    const float rh = rbf(rc);
    sts64(a, (__float_as_uint(mb) >> 16) | (extra << 16), pack_bf16(rh, rc - rh));
}

__device__ __forceinline__ void hcmul(uint32_t re, uint32_t im, uint32_t z, uint32_t& ore, uint32_t& oim) {
    asm("{\n.reg .b16 x, y;\n.reg .b32 xx, yy, ny, a, b;\nmov.b32 {x, y}, %4;\nmov.b32 xx, {x, x};\nmov.b32 yy, {y, y};\nneg.f16x2 ny, yy;\n"
        "mul.rn.f16x2 a, %2, xx;\nfma.rn.f16x2 %0, %3, ny, a;\nmul.rn.f16x2 b, %3, xx;\nfma.rn.f16x2 %1, %2, yy, b;\n}\n" : "=&r"(ore), "=r"(oim) : "r"(re), "r"(im), "r"(z));
}
__device__ __forceinline__ void hcmul(uint32_t re, uint32_t im, uint32_t zx, uint32_t zy, uint32_t& ore, uint32_t& oim) {
    asm("{\n.reg .b32 ny, a, b;\nneg.f16x2 ny, %5;\n"
        "mul.rn.f16x2 a, %2, %4;\nfma.rn.f16x2 %0, %3, ny, a;\nmul.rn.f16x2 b, %3, %4;\nfma.rn.f16x2 %1, %2, %5, b;\n}\n" : "=&r"(ore), "=r"(oim) : "r"(re), "r"(im), "r"(zx), "r"(zy));
}

struct KGen {
    uint32_t Af[4][4];
    float2 z1, z8, z64, z128, T[9];
    uint32_t zw;
};
__device__ __forceinline__ void kgen_setup(KGen& k, uint32_t pa, float dt) {
    const float A = rbf(expf(bf_lo(pa)));
    const float lr2 = -(A * dt) * 1.4426950408889634f;
    const float li = bf_hi(pa) * dt;
    const float rh = li * 0.15915494309189535f;
    const float rl = fmaf(li, 6.4206382986e-9f, fmaf(li, 0.15915494309189535f, -rh));
    k.z1 = cexp_e(lr2, rh, rl, 1.0f);
    k.z8 = cexp_e(lr2, rh, rl, 8.0f);
    k.z64 = cexp_e(lr2, rh, rl, 64.0f);
}
__device__ __forceinline__ void kgen_rows(KGen& k, uint32_t tb, int lane) {
    const float2 z8 = k.z8, z64 = k.z64;
    const uint32_t row = tb + lane * TBP;
    k.z128 = csq(z64);
    const float2 z16 = csq(z8), z32 = csq(z16), z48 = cmul(z32, z16), z80 = cmul(z64, z16), z96 = cmul(z64, z32), z112 = cmul(z64, z48);
    uint32_t re[4], im[4], a[4], b[4];
    re[0] = pack_f16(1.0f, z16.x); im[0] = pack_f16(0.0f, z16.y);
    re[1] = pack_f16(z32.x, z48.x); im[1] = pack_f16(z32.y, z48.y);
    re[2] = pack_f16(z64.x, z80.x); im[2] = pack_f16(z64.y, z80.y);
    re[3] = pack_f16(z96.x, z112.x); im[3] = pack_f16(z96.y, z112.y);
    sts128(row, re[0], re[1], re[2], re[3]);
    sts128(row + 32, im[0], im[1], im[2], im[3]);
    const uint32_t zz = pack_f16(z8.x, z8.y);
#pragma unroll
    for (int j = 0; j < 4; j++) hcmul(re[j], im[j], zz, a[j], b[j]);
    sts128(row + 16, a[0], a[1], a[2], a[3]);
    sts128(row + 48, b[0], b[1], b[2], b[3]);
    __syncwarp();
    const int mi = lane >> 3;
    const uint32_t ad = tb + (lane & 7) * TBP + mi * 16;
#pragma unroll
    for (int ks = 0; ks < 4; ks++) ldsm_x4_t(k.Af[ks][0], k.Af[ks][1], k.Af[ks][2], k.Af[ks][3], ad + ks * 8 * TBP);
}
__device__ __forceinline__ void kgen_chain(KGen& k, uint32_t pc, float cs) {
    k.T[0] = make_float2(bf_lo(pc) * cs, -bf_hi(pc) * cs);
    const float2 y1 = make_float2(k.z1.x, -k.z1.y);
#pragma unroll
    for (int c = 1; c < 8; c++) k.T[c] = cmul(k.T[c - 1], y1);
    k.T[8] = cmul(k.T[0], make_float2(k.z8.x, -k.z8.y));
}
__device__ __forceinline__ void kgen_cols(KGen& k, uint32_t tb, int lane) {
    const uint32_t row = tb + lane * TBP;
    const float2 (&T)[9] = k.T;
    const uint32_t zv = pack_f16(k.z128.x, k.z128.y), zo = __shfl_xor_sync(0xffffffffu, zv, 1);
    k.zw = (lane & 1) ? __byte_perm(zo, zv, 0x7632) : __byte_perm(zv, zo, 0x5410);
    const float2 y256 = csq(make_float2(k.z128.x, -k.z128.y)), y512 = csq(y256), y768 = cmul(y512, y256), y1024 = csq(y512);
    const float2 c1032 = cmul(T[8], y1024);
    const uint32_t r04 = pack_f16(T[0].x, T[4].x), i04 = pack_f16(T[0].y, T[4].y), r26 = pack_f16(T[2].x, T[6].x), i26 = pack_f16(T[2].y, T[6].y);
    const uint32_t r48 = pack_f16(T[4].x, T[8].x), i48 = pack_f16(T[4].y, T[8].y);
    __syncwarp();
    sts128(row, r04, pack_f16(T[1].x, T[5].x), r26, pack_f16(T[3].x, T[7].x));
    sts128(row + 16, i04, pack_f16(T[1].y, T[5].y), i26, pack_f16(T[3].y, T[7].y));
    uint32_t a[4], b[4];
    {
        const uint32_t zz = pack_f16(y256.x, y256.y);
        hcmul(r04, i04, zz, a[0], b[0]);
        hcmul(r26, i26, zz, a[2], b[2]);
        hcmul(r48, i48, zz, a[3], b[3]);
    }
    sts128(row + 32, a[0], a[0], a[2], a[3]);
    sts128(row + 48, b[0], b[0], b[2], b[3]);
    {
        hcmul(r48, i48, pack_f16(y512.x, y512.y), a[0], b[0]);
        hcmul(r48, i48, pack_f16(y768.x, y768.y), a[1], b[1]);
        const uint32_t zz = pack_f16(c1032.x, c1032.y);
        hcmul(pack_f16(1.0f, y256.x), pack_f16(0.0f, y256.y), zz, a[2], b[2]);
        hcmul(pack_f16(y512.x, y768.x), pack_f16(y512.y, y768.y), zz, a[3], b[3]);
    }
    sts128(row + 64, a[0], a[1], a[2], a[3]);
    sts128(row + 80, b[0], b[1], b[2], b[3]);
}
__device__ __forceinline__ void kgen_mma(const KGen& k, uint32_t tb, int lane) {
    const int t = lane & 3;
    const uint32_t zw = k.zw;
    uint32_t zx[4], zy[4];
#pragma unroll
    for (int ks = 0; ks < 4; ks++) { zx[ks] = __shfl_sync(0xffffffffu, zw, 8 * ks + 2 * t); zy[ks] = __shfl_sync(0xffffffffu, zw, 8 * ks + 2 * t + 1); }
    __syncwarp();
    float acc[2][3][4];
#pragma unroll
    for (int i = 0; i < 6; i++)
#pragma unroll
        for (int j = 0; j < 4; j++) acc[i / 3][i % 3][j] = 0.f;
    {
        const int mi = lane >> 3;
        const uint32_t bd = tb + ((lane & 7) + 8 * (mi >> 1)) * TBP + (mi & 1) * 16;
#pragma unroll
        for (int kp = 0; kp < 2; kp++) {
            uint32_t b[3][4];
#pragma unroll
            for (int j = 0; j < 3; j++) ldsm_x4_t(b[j][0], b[j][1], b[j][2], b[j][3], bd + kp * 16 * TBP + j * 32);
#pragma unroll
            for (int h = 0; h < 2; h++) {
                const int ks = 2 * kp + h;
                uint32_t d[4];
                hcmul(k.Af[ks][0], k.Af[ks][2], zx[ks], zy[ks], d[0], d[2]);
                hcmul(k.Af[ks][1], k.Af[ks][3], zx[ks], zy[ks], d[1], d[3]);
#pragma unroll
                for (int j = 0; j < 3; j++) {
                    mma_f16(acc[0][j], k.Af[ks][0], k.Af[ks][1], k.Af[ks][2], k.Af[ks][3], b[j][2 * h], b[j][2 * h + 1]);
                    mma_f16(acc[1][j], d[0], d[1], d[2], d[3], b[j][2 * h], b[j][2 * h + 1]);
                }
            }
        }
    }
    __syncwarp();
#pragma unroll
    for (int h = 0; h < 2; h++) {
        sts64(tb + h * 256 + lane * 8, pack_f16(acc[h][0][0], acc[h][0][1]), pack_f16(acc[h][0][2], acc[h][0][3]));
        sts64(tb + 512 + h * 256 + lane * 8, pack_f16(acc[h][1][0], acc[h][1][1]), pack_f16(acc[h][1][2], acc[h][1][3]));
        sts32(tb + 1024 + h * 256 + lane * 4, pack_f16(acc[h][2][0], t < 2 ? acc[h][2][1] : acc[h][2][2]));
        sts32(tb + 1152 + h * 256 + lane * 4, pack_f16(t < 2 ? acc[h][2][2] : acc[h][2][1], acc[h][2][3]));
    }
}
__device__ __forceinline__ uint32_t table_buf(uint32_t sb, int warp) { return sb + SM_TB + warp * TBW; }

__device__ __forceinline__ void kgen_combine(uint32_t sb, int warp, int lane, uint32_t kw, uint32_t ao) {
    const int wq = warp & 3;
    const uint32_t a = table_buf(sb, warp & ~3) + wq * 256 + lane * 8, c = table_buf(sb, warp & ~3) + 1024 + wq * 128 + lane * 4;
    const int t = lane & 3;
    const uint32_t o0 = (t < 2 ? KW_T2 + KW_KH + 16 + t * 256 - (wq & 1) * KW_KH : KW_T3 + 16 - 1024 + t * 512 + (wq & 1) * 256) + (lane >> 2) * 16;
    const uint4 o = make_uint4(o0 + t * 36, o0 + (t ^ 1) * 36, o0 + (t ^ 2) * 36, o0 + (t ^ 3) * 36);
    const uint2 u = lds64(a), v = lds64(a + TBW), w = lds64(a + 2 * TBW), x = lds64(a + 3 * TBW);
    const uint32_t kt = hadd2(hadd2(lds32(c), lds32(c + TBW)), hadd2(lds32(c + 2 * TBW), lds32(c + 3 * TBW)));
    const uint32_t k23 = hadd2(hadd2(u.y, v.y), hadd2(w.y, x.y));
    sts64(kw + wq * 64 + ao, hadd2(hadd2(u.x, v.x), hadd2(w.x, x.x)), k23);
    const uint32_t d = kw + (wq >> 1) * 128;
    const uint32_t kh = hmul2(kt, 0x38003800u);
    sts32(d + o.x, kh); sts32(d + o.y, kh); sts32(d + o.z, kh); sts32(d + o.w, kh);
    if (wq == 3) {
        if (lane == 31) { sts32(kw + 264, k23 >> 16); sts32(kw + 288 + 264, k23 >> 16); sts32(kw + 576 + 264, k23 >> 16); }
        if (lane == 29) { sts32(kw + 864 + 280, kt >> 16); sts32(kw + 280, kt & 0xffff0000u); }
    }
}

__device__ __forceinline__ int c_exponent(const uint2& r, const uint2& i) {
    uint32_t mx = __vmaxu2(__vmaxu2(r.x & 0x7fff7fffu, r.y & 0x7fff7fffu), __vmaxu2(i.x & 0x7fff7fffu, i.y & 0x7fff7fffu));
    mx = __reduce_max_sync(0xffffffffu, max(mx & 0xffffu, mx >> 16));
    return min(max((int)(mx >> 7), 4), 240);
}

__device__ __forceinline__ int warp_v() { int l; asm volatile("mov.u32 %0, %%tid.x;" : "=r"(l)); return __shfl_sync(0xffffffffu, l >> 5, 0); }
__device__ __forceinline__ int lane_v() { int l; asm volatile("mov.u32 %0, %%laneid;" : "=r"(l)); return l; }
__device__ __forceinline__ unsigned clock32() { unsigned c; asm volatile("mov.u32 %0, %%clock;" : "=r"(c)); return c; }
__device__ __forceinline__ uint32_t prmt(uint32_t a, uint32_t b, uint32_t s) { uint32_t d; asm("prmt.b32 %0, %1, %2, %3;\n" : "=r"(d) : "r"(a), "r"(b), "r"(s)); return d; }
__device__ __forceinline__ uint32_t prmt_v(uint32_t a, uint32_t b, uint32_t s) { uint32_t d; asm volatile("prmt.b32 %0, %1, %2, %3;\n" : "=r"(d) : "r"(a), "r"(b), "r"(s)); return d; }
__device__ __forceinline__ void mmah16(uint32_t& d0, uint32_t& d1, uint32_t a0, uint32_t a1, uint32_t a2, uint32_t a3, uint32_t b0, uint32_t b1, uint32_t c0, uint32_t c1) {
    asm volatile("mma.sync.aligned.m16n8k16.row.col.f16.f16.f16.f16 {%0,%1}, {%2,%3,%4,%5}, {%6,%7}, {%8,%9};\n"
                 : "=r"(d0), "=r"(d1) : "r"(a0), "r"(a1), "r"(a2), "r"(a3), "r"(b0), "r"(b1), "r"(c0), "r"(c1));
}
__device__ __forceinline__ void mmah8(uint32_t& d0, uint32_t& d1, uint32_t a0, uint32_t a1, uint32_t b0, uint32_t c0, uint32_t c1) {
    asm volatile("mma.sync.aligned.m16n8k8.row.col.f16.f16.f16.f16 {%0,%1}, {%2,%3}, {%4}, {%5,%6};\n"
                 : "=r"(d0), "=r"(d1) : "r"(a0), "r"(a1), "r"(b0), "r"(c0), "r"(c1));
}
template <int A = 8, int B = 32>
__device__ __forceinline__ void conv_rename(uint32_t (&acc)[32]) {
#pragma unroll
    for (int i = A; i < B; i++) { uint32_t v; asm volatile("mov.b32 %0, %1;\n" : "=r"(v) : "r"(acc[i])); acc[i] = v; }
}
__host__ __device__ constexpr uint32_t band_bits(int hw, int sh) {
    uint32_t c = 0;
    for (int s = 0; s <= 10; s++)
        for (int e = 0; e < 2; e++) {
            const int v = s - 3 + sh - 4 * e;
            if (v <= hw && v >= -hw) c |= 1u << (14 + 16 * e - s);
        }
    return c;
}
template <int HW, int SH, int J> __device__ __forceinline__ uint32_t band(uint32_t p2) {
    uint32_t d;
    asm volatile("{\n.reg .b32 t;\nmul.lo.u32 t, %1, %2;\nand.b32 %0, t, 0x40004000;\n}\n" : "=r"(d) : "r"(p2), "n"(band_bits(HW, SH) | J));
    return d;
}
template <int H0, int SH> __device__ __forceinline__ void band_pair(uint4& l, uint4& u, uint32_t p2) {
    l = make_uint4(band<H0, 8, 1>(p2), band<H0 - 1, SH + 8, 2>(p2), band<H0, 0, 1>(p2), band<H0 - 1, SH, 1>(p2));
    u = make_uint4(band<H0, 0, 2>(p2), band<H0 - 1, SH, 2>(p2), band<H0, -8, 1>(p2), band<H0 - 1, SH - 8, 1>(p2));
}
__device__ __forceinline__ void run_sums(uint32_t (&G)[3][2], const uint32_t (&c)[5], const uint4& l, const uint4& u) {
    mmah8(G[0][0], G[0][1], l.x, l.y, c[0], 0u, 0u);
    mmah8(G[1][0], G[1][1], u.z, u.w, c[3], 0u, 0u);
    mmah8(G[2][0], G[2][1], l.x, l.y, c[2], 0u, 0u);
    mmah16(G[0][0], G[0][1], u.x, u.y, u.z, u.w, c[1], c[2], G[0][0], G[0][1]);
    mmah16(G[1][0], G[1][1], l.x, l.y, l.z, l.w, c[1], c[2], G[1][0], G[1][1]);
    mmah16(G[2][0], G[2][1], u.x, u.y, u.z, u.w, c[3], c[4], G[2][0], G[2][1]);
}
__device__ __forceinline__ float h_lo(uint32_t w) { return __half2float(__ushort_as_half((unsigned short)(w & 0xffffu))); }
__device__ __forceinline__ float h_hi(uint32_t w) { return __half2float(__ushort_as_half((unsigned short)(w >> 16))); }
__device__ __forceinline__ uint64_t smem_desc(uint32_t sb, uint32_t o16, uint32_t lbo) {
    uint64_t d;
    asm("mov.b64 %0, {%1, %2};" : "=l"(d) : "r"(((sb & 0x3FFFF) >> 4) + o16 + (lbo << 12)), "r"(8));
    return d;
}
template <int I> struct IC { static constexpr int value = I; };

struct Conv {
    uint32_t u[3][5];
    uint32_t q2[3][2][4];
    uint32_t q3[2][4];
    uint32_t r[18];
};
struct ConvPre {
    uint32_t a[5], b[5];
    uint32_t t[4];
};
__device__ __forceinline__ void conv_pre(ConvPre& e, uint32_t ka, uint32_t ks, uint32_t sel) {
    const uint4 r = lds128(ka + 256), s = lds128(ka + 272);
    ldsm_x4(e.t[0], e.t[1], e.t[2], e.t[3], ks);
    const uint32_t sw = sel ^ 0x4444u;
    e.a[0] = prmt(r.y, r.z, sel); e.a[1] = prmt(r.w, r.z, sw); e.a[2] = prmt(r.x, r.y, sel); e.a[3] = prmt(r.z, r.y, sw); e.a[4] = prmt(r.z, r.w, sel);
    e.b[0] = prmt(s.y, s.z, sel); e.b[1] = prmt(s.w, s.z, sw); e.b[2] = prmt(s.x, s.y, sel); e.b[3] = prmt(s.z, s.y, sw); e.b[4] = prmt(s.z, s.w, sel);
}
__device__ __forceinline__ void conv_sums(Conv& c, uint32_t (&acc)[32], const ConvPre& e, uint32_t a0, uint32_t a1, const uint4 (&bd)[4], uint32_t ka, uint32_t sel, int wq, uint32_t zr) {
    {
        uint32_t x;
        ldsm_x4(c.u[0][1], c.u[0][2], c.u[0][3], c.u[0][4], a1);
        ldsm_x4(c.u[0][0], c.u[1][0], c.u[2][0], x, a0);
#pragma unroll
        for (int q = 1; q < 3; q++) ldsm_x4(c.u[q][1], c.u[q][2], c.u[q][3], c.u[q][4], a1 + q * 512);
    }
#pragma unroll
    for (int i = 0; i < 32; i++) acc[i] = 0u;
    uint32_t G[3][2];
#pragma unroll
    for (int q = 0; q < 3; q++) {
        mmah8(acc[8 * q + 8], acc[8 * q + 9], e.a[4], 0u, c.u[q][2], acc[8 * q + 8], acc[8 * q + 9]);
        mmah16(acc[8 * q + 8], acc[8 * q + 9], e.a[0], e.a[1], e.a[2], e.a[3], c.u[q][3], c.u[q][4], acc[8 * q + 8], acc[8 * q + 9]);
        if (q < 2) {
            mmah8(acc[8 * q + 16], acc[8 * q + 17], e.b[4], 0u, c.u[q][2], 0u, 0u);
            mmah16(acc[8 * q + 16], acc[8 * q + 17], e.b[0], e.b[1], e.b[2], e.b[3], c.u[q][3], c.u[q][4], acc[8 * q + 16], acc[8 * q + 17]);
            run_sums(G, c.u[q], bd[2], bd[3]);
            c.q3[q][0] = prmt(G[1][1], G[0][0], 0x7632u); c.q3[q][1] = prmt(G[2][1], G[1][0], 0x7632u);
            c.q3[q][2] = prmt(G[1][1], G[0][0], 0x5410u); c.q3[q][3] = prmt(G[2][1], G[1][0], 0x5410u);
        }
    }
    {
        const uint32_t a = (ka + wq * 64) ^ (((acc[8] | acc[16] | acc[24]) | (c.q3[0][0] | c.q3[0][1]) | (c.q3[1][0] | c.q3[1][1])) & zr);
#pragma unroll
        for (int i = 0; i < 4; i++) { const uint4 v = lds128(a + i * 16); c.r[4 * i] = v.x; c.r[4 * i + 1] = v.y; c.r[4 * i + 2] = v.z; c.r[4 * i + 3] = v.w; }
        const uint2 v = lds64(a + 64);
        c.r[16] = v.x; c.r[17] = v.y;
    }
#pragma unroll
    for (int q = 0; q < 3; q++) {
        run_sums(G, c.u[q], bd[0], bd[1]);
#pragma unroll
        for (int h = 0; h < 2; h++) {
            const uint32_t s = h ? 0x7632u : 0x5410u;
            c.q2[q][h][0] = prmt(G[0][1], G[0][0], s); c.q2[q][h][1] = prmt(G[1][1], G[1][0], s);
            c.q2[q][h][2] = prmt(G[1][0], G[1][1], s ^ 0x4444u); c.q2[q][h][3] = prmt(G[2][1], G[2][0], s);
            if (q < 2) mmah16(acc[8 * q + 16], acc[8 * q + 17], c.q2[q][h][0], c.q2[q][h][1], c.q2[q][h][2], c.q2[q][h][3], e.t[2 * h], e.t[2 * h + 1], acc[8 * q + 16], acc[8 * q + 17]);
        }
    }
    if (sel == 0u) {
#pragma unroll
        for (int i = 0; i < 6; i++) sts128(ka + i * 16, c.q2[i >> 1][i & 1][0], c.q2[i >> 1][i & 1][1], c.q2[i >> 1][i & 1][2], c.q2[i >> 1][i & 1][3]);
#pragma unroll
        for (int i = 0; i < 2; i++) sts128(ka + i * 16, c.q3[i][0], c.q3[i][1], c.q3[i][2], c.q3[i][3]);
#pragma unroll
        for (int i = 1; i < 4; i++) sts64(ka + i * 16, acc[8 * i], acc[8 * i + 1]);
    }
    conv_rename(acc);
}
#define SPACE 100
#define SPN 3
#define O4 4
#define B2L 1
#define GATE 2
#define HAND 2
#define GA 6
#define GB 4
template <int TA, int TB, int IA, class FG>
__device__ __forceinline__ void conv_tail(uint32_t (&acc)[32], const uint32_t (&a)[8][4], uint32_t sb, unsigned char* gy0, int warp, size_t ycopy, FG fg) {
    const int wg = warp >> 2, wq = warp & 3, ord = TA == 0 && TB == 16 ? 3 - wg + (3 - wg >= O4) : O4;
    const uint32_t ub = sb + SM_U + wg * USLOT_B + UPAD * 16, turn = sb + SM_MISC + 376 + ord * 8, sfs = sb + SM_MISC + 256 + wg * 8;
    const uint32_t du = wg * (USLOT_B / 16) + (SM_U / 16 + UPAD + TA * 8);
    uint32_t ud[8], fs;
    auto skip = [&]() {
        const int lane = lane_v();
        const uint32_t ua = ub + ((lane >> 3) & 1) * ULO_B + (8 * wq + (lane & 7)) * 16 + (lane >> 4) * 512;
        if (IA == 0) ldsm_x4_t(ud[0], ud[1], ud[2], ud[3], ua);
        if (TB == 16) ldsm_x4_t(ud[4], ud[5], ud[6], ud[7], ua + 1024);
        const uint2 fd = lds64(sfs);
        fs = fd.x;
        const float dsk = __uint_as_float(fd.y);
#pragma unroll
        for (int i = 2 * IA; i < TB / 2; i++) ud[i] = pack_bf16(h_lo(ud[i]) * dsk, h_hi(ud[i]) * dsk);
    };
    conv_rename<2 * TA, 2 * TB>(acc);
    if (__builtin_expect(ord != 0, 0)) {
        skip();
        mbar_wait(turn);
    } else if (B2L) {
        bar_sync(0, NWRK);
    }
    if (O4 < 4 || (TA == 0 && TB == 16)) asm volatile("{\n.reg .pred p;\nelect.sync _|p, 0xffffffff;\n@p mbarrier.arrive.shared::cta.b64 _, [%0];\n}\n" ::"r"(turn + 48) : "memory");
    fg(IC<8>());
    wg_fence();
#pragma unroll
    for (int m = 7; m >= 0; m--) {
        wg_h<TA, TB - TA>(acc, a[m], smem_desc(sb, du - m, ULO_B));
        if (m == GA || m == GB || m == HAND) wg_commit();
        if (m == GB) asm volatile("wgmma.wait_group.sync.aligned 1;\n" ::: "memory");
    }
    wg_commit();
    if (O4 < 4 || (TA == 0 && TB == 16)) {
        asm volatile("wgmma.wait_group.sync.aligned 1;\n" ::: "memory");
        asm volatile("{\n.reg .pred p;\nelect.sync _|p, 0xffffffff;\n@p mbarrier.arrive.shared::cta.b64 _, [%0];\n}\n" ::"r"(turn + 8) : "memory");
    }
    __syncwarp();
    fg(IC<3>());
    if (!ord) skip();
    fg(IC<4>());
    const int lane = lane_v();
    const uint32_t lp = sb + SM_PL + (ord >= 3 ? ord - 3 : ord) * PL_B + lane * 8;
    unsigned char* gy = gy0 + ((4 * wq + (lane & 3)) * DM + (TA == 0 && TB == 16 ? 4 * blockIdx.x + wg : 512 + (blockIdx.x >> 1))) * 64 + (lane >> 2) * 8;
    const uint32_t st = lp + (wq * 12 - ((wq * (wq - 1)) >> 1)) * 256;
    uint32_t ld[3];
#pragma unroll
    for (int s = 1; s < 4; s++) {
        const int w = (wq - s) & 3;
        ld[s - 1] = lp + (w * 12 - ((w * (w - 1)) >> 1) + s - 1 - (wq < s ? 3 : 0)) * 256;
    }
    const uint32_t one = 1u + (warp >> 8);
    if (one == 0u) stg64(gy, ld[0], ld[1]);
    if (ord >= 3) bar_sync(9 + ord, 256);
    wg_wait0();
    fg(IC<6>());
#pragma unroll
    for (int j = TA; j < TB; j++)
        if ((j & 3) && j + 3 >= 4 * IA && (j + 3 < TB || j + wq < TB)) sts64(st + (j - 1 - (j >> 2)) * 256, acc[2 * j], acc[2 * j + 1]);
    bar_sync(1 + wg, 128);
    fg(IC<7>());
    uint2 v[4][3];
#pragma unroll
    for (int i = IA; i < TB / 4; i++)
#pragma unroll
        for (int s = 0; s < 3; s++) {
            if (i == 0) { v[i][s] = make_uint2(0u, 0u); if (wq > s) v[i][s] = lds64(ld[s]); }
            else v[i][s] = lds64(ld[s] + i * 768);
        }
    fg(IC<5>());
#pragma unroll
    for (int i = IA; i < TB / 4; i++) {
        const uint32_t x0 = hadd2(v[i][0].x, acc[8 * i]), x1 = hadd2(v[i][1].x, v[i][2].x), y0 = hadd2(v[i][0].y, acc[8 * i + 1]), y1 = hadd2(v[i][1].y, v[i][2].y);
        const uint32_t x = hadd2(x0, x1), y = hadd2(y0, y1);
        const uint32_t lo = pack_bf16(h_lo(x), h_hi(x)), hi = pack_bf16(h_lo(y), h_hi(y));
        ud[2 * i] = max(hfma2_bf(lo, fs, ud[2 * i]), one); ud[2 * i + 1] = hfma2_bf(hi, fs, ud[2 * i + 1]);
    }
    if (SPACE && TA == 0 && TB == 16 && ord < SPN) {
#pragma unroll
        for (int i = 0; i < 4; i++) {
            stg64(gy + i * 16 * DM * 64, ud[2 * i], ud[2 * i + 1]);
            if (i < 3) { const unsigned c0 = clock32(); while (clock32() - c0 < SPACE) {} }
        }
    } else {
#pragma unroll
        for (int i = IA; i < TB / 4; i++) stg64(gy + i * 16 * DM * 64, ud[2 * i], ud[2 * i + 1]);
    }
    if (ord < 2) bar_arrive(12 + ord, 256);
}
template <int M0, int M1>
__device__ __forceinline__ void conv_frags(uint32_t (&a)[8][4], const uint32_t (&r)[18], uint32_t sel, uint32_t dep, int warp) {
    const uint32_t s = prmt_v(sel, dep, 0x3210u + (warp >> 8)), sw = s ^ 0x4444u;
#pragma unroll
    for (int m = M0; m < M1; m++) {
        a[m][0] = prmt_v(r[2 * m + 1], r[2 * m + 2], s); a[m][1] = prmt_v(r[2 * m + 2], r[2 * m + 3], s);
        a[m][2] = prmt_v(r[2 * m + 1], r[2 * m], sw); a[m][3] = prmt_v(r[2 * m + 2], r[2 * m + 1], sw);
    }
}
template <class FG>
__device__ __forceinline__ void conv_main(const Conv& c, uint32_t (&acc)[32], uint32_t sb, uint32_t sel, unsigned char* gy, int warp, size_t ycopy, FG fg) {
    const uint32_t kw = (warp >> 2) * (KW_B / 16) + SM_KW / 16;
    const uint64_t d2 = smem_desc(sb, kw + KW_T2 / 16, KW_KH), d2b = smem_desc(sb, kw + KW_T2 / 16 + 1, KW_KH), d3 = smem_desc(sb, kw + KW_T3 / 16, 16), d3b = smem_desc(sb, kw + KW_T3 / 16 + 32, 16);
    uint32_t a[8][4];
    {
        const int ord = warp < 16 ? 3 - (warp >> 2) + (3 - (warp >> 2) >= O4) : O4;
        if (__builtin_expect(ord >= GATE, 0)) {
            fg(IC<1>());
            mbar_wait(sb + SM_MISC + 376 + 48 + (ord - GATE) * 8);
        }
    }
    wg_fence();
    wg_h<12, 4>(acc, c.q3[0], d3b); wg_h<8, 4>(acc, c.q3[0], d3); wg_h<4, 4>(acc, c.q2[0][0], d2b);
    wg_h<12, 4>(acc, c.q3[1], d3); wg_h<8, 4>(acc, c.q2[1][0], d2b);
    wg_h<12, 4>(acc, c.q2[2][0], d2b); wg_h<4, 4>(acc, c.q2[0][1], d2); wg_h<8, 4>(acc, c.q2[1][1], d2);
    wg_h<12, 4>(acc, c.q2[2][1], d2);
    wg_commit(); __syncwarp();
    fg(IC<0>());
    wg_wait0();
    conv_frags<0, 8>(a, c.r, sel, acc[16], warp);
    fg(IC<2>());
    if (warp >= 16) {
        if (blockIdx.x & 1) conv_tail<4, 16, 2>(acc, a, sb, gy, warp, ycopy, fg);
        else conv_tail<0, 8, 0>(acc, a, sb, gy, warp, ycopy, fg);
    } else {
        conv_tail<0, 16, 0>(acc, a, sb, gy, warp, ycopy, fg);
    }
}
#define CONV_LT6 const int dd = (lane >> 3) + (lane & 4) - (lane & 3); \
        const uint4 lt6 = make_uint4(prmt_v((dd & 3) * 288, 0u, idn), prmt_v(0x3254u + (dd >> 2) * 0x2222u, 0u, idn), \
            prmt_v(UPAD * 16 + (lane & 7) * 16 + ULO_B - 32 + (lane >> 3) * 512, 0u, idn), prmt_v(UPAD * 16 + (lane & 7) * 16 + ((lane >> 3) & 1) * ULO_B - 16 + (lane & 16), 0u, idn));
#define CONV_PRE \
        CONV_LT6 \
        const uint32_t ka = kw + lt6.x, sel = lt6.y, ks = kw + lt7.x; \
        const uint32_t ca0 = sb + SM_U + wg * USLOT_B + (warp & 3) * 128 + lt6.z, ca1 = sb + SM_U + wg * USLOT_B + (warp & 3) * 128 + lt6.w; \
        uint4 bd[4]; \
        band_pair<2, 4>(bd[0], bd[1], lt7.w); band_pair<4, 0>(bd[2], bd[3], lt7.w);
#define CONV_PRE2 ConvPre ce_; conv_pre(ce_, ka, ks, sel);
#define CONV_BODY \
        Conv c; \
        uint32_t acc[32]; \
        conv_sums(c, acc, ce_, ca0, ca1, bd, ka, sel, warp & 3, warp >> 8);
#define WS a_b_0_1_2_34_xy_56_7__c__d____re__
#define WS_STR2(x) #x
#define WS_STR(x) WS_STR2(x)
__device__ constexpr char wunit(int pt, int k) {
    constexpr char t[] = WS_STR(WS);
    int i = 0;
    for (; pt > 0 && t[i]; i++) pt -= t[i] == '_';
    for (; k > 0 && t[i] && t[i] != '_'; i++) k--;
    return t[i] == '_' ? 0 : t[i];
}
__device__ constexpr bool wsched_ok() {
    int seen = 0;
    for (int p = 0; p < 21; p++)
        for (int k = 0; wunit(p, k); k++) {
            const char c = wunit(p, k);
            const int bit = 1 << (c == 'r' ? 13 : c >= 'x' ? c - 'x' + 14 : c >= 'a' ? c - 'a' + 8 : c - '0');
            if ((seen & bit) || k >= (p < 16 ? 4 : 2) || (p < 5 && c >= '4' && c <= '7') || (p < 6 && (c == 'c' || c == 'd')) || (p < 16 && c == 'e')) return false;
            seen |= bit;
        }
    return seen == 0xffff;
}
struct WMaps { CUtensorMap g, u, gr, ur, d, dr; };
static_assert(GATE <= 2 && O4 >= 2, "resets");
static_assert(wsched_ok(), "weight schedule");
template <int PT, int K>
__device__ __forceinline__ void weight_units(uint32_t sb, const WMaps& m, int w) {
    constexpr char U = wunit(PT, K);
    if constexpr (U != 0) {
        if (w == K && elect_one()) {
            const int P = blockIdx.x >> 1, odd = blockIdx.x & 1;
            constexpr int bar = SM_MISC + (U == 'e' ? 352 : U >= 'a' && U <= 'r' ? 336 : 328);
            if constexpr (U == 'e') { if (!odd) tma_2d(sb + SM_WD + 4 * 8192, &m.d, 256, 64 * P, sb + bar); }
            else if constexpr (U == 'r') tma_3d(sb + SM_WD + 40960, &m.dr, 0, 4096 + 8 * P, 5 * odd, sb + bar);
            else if constexpr (U >= 'x') tma_3d(sb + SM_WR + (U - 'x') * 4608, U == 'x' ? &m.gr : &m.ur, 4096 + 8 * P, 0, 2 * odd, sb + bar);
            else if constexpr (U >= 'a') tma_2d(sb + SM_WD + (U - 'a') * 8192, &m.d, 320 * odd + 64 * (U - 'a'), 64 * P, sb + bar);
            else tma_2d(sb + (U < '4' ? SM_WG : SM_WU) + (U & 3) * 9216, U < '4' ? &m.g : &m.u, 64 * P, 288 * odd + (U & 3) * 72, sb + bar);
        }
        weight_units<PT, K + 1>(sb, m, w);
    }
}
#define WPOINT(i, w) do { weight_units<i, 0>(sb, wm, w); } while (0)

__global__ void __launch_bounds__(NTHR, 1) __cluster_dims__(2, 1, 1)
fused_kernel(const Params p, const __grid_constant__ WMaps wm, const __grid_constant__ CUtensorMap tm_x,
             const __grid_constant__ CUtensorMap tm_y, const __grid_constant__ CUtensorMap tm_z) {
    extern __shared__ __align__(1024) unsigned char smem[];
    const uint32_t sb = smem_u32(smem);
    const int tid = threadIdx.x, warp = __shfl_sync(0xffffffffu, tid >> 5, 0), lane = tid & 31;
    const int b = blockIdx.x, P = b >> 1, odd = b & 1;
    const int g = lane >> 2, t = lane & 3;
    const int wg = warp >> 2, t128 = tid & 127;
    const uint32_t s_stat = sb + SM_MISC;
    const uint32_t s_key = sb + SM_MISC + 128;
    const uint32_t s_wm = sb + SM_MISC + 256;
    const uint32_t s_k16 = sb + SM_MISC + 192;
    const uint32_t s_fs = sb + SM_MISC + 256;
    const uint32_t s_cnt = sb + SM_MISC + 320;
    const uint32_t bar_w = sb + SM_MISC + 328, bar_d = bar_w + 8, bar_g = bar_w + 16, bar_r = bar_w + 32, bar_h = bar_w + 40, bar_x = bar_w + 48;
    STAMP(0);

    const unsigned tk0 = clock32();
    const bool lnw = (unsigned)(warp - 10) < 9u;
    const unsigned pm = tid + (tid < 512 ? 512 * b : 65024 + 128 * P), pq = (pm & ~127u) + 4 * lane;
    uint32_t pl = ldg16(p.lar + pm), ldt = ldg16(p.ldt + (pm >> 7));
    const uint32_t pa2 = ldg16(p.aim + pm), pc = ldg16(p.cre + pm), pi = ldg16(p.cim + pm);
    const uint2 call_re = ldg64(p.cre + pq), call_im = ldg64(p.cim + pq);
    const uint32_t dskl = ldg16(p.dsk + (pm >> 7));
    const uint32_t ep = ld_poll32(p.s->hint + (b & 7) * 32 + 1 + (lane >> 5));
    if ((unsigned)(tid - 320) < 288u) {
        const bf16* xp = p.x + (unsigned)((32 * P + 2 * odd + TOKEN_OF(g)) * DM + ((tid - 320) & ~31) + 8 * t);
        const uint32_t xt = sb + SM_XT + ((tid - 320) & ~31) * 32 + lane * 16;
        asm volatile("cp.async.cg.shared.global [%0], [%1], 16;\ncp.async.cg.shared.global [%0 + 512], [%1 + 9216], 16;\n"
                     "cp.async.cg.shared.global [%0 + 9216], [%1 + 576], 16;\ncp.async.cg.shared.global [%0 + 9728], [%1 + 9792], 16;\n" ::"r"(xt), "l"(xp) : "memory");
    }
    uint32_t* const std_ = p.s->st + ((lane & 12) * 128 + odd * 256 + 4 * P + 2 * (lane & 1) + ((lane >> 1) & 1)) * 2;
    unsigned char* const ud = reinterpret_cast<unsigned char*>(p.s->uT) + (32 * (warp - UW) + 8 * (g >> 1) + (g & 1)) * 4096 + b * 32 + t * 8;
    if (warp == 0) {
        if (lane == 0) {
            mbar_init(bar_x, 1); mbar_init(bar_w, 1); mbar_init(bar_d, 1); mbar_init(bar_d + 16, 1); mbar_init(bar_g, 1); mbar_init(bar_h, 3); mbar_init(bar_r, 1);
            #pragma unroll
            for (int i = 1; i < 11; i++) mbar_init(bar_x + 8 * i, 4);
            asm volatile("fence.mbarrier_init.release.cluster;\n" ::: "memory");
            mbar_expect(bar_x, 16384); mbar_expect(bar_r, 8192);
            mbar_expect(bar_w, 2 * 41472); mbar_expect(bar_d, 32768 + 5120); mbar_expect(bar_d + 16, 8192); mbar_expect(bar_g, 9 * 512);
        }
        __syncwarp();
        bar_arrive(0, NWRK);
    }
    if (warp == 0 && elect_one()) tma_3d(sb + SM_XC, &tm_x, 8 * P, 0, 8 * odd, bar_x);
    asm volatile("barrier.cluster.arrive.relaxed.aligned;\n" ::: "memory");
    const uint32_t kw = sb + SM_KW + wg * KW_B;
    if (t128 < 2 * UPAD) sts128(sb + SM_U + wg * USLOT_B + (t128 & 1) * ULO_B + (t128 >> 1) * 16, 0u, 0u, 0u, 0u);
    sts128(kw + t128 * 16, 0u, 0u, 0u, 0u);
    if (t128 < KW_B / 16 - 128) sts128(kw + 2048 + t128 * 16, 0u, 0u, 0u, 0u);
    if (tid < 128) {
#pragma unroll
        for (int i = 0; i < 4; i++) sts128(sb + SM_ZERO + i * 2048 + tid * 16, 0u, 0u, 0u, 0u);
    }
    if (warp != 0) bar_sync(0, NWRK);
    STAMP(1);
    if (warp == 19 || warp == UW || warp == UW + 1) {
        if (warp == 19) {
            if (lane < 16) stg64(std_, 0u, 0u);
            if (lane < 9) asm volatile("prefetch.global.L2 [%0];\n" ::"l"(p.wr + lane * 64));
        } else {
#pragma unroll
            for (int k = 0; k < 4; k++) stg64(ud + k * 8192, 0u, 0u);
        }
    }
    uint32_t X[2][8];
    auto partial = [&]() {
        const uint32_t xt = sb + SM_XT + (warp - 10) * 1024 + lane * 16;
        asm volatile("cp.async.wait_all;\n" ::: "memory");
        STAMP(23);
        const uint4 a = lds128(xt), c = lds128(xt + 512), d = lds128(xt + 9216), e = lds128(xt + 9728);
        X[0][0] = a.x; X[0][1] = a.y; X[0][2] = a.z; X[0][3] = a.w; X[0][4] = d.x; X[0][5] = d.y; X[0][6] = d.z; X[0][7] = d.w;
        X[1][0] = c.x; X[1][1] = c.y; X[1][2] = c.z; X[1][3] = c.w; X[1][4] = e.x; X[1][5] = e.y; X[1][6] = e.z; X[1][7] = e.w;
        const uint32_t one[8] = {0x3f803f80u, 0x3f803f80u, 0x3f803f80u, 0x3f803f80u, 0x3f803f80u, 0x3f803f80u, 0x3f803f80u, 0x3f803f80u};
        ln_partial<8>(X, one, sb + SM_LNP, warp - 10, g, t);
        bar_arrive(6, 320);
        if (PAUSE & 1) bar_sync(7, PCNT);
    };
    if (LNAT == 0 && lnw) {
        partial();
        pl = prmt_v(pl, X[0][0], 0x3210u + (warp >> 8)); ldt = prmt_v(ldt, X[0][0], 0x3210u + (warp >> 8));
    }
    auto finish = [&]() {
        bar_sync(6, 320);
        float mb, rc;
        ln_finish<9>(sb + SM_LNP, lane, mb, rc);
        const float rh = rbf(rc);
        const uint32_t s0 = (__float_as_uint(mb) >> 16) | (((ep & 0x7fffu) + 1u) << 16), s1 = pack_bf16(rh, rc - rh);
        if (lane < 16) { stg64(std_, s0, s1); sts64(s_stat + lane * 8, s0, s1); }
        if (lane == 16) sts32(s_cnt + 4, ep);
        bar_arrive(7, PCNT);
        STAMP(28);
    };
    auto upub = [&]() {
        if (!(PAUSE & 6)) bar_sync(7, PCNT);
        const uint32_t utag = ((ep & 3u) + 1u) * 0x10001u;
        uint32_t U[2][4];
#pragma unroll
        for (int hf = 0; hf < 2; hf++) {
            const uint2 st = lds64(s_stat + (g + 8 * hf) * 8);
            const uint4 xv = lds128(sb + SM_XT + (16 + warp - UW) * 1024 + hf * 512 + lane * 16);
            const uint32_t xs[4] = {xv.x, xv.y, xv.z, xv.w};
#pragma unroll
            for (int k = 0; k < 4; k++) {
                const uint32_t u = ln_apply(xs[k], st);
                U[hf][k] = movm((pack_f16_rz(bf_lo(u), __uint_as_float(u)) & 0xfff8fff8u) | utag);
            }
        }
#pragma unroll
        for (int k = 0; k < 4; k++) stg64(ud + k * 8192, U[0][k], U[1][k]);
    };
    if (FINAT == 0 && warp == 19) finish();
    const uint32_t tb = table_buf(sb, warp);
    const float dt = rbf(expf(bf_lo(ldt)));
    KGen kg;
    kgen_setup(kg, pl | (pa2 << 16), dt);
    if (LNAT == 1 && lnw) {
        partial();
        kg.z8.x = __uint_as_float(prmt_v(__float_as_uint(kg.z8.x), X[0][0], 0x3210u + (warp >> 8)));
        kg.z1.x = __uint_as_float(prmt_v(__float_as_uint(kg.z1.x), X[0][0], 0x3210u + (warp >> 8)));
    }
    if (FINAT == 1 && warp == 19) finish();
    if (UAT == 0 && (warp == UW || warp == UW + 1)) upub();
    kgen_rows(kg, tb, lane);
    if (wg == 0) fence_async();
    if (LNAT == 2 && lnw) {
        partial();
        kg.z128.x = __uint_as_float(prmt_v(__float_as_uint(kg.z128.x), X[0][0], 0x3210u + (warp >> 8)));
        kg.z1.x = __uint_as_float(prmt_v(__float_as_uint(kg.z1.x), X[0][0], 0x3210u + (warp >> 8)));
    }
    if (FINAT == 2 && warp == 19) finish();
    if (UAT == 1 && (warp == UW || warp == UW + 1)) upub();
    STAMP(2);
    WPOINT(0, warp - 4);
    const int ce = c_exponent(call_re, call_im);
    if (t128 == 0) sts64(s_fs + wg * 8, (uint32_t)min(max(ce + (int)(__float_as_uint(dt) >> 23) - 116, 0), 254) * 0x800080u, dskl << 16);
    kgen_chain(kg, pc | (pi << 16), __uint_as_float(((uint32_t)(244 - ce) << 23) | (__float_as_uint(dt) & 0x7fffffu)));
    if ((PAUSE & 4) && warp < 10) bar_sync(7, PCNT);
    if (UAT == 4 && (warp == UW || warp == UW + 1)) upub();
    STAMP(3);
    WPOINT(1, warp - 6);
    kgen_cols(kg, tb, lane);
    if (LNAT == 3 && lnw) partial();
    if (FINAT == 3 && warp == 19) finish();
    if ((PAUSE & 2) && warp < 10) bar_sync(7, PCNT);
    if (UAT == 2 && (warp == UW || warp == UW + 1)) upub();
    STAMP(4);
    WPOINT(2, warp - 8);
    const uint4* usrc = wg < 4 ? reinterpret_cast<const uint4*>(p.s->st) + odd * 512 + (lane & 1) * 128 + 16 * (warp & 7) + (lane >> 1)
                               : reinterpret_cast<const uint4*>(p.s->uT) + P * 256 + 2 * t128;
    const int ustep = wg < 4 ? 256 : 1;
    uint4 uv0, uv1;
    kgen_mma(kg, tb, lane);
    if (UAT == 3 && (warp == UW || warp == UW + 1)) upub();
    STAMP(26);
    WPOINT(3, warp - 5);
    const uint32_t idn = 0x3210u + (warp >> 8);
    uint4 lt7 = make_uint4(prmt_v(KW_T2 + ((lane >> 3) & 1) * KW_KH + (33 + (lane & 7)) * 16 - (lane & 16), 0u, idn), t * 288 + g * 8 + 8, (lane & 1) * 4096 + (lane >> 1) * 16,
                                 prmt_v(8u << ((lane >> 3) + (lane & 4)) >> (lane & 3), 0u, idn));
    asm volatile("barrier.cluster.wait.acquire.aligned;\n" ::: "memory");
    const bool pe = (int)(clock32() - tk0) >= (wg < 4 ? TP0 : TP4);
    if (pe) { uv0 = ld_poll(usrc); uv1 = ld_poll(usrc + ustep); }
    bar_sync(1 + wg, 128);
    kgen_combine(sb, warp, lane, kw, lt7.y);
    if (warp < 3 || warp > 6) bar_arrive(14, NWRK);
    STAMP(5);
    WPOINT(4, warp - 7);
    if (!pe) {
        while ((int)(clock32() - tk0) < (wg < 4 ? TP0 : TP4)) {}
        uv0 = ld_poll(usrc); uv1 = ld_poll(usrc + ustep);
    }
    if (wg < 4) {
        mbar_wait(bar_x);
        const bool far = warp < 8;
        const uint32_t xa = sb + SM_XC + (warp & 7) * 256 + (odd ^ far) * 8 + lt7.z;
        uint2 xv[4] = {lds64(xa), lds64(xa + 8192), lds64(xa + 2048), lds64(xa + 10240)};
        const uint32_t tag = ((ep & 0x7fffu) + 1u) << 16;
        int it = 0;
        while (true) {
            const bool bad = (((uv0.x ^ tag) | (uv0.z ^ tag)) | ((uv1.x ^ tag) | (uv1.z ^ tag))) >> 16;
            if (!__any_sync(0xffffffffu, bad)) break;
            if (++it > SPIN_LIMIT) TRAP();
            if (bad) { uv0 = ld_poll(usrc); uv1 = ld_poll(usrc + 256); }
        }
        STAMP(6);
        DBG(wg, it);
        const uint2 st[4] = {make_uint2(uv0.x, uv0.y), make_uint2(uv0.z, uv0.w), make_uint2(uv1.x, uv1.y), make_uint2(uv1.z, uv1.w)};
#pragma unroll
        for (int i = 0; i < 4; i++) {
            xv[i].x = ln_apply(xv[i].x, st[i]);
            xv[i].y = ln_apply(xv[i].y, st[i]);
        }
        const uint32_t ub = sb + SM_U + UPAD * 16 + odd * ULO_B + (warp & 7) * 256 + lane * 8;
        const uint32_t w[4][2] = {{pack_f16(bf_lo(xv[0].x), bf_lo(xv[1].x)), pack_f16(bf_lo(xv[2].x), bf_lo(xv[3].x))}, {HI2(xv[0].x, xv[1].x), HI2(xv[2].x, xv[3].x)},
                                  {pack_f16(bf_lo(xv[0].y), bf_lo(xv[1].y)), pack_f16(bf_lo(xv[2].y), bf_lo(xv[3].y))}, {HI2(xv[0].y, xv[1].y), HI2(xv[2].y, xv[3].y)}};
#pragma unroll
        for (int i = 0; i < 4; i++) {
            if (far) asm volatile("st.async.shared::cluster.mbarrier::complete_tx::bytes.v2.b32 [%0], {%1,%2}, [%3];\n" ::"r"((ub ^ 0x1000000u) + i * USLOT_B), "r"(w[i][0]), "r"(w[i][1]), "r"(bar_r ^ 0x1000000u) : "memory");
            else sts64(ub + i * USLOT_B, w[i][0], w[i][1]);
        }
    } else {
        const uint32_t utag = ((ep & 3u) + 1u) * 0x10001u;
        int it = 0;
        while (true) {
            const bool bad = (((uv0.x ^ utag) | (uv0.y ^ utag) | (uv0.z ^ utag) | (uv0.w ^ utag)) | ((uv1.x ^ utag) | (uv1.y ^ utag) | (uv1.z ^ utag) | (uv1.w ^ utag))) & 0x70007u;
            if (!__any_sync(0xffffffffu, bad)) break;
            if (++it > SPIN_LIMIT) TRAP();
            if (bad) { uv0 = ld_poll(usrc); uv1 = ld_poll(usrc + 1); }
        }
        STAMP(6);
        DBG(4, it);
        const uint32_t ub = sb + SM_U + UPAD * 16 + 4 * USLOT_B + (t128 >> 1) * 32 + (t128 & 1) * 8;
        sts64(ub, prmt(uv0.x, uv0.z, 0x5410u) ^ utag, prmt(uv1.x, uv1.z, 0x5410u) ^ utag);
        sts64(ub + 16, prmt(uv0.x, uv0.z, 0x7632u) ^ utag, prmt(uv1.x, uv1.z, 0x7632u) ^ utag);
        sts64(ub + ULO_B, prmt(uv0.y, uv0.w, 0x5410u) ^ utag, prmt(uv1.y, uv1.w, 0x5410u) ^ utag);
        sts64(ub + ULO_B + 16, prmt(uv0.y, uv0.w, 0x7632u) ^ utag, prmt(uv1.y, uv1.w, 0x7632u) ^ utag);
    }
    lt7.w = prmt_v(lt7.w, uv0.x, idn);
    CONV_PRE
    if (warp < 3 && elect_one()) tma_st_3d(warp < 2 ? &tm_y : &tm_z, sb + SM_ZERO, warp < 2 ? 128 * b : 32 * (512 + P), 0, 2 * (warp < 2 ? warp : odd));
    if (warp >= 3 && warp <= 6) {
        bar_sync(14, NWRK);
        WPOINT(5, warp - 3);
    }
    bar_sync(1 + wg, 128);
    CONV_PRE2
    mbar_wait(bar_r);
    fence_async();
    bar_sync(0, NWRK);
    STAMP(7);
    uint32_t hv0 = 0;
    {
        WPOINT(6, 19 - warp);
        CONV_BODY
        WPOINT(7, 19 - warp);
        if (!B2L) bar_sync(0, NWRK); else if (wg != 3) bar_arrive(0, NWRK);
        STAMP(8);
        size_t ycopy = 0;
        auto hook = [&](auto gi) {
                     constexpr int G = decltype(gi)::value;
                     if (G == 4 && warp == HINTW) hv0 = ld_poll32(p.s->hint + (lane_v() & 7) * 32);
                     if (G == 4) mbar_wait(bar_h);
                     if (G == 1 || G == 2) WPOINT(7 + G, warp - 16);
                     if (G == 3) { WPOINT(10, warp - 12); WPOINT(12, warp - 8); WPOINT(14, warp - 4); }
                     if (G == 5) { WPOINT(11, warp - 13); WPOINT(13, warp - 9); WPOINT(15, warp - 5); }
                     if (G == 1 && warp >= 17 && elect_one())
                         bulk_s2g(warp == 17 ? p.s->part + b * (PBYTES / 4) : warp == 18 ? p.s->rows + b * 1152 : p.s->sc + b * 64, sb + SM_ZERO, warp == 17 ? PBYTES : warp == 18 ? 4608 : 160);
                     if (G == 4 && warp >= 17 && elect_one()) {
                         asm volatile("cp.async.bulk.wait_group 0;\n" ::: "memory");
                         hint_arrive(p.s->hint, 2, b & 7);
                     }
                     if (G == 1 && warp < 3) {
                         if (elect_one()) {
                             asm volatile("cp.async.bulk.wait_group 0;\n" ::: "memory");
                             mbar_arrive(bar_h);
                             hint_arrive(p.s->hint, 0, b & 7);
                         }
                         __syncwarp();
                         STAMP(17);
                     }
                 };
        conv_main(c, acc, sb, sel, reinterpret_cast<unsigned char*>(p.s->y), warp, ycopy, hook);
        STAMP(10);
    }
    {
    const int warp = warp_v(), lane = lane_v(), tid = 32 * warp + lane, g = lane >> 2, t = lane & 3;
    if (warp == HINTW) {
        const uint32_t target = (lds32(s_cnt + 4) + 1u) * 48u;
        if (__any_sync(0xffffffffu, (int)(hv0 - target) < 0)) hint_wait(p.s->hint, 0, target);
    }
    const unsigned char* ys = reinterpret_cast<const unsigned char*>(p.s->y) + ((size_t)P * DM + 32 * warp + 8 * (g >> 1) + (g & 1)) * 64 + odd * 32 + t * 8;
    STAMP(27);
    bar_sync(0, NWRK);
    STAMP(11);
    const uint32_t zr = warp >> 8;
    auto late_rows = [&](auto pub) {
        const uint32_t k = lds32(s_key + (lane & 7) * 4), ep = lds32(s_cnt + 4);
        const bool late = k & 256u, mine = late && ((k & 255u) >> 1) == (uint32_t)b;
        uint32_t todo = __ballot_sync(0xffffffffu, mine) & 0xffu;
        if (todo) {
#pragma unroll 1
            while (todo) {
                const int s = __ffs(todo) - 1, row = (__shfl_sync(0xffffffffu, k, s) >> 9) & 15;
                todo &= todo - 1;
                if ((row & 7) == g) pub(row & 8, 2 * NCTA + s);
            }
            __threadfence();
            bar_sync(0, NWRK);
            if (tid < NSEL && mine) *reinterpret_cast<volatile unsigned*>(p.s->flag + tid) = ep + 1u;
        }
        int it = 0;
        while (__any_sync(0xffffffffu, late && ld_poll32(p.s->flag + (lane & 7)) != ep + 1u)) { if (++it > SPIN_LIMIT) TRAP(); }
        __threadfence();
        const int gs = tid / 36;
        const uint4* src = reinterpret_cast<const uint4*>(p.s->rows) + __shfl_sync(0xffffffffu, late ? 2 * NCTA + (lane & 7) : (k & 255u), gs & 7) * 144 + 36 * odd + (tid - gs * 36);
        if (tid < 288) {
            uint4 v0;
            do { v0 = ld_poll(src); if (++it > SPIN_LIMIT) TRAP(); } while (!v0.x);
            sts128(sb + SM_XS + gs * XS_PITCH + (tid - gs * 36) * 16, v0.x, v0.y, v0.z, v0.w);
        }
        bar_sync(0, NWRK);
    };
    if (warp >= 18) {
        uint32_t* const kp = pin(p.s->sc + 64 * b + 32 * (19 - warp), zr);
        const uint32_t kid = pin(0xc0000000u | ((lane & 15) << 9) | 2 * b, zr), ka = pin(s_k16 + (warp & 1) * 288 + (lane & 15) * 4, zr), kb = pin(s_k16 + (warp & 1) * 288 + (lane & 16) * 2, zr);
        const uint4* ksrc = pin(reinterpret_cast<const uint4*>(p.s->sc) + 8 * (19 - warp) + 16 * lane, zr);
        const uint4* rsrc = pin(reinterpret_cast<const uint4*>(p.s->rows) + 36 * odd + t, zr);
        uint32_t bits, early = 0;
        if (warp == 18) {
            weight_units<20, 0>(sb, wm, 0); weight_units<20, 1>(sb, wm, 1);
            bar_sync(8, 640);
            float mb, rc;
            ln_finish<18>(sb + SM_LNP, lane, mb, rc);
            if (lane < 16) stat_store(s_stat + lane * 8, mb, rc, 0u);
            bar_arrive(13, 608);
            bar_sync(10, 640);
            early = lds32(s_wm + (lane & 15) * 4);
            bits = pack_bf16(0.f, sum18(sb + SM_LNP + (32 + (lane & 15)) * 80));
        } else {
            float sw = 0.f;
#pragma unroll
            for (int i = 0; i < 9; i++) { const uint32_t w = reinterpret_cast<const uint32_t*>(p.wr)[32 * i + lane]; sw += bf_lo(w) + bf_hi(w); }
#pragma unroll
            for (int i = 16; i; i >>= 1) sw += __shfl_xor_sync(0xffffffffu, sw, i);
            early = ld_poll32(p.s->hint + (lane & 7) * 32 + 2);
            if (zr) stsf(sb, sw);
            bar_sync(8, 640);
            const float v = sum18(sb + SM_LNP + lane * 80), hw = sum18(sb + SM_LNP + (48 + (lane & 15)) * 80);
            const float o = __shfl_xor_sync(0xffffffffu, v, 16), mean = (lane < 16 ? v : o) * (1.0f / 576.0f);
            const float var = fmaxf(fmaf(lane < 16 ? o : v, 1.0f / 576.0f, -(mean * mean)), 0.f);
            bits = __float_as_uint(fmaf(-rbf(mean), sw, hw) * rcp_approx(rbf(sqrt_approx(rbf(rbf(var) + 1e-5f)))));
        }
        {
            const uint32_t me = (((bits ^ ((uint32_t)((int)bits >> 31) & 0x7fffffffu)) >> 1) & 0x7fffe000u) ^ kid;
            sts32(ka, me);
            __syncwarp();
            const uint4 v = lds128(kb), w = lds128(kb + 16);
#define GT(x) ((me - (x)) >> 31)
            uint32_t rank = pin(GT(v.x) + GT(v.y) + GT(v.z), zr) + pin(GT(v.w) + GT(w.x) + GT(w.y), zr) + pin(GT(w.z) + GT(w.w), zr);
#undef GT
            rank += __shfl_xor_sync(0xffffffffu, rank, 16);
            const uint32_t sl = warp == 18 ? early : rank;
            if (lane < 16 && rank < 8) stg32(kp + rank, me + (sl < 2 ? sl : 256u));
            if (warp == 19) {
                sts32(s_wm + (lane & 15) * 4, rank);
                const uint32_t target = (lds32(s_cnt + 4) + 1u) * 48u;
                if (__any_sync(0xffffffffu, (int)(early - target) < 0)) hint_wait(p.s->hint, 2, target);
                bar_arrive(10, 640); bar_arrive(11, 608);
            }
        }
        bool slow;
        int it = 0;
        uint4 q[4];
        STAMP(13);
        DELAY(warp == 19 ? KDEL : KDEL2);
#pragma unroll
        for (int i = 0; i < 4; i++) q[i] = ld_poll(ksrc + 512 * i);
        while (true) {
            uint32_t a[4];
#pragma unroll
            for (int i = 0; i < 4; i++) a[i] = q[i].x & q[i].y & q[i].z & q[i].w;
            if (__all_sync(0xffffffffu, a[0] & a[1] & a[2] & a[3])) break;
#pragma unroll
            for (int i = 0; i < 4; i++)
                if (!a[i]) q[i] = ld_poll(ksrc + 512 * i);
            if (++it > SPIN_LIMIT) TRAP();
        }
        STAMP(16);
        if (warp == 19) {
            auto merge = [](const uint4& x, const uint4& y) {
                const uint32_t a = max(x.x, y.w), c = max(x.y, y.z), d = max(x.z, y.y), e = max(x.w, y.x);
                const uint32_t a2 = max(a, d), d2 = min(a, d), c2 = max(c, e), e2 = min(c, e);
                return make_uint4(max(a2, c2), min(a2, c2), max(d2, e2), min(d2, e2));
            };
            uint4 h = merge(merge(q[0], q[1]), merge(q[2], q[3]));
            uint4 v[9];
            uint32_t key = 0;
#pragma unroll
            for (int s = 0; s < 8; s++) {
                const uint32_t m = __reduce_max_sync(0xffffffffu, h.x);
                const bool w = h.x == m;
                h.x = w ? h.y : h.x; h.y = w ? h.z : h.y; h.z = w ? h.w : h.z; h.w = w ? 0u : h.w;
                if (g == s) key = m;
            }
            rsrc += (key & 255u) * 144;
#pragma unroll
            for (int j = 0; j < 9; j++) v[j] = ld_poll(rsrc + 4 * j);
            const uint32_t xsa = sb + SM_XS + g * XS_PITCH + t * 16;
            sts32(s_key + 32 + g * 4, key);
            sts32(xsa, 0u);
            bar_arrive(15, 64);
            bar_arrive(12, 608);
            STAMP(18);
#pragma unroll
            for (int j = 0; j < 9; j++) sts128(xsa + j * 64, v[j].x, v[j].y, v[j].z, v[j].w);
            slow = min(min(min(min(v[0].x, v[1].x), v[2].x), min(min(v[3].x, v[4].x), v[5].x)), min(min(v[6].x, v[7].x), v[8].x)) == 0u;
        } else {
            const uint32_t kt = sb + SM_KEYS;
#pragma unroll
            for (int i = 0; i < 4; i++) sts128(kt + i * 512 + lane * 16, q[i].x, q[i].y, q[i].z, q[i].w);
            bar_sync(15, 64);
            const uint32_t c = lds32(s_key + 32 + g * 4), e = lds32(kt + (c & 254u) * 8 + t * 4);
            const bool hit = ((e ^ c) & 0x1fffu) == 0u && !(c & 256u);
            if (hit) sts32(s_key + g * 4, e);
            const uint32_t lo = __reduce_min_sync(0xffffffffu, hit ? e : 0xffffffffu) | 0x1fffu;
#define GT(x) ((lo - (x)) >> 31)
            uint32_t n = hit ? 256u - GT(e) : 0u;
#pragma unroll
            for (int i = 0; i < 4; i++) n += pin(GT(q[i].x) + GT(q[i].y) + GT(q[i].z) + GT(q[i].w), zr) << 12;
#undef GT
            n = __reduce_add_sync(0xffffffffu, n);
            slow = (n >> 12) + (n & 4095u) != 2048u || (n & 4095u) <= 2040u;
            if (slow) {
                uint4 r[4];
                it = 0;
                while (true) {
#pragma unroll
                    for (int i = 0; i < 4; i++) r[i] = ld_poll(ksrc + 512 * i + 1);
                    if (__all_sync(0xffffffffu, all_nz(r[0]) && all_nz(r[1]) && all_nz(r[2]) && all_nz(r[3]))) break;
                    if (++it > SPIN_LIMIT) TRAP();
                }
                uint32_t m = 0u;
#pragma unroll 1
                for (int s = 0; s < 8; s++) {
                    uint32_t x = 0;
#pragma unroll
                    for (int i = 0; i < 4; i++) {
                        x = max(max(max(x, q[i].x - m), max(q[i].y - m, q[i].z - m)), q[i].w - m);
                        x = max(max(max(x, r[i].x - m), max(r[i].y - m, r[i].z - m)), r[i].w - m);
                    }
                    m += __reduce_max_sync(0xffffffffu, x);
                    if (lane == 0) sts32(s_key + s * 4, m);
                }
            }
            DBG(7, slow);
        }
        if (bar_or(0, NWRK, slow)) late_rows([](bool, int) {});
        STAMP(19);
        const int fl = 16 * (b & 1) + ((tid >> 2) & 15), fc = 16 * (b >> 1) + (fl >> 2) + 8 * ((tid >> 1) & 1), fsl = 2 * (fl & 3) + (tid & 1);
        const uint32_t kk = lds32(s_key + fsl * 4);
        const uint32_t* fsrc = p.s->rows + ((kk & 256u) ? 2 * NCTA + fsl : (kk & 255u)) * DM + (fc >> 1);
        uint32_t hw = 1u, uw = 1u;
        if (b < 72) { uw = ld_poll32(fsrc); hw = ld_poll32(fsrc + 288); }
        if (b < 72) {
            it = 0;
            while (!hw || !uw) { uw = ld_poll32(fsrc); hw = ld_poll32(fsrc + 288); if (++it > SPIN_LIMIT) TRAP(); }
            const int row = (kk >> 9) & 15, ftok = 8 * (kk & 252u) + (kk & 2u) + TOKEN_OF(row & 7) + (row & 8);
            const unsigned k16 = (kk >> 15) & 0xffffu;
            const unsigned bits = (k16 & 0x8000u) ? (k16 & 0x7fffu) : (~k16 & 0xffffu);
            const float rs = 512.0f * rbf(__fdividef(1.0f, 1.0f + __expf(-__uint_as_float(bits << 16))));
            bf16* const op = p.out + (unsigned)(ftok * DM + fc);
            const float uv = (fc & 1) ? bf_hi(uw) : bf_lo(uw), hv = (fc & 1) ? bf_hi(hw) : bf_lo(hw);
            const uint32_t a = sb + SM_FIN + (tid - 576) * 80;
            sts128(a + 64, __float_as_uint(rs), __float_as_uint(uv), __float_as_uint(hv), (uint32_t)(size_t)op ^ (uint32_t)((size_t)op >> 32));
            bar_sync(14, 576);
            const uint4 p0 = lds128(a), p1 = lds128(a + 16), p2 = lds128(a + 32), p3 = lds128(a + 48);
#define F4(p) ((__uint_as_float(p.x) + __uint_as_float(p.y)) + (__uint_as_float(p.z) + __uint_as_float(p.w)))
            const float v0 = F4(p0), v1 = F4(p1), v2 = F4(p2), v3 = F4(p3);
#undef F4
            const float y3 = rbf(rbf((v0 + v1) + (v2 + v3)) * rs);
            asm volatile("st.global.u16 [%0], %1;\n" ::"l"(op), "h"((unsigned short)pack_bf16(hv + rbf(uv + y3), 0.f)) : "memory");
        }
        if (b == 0 && tid >= 632) *reinterpret_cast<volatile unsigned*>(p.s->hint + (tid & 7) * 32 + 1) = lds32(s_cnt + 4) + 1u;
    } else {
        uint32_t H[2][4], U2[2][4], WA[9][4], WD[18], WE[18];
        const int fkh = warp >= 9, fmt = warp - 9 * fkh;
        auto load_wa = [&](auto k0, auto k1) {
            if (k0.value >= k1.value) return;
            if (k0.value == 0) mbar_wait(bar_w);
            const int mi = lane >> 3, rr = lane & 7;
            const int row = fkh * 144 + rr + 8 * (mi >> 1);
            const uint32_t aad = sb + (fmt < 8 ? SM_WG + (mi & 1) * (SM_WU - SM_WG) + row * 128 + (fmt ^ rr) * 16 : SM_WR + (mi & 1) * 4608 + row * 16), ks = fmt < 8 ? 2048 : 256;
#pragma unroll
            for (int k = k0.value; k < k1.value; k++) ldsm_x4_t(WA[k][0], WA[k][1], WA[k][2], WA[k][3], aad + k * ks);
        };
        auto load_wd = [&](uint32_t (&WD)[18], int tile) {
            mbar_wait(bar_d);
            if (tile & 16) mbar_wait(bar_d + 16);
            const int mi = lane >> 3, rr = lane & 7;
            const uint32_t base = sb + SM_WD + rr * 128 + (((2 * tile + (mi & 1)) & 7) ^ rr) * 16;
#pragma unroll
            for (int k = 0; k < 4; k++) ldsm_x4_t(WD[4 * k], WD[4 * k + 1], WD[4 * k + 2], WD[4 * k + 3], base + (tile >> 2) * 8192 + (k * 16 + 8 * (mi >> 1)) * 128);
            ldsm_x2_t(WD[16], WD[17], base + 40960 + (tile >> 2) * 1024);
        };
        auto publish = [&](bool hi, int slot) {
            uint4* rowp = reinterpret_cast<uint4*>(p.s->rows) + slot * 144 + warp * 4 + t;
            stg128(rowp, nzw(hi ? U2[1][0] : U2[0][0]), nzw(hi ? U2[1][1] : U2[0][1]), nzw(hi ? U2[1][2] : U2[0][2]), nzw(hi ? U2[1][3] : U2[0][3]));
            stg128(rowp + 72, nzw(hi ? H[1][0] : H[0][0]), nzw(hi ? H[1][1] : H[0][1]), nzw(hi ? H[1][2] : H[0][2]), nzw(hi ? H[1][3] : H[0][3]));
        };
        uint4 wr = make_uint4(0x3f803f80u, 0x3f803f80u, 0x3f803f80u, 0x3f803f80u);
        {
            uint2 yv[4];
#pragma unroll
            for (int k = 0; k < 4; k++) yv[k] = ld_poll64(ys + k * 128);
            if (g == 0) wr = ldg128(p.wr + 32 * warp + 8 * t);
            const uint4 x0 = lds128(sb + SM_XT + warp * 1024 + lane * 16), x1 = lds128(sb + SM_XT + warp * 1024 + 512 + lane * 16);
            load_wa(IC<0>(), IC<WA0>());
            int it = 0;
            while (!__all_sync(0xffffffffu, yv[0].x && yv[1].x && yv[2].x && yv[3].x)) {
#pragma unroll
                for (int k = 0; k < 4; k++) yv[k] = ld_poll64(ys + k * 128);
                if (++it > SPIN_LIMIT) TRAP();
            }
            STAMP(12);
            const uint32_t Z[2][4] = {{x0.x, x0.y, x0.z, x0.w}, {x1.x, x1.y, x1.z, x1.w}};
#pragma unroll
            for (int k = 0; k < 4; k++) {
                H[0][k] = hadd2_bf(Z[0][k], movm(yv[k].x));
                H[1][k] = hadd2_bf(Z[1][k], movm(yv[k].y));
            }
            const uint32_t bw[4] = {wr.x, wr.y, wr.z, wr.w};
            ln_partial<4>(H, bw, sb + SM_LNP, warp, g, t);
        }
        bar_arrive(8, 640);
        WPOINT(16, warp - 12);
        load_wa(IC<WA0>(), IC<WA1>());
        STAMP(13);
        bar_sync(13, 608);
        STAMP(14);
#pragma unroll
        for (int hf = 0; hf < 2; hf++) {
            const uint2 st = lds64(s_stat + (g + 8 * hf) * 8);
#pragma unroll
            for (int k = 0; k < 4; k++) U2[hf][k] = ln_apply(H[hf][k], st);
        }
        {
            float cs[4] = {0.f, 0.f, 0.f, 0.f}, ct[4] = {0.f, 0.f, 0.f, 0.f};
            mma_bf16(cs, U2[0][0], U2[1][0], U2[0][1], U2[1][1], wr.x, wr.y);
            mma_bf16(ct, U2[0][2], U2[1][2], U2[0][3], U2[1][3], wr.z, wr.w);
            if (t == 0) { stsf(sb + SM_LNP + ((32 + g) * 20 + warp) * 4, cs[0] + ct[0]); stsf(sb + SM_LNP + ((40 + g) * 20 + warp) * 4, cs[2] + ct[2]); }
            bar_arrive(10, 640);
        }
        load_wa(IC<WA1>(), IC<WA2>());
        bar_sync(11, 608);
        {
            const uint32_t rk[2] = {lds32(s_wm + g * 4), lds32(s_wm + 32 + g * 4)};
            uint32_t lo = min(rk[0], rk[1]), hi = max(rk[0], rk[1]);
#pragma unroll 1
            while (lo < 2) { publish(lo == rk[1], 2 * b + lo); lo = hi; hi = 16; }
        }
        load_wa(IC<WA2>(), IC<WA3>());
        load_wa(IC<WA3>(), IC<9>());
#pragma unroll
        for (int hf = 0; hf < 2; hf++)
            sts128(sb + SM_OUT + (g + 8 * hf) * OUT_PITCH + warp * 64 + t * 16,
                   hadd2_bf(H[hf][0], U2[hf][0]), hadd2_bf(H[hf][1], U2[hf][1]), hadd2_bf(H[hf][2], U2[hf][2]), hadd2_bf(H[hf][3], U2[hf][3]));
        fence_async();
        WPOINT(17, warp - 16);
        if ((WDAT == 0 || (WDAT == 2 && fkh)) && (warp < 16 || !odd)) load_wd(WD, warp);
        const uint32_t bad = pin(sb + SM_XS + (lane & 7) * XS_PITCH + (fkh * 144 + 8 * (lane >> 3)) * 2, zr), ex = pin(sb + SM_EX + warp * 512 + lane * 16, zr);
        uint32_t* pp = pin(p.s->part + ((size_t)(2 * (20 * odd + warp) + (lane >> 4)) * 64 + P) * 32 + (lane & 15) * 2, zr);
        bar_sync(12, 608);
        const bool routed = __any_sync(0xffffffffu, (lds32(s_key + 32 + (lane & 7) * 4) & 0x1efeu) == (uint32_t)((warp << 9) | 2 * b));
        auto store_row = [&]() { if (warp < 16 && elect_one()) bulk_s2g(p.out + (size_t)(32 * P + 2 * odd + TOKEN_OF(warp & 7) + (warp & 8)) * DM, sb + SM_OUT + warp * OUT_PITCH, DM * 2); };
        if (!routed) store_row();
        WPOINT(18, warp - 16);
        STAMP(15);
        if (bar_or(0, NWRK, false)) {
            if (routed) store_row();
            asm volatile("cp.async.bulk.wait_group 0;\n" ::: "memory");
            late_rows(publish);
        }
        STAMP(19);
        float gp[4];
        {
            float c4[3][4];
#pragma unroll
            for (int i = 0; i < 3; i++)
#pragma unroll
                for (int j = 0; j < 4; j++) c4[i][j] = 0.f;
#pragma unroll
            for (int k = 0; k < 10; k += 2) {
                uint32_t b0, b1, b2, b3;
                ldsm_x4(b0, b1, b2, b3, bad + k * 32);
                mma_bf16(c4[k % 3], WA[k][0], WA[k][1], WA[k][2], WA[k][3], b0, b1);
                if (k < 8) mma_bf16(c4[(k + 1) % 3], WA[k + 1][0], WA[k + 1][1], WA[k + 1][2], WA[k + 1][3], b2, b3);
            }
#pragma unroll
            for (int j = 0; j < 4; j++) gp[j] = c4[0][j] + (c4[1][j] + c4[2][j]);
            if (warp >= 9) {
                sts128f(ex, gp);
                bar_arrive(6, 576);
            } else {
                bar_sync(6, 576);
                const uint4 o = lds128(ex + 4608);
                gp[0] += __uint_as_float(o.x); gp[1] += __uint_as_float(o.y); gp[2] += __uint_as_float(o.z); gp[3] += __uint_as_float(o.w);
                asm volatile("st.async.shared::cluster.mbarrier::complete_tx::bytes.v4.b32 [%0], {%1,%2,%3,%4}, [%5];\n"
                             ::"r"(ex ^ 0x1000000u), "r"(__float_as_uint(gp[0])), "r"(__float_as_uint(gp[1])), "r"(__float_as_uint(gp[2])), "r"(__float_as_uint(gp[3])), "r"(bar_g ^ 0x1000000u) : "memory");
                if (WDAT == 2) load_wd(WD, warp);
            }
            if (WDAT == 1 && (warp < 16 || !odd)) load_wd(WD, warp);
            if (warp >= 16 && !odd) load_wd(WE, warp + 2);
        }
        STAMP(20);
        if (warp < 9) {
            mbar_wait(bar_g);
            const uint4 u = lds128(ex);
            const uint32_t G = pack_bf16(gp[0] + __uint_as_float(u.x), gp[1] + __uint_as_float(u.y)), U = pack_bf16(gp[2] + __uint_as_float(u.z), gp[3] + __uint_as_float(u.w));
            const float G0 = bf_lo(G), G1 = bf_hi(G);
            sts32(sb + SM_GU + tid * 4, hmul2_bf(pack_bf16(G0 * rcp_approx(1.0f + ex2_approx(G0 * -1.4426950408889634f)), G1 * rcp_approx(1.0f + ex2_approx(G1 * -1.4426950408889634f))), U));
        }
        bar_sync(7, 576);
        STAMP(21);
        if (warp < 16 || !odd) {
            uint32_t gb[9];
            ldsm_x4_t(gb[0], gb[1], gb[2], gb[3], sb + SM_GU + lane * 16);
            ldsm_x4_t(gb[4], gb[5], gb[6], gb[7], sb + SM_GU + 512 + lane * 16);
            ldsm_x1_t(gb[8], sb + SM_GU + 1024 + (lane & 7) * 16);
            auto down = [&](const uint32_t (&W)[18], uint32_t* dst) {
                float c4[4] = {0.f, 0.f, 0.f, 0.f}, d4[4] = {0.f, 0.f, 0.f, 0.f}, e4[4] = {0.f, 0.f, 0.f, 0.f};
                mma_bf16(c4, W[0], W[1], W[2], W[3], gb[0], gb[1]);
                mma_bf16(d4, W[4], W[5], W[6], W[7], gb[2], gb[3]);
                mma_bf16(e4, W[8], W[9], W[10], W[11], gb[4], gb[5]);
                mma_bf16_k8(c4, W[16], W[17], gb[8]);
                mma_bf16(d4, W[12], W[13], W[14], W[15], gb[6], gb[7]);
                const float v0 = (c4[0] + e4[0]) + d4[0], v1 = (c4[1] + e4[1]) + d4[1], v2 = (c4[2] + e4[2]) + d4[2], v3 = (c4[3] + e4[3]) + d4[3];
                const uint32_t e = max(max(__float_as_uint(fmaxf(fabsf(v0), fabsf(v1))), __float_as_uint(fmaxf(fabsf(v2), fabsf(v3)))), 16u << 23) >> 23;
                const float sc = __uint_as_float((245u - e) << 23);
                stg64(dst, pack_f16(v0 * sc, v1 * sc) | ((e * 0x8002000u) & 0x60006000u), pack_f16(v2 * sc, v3 * sc) | ((e * 0x800200u) & 0x60006000u));
            };
            if (warp >= 16) { down(WE, pp + 4 * 64 * 32); down(WD, pp); }
            else down(WD, pp);
        }
        asm volatile("cp.async.bulk.wait_group.read 0;\n" ::: "memory");
        STAMP(22);
        if (b < 72 && warp < 16) {
            const uint2* src = reinterpret_cast<const uint2*>(p.s->part) + (unsigned)(b * 1024 + tid);
            uint2 a, c;
            int it = 0;
            DELAY(PDEL);
            a = ld_poll64(src); c = ld_poll64(src + 512);
            while (!__all_sync(0xffffffffu, a.y && c.y)) {
                a = ld_poll64(src); c = ld_poll64(src + 512);
                if (++it > SPIN_LIMIT) TRAP();
            }
            STAMP(24);
            const float ea = __uint_as_float((((a.y & 0x60006000u) | ((a.x >> 4) & 0x06000600u)) * 0x4001u) & 0x7f800000u);
            const float ec = __uint_as_float((((c.y & 0x60006000u) | ((c.x >> 4) & 0x06000600u)) * 0x4001u) & 0x7f800000u);
            a.x &= 0x9fff9fffu; a.y &= 0x9fff9fffu; c.x &= 0x9fff9fffu; c.y &= 0x9fff9fffu;
            const float s0 = fmaf(h_lo(a.x), ea, h_lo(c.x) * ec), s1 = fmaf(h_hi(a.x), ea, h_hi(c.x) * ec), s2 = fmaf(h_lo(a.y), ea, h_lo(c.y) * ec), s3 = fmaf(h_hi(a.y), ea, h_hi(c.y) * ec);
            const bool up = lane & 16;
            const float r0 = __shfl_xor_sync(0xffffffffu, up ? s0 : s2, 16), r1 = __shfl_xor_sync(0xffffffffu, up ? s1 : s3, 16);
            const uint32_t fa = sb + SM_FIN + ((lane & 15) * 4 + (up ? 2 : 0)) * 80 + warp * 4;
            stsf(fa, (up ? s2 : s0) + r0); stsf(fa + 80, (up ? s3 : s1) + r1);
            bar_arrive(14, 576);
        }
    }
    STAMP(25);
    }
}

typedef CUresult (*PFN_tmEncode)(CUtensorMap*, CUtensorMapDataType, cuuint32_t, void*, const cuuint64_t*, const cuuint64_t*, const cuuint32_t*,
                                 const cuuint32_t*, CUtensorMapInterleave, CUtensorMapSwizzle, CUtensorMapL2promotion, CUtensorMapFloatOOBfill);

extern "C" void kernel_launch(void* const* d_in, const int* in_sizes, int n_in, void* d_out, int out_size) {
    Params p;
    p.x = (const bf16*)d_in[0];
    p.lar = (const bf16*)d_in[1];
    p.aim = (const bf16*)d_in[2];
    p.cre = (const bf16*)d_in[3];
    p.cim = (const bf16*)d_in[4];
    p.ldt = (const bf16*)d_in[5];
    p.dsk = (const bf16*)d_in[6];
    p.wr = (const bf16*)d_in[8];
    p.out = (bf16*)d_out;
    static PFN_tmEncode enc = nullptr;
    static void* scratch = nullptr;
    if (!enc) {
        cudaFuncSetAttribute(fused_kernel, cudaFuncAttributeMaxDynamicSharedMemorySize, SMEM_TOTAL);
        void* fn = nullptr;
        cudaDriverEntryPointQueryResult qr;
        cudaGetDriverEntryPoint("cuTensorMapEncodeTiled", &fn, cudaEnableDefault, &qr);
        enc = (PFN_tmEncode)fn;
        cudaGetSymbolAddress(&scratch, g_scratch);
    }
    p.s = (Scratch*)scratch;
    WMaps wm;
    CUtensorMap tm_x, tm_y, tm_z;
    const cuuint64_t dims[2] = {FF, DM}, strides[1] = {FF * 2}, rdims[3] = {FF, 144, 4}, rstrides[2] = {FF * 2, 144 * FF * 2};
    const cuuint32_t box[2] = {64, 72}, rbox[3] = {8, 144, 2}, es3[3] = {1, 1, 1};
    for (int i = 0; i < 2; i++) {
        enc(i ? &wm.u : &wm.g, CU_TENSOR_MAP_DATA_TYPE_BFLOAT16, 2, d_in[9 + i], dims, strides, box, es3, CU_TENSOR_MAP_INTERLEAVE_NONE, CU_TENSOR_MAP_SWIZZLE_128B,
            CU_TENSOR_MAP_L2_PROMOTION_NONE, CU_TENSOR_MAP_FLOAT_OOB_FILL_NONE);
        enc(i ? &wm.ur : &wm.gr, CU_TENSOR_MAP_DATA_TYPE_BFLOAT16, 3, d_in[9 + i], rdims, rstrides, rbox, es3, CU_TENSOR_MAP_INTERLEAVE_NONE, CU_TENSOR_MAP_SWIZZLE_NONE,
            CU_TENSOR_MAP_L2_PROMOTION_NONE, CU_TENSOR_MAP_FLOAT_OOB_FILL_NONE);
    }
    const cuuint64_t ddims[2] = {DM, FF}, dstrides[1] = {DM * 2}, edims[3] = {64, FF, 9}, estrides[2] = {DM * 2, 128};
    const cuuint32_t dbox[2] = {64, 64}, ebox[3] = {64, 8, 5};
    enc(&wm.d, CU_TENSOR_MAP_DATA_TYPE_BFLOAT16, 2, d_in[11], ddims, dstrides, dbox, es3, CU_TENSOR_MAP_INTERLEAVE_NONE, CU_TENSOR_MAP_SWIZZLE_128B,
        CU_TENSOR_MAP_L2_PROMOTION_NONE, CU_TENSOR_MAP_FLOAT_OOB_FILL_NONE);
    enc(&wm.dr, CU_TENSOR_MAP_DATA_TYPE_BFLOAT16, 3, d_in[11], edims, estrides, ebox, es3, CU_TENSOR_MAP_INTERLEAVE_NONE, CU_TENSOR_MAP_SWIZZLE_128B,
        CU_TENSOR_MAP_L2_PROMOTION_NONE, CU_TENSOR_MAP_FLOAT_OOB_FILL_NONE);
    const cuuint64_t xdims[3] = {DM, LSEQ / 16, 16}, xstrides[2] = {16 * DM * 2, DM * 2};
    const cuuint32_t xbox[3] = {8, LSEQ / 16, 8};
    enc(&tm_x, CU_TENSOR_MAP_DATA_TYPE_BFLOAT16, 3, d_in[0], xdims, xstrides, xbox, es3, CU_TENSOR_MAP_INTERLEAVE_NONE, CU_TENSOR_MAP_SWIZZLE_NONE,
        CU_TENSOR_MAP_L2_PROMOTION_NONE, CU_TENSOR_MAP_FLOAT_OOB_FILL_NONE);
    const cuuint64_t ydims[3] = {DM * 32, 16, 4}, ystrides[2] = {DM * 64, 16 * DM * 64};
    const cuuint32_t ybox[3] = {128, 16, 2}, zbox[3] = {32, 16, 2};
    enc(&tm_y, CU_TENSOR_MAP_DATA_TYPE_BFLOAT16, 3, p.s->y, ydims, ystrides, ybox, es3, CU_TENSOR_MAP_INTERLEAVE_NONE, CU_TENSOR_MAP_SWIZZLE_NONE,
        CU_TENSOR_MAP_L2_PROMOTION_NONE, CU_TENSOR_MAP_FLOAT_OOB_FILL_NONE);
    enc(&tm_z, CU_TENSOR_MAP_DATA_TYPE_BFLOAT16, 3, p.s->y, ydims, ystrides, zbox, es3, CU_TENSOR_MAP_INTERLEAVE_NONE, CU_TENSOR_MAP_SWIZZLE_NONE,
        CU_TENSOR_MAP_L2_PROMOTION_NONE, CU_TENSOR_MAP_FLOAT_OOB_FILL_NONE);
    fused_kernel<<<NCTA, NTHR, SMEM_TOTAL>>>(p, wm, tm_x, tm_y, tm_z);
}
```

```cpp
#include <cuda_runtime.h>
#include <cuda.h>
#include <cuda_fp16.h>
#include <cuda_bf16.h>
#include <stdint.h>

#define LSEQ 2048
#define DM 576
#define NST 128
#define FF 4608
#define NSEL 8
#define NCTA 128
#define NTHR 640
#define NWRK 640

typedef __nv_bfloat16 bf16;

#define SM_WD 0
#define SM_WG 46080
#define SM_WR 82944
#define SM_WU 92160
#define SM_ZERO 32768
#define SM_XC 16384
#define SM_TB 96000
#define SM_PL 129024
#define PL_B 10752
#define SM_XT (SM_TB + 20 * TBW)
#define SM_U (SM_XT + 18432)
#define UPAD 8
#define ULO_B ((UPAD + 128) * 16)
#define USLOT_B (2 * ULO_B)
#define SM_KW (SM_U + 5 * USLOT_B)
#define KW_B 3600
#define KW_T2 1152
#define KW_KH 656
#define KW_T3 2464
#define SM_MISC (SM_KW + 5 * KW_B)
#define SM_LNP (SM_MISC + 576)
#define SMEM_TOTAL (SM_LNP + 5120)
#define TBP 112
#define TBW (32 * TBP)
#define SM_OUT SM_PL
#define OUT_PITCH 1216
#define SM_XS (SM_PL + 19456)
#define XS_PITCH 592
#define SM_EX (SM_PL + 24320)
#define SM_KEYS (SM_KW + 5120)
#define SM_FIN SM_KW
#define SM_GU (SM_PL + 33536)

struct __align__(128) Scratch {
    unsigned hint[8 * 32];
    unsigned flag[32];
    uint32_t sc[NCTA * 64];
    uint32_t st[LSEQ * 2];
    uint32_t uT[64 * (LSEQ / 2)];
    uint32_t y[NCTA * DM * 8];
    uint32_t part[72 * 64 * 32];
    uint32_t rows[(2 * NCTA + NSEL) * DM];
};
__device__ Scratch g_scratch;
#define STAMP(i)
#define DBG(i, v)

__device__ __forceinline__ float rbf(float x) {
    uint32_t r;
    asm("cvt.rn.bf16x2.f32 %0, %1, %2;\n" : "=r"(r) : "f"(x), "f"(0.f));
    return __uint_as_float(r);
}
__device__ __forceinline__ uint32_t pack_bf16(float lo, float hi) {
    uint32_t r;
    asm("cvt.rn.bf16x2.f32 %0, %1, %2;\n" : "=r"(r) : "f"(hi), "f"(lo));
    return r;
}
__device__ __forceinline__ uint32_t pack_f16(float lo, float hi) {
    uint32_t r;
    asm("cvt.rn.f16x2.f32 %0, %1, %2;\n" : "=r"(r) : "f"(hi), "f"(lo));
    return r;
}
__device__ __forceinline__ uint32_t pack_f16_rz(float lo, float hi) {
    uint32_t r;
    asm("cvt.rz.f16x2.f32 %0, %1, %2;\n" : "=r"(r) : "f"(hi), "f"(lo));
    return r;
}
__device__ __forceinline__ float bf_lo(uint32_t w) { return __uint_as_float(w << 16); }
__device__ __forceinline__ float bf_hi(uint32_t w) { return __uint_as_float(w & 0xffff0000u); }
__device__ __forceinline__ uint32_t hadd2_bf(uint32_t a, uint32_t b) {
    __nv_bfloat162 r = __hadd2_rn(*reinterpret_cast<__nv_bfloat162*>(&a), *reinterpret_cast<__nv_bfloat162*>(&b));
    return *reinterpret_cast<uint32_t*>(&r);
}
__device__ __forceinline__ uint32_t hmul2_bf(uint32_t a, uint32_t b) {
    __nv_bfloat162 r = __hmul2_rn(*reinterpret_cast<__nv_bfloat162*>(&a), *reinterpret_cast<__nv_bfloat162*>(&b));
    return *reinterpret_cast<uint32_t*>(&r);
}
__device__ __forceinline__ uint32_t hfma2_bf(uint32_t a, uint32_t b, uint32_t c) { uint32_t r; asm("fma.rn.bf16x2 %0, %1, %2, %3;\n" : "=r"(r) : "r"(a), "r"(b), "r"(c)); return r; }
__device__ __forceinline__ uint32_t hmul2(uint32_t a, uint32_t b) { uint32_t r; asm("mul.rn.f16x2 %0, %1, %2;\n" : "=r"(r) : "r"(a), "r"(b)); return r; }
__device__ __forceinline__ uint32_t hadd2(uint32_t a, uint32_t b) { uint32_t r; asm("add.rn.f16x2 %0, %1, %2;\n" : "=r"(r) : "r"(a), "r"(b)); return r; }
__device__ __forceinline__ uint32_t nzw(uint32_t w) { return w ? w : 0x8000u; }
__device__ __forceinline__ uint32_t smem_u32(const void* p) { return (uint32_t)__cvta_generic_to_shared(p); }
__device__ __forceinline__ uint32_t lds32(uint32_t addr) {
    uint32_t v;
    asm volatile("ld.shared.u32 %0, [%1];\n" : "=r"(v) : "r"(addr) : "memory");
    return v;
}
__device__ __forceinline__ uint2 lds64(uint32_t addr) {
    uint2 v;
    asm volatile("ld.shared.v2.u32 {%0,%1}, [%2];\n" : "=r"(v.x), "=r"(v.y) : "r"(addr) : "memory");
    return v;
}
__device__ __forceinline__ uint4 lds128(uint32_t addr) {
    uint4 v;
    asm volatile("ld.shared.v4.u32 {%0,%1,%2,%3}, [%4];\n" : "=r"(v.x), "=r"(v.y), "=r"(v.z), "=r"(v.w) : "r"(addr) : "memory");
    return v;
}
__device__ __forceinline__ float ldsf(uint32_t addr) { return __uint_as_float(lds32(addr)); }
__device__ __forceinline__ void sts32(uint32_t addr, uint32_t v) { asm volatile("st.shared.u32 [%0], %1;\n" ::"r"(addr), "r"(v) : "memory"); }
__device__ __forceinline__ void stsf(uint32_t addr, float v) { sts32(addr, __float_as_uint(v)); }
__device__ __forceinline__ void sts64(uint32_t addr, uint32_t a, uint32_t b) { asm volatile("st.shared.v2.u32 [%0], {%1,%2};\n" ::"r"(addr), "r"(a), "r"(b) : "memory"); }
__device__ __forceinline__ void sts128(uint32_t addr, uint32_t a, uint32_t b, uint32_t c, uint32_t d) {
    asm volatile("st.shared.v4.u32 [%0], {%1,%2,%3,%4};\n" ::"r"(addr), "r"(a), "r"(b), "r"(c), "r"(d) : "memory");
}
__device__ __forceinline__ void sts128f(uint32_t addr, const float (&v)[4]) {
    sts128(addr, __float_as_uint(v[0]), __float_as_uint(v[1]), __float_as_uint(v[2]), __float_as_uint(v[3]));
}
__device__ __forceinline__ void ldsm_x4(uint32_t& r0, uint32_t& r1, uint32_t& r2, uint32_t& r3, uint32_t addr) {
    asm volatile("ldmatrix.sync.aligned.m8n8.x4.shared.b16 {%0,%1,%2,%3}, [%4];\n"
                 : "=r"(r0), "=r"(r1), "=r"(r2), "=r"(r3) : "r"(addr) : "memory");
}
__device__ __forceinline__ void ldsm_x4_t(uint32_t& r0, uint32_t& r1, uint32_t& r2, uint32_t& r3, uint32_t addr) {
    asm volatile("ldmatrix.sync.aligned.m8n8.x4.trans.shared.b16 {%0,%1,%2,%3}, [%4];\n"
                 : "=r"(r0), "=r"(r1), "=r"(r2), "=r"(r3) : "r"(addr) : "memory");
}
__device__ __forceinline__ void ldsm_x2_t(uint32_t& r0, uint32_t& r1, uint32_t addr) {
    asm volatile("ldmatrix.sync.aligned.m8n8.x2.trans.shared.b16 {%0,%1}, [%2];\n" : "=r"(r0), "=r"(r1) : "r"(addr) : "memory");
}
__device__ __forceinline__ void ldsm_x1_t(uint32_t& r0, uint32_t addr) {
    asm volatile("ldmatrix.sync.aligned.m8n8.x1.trans.shared.b16 {%0}, [%1];\n" : "=r"(r0) : "r"(addr) : "memory");
}
__device__ __forceinline__ uint32_t movm(uint32_t a) {
    uint32_t d;
    asm volatile("movmatrix.sync.aligned.m8n8.trans.b16 %0, %1;\n" : "=r"(d) : "r"(a));
    return d;
}
__device__ __forceinline__ void mma_f16(float (&c)[4], uint32_t a0, uint32_t a1, uint32_t a2, uint32_t a3, uint32_t b0, uint32_t b1) {
    asm volatile(
        "mma.sync.aligned.m16n8k16.row.col.f32.f16.f16.f32 {%0,%1,%2,%3}, {%4,%5,%6,%7}, {%8,%9}, {%0,%1,%2,%3};\n"
        : "+f"(c[0]), "+f"(c[1]), "+f"(c[2]), "+f"(c[3])
        : "r"(a0), "r"(a1), "r"(a2), "r"(a3), "r"(b0), "r"(b1));
}
__device__ __forceinline__ void mma_bf16(float (&c)[4], uint32_t a0, uint32_t a1, uint32_t a2, uint32_t a3, uint32_t b0, uint32_t b1) {
    asm volatile(
        "mma.sync.aligned.m16n8k16.row.col.f32.bf16.bf16.f32 {%0,%1,%2,%3}, {%4,%5,%6,%7}, {%8,%9}, {%0,%1,%2,%3};\n"
        : "+f"(c[0]), "+f"(c[1]), "+f"(c[2]), "+f"(c[3])
        : "r"(a0), "r"(a1), "r"(a2), "r"(a3), "r"(b0), "r"(b1));
}
__device__ __forceinline__ void mma_bf16_k8(float (&c)[4], uint32_t a0, uint32_t a1, uint32_t b0) {
    asm volatile("mma.sync.aligned.m16n8k8.row.col.f32.bf16.bf16.f32 {%0,%1,%2,%3}, {%4,%5}, {%6}, {%0,%1,%2,%3};\n"
        : "+f"(c[0]), "+f"(c[1]), "+f"(c[2]), "+f"(c[3]) : "r"(a0), "r"(a1), "r"(b0));
}
__device__ __forceinline__ void bar_sync(int id, int n) { asm volatile("bar.sync %0, %1;\n" ::"r"(id), "r"(n) : "memory"); }
__device__ __forceinline__ void bar_arrive(int id, int n) { asm volatile("bar.arrive %0, %1;\n" ::"r"(id), "r"(n) : "memory"); }
__device__ __forceinline__ bool bar_or(int id, int n, bool v) {
    uint32_t r;
    asm volatile("{\n.reg .pred p, q;\nsetp.ne.u32 p, %3, 0;\nbar.red.or.pred q, %1, %2, p;\nselp.u32 %0, 1, 0, q;\n}\n" : "=r"(r) : "r"(id), "r"(n), "r"((uint32_t)v) : "memory");
    return r;
}
__device__ __forceinline__ uint4 ld_poll(const void* p) {
    uint4 v;
    asm volatile("ld.relaxed.gpu.global.v4.u32 {%0,%1,%2,%3}, [%4];\n" : "=r"(v.x), "=r"(v.y), "=r"(v.z), "=r"(v.w) : "l"(p) : "memory");
    return v;
}
template <class T> __device__ __forceinline__ T* pin(T* p, uint32_t z) {
    uint32_t lo, hi;
    asm volatile("mov.b64 {%0, %1}, %2;\n" : "=r"(lo), "=r"(hi) : "l"(p));
    asm volatile("xor.b32 %0, %0, %1;\n" : "+r"(lo) : "r"(z));
    asm volatile("xor.b32 %0, %0, %1;\n" : "+r"(hi) : "r"(z));
    asm volatile("mov.b64 %0, {%1, %2};\n" : "=l"(p) : "r"(lo), "r"(hi));
    return p;
}
__device__ __forceinline__ uint32_t pin(uint32_t a, uint32_t z) { asm volatile("xor.b32 %0, %0, %1;\n" : "+r"(a) : "r"(z)); return a; }
__device__ __forceinline__ uint2 ld_poll64(const void* p) {
    uint2 v;
    asm volatile("ld.relaxed.gpu.global.v2.u32 {%0,%1}, [%2];\n" : "=r"(v.x), "=r"(v.y) : "l"(p) : "memory");
    return v;
}
__device__ __forceinline__ uint32_t ld_poll32(const void* p) {
    uint32_t v;
    asm volatile("ld.relaxed.gpu.global.u32 %0, [%1];\n" : "=r"(v) : "l"(p) : "memory");
    return v;
}
__device__ __forceinline__ uint4 ldg128(const void* p) {
    uint4 v;
    asm volatile("ld.global.nc.v4.u32 {%0,%1,%2,%3}, [%4];\n" : "=r"(v.x), "=r"(v.y), "=r"(v.z), "=r"(v.w) : "l"(p));
    return v;
}
__device__ __forceinline__ uint2 ldg64(const void* p) {
    uint2 v;
    asm volatile("ld.global.nc.v2.u32 {%0,%1}, [%2];\n" : "=r"(v.x), "=r"(v.y) : "l"(p));
    return v;
}
__device__ __forceinline__ uint32_t ldg16(const void* p) {
    uint32_t v;
    asm volatile("ld.global.nc.u16 %0, [%1];\n" : "=r"(v) : "l"(p));
    return v;
}
__device__ __forceinline__ void stg128(void* p, uint32_t a, uint32_t b, uint32_t c, uint32_t d) {
    asm volatile("st.global.v4.u32 [%0], {%1,%2,%3,%4};\n" ::"l"(p), "r"(a), "r"(b), "r"(c), "r"(d) : "memory");
}
__device__ __forceinline__ void stg64(void* p, uint32_t a, uint32_t b) { asm volatile("st.global.v2.u32 [%0], {%1,%2};\n" ::"l"(p), "r"(a), "r"(b) : "memory"); }
__device__ __forceinline__ void stg32(void* p, uint32_t a) { asm volatile("st.global.u32 [%0], %1;\n" ::"l"(p), "r"(a) : "memory"); }
__device__ __forceinline__ bool all_nz(const uint4& v) { return v.x && v.y && v.z && v.w; }
#define SPIN_LIMIT (1 << 21)
#define TRAP() __trap()
__device__ __forceinline__ void hint_arrive(unsigned* g_hint, int idx, int sub) {
    asm volatile("red.relaxed.gpu.global.add.u32 [%0], 1;\n" ::"l"(&g_hint[sub * 32 + idx]) : "memory");
}
__device__ __forceinline__ void hint_wait(const unsigned* g_hint, int idx, unsigned target) {
    unsigned l;
    asm volatile("mov.u32 %0, %%laneid;" : "=r"(l));
    const unsigned* c = &g_hint[(l & 7) * 32 + idx];
    int it = 0;
    while (__any_sync(0xffffffffu, (int)(ld_poll32(c) - target) < 0)) { if (++it > SPIN_LIMIT) TRAP(); }
}
__device__ __forceinline__ void mbar_init(uint32_t bar, uint32_t cnt) { asm volatile("mbarrier.init.shared::cta.b64 [%0], %1;\n" ::"r"(bar), "r"(cnt) : "memory"); }
__device__ __forceinline__ void mbar_expect(uint32_t bar, uint32_t bytes) {
    asm volatile("mbarrier.arrive.expect_tx.shared::cta.b64 _, [%0], %1;\n" ::"r"(bar), "r"(bytes) : "memory");
}
__device__ __forceinline__ void mbar_arrive(uint32_t bar) { asm volatile("mbarrier.arrive.shared::cta.b64 _, [%0];\n" ::"r"(bar) : "memory"); }
__device__ __forceinline__ void mbar_wait(uint32_t bar) {
    asm volatile(
        "{\n.reg .pred p;\n"
        "W_%=:\n"
        "mbarrier.try_wait.parity.shared::cta.b64 p, [%0], 0;\n"
        "@!p bra W_%=;\n}\n" ::"r"(bar) : "memory");
}
__device__ __forceinline__ void bulk_s2g(void* dst, uint32_t src, uint32_t bytes) {
    asm volatile("cp.async.bulk.global.shared::cta.bulk_group [%0], [%1], %2;\ncp.async.bulk.commit_group;\n" ::"l"(dst), "r"(src), "r"(bytes) : "memory");
}
__device__ __forceinline__ void tma_2d(uint32_t dst, const CUtensorMap* tm, int c0, int c1, uint32_t bar) {
    asm volatile("cp.async.bulk.tensor.2d.shared::cluster.global.mbarrier::complete_tx::bytes [%0], [%1, {%3, %4}], [%2];\n"
                 ::"r"(dst), "l"(tm), "r"(bar), "r"(c0), "r"(c1) : "memory");
}
__device__ __forceinline__ void tma_3d(uint32_t dst, const CUtensorMap* tm, int c0, int c1, int c2, uint32_t bar) {
    asm volatile("cp.async.bulk.tensor.3d.shared::cluster.global.mbarrier::complete_tx::bytes [%0], [%1, {%3, %4, %5}], [%2];\n"
                 ::"r"(dst), "l"(tm), "r"(bar), "r"(c0), "r"(c1), "r"(c2) : "memory");
}
__device__ __forceinline__ void tma_st_3d(const CUtensorMap* tm, uint32_t src, int c0, int c1, int c2) {
    asm volatile("cp.async.bulk.tensor.3d.global.shared::cta.bulk_group [%0, {%2, %3, %4}], [%1];\ncp.async.bulk.commit_group;\n"
                 ::"l"(tm), "r"(src), "r"(c0), "r"(c1), "r"(c2) : "memory");
}
__device__ __forceinline__ bool elect_one() {
    uint32_t r;
    asm volatile("{\n.reg .pred p;\nelect.sync _|p, 0xffffffff;\nselp.u32 %0, 1, 0, p;\n}\n" : "=r"(r));
    return r;
}
__device__ __forceinline__ void fence_async() { asm volatile("fence.proxy.async.shared::cta;\n" ::: "memory"); }

__device__ __forceinline__ float2 cmul(float2 a, float2 b) {
    return make_float2(fmaf(a.x, b.x, -a.y * b.y), fmaf(a.x, b.y, a.y * b.x));
}
__device__ __forceinline__ float2 csq(float2 a) {
    float p = a.x * a.y;
    return make_float2(fmaf(a.x, a.x, -a.y * a.y), p + p);
}
__device__ __forceinline__ float2 cexp_e(float lr2, float rh, float rl, float e) {
    float m;
    asm("ex2.approx.ftz.f32 %0, %1;\n" : "=f"(m) : "f"(lr2 * e));
    const float a = rh * e;
    const float r = fmaf(rl, e, a - rintf(a)) * 6.283185307179586f;
    return make_float2(m * __cosf(r), m * __sinf(r));
}
__device__ __forceinline__ float rcp_approx(float x) { float r; asm("rcp.approx.ftz.f32 %0, %1;\n" : "=f"(r) : "f"(x)); return r; }
__device__ __forceinline__ float ex2_approx(float x) { float r; asm("ex2.approx.ftz.f32 %0, %1;\n" : "=f"(r) : "f"(x)); return r; }
__device__ __forceinline__ float sqrt_approx(float x) { float r; asm("sqrt.approx.ftz.f32 %0, %1;\n" : "=f"(r) : "f"(x)); return r; }

__device__ __forceinline__ void wg_fence() { asm volatile("wgmma.fence.sync.aligned;\n" ::: "memory"); }
__device__ __forceinline__ void wg_commit() { asm volatile("wgmma.commit_group.sync.aligned;\n" ::: "memory"); }
__device__ __forceinline__ void wg_wait0() { asm volatile("wgmma.wait_group.sync.aligned 0;\n" ::: "memory"); }
template <int T0, int NT> __device__ __forceinline__ void wg_h(uint32_t (&acc)[32], const uint32_t (&a)[4], uint64_t desc);
template <> __device__ __forceinline__ void wg_h<0, 16>(uint32_t (&acc)[32], const uint32_t (&a)[4], uint64_t desc) {
    asm volatile("wgmma.mma_async.sync.aligned.m64n128k16.f16.f16.f16 {%0,%1,%2,%3,%4,%5,%6,%7,%8,%9,%10,%11,%12,%13,%14,%15,%16,%17,%18,%19,%20,%21,%22,%23,%24,%25,%26,%27,%28,%29,%30,%31}, {%32,%33,%34,%35}, %36, 1, 1, 1, 0;\n"
                 : "+r"(acc[0]), "+r"(acc[1]), "+r"(acc[2]), "+r"(acc[3]), "+r"(acc[4]), "+r"(acc[5]), "+r"(acc[6]), "+r"(acc[7]), "+r"(acc[8]), "+r"(acc[9]), "+r"(acc[10]), "+r"(acc[11]), "+r"(acc[12]), "+r"(acc[13]), "+r"(acc[14]), "+r"(acc[15]), "+r"(acc[16]), "+r"(acc[17]), "+r"(acc[18]), "+r"(acc[19]), "+r"(acc[20]), "+r"(acc[21]), "+r"(acc[22]), "+r"(acc[23]), "+r"(acc[24]), "+r"(acc[25]), "+r"(acc[26]), "+r"(acc[27]), "+r"(acc[28]), "+r"(acc[29]), "+r"(acc[30]), "+r"(acc[31])
                 : "r"(a[0]), "r"(a[1]), "r"(a[2]), "r"(a[3]), "l"(desc));
}
template <> __device__ __forceinline__ void wg_h<4, 4>(uint32_t (&acc)[32], const uint32_t (&a)[4], uint64_t desc) {
    asm volatile("wgmma.mma_async.sync.aligned.m64n32k16.f16.f16.f16 {%0,%1,%2,%3,%4,%5,%6,%7}, {%8,%9,%10,%11}, %12, 1, 1, 1, 0;\n"
                 : "+r"(acc[8]), "+r"(acc[9]), "+r"(acc[10]), "+r"(acc[11]), "+r"(acc[12]), "+r"(acc[13]), "+r"(acc[14]), "+r"(acc[15])
                 : "r"(a[0]), "r"(a[1]), "r"(a[2]), "r"(a[3]), "l"(desc));
}
template <> __device__ __forceinline__ void wg_h<8, 4>(uint32_t (&acc)[32], const uint32_t (&a)[4], uint64_t desc) {
    asm volatile("wgmma.mma_async.sync.aligned.m64n32k16.f16.f16.f16 {%0,%1,%2,%3,%4,%5,%6,%7}, {%8,%9,%10,%11}, %12, 1, 1, 1, 0;\n"
                 : "+r"(acc[16]), "+r"(acc[17]), "+r"(acc[18]), "+r"(acc[19]), "+r"(acc[20]), "+r"(acc[21]), "+r"(acc[22]), "+r"(acc[23])
                 : "r"(a[0]), "r"(a[1]), "r"(a[2]), "r"(a[3]), "l"(desc));
}
template <> __device__ __forceinline__ void wg_h<12, 4>(uint32_t (&acc)[32], const uint32_t (&a)[4], uint64_t desc) {
    asm volatile("wgmma.mma_async.sync.aligned.m64n32k16.f16.f16.f16 {%0,%1,%2,%3,%4,%5,%6,%7}, {%8,%9,%10,%11}, %12, 1, 1, 1, 0;\n"
                 : "+r"(acc[24]), "+r"(acc[25]), "+r"(acc[26]), "+r"(acc[27]), "+r"(acc[28]), "+r"(acc[29]), "+r"(acc[30]), "+r"(acc[31])
                 : "r"(a[0]), "r"(a[1]), "r"(a[2]), "r"(a[3]), "l"(desc));
}
template <> __device__ __forceinline__ void wg_h<0, 8>(uint32_t (&acc)[32], const uint32_t (&a)[4], uint64_t desc) {
    asm volatile("wgmma.mma_async.sync.aligned.m64n64k16.f16.f16.f16 {%0,%1,%2,%3,%4,%5,%6,%7,%8,%9,%10,%11,%12,%13,%14,%15}, {%16,%17,%18,%19}, %20, 1, 1, 1, 0;\n"
                 : "+r"(acc[0]), "+r"(acc[1]), "+r"(acc[2]), "+r"(acc[3]), "+r"(acc[4]), "+r"(acc[5]), "+r"(acc[6]), "+r"(acc[7]), "+r"(acc[8]), "+r"(acc[9]), "+r"(acc[10]), "+r"(acc[11]), "+r"(acc[12]), "+r"(acc[13]), "+r"(acc[14]), "+r"(acc[15])
                 : "r"(a[0]), "r"(a[1]), "r"(a[2]), "r"(a[3]), "l"(desc));
}
template <> __device__ __forceinline__ void wg_h<4, 12>(uint32_t (&acc)[32], const uint32_t (&a)[4], uint64_t desc) {
    asm volatile("wgmma.mma_async.sync.aligned.m64n96k16.f16.f16.f16 {%0,%1,%2,%3,%4,%5,%6,%7,%8,%9,%10,%11,%12,%13,%14,%15,%16,%17,%18,%19,%20,%21,%22,%23}, {%24,%25,%26,%27}, %28, 1, 1, 1, 0;\n"
                 : "+r"(acc[8]), "+r"(acc[9]), "+r"(acc[10]), "+r"(acc[11]), "+r"(acc[12]), "+r"(acc[13]), "+r"(acc[14]), "+r"(acc[15]), "+r"(acc[16]), "+r"(acc[17]), "+r"(acc[18]), "+r"(acc[19]), "+r"(acc[20]), "+r"(acc[21]), "+r"(acc[22]), "+r"(acc[23]), "+r"(acc[24]), "+r"(acc[25]), "+r"(acc[26]), "+r"(acc[27]), "+r"(acc[28]), "+r"(acc[29]), "+r"(acc[30]), "+r"(acc[31])
                 : "r"(a[0]), "r"(a[1]), "r"(a[2]), "r"(a[3]), "l"(desc));
}

#define PBYTES 4608
#define DELAY(n) do { if (n) { const unsigned c0_ = clock32(); while ((int)(clock32() - c0_) < (n)) {} } } while (0)
#define KDEL 300
#define PDEL 300
#define CST(i) do { if ((warp & 3) == 0 && lane_v() == 0) { unsigned t_; asm volatile("mov.u32 %0, %%globaltimer_lo;" : "=r"(t_) :: "memory"); sts32(sb + SMEM_TOTAL - 768 + (warp >> 2) * 128 + (i) * 4, t_); } } while (0)
#define TP0 5000
#define TP4 5800
#define KDEL2 300
#define WSP 450
#define WS0 0
#define HINTW 10
#define WAS 0x0005
#define WA0 (WAS >> 12)
#define WA1 ((WAS >> 8) & 15)
#define WA2 ((WAS >> 4) & 15)
#define WA3 (WAS & 15)
#define WDAT 1
#define PAUSE 2
#define PCNT (32 + ((PAUSE & 1) ? 288 : 0) + ((PAUSE & 6) ? 320 : 64))
#define LNAT 2
#define UW 8
#define FINAT 3
#define UAT 2
#define TOKEN_OF(g) (16 * ((g) & 1) + ((g) >> 2) + 2 * ((g) & 2))
#define HI2(a, b) (pack_f16_rz(__uint_as_float(a), __uint_as_float(b)) & 0xfff8fff8u)
struct Params {
    const bf16 *x, *lar, *aim, *cre, *cim, *ldt, *dsk;
    Scratch* s;
    const bf16* wr;
    bf16* out;
};

template <int NK>
__device__ __forceinline__ void ln_partial(const uint32_t (&H)[2][NK], const uint32_t (&bw)[NK], uint32_t lp, int warp, int g, int t) {
    float cs[4] = {0.f, 0.f, 0.f, 0.f}, cl[4] = {0.f, 0.f, 0.f, 0.f}, ch[4] = {0.f, 0.f, 0.f, 0.f};
#pragma unroll
    for (int k = 0; k < NK; k += 2) {
        uint32_t a0, a1, a2, a3;
        asm volatile("prmt.b32 %0, %4, %4, %8;\nprmt.b32 %1, %5, %5, %8;\nprmt.b32 %2, %6, %6, %8;\nprmt.b32 %3, %7, %7, %8;\n"
                     : "=r"(a0), "=r"(a1), "=r"(a2), "=r"(a3) : "r"(H[0][k]), "r"(H[1][k]), "r"(H[0][k + 1]), "r"(H[1][k + 1]), "r"(0x3210u + (warp >> 8)));
        mma_bf16(cl, a0, a1, a2, a3, H[0][k], H[0][k + 1]);
        mma_bf16(ch, a0, a1, a2, a3, H[1][k], H[1][k + 1]);
        mma_bf16(cs, a0, a1, a2, a3, bw[k], bw[k + 1]);
    }
    const uint32_t a = lp + (g * 20 + warp) * 4;
    if (t == 0) {
        stsf(a, cs[1]); stsf(a + 8 * 80, cs[3]);
        if (NK == 4) { stsf(a + 48 * 80, cs[0]); stsf(a + 56 * 80, cs[2]); }
    }
    if (t == (g >> 1)) { stsf(a + 16 * 80, (g & 1) ? cl[1] : cl[0]); stsf(a + 24 * 80, (g & 1) ? ch[3] : ch[2]); }
}
__device__ __forceinline__ float sum18(uint32_t a) {
    const uint4 p = lds128(a), q = lds128(a + 16), r = lds128(a + 32), s = lds128(a + 48);
    const uint2 u = lds64(a + 64);
#define F(x) __uint_as_float(x)
    return (((F(p.x) + F(p.y)) + (F(p.z) + F(p.w))) + ((F(q.x) + F(q.y)) + (F(q.z) + F(q.w)))) +
           (((F(r.x) + F(r.y)) + (F(r.z) + F(r.w))) + ((F(s.x) + F(s.y)) + (F(s.z) + F(s.w))) + (F(u.x) + F(u.y)));
#undef F
}
__device__ __forceinline__ float sum9(uint32_t a) {
    const uint4 p = lds128(a), q = lds128(a + 16);
#define F(x) __uint_as_float(x)
    return (((F(p.x) + F(p.y)) + (F(p.z) + F(p.w))) + ((F(q.x) + F(q.y)) + (F(q.z) + F(q.w)))) + ldsf(a + 32);
#undef F
}
template <int N>
__device__ __forceinline__ void ln_finish(uint32_t lp, int lane, float& mb, float& rc) {
    const float v = N == 9 ? sum9(lp + lane * 80) : sum18(lp + lane * 80);
    const float o = __shfl_xor_sync(0xffffffffu, v, 16);
    const float m0 = v * (1.0f / 576.0f);
    const float mean = fmaf(fmaf(-m0, 576.0f, v), 1.0f / 576.0f, m0);
    const float var = fmaxf(fmaf(o, 1.0f / 576.0f, -(mean * mean)), 0.f);
    mb = rbf(mean);
    rc = rcp_approx(rbf(sqrt_approx(rbf(rbf(var) + 1e-5f))));
}
__device__ __forceinline__ uint32_t ln_apply(uint32_t w, const uint2& st) {
    uint32_t r;
    asm("{\n.reg .b16 m, t, h, l;\n.reg .b32 mm, hh, ll, d, e;\nmov.b32 {m, t}, %2;\nmov.b32 {h, l}, %3;\nmov.b32 mm, {m, m};\nmov.b32 hh, {h, h};\nmov.b32 ll, {l, l};\n"
        "sub.rn.bf16x2 d, %1, mm;\nmul.rn.bf16x2 e, d, ll;\nfma.rn.bf16x2 %0, d, hh, e;\n}\n" : "=r"(r) : "r"(w), "r"(st.x), "r"(st.y));
    return r;
}
__device__ __forceinline__ void stat_store(uint32_t a, float mb, float rc, uint32_t extra) {
    const float rh = rbf(rc);
    sts64(a, (__float_as_uint(mb) >> 16) | (extra << 16), pack_bf16(rh, rc - rh));
}

__device__ __forceinline__ void hcmul(uint32_t re, uint32_t im, uint32_t z, uint32_t& ore, uint32_t& oim) {
    asm("{\n.reg .b16 x, y;\n.reg .b32 xx, yy, ny, a, b;\nmov.b32 {x, y}, %4;\nmov.b32 xx, {x, x};\nmov.b32 yy, {y, y};\nneg.f16x2 ny, yy;\n"
        "mul.rn.f16x2 a, %2, xx;\nfma.rn.f16x2 %0, %3, ny, a;\nmul.rn.f16x2 b, %3, xx;\nfma.rn.f16x2 %1, %2, yy, b;\n}\n" : "=&r"(ore), "=r"(oim) : "r"(re), "r"(im), "r"(z));
}
__device__ __forceinline__ void hcmul(uint32_t re, uint32_t im, uint32_t zx, uint32_t zy, uint32_t& ore, uint32_t& oim) {
    asm("{\n.reg .b32 ny, a, b;\nneg.f16x2 ny, %5;\n"
        "mul.rn.f16x2 a, %2, %4;\nfma.rn.f16x2 %0, %3, ny, a;\nmul.rn.f16x2 b, %3, %4;\nfma.rn.f16x2 %1, %2, %5, b;\n}\n" : "=&r"(ore), "=r"(oim) : "r"(re), "r"(im), "r"(zx), "r"(zy));
}

struct KGen {
    uint32_t Af[4][4];
    float2 z1, z8, z64, z128, T[9];
    uint32_t zw;
};
__device__ __forceinline__ void kgen_setup(KGen& k, uint32_t pa, float dt) {
    const float A = rbf(expf(bf_lo(pa)));
    const float lr2 = -(A * dt) * 1.4426950408889634f;
    const float li = bf_hi(pa) * dt;
    const float rh = li * 0.15915494309189535f;
    const float rl = fmaf(li, 6.4206382986e-9f, fmaf(li, 0.15915494309189535f, -rh));
    k.z1 = cexp_e(lr2, rh, rl, 1.0f);
    k.z8 = cexp_e(lr2, rh, rl, 8.0f);
    k.z64 = cexp_e(lr2, rh, rl, 64.0f);
}
__device__ __forceinline__ void kgen_rows(KGen& k, uint32_t tb, int lane) {
    const float2 z8 = k.z8, z64 = k.z64;
    const uint32_t row = tb + lane * TBP;
    k.z128 = csq(z64);
    const float2 z16 = csq(z8), z32 = csq(z16), z48 = cmul(z32, z16), z80 = cmul(z64, z16), z96 = cmul(z64, z32), z112 = cmul(z64, z48);
    uint32_t re[4], im[4], a[4], b[4];
    re[0] = pack_f16(1.0f, z16.x); im[0] = pack_f16(0.0f, z16.y);
    re[1] = pack_f16(z32.x, z48.x); im[1] = pack_f16(z32.y, z48.y);
    re[2] = pack_f16(z64.x, z80.x); im[2] = pack_f16(z64.y, z80.y);
    re[3] = pack_f16(z96.x, z112.x); im[3] = pack_f16(z96.y, z112.y);
    sts128(row, re[0], re[1], re[2], re[3]);
    sts128(row + 32, im[0], im[1], im[2], im[3]);
    const uint32_t zz = pack_f16(z8.x, z8.y);
#pragma unroll
    for (int j = 0; j < 4; j++) hcmul(re[j], im[j], zz, a[j], b[j]);
    sts128(row + 16, a[0], a[1], a[2], a[3]);
    sts128(row + 48, b[0], b[1], b[2], b[3]);
    __syncwarp();
    const int mi = lane >> 3;
    const uint32_t ad = tb + (lane & 7) * TBP + mi * 16;
#pragma unroll
    for (int ks = 0; ks < 4; ks++) ldsm_x4_t(k.Af[ks][0], k.Af[ks][1], k.Af[ks][2], k.Af[ks][3], ad + ks * 8 * TBP);
}
__device__ __forceinline__ void kgen_chain(KGen& k, uint32_t pc, float cs) {
    k.T[0] = make_float2(bf_lo(pc) * cs, -bf_hi(pc) * cs);
    const float2 y1 = make_float2(k.z1.x, -k.z1.y);
#pragma unroll
    for (int c = 1; c < 8; c++) k.T[c] = cmul(k.T[c - 1], y1);
    k.T[8] = cmul(k.T[0], make_float2(k.z8.x, -k.z8.y));
}
__device__ __forceinline__ void kgen_cols(KGen& k, uint32_t tb, int lane) {
    const uint32_t row = tb + lane * TBP;
    const float2 (&T)[9] = k.T;
    const uint32_t zv = pack_f16(k.z128.x, k.z128.y), zo = __shfl_xor_sync(0xffffffffu, zv, 1);
    k.zw = (lane & 1) ? __byte_perm(zo, zv, 0x7632) : __byte_perm(zv, zo, 0x5410);
    const float2 y256 = csq(make_float2(k.z128.x, -k.z128.y)), y512 = csq(y256), y768 = cmul(y512, y256), y1024 = csq(y512);
    const float2 c1032 = cmul(T[8], y1024);
    const uint32_t r04 = pack_f16(T[0].x, T[4].x), i04 = pack_f16(T[0].y, T[4].y), r26 = pack_f16(T[2].x, T[6].x), i26 = pack_f16(T[2].y, T[6].y);
    const uint32_t r48 = pack_f16(T[4].x, T[8].x), i48 = pack_f16(T[4].y, T[8].y);
    __syncwarp();
    sts128(row, r04, pack_f16(T[1].x, T[5].x), r26, pack_f16(T[3].x, T[7].x));
    sts128(row + 16, i04, pack_f16(T[1].y, T[5].y), i26, pack_f16(T[3].y, T[7].y));
    uint32_t a[4], b[4];
    {
        const uint32_t zz = pack_f16(y256.x, y256.y);
        hcmul(r04, i04, zz, a[0], b[0]);
        hcmul(r26, i26, zz, a[2], b[2]);
        hcmul(r48, i48, zz, a[3], b[3]);
    }
    sts128(row + 32, a[0], a[0], a[2], a[3]);
    sts128(row + 48, b[0], b[0], b[2], b[3]);
    {
        hcmul(r48, i48, pack_f16(y512.x, y512.y), a[0], b[0]);
        hcmul(r48, i48, pack_f16(y768.x, y768.y), a[1], b[1]);
        const uint32_t zz = pack_f16(c1032.x, c1032.y);
        hcmul(pack_f16(1.0f, y256.x), pack_f16(0.0f, y256.y), zz, a[2], b[2]);
        hcmul(pack_f16(y512.x, y768.x), pack_f16(y512.y, y768.y), zz, a[3], b[3]);
    }
    sts128(row + 64, a[0], a[1], a[2], a[3]);
    sts128(row + 80, b[0], b[1], b[2], b[3]);
}
__device__ __forceinline__ void kgen_mma(const KGen& k, uint32_t tb, int lane) {
    const int t = lane & 3;
    const uint32_t zw = k.zw;
    uint32_t zx[4], zy[4];
#pragma unroll
    for (int ks = 0; ks < 4; ks++) { zx[ks] = __shfl_sync(0xffffffffu, zw, 8 * ks + 2 * t); zy[ks] = __shfl_sync(0xffffffffu, zw, 8 * ks + 2 * t + 1); }
    __syncwarp();
    float acc[2][3][4];
#pragma unroll
    for (int i = 0; i < 6; i++)
#pragma unroll
        for (int j = 0; j < 4; j++) acc[i / 3][i % 3][j] = 0.f;
    {
        const int mi = lane >> 3;
        const uint32_t bd = tb + ((lane & 7) + 8 * (mi >> 1)) * TBP + (mi & 1) * 16;
#pragma unroll
        for (int kp = 0; kp < 2; kp++) {
            uint32_t b[3][4];
#pragma unroll
            for (int j = 0; j < 3; j++) ldsm_x4_t(b[j][0], b[j][1], b[j][2], b[j][3], bd + kp * 16 * TBP + j * 32);
#pragma unroll
            for (int h = 0; h < 2; h++) {
                const int ks = 2 * kp + h;
                uint32_t d[4];
                hcmul(k.Af[ks][0], k.Af[ks][2], zx[ks], zy[ks], d[0], d[2]);
                hcmul(k.Af[ks][1], k.Af[ks][3], zx[ks], zy[ks], d[1], d[3]);
#pragma unroll
                for (int j = 0; j < 3; j++) {
                    mma_f16(acc[0][j], k.Af[ks][0], k.Af[ks][1], k.Af[ks][2], k.Af[ks][3], b[j][2 * h], b[j][2 * h + 1]);
                    mma_f16(acc[1][j], d[0], d[1], d[2], d[3], b[j][2 * h], b[j][2 * h + 1]);
                }
            }
        }
    }
    __syncwarp();
#pragma unroll
    for (int h = 0; h < 2; h++) {
        sts64(tb + h * 256 + lane * 8, pack_f16(acc[h][0][0], acc[h][0][1]), pack_f16(acc[h][0][2], acc[h][0][3]));
        sts64(tb + 512 + h * 256 + lane * 8, pack_f16(acc[h][1][0], acc[h][1][1]), pack_f16(acc[h][1][2], acc[h][1][3]));
        sts32(tb + 1024 + h * 256 + lane * 4, pack_f16(acc[h][2][0], t < 2 ? acc[h][2][1] : acc[h][2][2]));
        sts32(tb + 1152 + h * 256 + lane * 4, pack_f16(t < 2 ? acc[h][2][2] : acc[h][2][1], acc[h][2][3]));
    }
}
__device__ __forceinline__ uint32_t table_buf(uint32_t sb, int warp) { return sb + SM_TB + warp * TBW; }

__device__ __forceinline__ void kgen_combine(uint32_t sb, int warp, int lane, uint32_t kw, uint32_t ao) {
    const int wq = warp & 3;
    const uint32_t a = table_buf(sb, warp & ~3) + wq * 256 + lane * 8, c = table_buf(sb, warp & ~3) + 1024 + wq * 128 + lane * 4;
    const int t = lane & 3;
    const uint32_t o0 = (t < 2 ? KW_T2 + KW_KH + 16 + t * 256 - (wq & 1) * KW_KH : KW_T3 + 16 - 1024 + t * 512 + (wq & 1) * 256) + (lane >> 2) * 16;
    const uint4 o = make_uint4(o0 + t * 36, o0 + (t ^ 1) * 36, o0 + (t ^ 2) * 36, o0 + (t ^ 3) * 36);
    const uint2 u = lds64(a), v = lds64(a + TBW), w = lds64(a + 2 * TBW), x = lds64(a + 3 * TBW);
    const uint32_t kt = hadd2(hadd2(lds32(c), lds32(c + TBW)), hadd2(lds32(c + 2 * TBW), lds32(c + 3 * TBW)));
    const uint32_t k23 = hadd2(hadd2(u.y, v.y), hadd2(w.y, x.y));
    sts64(kw + wq * 64 + ao, hadd2(hadd2(u.x, v.x), hadd2(w.x, x.x)), k23);
    const uint32_t d = kw + (wq >> 1) * 128;
    const uint32_t kh = hmul2(kt, 0x38003800u);
    sts32(d + o.x, kh); sts32(d + o.y, kh); sts32(d + o.z, kh); sts32(d + o.w, kh);
    if (wq == 3) {
        if (lane == 31) { sts32(kw + 264, k23 >> 16); sts32(kw + 288 + 264, k23 >> 16); sts32(kw + 576 + 264, k23 >> 16); }
        if (lane == 29) { sts32(kw + 864 + 280, kt >> 16); sts32(kw + 280, kt & 0xffff0000u); }
    }
}

__device__ __forceinline__ int c_exponent(const uint2& r, const uint2& i) {
    uint32_t mx = __vmaxu2(__vmaxu2(r.x & 0x7fff7fffu, r.y & 0x7fff7fffu), __vmaxu2(i.x & 0x7fff7fffu, i.y & 0x7fff7fffu));
    mx = __reduce_max_sync(0xffffffffu, max(mx & 0xffffu, mx >> 16));
    return min(max((int)(mx >> 7), 4), 240);
}

__device__ __forceinline__ int warp_v() { int l; asm volatile("mov.u32 %0, %%tid.x;" : "=r"(l)); return __shfl_sync(0xffffffffu, l >> 5, 0); }
__device__ __forceinline__ int lane_v() { int l; asm volatile("mov.u32 %0, %%laneid;" : "=r"(l)); return l; }
__device__ __forceinline__ unsigned clock32() { unsigned c; asm volatile("mov.u32 %0, %%clock;" : "=r"(c)); return c; }
__device__ __forceinline__ uint32_t prmt(uint32_t a, uint32_t b, uint32_t s) { uint32_t d; asm("prmt.b32 %0, %1, %2, %3;\n" : "=r"(d) : "r"(a), "r"(b), "r"(s)); return d; }
__device__ __forceinline__ uint32_t prmt_v(uint32_t a, uint32_t b, uint32_t s) { uint32_t d; asm volatile("prmt.b32 %0, %1, %2, %3;\n" : "=r"(d) : "r"(a), "r"(b), "r"(s)); return d; }
__device__ __forceinline__ void mmah16(uint32_t& d0, uint32_t& d1, uint32_t a0, uint32_t a1, uint32_t a2, uint32_t a3, uint32_t b0, uint32_t b1, uint32_t c0, uint32_t c1) {
    asm volatile("mma.sync.aligned.m16n8k16.row.col.f16.f16.f16.f16 {%0,%1}, {%2,%3,%4,%5}, {%6,%7}, {%8,%9};\n"
                 : "=r"(d0), "=r"(d1) : "r"(a0), "r"(a1), "r"(a2), "r"(a3), "r"(b0), "r"(b1), "r"(c0), "r"(c1));
}
__device__ __forceinline__ void mmah8(uint32_t& d0, uint32_t& d1, uint32_t a0, uint32_t a1, uint32_t b0, uint32_t c0, uint32_t c1) {
    asm volatile("mma.sync.aligned.m16n8k8.row.col.f16.f16.f16.f16 {%0,%1}, {%2,%3}, {%4}, {%5,%6};\n"
                 : "=r"(d0), "=r"(d1) : "r"(a0), "r"(a1), "r"(b0), "r"(c0), "r"(c1));
}
template <int A = 8, int B = 32>
__device__ __forceinline__ void conv_rename(uint32_t (&acc)[32]) {
#pragma unroll
    for (int i = A; i < B; i++) { uint32_t v; asm volatile("mov.b32 %0, %1;\n" : "=r"(v) : "r"(acc[i])); acc[i] = v; }
}
__host__ __device__ constexpr uint32_t band_bits(int hw, int sh) {
    uint32_t c = 0;
    for (int s = 0; s <= 10; s++)
        for (int e = 0; e < 2; e++) {
            const int v = s - 3 + sh - 4 * e;
            if (v <= hw && v >= -hw) c |= 1u << (14 + 16 * e - s);
        }
    return c;
}
template <int HW, int SH, int J> __device__ __forceinline__ uint32_t band(uint32_t p2) {
    uint32_t d;
    asm volatile("{\n.reg .b32 t;\nmul.lo.u32 t, %1, %2;\nand.b32 %0, t, 0x40004000;\n}\n" : "=r"(d) : "r"(p2), "n"(band_bits(HW, SH) | J));
    return d;
}
__device__ __forceinline__ void band_quads(uint4 (&b)[3], uint32_t p2, uint32_t pm) {
    b[0] = make_uint4(band<2, 4, 1>(pm), band<1, 4, 1>(p2), band<2, -4, 1>(pm), band<1, -4, 1>(p2));
    b[1] = make_uint4(band<4, 4, 1>(pm), band<3, 4, 1>(pm), band<4, -4, 1>(pm), band<3, -4, 1>(pm));
    b[2] = make_uint4(band<2, 4, 2>(pm), band<4, 4, 2>(pm), band<2, -4, 2>(pm), band<4, -4, 2>(pm));
}
__device__ __forceinline__ uint2 run_sums(const uint4& a, uint32_t b0, uint32_t b1) {
    uint2 d;
    mmah16(d.x, d.y, a.x, a.y, a.z, a.w, b0, b1, 0u, 0u);
    return d;
}
__device__ __forceinline__ float h_lo(uint32_t w) { return __half2float(__ushort_as_half((unsigned short)(w & 0xffffu))); }
__device__ __forceinline__ float h_hi(uint32_t w) { return __half2float(__ushort_as_half((unsigned short)(w >> 16))); }
__device__ __forceinline__ uint64_t smem_desc(uint32_t sb, uint32_t o16, uint32_t lbo) {
    uint64_t d;
    asm("mov.b64 %0, {%1, %2};" : "=l"(d) : "r"(((sb & 0x3FFFF) >> 4) + o16 + (lbo << 12)), "r"(8));
    return d;
}
template <int I> struct IC { static constexpr int value = I; };

#define STG3 1
struct Conv {
    uint32_t q2[3][2][4];
    uint32_t q3[2][4];
    uint32_t r[18];
};
struct ConvPre {
    uint32_t a[5], b[5];
    uint32_t t[4];
};
__device__ __forceinline__ void conv_pre(ConvPre& e, uint32_t ka, uint32_t ks, uint32_t sel) {
    const uint4 r = lds128(ka + 256), s = lds128(ka + 272);
    ldsm_x4(e.t[0], e.t[1], e.t[2], e.t[3], ks);
    const uint32_t sw = sel ^ 0x4444u;
    e.a[0] = prmt(r.y, r.z, sel); e.a[1] = prmt(r.w, r.z, sw); e.a[2] = prmt(r.x, r.y, sel); e.a[3] = prmt(r.z, r.y, sw); e.a[4] = prmt(r.z, r.w, sel);
    e.b[0] = prmt(s.y, s.z, sel); e.b[1] = prmt(s.w, s.z, sw); e.b[2] = prmt(s.x, s.y, sel); e.b[3] = prmt(s.z, s.y, sw); e.b[4] = prmt(s.z, s.w, sel);
}
__device__ __forceinline__ void conv_sums(Conv& c, uint32_t (&acc)[32], const ConvPre& e, uint32_t a0, uint32_t a1, const uint4 (&bd)[3], uint32_t ka, uint32_t sel, int wq, bool odd) {
#pragma unroll
    for (int i = 0; i < 32; i++) acc[i] = 0u;
    uint32_t un[4], vn[4];
    ldsm_x4(un[0], un[1], un[2], un[3], a1);
    ldsm_x4(vn[0], vn[1], vn[2], vn[3], a0);
#pragma unroll
    for (int q = 0; q < 3; q++) {
        const uint32_t u[4] = {un[0], un[1], un[2], un[3]}, v[4] = {vn[0], vn[1], vn[2], vn[3]};
        if (STG3 && q && sel == 0u) {
            sts128(ka, c.q3[q - 1][0], c.q3[q - 1][1], c.q3[q - 1][2], c.q3[q - 1][3]);
            sts64(ka, acc[8 * q], acc[8 * q + 8]);
        }
        if (q < 2) {
            ldsm_x4(un[0], un[1], un[2], un[3], a1 + q * 512 + 512);
            ldsm_x4(vn[0], vn[1], vn[2], vn[3], a0 + q * 512 + 512);
        } else if (STG3 == 2) {
            const uint32_t a = ka + wq * 64;
#pragma unroll
            for (int i = 0; i < 4; i++) { const uint4 v = lds128(a + i * 16); c.r[4 * i] = v.x; c.r[4 * i + 1] = v.y; c.r[4 * i + 2] = v.z; c.r[4 * i + 3] = v.w; }
            const uint2 v = lds64(a + 64);
            c.r[16] = v.x; c.r[17] = v.y;
            if (sel == 1u) sts32(ka, 0u);
        }
        mmah8(acc[8 * q + 8], acc[8 * q + 9], e.a[4], 0u, u[1], acc[8 * q + 8], acc[8 * q + 9]);
        mmah16(acc[8 * q + 8], acc[8 * q + 9], e.a[0], e.a[1], e.a[2], e.a[3], u[2], u[3], acc[8 * q + 8], acc[8 * q + 9]);
        const uint2 z0 = run_sums(bd[2], v[0], v[1]);
        if (q < 2) {
            mmah8(acc[8 * q + 16], acc[8 * q + 17], e.b[4], 0u, u[1], 0u, 0u);
            mmah16(acc[8 * q + 16], acc[8 * q + 17], e.b[0], e.b[1], e.b[2], e.b[3], u[2], u[3], acc[8 * q + 16], acc[8 * q + 17]);
            const uint2 y1 = run_sums(bd[1], u[0], u[1]), y2 = run_sums(bd[1], v[2], v[3]), y3 = run_sums(bd[1], u[2], u[3]);
            const uint32_t n0 = odd ? y1.x : z0.y, n1 = odd ? y2.x : y1.x, s1 = odd ? y2.y : y1.y, s2 = odd ? y3.y : y2.y;
            c.q3[q][0] = prmt(s1, n0, 0x7632u); c.q3[q][1] = prmt(s2, n1, 0x7632u);
            c.q3[q][2] = prmt(s1, n0, 0x5410u); c.q3[q][3] = prmt(s2, n1, 0x5410u);
        }
        const uint2 x1 = run_sums(bd[0], u[0], u[1]), x2 = run_sums(bd[0], v[2], v[3]), x3 = run_sums(bd[0], u[2], u[3]);
        const uint32_t f0 = odd ? x1.x : z0.x, f1 = odd ? x2.x : x1.x, f2 = odd ? x3.x : x2.x;
#pragma unroll
        for (int h = 0; h < 2; h++) {
            const uint32_t s = h ? 0x7632u : 0x5410u;
            c.q2[q][h][0] = prmt(x1.y, f0, s); c.q2[q][h][1] = prmt(x2.y, f1, s);
            c.q2[q][h][2] = prmt(f1, x2.y, s ^ 0x4444u); c.q2[q][h][3] = prmt(x3.y, f2, s);
            if (q < 2) mmah16(acc[8 * q + 16], acc[8 * q + 17], c.q2[q][h][0], c.q2[q][h][1], c.q2[q][h][2], c.q2[q][h][3], e.t[2 * h], e.t[2 * h + 1], acc[8 * q + 16], acc[8 * q + 17]);
        }
    }
    if (STG3 != 2) {
        const uint32_t a = ka + wq * 64;
#pragma unroll
        for (int i = 0; i < 4; i++) { const uint4 v = lds128(a + i * 16); c.r[4 * i] = v.x; c.r[4 * i + 1] = v.y; c.r[4 * i + 2] = v.z; c.r[4 * i + 3] = v.w; }
        const uint2 v = lds64(a + 64);
        c.r[16] = v.x; c.r[17] = v.y;
    }
    if (sel == 0u) {
#pragma unroll
        for (int i = 0; i < 6; i++) sts128(ka + i * 16, c.q2[i >> 1][i & 1][0], c.q2[i >> 1][i & 1][1], c.q2[i >> 1][i & 1][2], c.q2[i >> 1][i & 1][3]);
#pragma unroll
        for (int i = 0; i < 2; i++) sts128(ka + i * 16, c.q3[i][0], c.q3[i][1], c.q3[i][2], c.q3[i][3]);
#pragma unroll
        for (int i = 1; i < 4; i++) sts64(ka + i * 16, acc[8 * i], acc[8 * i + 1]);
    }
    conv_rename(acc);
}
#define SPACE 100
#define SPN 3
#define O4 4
#define B2L 1
#define GATE 2
#define HAND 2
#define GA 6
#define GB 4
template <int TA, int TB, int IA, class FG>
__device__ __forceinline__ void conv_tail(uint32_t (&acc)[32], const uint32_t (&a)[8][4], uint32_t sb, unsigned char* gy0, int warp, size_t ycopy, FG fg) {
    const int wg = warp >> 2, wq = warp & 3, ord = TA == 0 && TB == 16 ? 3 - wg + (3 - wg >= O4) : O4;
    const uint32_t ub = sb + SM_U + wg * USLOT_B + UPAD * 16, turn = sb + SM_MISC + 376 + ord * 8, sfs = sb + SM_MISC + 256 + wg * 8;
    const uint32_t du = wg * (USLOT_B / 16) + (SM_U / 16 + UPAD + TA * 8);
    uint32_t ud[8], fs;
    auto skip = [&]() {
        const int lane = lane_v();
        const uint32_t ua = ub + ((lane >> 3) & 1) * ULO_B + (8 * wq + (lane & 7)) * 16 + (lane >> 4) * 512;
        if (IA == 0) ldsm_x4_t(ud[0], ud[1], ud[2], ud[3], ua);
        if (TB == 16) ldsm_x4_t(ud[4], ud[5], ud[6], ud[7], ua + 1024);
        const uint2 fd = lds64(sfs);
        fs = fd.x;
        const float dsk = __uint_as_float(fd.y);
#pragma unroll
        for (int i = 2 * IA; i < TB / 2; i++) ud[i] = pack_bf16(h_lo(ud[i]) * dsk, h_hi(ud[i]) * dsk);
    };
    conv_rename<2 * TA, 2 * TB>(acc);
    if (__builtin_expect(ord != 0, 0)) {
        skip();
        mbar_wait(turn);
    } else if (B2L) {
        bar_sync(0, NWRK);
    }
    if (O4 < 4 || (TA == 0 && TB == 16)) asm volatile("{\n.reg .pred p;\nelect.sync _|p, 0xffffffff;\n@p mbarrier.arrive.shared::cta.b64 _, [%0];\n}\n" ::"r"(turn + 48) : "memory");
    fg(IC<8>());
    wg_fence();
#pragma unroll
    for (int m = 7; m >= 0; m--) {
        wg_h<TA, TB - TA>(acc, a[m], smem_desc(sb, du - m, ULO_B));
        if (m == GA || m == GB || m == HAND) wg_commit();
        if (m == GB) asm volatile("wgmma.wait_group.sync.aligned 1;\n" ::: "memory");
    }
    wg_commit();
    if (O4 < 4 || (TA == 0 && TB == 16)) {
        asm volatile("wgmma.wait_group.sync.aligned 1;\n" ::: "memory");
        asm volatile("{\n.reg .pred p;\nelect.sync _|p, 0xffffffff;\n@p mbarrier.arrive.shared::cta.b64 _, [%0];\n}\n" ::"r"(turn + 8) : "memory");
    }
    __syncwarp();
    fg(IC<3>());
    if (!ord) skip();
    fg(IC<4>());
    const int lane = lane_v();
    const uint32_t lp = sb + SM_PL + (ord >= 3 ? ord - 3 : ord) * PL_B + lane * 8;
    unsigned char* gy = gy0 + ((4 * wq + (lane & 3)) * DM + (TA == 0 && TB == 16 ? 4 * blockIdx.x + wg : 512 + (blockIdx.x >> 1))) * 64 + (lane >> 2) * 8;
    const uint32_t st = lp + (wq * 12 - ((wq * (wq - 1)) >> 1)) * 256;
    uint32_t ld[3];
#pragma unroll
    for (int s = 1; s < 4; s++) {
        const int w = (wq - s) & 3;
        ld[s - 1] = lp + (w * 12 - ((w * (w - 1)) >> 1) + s - 1 - (wq < s ? 3 : 0)) * 256;
    }
    const uint32_t one = 1u + (warp >> 8);
    if (one == 0u) stg64(gy, ld[0], ld[1]);
    if (ord >= 3) bar_sync(9 + ord, 256);
    wg_wait0();
    fg(IC<6>());
#pragma unroll
    for (int j = TA; j < TB; j++)
        if ((j & 3) && j + 3 >= 4 * IA && (j + 3 < TB || j + wq < TB)) sts64(st + (j - 1 - (j >> 2)) * 256, acc[2 * j], acc[2 * j + 1]);
    bar_sync(1 + wg, 128);
    fg(IC<7>());
    uint2 v[4][3];
#pragma unroll
    for (int i = IA; i < TB / 4; i++)
#pragma unroll
        for (int s = 0; s < 3; s++) {
            if (i == 0) { v[i][s] = make_uint2(0u, 0u); if (wq > s) v[i][s] = lds64(ld[s]); }
            else v[i][s] = lds64(ld[s] + i * 768);
        }
    fg(IC<5>());
#pragma unroll
    for (int i = IA; i < TB / 4; i++) {
        const uint32_t x0 = hadd2(v[i][0].x, acc[8 * i]), x1 = hadd2(v[i][1].x, v[i][2].x), y0 = hadd2(v[i][0].y, acc[8 * i + 1]), y1 = hadd2(v[i][1].y, v[i][2].y);
        const uint32_t lo = pack_bf16(h_lo(x0) + h_lo(x1), h_hi(x0) + h_hi(x1)), hi = pack_bf16(h_lo(y0) + h_lo(y1), h_hi(y0) + h_hi(y1));
        ud[2 * i] = max(hfma2_bf(lo, fs, ud[2 * i]), one); ud[2 * i + 1] = hfma2_bf(hi, fs, ud[2 * i + 1]);
    }
    if (SPACE && TA == 0 && TB == 16 && ord < SPN) {
#pragma unroll
        for (int i = 0; i < 4; i++) {
            stg64(gy + i * 16 * DM * 64, ud[2 * i], ud[2 * i + 1]);
            if (i < 3) { const unsigned c0 = clock32(); while (clock32() - c0 < SPACE) {} }
        }
    } else {
#pragma unroll
        for (int i = IA; i < TB / 4; i++) stg64(gy + i * 16 * DM * 64, ud[2 * i], ud[2 * i + 1]);
    }
    if (ord < 2) bar_arrive(12 + ord, 256);
}
template <int M0, int M1>
__device__ __forceinline__ void conv_frags(uint32_t (&a)[8][4], const uint32_t (&r)[18], uint32_t sel, uint32_t dep, int warp) {
    const uint32_t s = prmt_v(sel, dep, 0x3210u + (warp >> 8)), sw = s ^ 0x4444u;
#pragma unroll
    for (int m = M0; m < M1; m++) {
        a[m][0] = prmt_v(r[2 * m + 1], r[2 * m + 2], s); a[m][1] = prmt_v(r[2 * m + 2], r[2 * m + 3], s);
        a[m][2] = prmt_v(r[2 * m + 1], r[2 * m], sw); a[m][3] = prmt_v(r[2 * m + 2], r[2 * m + 1], sw);
    }
}
template <class FG>
__device__ __forceinline__ void conv_main(const Conv& c, uint32_t (&acc)[32], uint32_t sb, uint32_t sel, unsigned char* gy, int warp, size_t ycopy, FG fg) {
    const uint32_t kw = (warp >> 2) * (KW_B / 16) + SM_KW / 16;
    const uint64_t d2 = smem_desc(sb, kw + KW_T2 / 16, KW_KH), d2b = smem_desc(sb, kw + KW_T2 / 16 + 1, KW_KH), d3 = smem_desc(sb, kw + KW_T3 / 16, 16), d3b = smem_desc(sb, kw + KW_T3 / 16 + 32, 16);
    uint32_t a[8][4];
    {
        const int ord = warp < 16 ? 3 - (warp >> 2) + (3 - (warp >> 2) >= O4) : O4;
        if (__builtin_expect(ord >= GATE, 0)) {
            fg(IC<1>());
            mbar_wait(sb + SM_MISC + 376 + 48 + (ord - GATE) * 8);
        }
    }
    wg_fence();
    wg_h<12, 4>(acc, c.q3[0], d3b); wg_h<8, 4>(acc, c.q3[0], d3); wg_h<4, 4>(acc, c.q2[0][0], d2b);
    wg_h<12, 4>(acc, c.q3[1], d3); wg_h<8, 4>(acc, c.q2[1][0], d2b);
    wg_h<12, 4>(acc, c.q2[2][0], d2b); wg_h<4, 4>(acc, c.q2[0][1], d2); wg_h<8, 4>(acc, c.q2[1][1], d2);
    wg_h<12, 4>(acc, c.q2[2][1], d2);
    wg_commit(); __syncwarp();
    fg(IC<0>());
    wg_wait0();
    conv_frags<0, 8>(a, c.r, sel, acc[16], warp);
    fg(IC<2>());
    if (warp >= 16) {
        if (blockIdx.x & 1) conv_tail<4, 16, 2>(acc, a, sb, gy, warp, ycopy, fg);
        else conv_tail<0, 8, 0>(acc, a, sb, gy, warp, ycopy, fg);
    } else {
        conv_tail<0, 16, 0>(acc, a, sb, gy, warp, ycopy, fg);
    }
}
#define CONV_LT6 const int dd = (lane >> 3) + (lane & 4) - (lane & 3); \
        const uint4 lt6 = make_uint4(prmt_v((dd & 3) * 288, 0u, idn), prmt_v(0x3254u + (dd >> 2) * 0x2222u, 0u, idn), \
            prmt_v(UPAD * 16 + (lane & 7) * 16 + ((lane >> 3) & 1) * (16 - ULO_B) + ULO_B - 32 + (lane & 16), 0u, idn), prmt_v(UPAD * 16 + (lane & 7) * 16 + ((lane >> 3) & 1) * ULO_B - 16 + (lane & 16), 0u, idn));
#define CONV_PRE \
        CONV_LT6 \
        const uint32_t ka = kw + lt6.x, sel = lt6.y, ks = kw + lt7.x; \
        const uint32_t ca0 = sb + SM_U + wg * USLOT_B + (warp & 3) * 128 + lt6.z, ca1 = sb + SM_U + wg * USLOT_B + (warp & 3) * 128 + lt6.w; \
        uint4 bd[3]; \
        band_quads(bd, lt7.w, (lane & 4) ? lt7.w >> 4 : lt7.w << 4);
#define CONV_PRE2 ConvPre ce_; conv_pre(ce_, ka, ks, sel);
#define CONV_BODY \
        Conv c; \
        uint32_t acc[32]; \
        conv_sums(c, acc, ce_, ca0, ca1, bd, ka, sel, warp & 3, lane & 4);
#define WS a_b_0_1_2_34_x__y567____c____de_r_
#define WS_STR2(x) #x
#define WS_STR(x) WS_STR2(x)
__device__ constexpr char wunit(int pt, int k) {
    constexpr char t[] = WS_STR(WS);
    int i = 0;
    for (; pt > 0 && t[i]; i++) pt -= t[i] == '_';
    for (; k > 0 && t[i] && t[i] != '_'; i++) k--;
    return t[i] == '_' ? 0 : t[i];
}
__device__ constexpr bool wsched_ok() {
    int seen = 0;
    for (int p = 0; p < 21; p++)
        for (int k = 0; wunit(p, k); k++) {
            const char c = wunit(p, k);
            const int bit = 1 << (c == 'r' ? 13 : c >= 'x' ? c - 'x' + 14 : c >= 'a' ? c - 'a' + 8 : c - '0');
            if ((seen & bit) || k >= (p < 16 ? 4 : 2) || (p < 5 && c >= '4' && c <= '7') || (p < 6 && (c == 'c' || c == 'd')) || (p < 16 && c == 'e')) return false;
            seen |= bit;
        }
    return seen == 0xffff;
}
struct WMaps { CUtensorMap g, u, gr, ur, d, dr; };
static_assert(GATE <= 2 && O4 >= 2, "resets");
static_assert(wsched_ok(), "weight schedule");
template <int PT, int K>
__device__ __forceinline__ void weight_units(uint32_t sb, const WMaps& m, int w) {
    constexpr char U = wunit(PT, K);
    if constexpr (U != 0) {
        if (w == K && elect_one()) {
            if (PT == 8) DELAY(K * WSP + WS0);
            const int P = blockIdx.x >> 1, odd = blockIdx.x & 1;
            constexpr int bar = SM_MISC + (U == 'e' ? 352 : U >= 'a' && U <= 'r' ? 336 : 328);
            if constexpr (U == 'e') { if (!odd) tma_2d(sb + SM_WD + 4 * 8192, &m.d, 256, 64 * P, sb + bar); }
            else if constexpr (U == 'r') tma_3d(sb + SM_WD + 40960, &m.dr, 0, 4096 + 8 * P, 5 * odd, sb + bar);
            else if constexpr (U >= 'x') tma_3d(sb + SM_WR + (U - 'x') * 4608, U == 'x' ? &m.gr : &m.ur, 4096 + 8 * P, 0, 2 * odd, sb + bar);
            else if constexpr (U >= 'a') tma_2d(sb + SM_WD + (U - 'a') * 8192, &m.d, 320 * odd + 64 * (U - 'a'), 64 * P, sb + bar);
            else tma_2d(sb + (U < '4' ? SM_WG : SM_WU) + (U & 3) * 9216, U < '4' ? &m.g : &m.u, 64 * P, 288 * odd + (U & 3) * 72, sb + bar);
        }
        weight_units<PT, K + 1>(sb, m, w);
    }
}
#define WPOINT(i, w) do { weight_units<i, 0>(sb, wm, w); } while (0)

__global__ void __launch_bounds__(NTHR, 1) __cluster_dims__(2, 1, 1)
fused_kernel(const Params p, const __grid_constant__ WMaps wm, const __grid_constant__ CUtensorMap tm_x,
             const __grid_constant__ CUtensorMap tm_y, const __grid_constant__ CUtensorMap tm_z) {
    extern __shared__ __align__(1024) unsigned char smem[];
    const uint32_t sb = smem_u32(smem);
    const int tid = threadIdx.x, warp = __shfl_sync(0xffffffffu, tid >> 5, 0), lane = tid & 31;
    const int b = blockIdx.x, P = b >> 1, odd = b & 1;
    const int g = lane >> 2, t = lane & 3;
    const int wg = warp >> 2, t128 = tid & 127;
    const uint32_t s_stat = sb + SM_MISC;
    const uint32_t s_key = sb + SM_MISC + 128;
    const uint32_t s_wm = sb + SM_MISC + 256;
    const uint32_t s_k16 = sb + SM_MISC + 192;
    const uint32_t s_fs = sb + SM_MISC + 256;
    const uint32_t s_cnt = sb + SM_MISC + 320;
    const uint32_t bar_w = sb + SM_MISC + 328, bar_d = bar_w + 8, bar_g = bar_w + 16, bar_r = bar_w + 32, bar_h = bar_w + 40, bar_x = bar_w + 48;
    STAMP(0);

    const unsigned tk0 = clock32();
    const bool lnw = (unsigned)(warp - 10) < 9u;
    const unsigned pm = tid + (tid < 512 ? 512 * b : 65024 + 128 * P), pq = (pm & ~127u) + 4 * lane;
    uint32_t pl = ldg16(p.lar + pm), ldt = ldg16(p.ldt + (pm >> 7));
    const uint32_t pa2 = ldg16(p.aim + pm), pc = ldg16(p.cre + pm), pi = ldg16(p.cim + pm);
    const uint2 call_re = ldg64(p.cre + pq), call_im = ldg64(p.cim + pq);
    const uint32_t dskl = ldg16(p.dsk + (pm >> 7));
    const uint32_t ep = ld_poll32(p.s->hint + (b & 7) * 32 + 1 + (lane >> 5));
    if ((unsigned)(tid - 320) < 288u) {
        const bf16* xp = p.x + (unsigned)((32 * P + 2 * odd + TOKEN_OF(g)) * DM + ((tid - 320) & ~31) + 8 * t);
        const uint32_t xt = sb + SM_XT + ((tid - 320) & ~31) * 32 + lane * 16;
        asm volatile("cp.async.cg.shared.global [%0], [%1], 16;\ncp.async.cg.shared.global [%0 + 512], [%1 + 9216], 16;\n"
                     "cp.async.cg.shared.global [%0 + 9216], [%1 + 576], 16;\ncp.async.cg.shared.global [%0 + 9728], [%1 + 9792], 16;\n" ::"r"(xt), "l"(xp) : "memory");
    }
    uint32_t* const std_ = p.s->st + ((lane & 12) * 128 + odd * 256 + 4 * P + 2 * (lane & 1) + ((lane >> 1) & 1)) * 2;
    unsigned char* const ud = reinterpret_cast<unsigned char*>(p.s->uT) + (32 * (warp - UW) + 8 * (g >> 1) + (g & 1)) * 4096 + b * 32 + t * 8;
    if (warp == 0) {
        if (lane == 0) {
            mbar_init(bar_x, 1); mbar_init(bar_w, 1); mbar_init(bar_d, 1); mbar_init(bar_d + 16, 1); mbar_init(bar_g, 1); mbar_init(bar_h, 3); mbar_init(bar_r, 1);
            #pragma unroll
            for (int i = 1; i < 11; i++) mbar_init(bar_x + 8 * i, 4);
            asm volatile("fence.mbarrier_init.release.cluster;\n" ::: "memory");
            mbar_expect(bar_x, 16384); mbar_expect(bar_r, 8192);
            mbar_expect(bar_w, 2 * 41472); mbar_expect(bar_d, 32768 + 5120); mbar_expect(bar_d + 16, 8192); mbar_expect(bar_g, 9 * 512);
        }
        __syncwarp();
        bar_arrive(0, NWRK);
    }
    if (warp == 0 && elect_one()) tma_3d(sb + SM_XC, &tm_x, 8 * P, 0, 8 * odd, bar_x);
    asm volatile("barrier.cluster.arrive.relaxed.aligned;\n" ::: "memory");
    const uint32_t kw = sb + SM_KW + wg * KW_B;
    if (t128 < 2 * UPAD) sts128(sb + SM_U + wg * USLOT_B + (t128 & 1) * ULO_B + (t128 >> 1) * 16, 0u, 0u, 0u, 0u);
    sts128(kw + t128 * 16, 0u, 0u, 0u, 0u);
    if (t128 < KW_B / 16 - 128) sts128(kw + 2048 + t128 * 16, 0u, 0u, 0u, 0u);
    if (tid < 128) {
#pragma unroll
        for (int i = 0; i < 4; i++) sts128(sb + SM_ZERO + i * 2048 + tid * 16, 0u, 0u, 0u, 0u);
    }
    if (warp != 0) bar_sync(0, NWRK);
    STAMP(1);
    if (warp == 19 || warp == UW || warp == UW + 1) {
        if (warp == 19) {
            if (lane < 16) stg64(std_, 0u, 0u);
            if (lane < 9) asm volatile("prefetch.global.L2 [%0];\n" ::"l"(p.wr + lane * 64));
        } else {
#pragma unroll
            for (int k = 0; k < 4; k++) stg64(ud + k * 8192, 0u, 0u);
        }
    }
    uint32_t X[2][8];
    auto partial = [&]() {
        const uint32_t xt = sb + SM_XT + (warp - 10) * 1024 + lane * 16;
        asm volatile("cp.async.wait_all;\n" ::: "memory");
        STAMP(23);
        const uint4 a = lds128(xt), c = lds128(xt + 512), d = lds128(xt + 9216), e = lds128(xt + 9728);
        X[0][0] = a.x; X[0][1] = a.y; X[0][2] = a.z; X[0][3] = a.w; X[0][4] = d.x; X[0][5] = d.y; X[0][6] = d.z; X[0][7] = d.w;
        X[1][0] = c.x; X[1][1] = c.y; X[1][2] = c.z; X[1][3] = c.w; X[1][4] = e.x; X[1][5] = e.y; X[1][6] = e.z; X[1][7] = e.w;
        const uint32_t one[8] = {0x3f803f80u, 0x3f803f80u, 0x3f803f80u, 0x3f803f80u, 0x3f803f80u, 0x3f803f80u, 0x3f803f80u, 0x3f803f80u};
        ln_partial<8>(X, one, sb + SM_LNP, warp - 10, g, t);
        bar_arrive(6, 320);
        if (PAUSE & 1) bar_sync(7, PCNT);
    };
    if (LNAT == 0 && lnw) {
        partial();
        pl = prmt_v(pl, X[0][0], 0x3210u + (warp >> 8)); ldt = prmt_v(ldt, X[0][0], 0x3210u + (warp >> 8));
    }
    auto finish = [&]() {
        bar_sync(6, 320);
        float mb, rc;
        ln_finish<9>(sb + SM_LNP, lane, mb, rc);
        const float rh = rbf(rc);
        const uint32_t s0 = (__float_as_uint(mb) >> 16) | (((ep & 0x7fffu) + 1u) << 16), s1 = pack_bf16(rh, rc - rh);
        if (lane < 16) { stg64(std_, s0, s1); sts64(s_stat + lane * 8, s0, s1); }
        if (lane == 16) sts32(s_cnt + 4, ep);
        bar_arrive(7, PCNT);
        STAMP(28);
    };
    auto upub = [&]() {
        if (!(PAUSE & 6)) bar_sync(7, PCNT);
        const uint32_t utag = ((ep & 3u) + 1u) * 0x10001u;
        uint32_t U[2][4];
#pragma unroll
        for (int hf = 0; hf < 2; hf++) {
            const uint2 st = lds64(s_stat + (g + 8 * hf) * 8);
            const uint4 xv = lds128(sb + SM_XT + (16 + warp - UW) * 1024 + hf * 512 + lane * 16);
            const uint32_t xs[4] = {xv.x, xv.y, xv.z, xv.w};
#pragma unroll
            for (int k = 0; k < 4; k++) {
                const uint32_t u = ln_apply(xs[k], st);
                U[hf][k] = movm((pack_f16_rz(bf_lo(u), __uint_as_float(u)) & 0xfff8fff8u) | utag);
            }
        }
#pragma unroll
        for (int k = 0; k < 4; k++) stg64(ud + k * 8192, U[0][k], U[1][k]);
    };
    if (FINAT == 0 && warp == 19) finish();
    const uint32_t tb = table_buf(sb, warp);
    const float dt = rbf(expf(bf_lo(ldt)));
    KGen kg;
    kgen_setup(kg, pl | (pa2 << 16), dt);
    if (LNAT == 1 && lnw) {
        partial();
        kg.z8.x = __uint_as_float(prmt_v(__float_as_uint(kg.z8.x), X[0][0], 0x3210u + (warp >> 8)));
        kg.z1.x = __uint_as_float(prmt_v(__float_as_uint(kg.z1.x), X[0][0], 0x3210u + (warp >> 8)));
    }
    if (FINAT == 1 && warp == 19) finish();
    if (UAT == 0 && (warp == UW || warp == UW + 1)) upub();
    kgen_rows(kg, tb, lane);
    if (wg == 0) fence_async();
    if (LNAT == 2 && lnw) {
        partial();
        kg.z128.x = __uint_as_float(prmt_v(__float_as_uint(kg.z128.x), X[0][0], 0x3210u + (warp >> 8)));
        kg.z1.x = __uint_as_float(prmt_v(__float_as_uint(kg.z1.x), X[0][0], 0x3210u + (warp >> 8)));
    }
    if (FINAT == 2 && warp == 19) finish();
    if (UAT == 1 && (warp == UW || warp == UW + 1)) upub();
    STAMP(2);
    WPOINT(0, warp - 4);
    const int ce = c_exponent(call_re, call_im);
    if (t128 == 0) sts64(s_fs + wg * 8, (uint32_t)min(max(ce + (int)(__float_as_uint(dt) >> 23) - 116, 0), 254) * 0x800080u, dskl << 16);
    kgen_chain(kg, pc | (pi << 16), __uint_as_float(((uint32_t)(244 - ce) << 23) | (__float_as_uint(dt) & 0x7fffffu)));
    if ((PAUSE & 4) && warp < 10) bar_sync(7, PCNT);
    if (UAT == 4 && (warp == UW || warp == UW + 1)) upub();
    STAMP(3);
    WPOINT(1, warp - 6);
    kgen_cols(kg, tb, lane);
    if (LNAT == 3 && lnw) partial();
    if (FINAT == 3 && warp == 19) finish();
    if ((PAUSE & 2) && warp < 10) bar_sync(7, PCNT);
    if (UAT == 2 && (warp == UW || warp == UW + 1)) upub();
    STAMP(4);
    WPOINT(2, warp - 8);
    const uint4* usrc = wg < 4 ? reinterpret_cast<const uint4*>(p.s->st) + odd * 512 + (lane & 1) * 128 + 16 * (warp & 7) + (lane >> 1)
                               : reinterpret_cast<const uint4*>(p.s->uT) + P * 256 + 2 * t128;
    const int ustep = wg < 4 ? 256 : 1;
    uint4 uv0, uv1;
    kgen_mma(kg, tb, lane);
    if (UAT == 3 && (warp == UW || warp == UW + 1)) upub();
    STAMP(26);
    WPOINT(3, warp - 5);
    const uint32_t idn = 0x3210u + (warp >> 8);
    uint4 lt7 = make_uint4(prmt_v(KW_T2 + ((lane >> 3) & 1) * KW_KH + (33 + (lane & 7)) * 16 - (lane & 16), 0u, idn), t * 288 + g * 8 + 8, (lane & 1) * 4096 + (lane >> 1) * 16,
                                 prmt_v(8u << ((lane >> 3) + (lane & 4)) >> (lane & 3), 0u, idn));
    asm volatile("barrier.cluster.wait.acquire.aligned;\n" ::: "memory");
    const bool pe = (int)(clock32() - tk0) >= (wg < 4 ? TP0 : TP4);
    if (pe) { uv0 = ld_poll(usrc); uv1 = ld_poll(usrc + ustep); }
    bar_sync(1 + wg, 128);
    kgen_combine(sb, warp, lane, kw, lt7.y);
    if (warp < 3 || warp > 6) bar_arrive(14, NWRK);
    STAMP(5);
    WPOINT(4, warp - 7);
    if (!pe) {
        while ((int)(clock32() - tk0) < (wg < 4 ? TP0 : TP4)) {}
        uv0 = ld_poll(usrc); uv1 = ld_poll(usrc + ustep);
    }
    if (wg < 4) {
        mbar_wait(bar_x);
        const bool far = warp < 8;
        const uint32_t xa = sb + SM_XC + (warp & 7) * 256 + (odd ^ far) * 8 + lt7.z;
        uint2 xv[4] = {lds64(xa), lds64(xa + 8192), lds64(xa + 2048), lds64(xa + 10240)};
        const uint32_t tag = ((ep & 0x7fffu) + 1u) << 16;
        int it = 0;
        while (true) {
            const bool bad = (((uv0.x ^ tag) | (uv0.z ^ tag)) | ((uv1.x ^ tag) | (uv1.z ^ tag))) >> 16;
            if (!__any_sync(0xffffffffu, bad)) break;
            if (++it > SPIN_LIMIT) TRAP();
            if (bad) { uv0 = ld_poll(usrc); uv1 = ld_poll(usrc + 256); }
        }
        STAMP(6);
        DBG(wg, it);
        const uint2 st[4] = {make_uint2(uv0.x, uv0.y), make_uint2(uv0.z, uv0.w), make_uint2(uv1.x, uv1.y), make_uint2(uv1.z, uv1.w)};
#pragma unroll
        for (int i = 0; i < 4; i++) {
            xv[i].x = ln_apply(xv[i].x, st[i]);
            xv[i].y = ln_apply(xv[i].y, st[i]);
        }
        const uint32_t ub = sb + SM_U + UPAD * 16 + odd * ULO_B + (warp & 7) * 256 + lane * 8;
        const uint32_t w[4][2] = {{pack_f16(bf_lo(xv[0].x), bf_lo(xv[1].x)), pack_f16(bf_lo(xv[2].x), bf_lo(xv[3].x))}, {HI2(xv[0].x, xv[1].x), HI2(xv[2].x, xv[3].x)},
                                  {pack_f16(bf_lo(xv[0].y), bf_lo(xv[1].y)), pack_f16(bf_lo(xv[2].y), bf_lo(xv[3].y))}, {HI2(xv[0].y, xv[1].y), HI2(xv[2].y, xv[3].y)}};
#pragma unroll
        for (int i = 0; i < 4; i++) {
            if (far) asm volatile("st.async.shared::cluster.mbarrier::complete_tx::bytes.v2.b32 [%0], {%1,%2}, [%3];\n" ::"r"((ub ^ 0x1000000u) + i * USLOT_B), "r"(w[i][0]), "r"(w[i][1]), "r"(bar_r ^ 0x1000000u) : "memory");
            else sts64(ub + i * USLOT_B, w[i][0], w[i][1]);
        }
    } else {
        const uint32_t utag = ((ep & 3u) + 1u) * 0x10001u;
        int it = 0;
        while (true) {
            const bool bad = (((uv0.x ^ utag) | (uv0.y ^ utag) | (uv0.z ^ utag) | (uv0.w ^ utag)) | ((uv1.x ^ utag) | (uv1.y ^ utag) | (uv1.z ^ utag) | (uv1.w ^ utag))) & 0x70007u;
            if (!__any_sync(0xffffffffu, bad)) break;
            if (++it > SPIN_LIMIT) TRAP();
            if (bad) { uv0 = ld_poll(usrc); uv1 = ld_poll(usrc + 1); }
        }
        STAMP(6);
        DBG(4, it);
        const uint32_t ub = sb + SM_U + UPAD * 16 + 4 * USLOT_B + (t128 >> 1) * 32 + (t128 & 1) * 8;
        sts64(ub, prmt(uv0.x, uv0.z, 0x5410u) ^ utag, prmt(uv1.x, uv1.z, 0x5410u) ^ utag);
        sts64(ub + 16, prmt(uv0.x, uv0.z, 0x7632u) ^ utag, prmt(uv1.x, uv1.z, 0x7632u) ^ utag);
        sts64(ub + ULO_B, prmt(uv0.y, uv0.w, 0x5410u) ^ utag, prmt(uv1.y, uv1.w, 0x5410u) ^ utag);
        sts64(ub + ULO_B + 16, prmt(uv0.y, uv0.w, 0x7632u) ^ utag, prmt(uv1.y, uv1.w, 0x7632u) ^ utag);
    }
    lt7.w = prmt_v(lt7.w, uv0.x, idn);
    CONV_PRE
    if (warp < 3 && elect_one()) tma_st_3d(warp < 2 ? &tm_y : &tm_z, sb + SM_ZERO, warp < 2 ? 128 * b : 32 * (512 + P), 0, 2 * (warp < 2 ? warp : odd));
    if (warp >= 3 && warp <= 6) {
        bar_sync(14, NWRK);
        WPOINT(5, warp - 3);
    }
    bar_sync(1 + wg, 128);
    CONV_PRE2
    mbar_wait(bar_r);
    fence_async();
    bar_sync(0, NWRK);
    STAMP(7);
    uint32_t hv0 = 0;
    {
        WPOINT(6, 19 - warp);
        CONV_BODY
        WPOINT(7, 19 - warp);
        if (!B2L) bar_sync(0, NWRK); else if (wg != 3) bar_arrive(0, NWRK);
        STAMP(8);
        size_t ycopy = 0;
        auto hook = [&](auto gi) {
                     constexpr int G = decltype(gi)::value;
                     if (G == 4 && warp == HINTW) hv0 = ld_poll32(p.s->hint + (lane_v() & 7) * 32);
                     if (G == 4) mbar_wait(bar_h);
                     if (G == 2) WPOINT(9, warp - 16);
                     if (G == 3) { WPOINT(10, warp - 12); WPOINT(12, warp - 8); WPOINT(14, warp - 4); }
                     if (G == 5) { WPOINT(11, warp - 13); WPOINT(13, warp - 9); WPOINT(15, warp - 5); }
                     if (G == 1 && warp >= 17 && elect_one())
                         bulk_s2g(warp == 17 ? p.s->part + b * (PBYTES / 4) : warp == 18 ? p.s->rows + b * 1152 : p.s->sc + b * 64, sb + SM_ZERO, warp == 17 ? PBYTES : warp == 18 ? 4608 : 160);
                     if (G == 4 && warp >= 17 && elect_one()) {
                         asm volatile("cp.async.bulk.wait_group 0;\n" ::: "memory");
                         hint_arrive(p.s->hint, 2, b & 7);
                     }
                     if (G == 1 && warp < 3) {
                         if (elect_one()) {
                             asm volatile("cp.async.bulk.wait_group 0;\n" ::: "memory");
                             mbar_arrive(bar_h);
                             hint_arrive(p.s->hint, 0, b & 7);
                         }
                         __syncwarp();
                         STAMP(17);
                     }
                     if (G == 1) WPOINT(8, warp - 16);
                 };
        conv_main(c, acc, sb, sel, reinterpret_cast<unsigned char*>(p.s->y), warp, ycopy, hook);
        STAMP(10);
    }
    {
    const int warp = warp_v(), lane = lane_v(), tid = 32 * warp + lane, g = lane >> 2, t = lane & 3;
    if (warp == HINTW) {
        const uint32_t target = (lds32(s_cnt + 4) + 1u) * 48u;
        if (__any_sync(0xffffffffu, (int)(hv0 - target) < 0)) hint_wait(p.s->hint, 0, target);
    }
    const unsigned char* ys = reinterpret_cast<const unsigned char*>(p.s->y) + ((size_t)P * DM + 32 * warp + 8 * (g >> 1) + (g & 1)) * 64 + odd * 32 + t * 8;
    STAMP(27);
    bar_sync(0, NWRK);
    STAMP(11);
    const uint32_t zr = warp >> 8;
    auto late_rows = [&](auto pub) {
        const uint32_t k = lds32(s_key + (lane & 7) * 4), ep = lds32(s_cnt + 4);
        const bool late = k & 256u, mine = late && ((k & 255u) >> 1) == (uint32_t)b;
        uint32_t todo = __ballot_sync(0xffffffffu, mine) & 0xffu;
        if (todo) {
#pragma unroll 1
            while (todo) {
                const int s = __ffs(todo) - 1, row = (__shfl_sync(0xffffffffu, k, s) >> 9) & 15;
                todo &= todo - 1;
                if ((row & 7) == g) pub(row & 8, 2 * NCTA + s);
            }
            __threadfence();
            bar_sync(0, NWRK);
            if (tid < NSEL && mine) *reinterpret_cast<volatile unsigned*>(p.s->flag + tid) = ep + 1u;
        }
        int it = 0;
        while (__any_sync(0xffffffffu, late && ld_poll32(p.s->flag + (lane & 7)) != ep + 1u)) { if (++it > SPIN_LIMIT) TRAP(); }
        __threadfence();
        const int gs = tid / 36;
        const uint4* src = reinterpret_cast<const uint4*>(p.s->rows) + __shfl_sync(0xffffffffu, late ? 2 * NCTA + (lane & 7) : (k & 255u), gs & 7) * 144 + 36 * odd + (tid - gs * 36);
        if (tid < 288) {
            uint4 v0;
            do { v0 = ld_poll(src); if (++it > SPIN_LIMIT) TRAP(); } while (!v0.x);
            sts128(sb + SM_XS + gs * XS_PITCH + (tid - gs * 36) * 16, v0.x, v0.y, v0.z, v0.w);
        }
        bar_sync(0, NWRK);
    };
    if (warp >= 18) {
        uint32_t* const kp = pin(p.s->sc + 64 * b + 32 * (19 - warp), zr);
        const uint32_t kid = pin(0xc0000000u | ((lane & 15) << 9) | 2 * b, zr), ka = pin(s_k16 + (warp & 1) * 288 + (lane & 15) * 4, zr), kb = pin(s_k16 + (warp & 1) * 288 + (lane & 16) * 2, zr);
        const uint4* ksrc = pin(reinterpret_cast<const uint4*>(p.s->sc) + 8 * (19 - warp) + 16 * lane, zr);
        const uint4* rsrc = pin(reinterpret_cast<const uint4*>(p.s->rows) + 36 * odd + t, zr);
        uint32_t bits, early = 0;
        if (warp == 18) {
            weight_units<20, 0>(sb, wm, 0); weight_units<20, 1>(sb, wm, 1);
            bar_sync(8, 640);
            float mb, rc;
            ln_finish<18>(sb + SM_LNP, lane, mb, rc);
            if (lane < 16) stat_store(s_stat + lane * 8, mb, rc, 0u);
            bar_arrive(13, 608);
            bar_sync(10, 640);
            early = lds32(s_wm + (lane & 15) * 4);
            bits = pack_bf16(0.f, sum18(sb + SM_LNP + (32 + (lane & 15)) * 80));
        } else {
            float sw = 0.f;
#pragma unroll
            for (int i = 0; i < 9; i++) { const uint32_t w = reinterpret_cast<const uint32_t*>(p.wr)[32 * i + lane]; sw += bf_lo(w) + bf_hi(w); }
#pragma unroll
            for (int i = 16; i; i >>= 1) sw += __shfl_xor_sync(0xffffffffu, sw, i);
            early = ld_poll32(p.s->hint + (lane & 7) * 32 + 2);
            if (zr) stsf(sb, sw);
            bar_sync(8, 640);
            const float v = sum18(sb + SM_LNP + lane * 80), hw = sum18(sb + SM_LNP + (48 + (lane & 15)) * 80);
            const float o = __shfl_xor_sync(0xffffffffu, v, 16), mean = (lane < 16 ? v : o) * (1.0f / 576.0f);
            const float var = fmaxf(fmaf(lane < 16 ? o : v, 1.0f / 576.0f, -(mean * mean)), 0.f);
            bits = __float_as_uint(fmaf(-rbf(mean), sw, hw) * rcp_approx(rbf(sqrt_approx(rbf(rbf(var) + 1e-5f)))));
        }
        {
            const uint32_t me = (((bits ^ ((uint32_t)((int)bits >> 31) & 0x7fffffffu)) >> 1) & 0x7fffe000u) ^ kid;
            sts32(ka, me);
            __syncwarp();
            const uint4 v = lds128(kb), w = lds128(kb + 16);
#define GT(x) ((me - (x)) >> 31)
            uint32_t rank = pin(GT(v.x) + GT(v.y) + GT(v.z), zr) + pin(GT(v.w) + GT(w.x) + GT(w.y), zr) + pin(GT(w.z) + GT(w.w), zr);
#undef GT
            rank += __shfl_xor_sync(0xffffffffu, rank, 16);
            const uint32_t sl = warp == 18 ? early : rank;
            if (lane < 16 && rank < 8) stg32(kp + rank, me + (sl < 2 ? sl : 256u));
            if (warp == 19) {
                sts32(s_wm + (lane & 15) * 4, rank);
                const uint32_t target = (lds32(s_cnt + 4) + 1u) * 48u;
                if (__any_sync(0xffffffffu, (int)(early - target) < 0)) hint_wait(p.s->hint, 2, target);
                bar_arrive(10, 640); bar_arrive(11, 608);
            }
        }
        bool slow;
        int it = 0;
        uint4 q[4];
        STAMP(13);
        DELAY(warp == 19 ? KDEL : KDEL2);
#pragma unroll
        for (int i = 0; i < 4; i++) q[i] = ld_poll(ksrc + 512 * i);
        while (true) {
            uint32_t a[4];
#pragma unroll
            for (int i = 0; i < 4; i++) a[i] = q[i].x & q[i].y & q[i].z & q[i].w;
            if (__all_sync(0xffffffffu, a[0] & a[1] & a[2] & a[3])) break;
#pragma unroll
            for (int i = 0; i < 4; i++)
                if (!a[i]) q[i] = ld_poll(ksrc + 512 * i);
            if (++it > SPIN_LIMIT) TRAP();
        }
        STAMP(16);
        if (warp == 19) {
            auto merge = [](const uint4& x, const uint4& y) {
                const uint32_t a = max(x.x, y.w), c = max(x.y, y.z), d = max(x.z, y.y), e = max(x.w, y.x);
                const uint32_t a2 = max(a, d), d2 = min(a, d), c2 = max(c, e), e2 = min(c, e);
                return make_uint4(max(a2, c2), min(a2, c2), max(d2, e2), min(d2, e2));
            };
            uint4 h = merge(merge(q[0], q[1]), merge(q[2], q[3]));
            uint4 v[9];
            uint32_t key = 0;
#pragma unroll
            for (int s = 0; s < 8; s++) {
                const uint32_t m = __reduce_max_sync(0xffffffffu, h.x);
                const bool w = h.x == m;
                h.x = w ? h.y : h.x; h.y = w ? h.z : h.y; h.z = w ? h.w : h.z; h.w = w ? 0u : h.w;
                if (g == s) key = m;
            }
            rsrc += (key & 255u) * 144;
#pragma unroll
            for (int j = 0; j < 9; j++) v[j] = ld_poll(rsrc + 4 * j);
            const uint32_t xsa = sb + SM_XS + g * XS_PITCH + t * 16;
            sts32(s_key + 32 + g * 4, key);
            sts32(xsa, 0u);
            bar_arrive(15, 64);
            bar_arrive(12, 608);
            STAMP(18);
#pragma unroll
            for (int j = 0; j < 9; j++) sts128(xsa + j * 64, v[j].x, v[j].y, v[j].z, v[j].w);
            slow = min(min(min(min(v[0].x, v[1].x), v[2].x), min(min(v[3].x, v[4].x), v[5].x)), min(min(v[6].x, v[7].x), v[8].x)) == 0u;
        } else {
            const uint32_t kt = sb + SM_KEYS;
#pragma unroll
            for (int i = 0; i < 4; i++) sts128(kt + i * 512 + lane * 16, q[i].x, q[i].y, q[i].z, q[i].w);
            bar_sync(15, 64);
            const uint32_t c = lds32(s_key + 32 + g * 4), e = lds32(kt + (c & 254u) * 8 + t * 4);
            const bool hit = ((e ^ c) & 0x1fffu) == 0u && !(c & 256u);
            if (hit) sts32(s_key + g * 4, e);
            const uint32_t lo = __reduce_min_sync(0xffffffffu, hit ? e : 0xffffffffu) | 0x1fffu;
#define GT(x) ((lo - (x)) >> 31)
            uint32_t n = hit ? 256u - GT(e) : 0u;
#pragma unroll
            for (int i = 0; i < 4; i++) n += pin(GT(q[i].x) + GT(q[i].y) + GT(q[i].z) + GT(q[i].w), zr) << 12;
#undef GT
            n = __reduce_add_sync(0xffffffffu, n);
            slow = (n >> 12) + (n & 4095u) != 2048u || (n & 4095u) <= 2040u;
            if (slow) {
                uint4 r[4];
                it = 0;
                while (true) {
#pragma unroll
                    for (int i = 0; i < 4; i++) r[i] = ld_poll(ksrc + 512 * i + 1);
                    if (__all_sync(0xffffffffu, all_nz(r[0]) && all_nz(r[1]) && all_nz(r[2]) && all_nz(r[3]))) break;
                    if (++it > SPIN_LIMIT) TRAP();
                }
                uint32_t m = 0u;
#pragma unroll 1
                for (int s = 0; s < 8; s++) {
                    uint32_t x = 0;
#pragma unroll
                    for (int i = 0; i < 4; i++) {
                        x = max(max(max(x, q[i].x - m), max(q[i].y - m, q[i].z - m)), q[i].w - m);
                        x = max(max(max(x, r[i].x - m), max(r[i].y - m, r[i].z - m)), r[i].w - m);
                    }
                    m += __reduce_max_sync(0xffffffffu, x);
                    if (lane == 0) sts32(s_key + s * 4, m);
                }
            }
            DBG(7, slow);
        }
        if (bar_or(0, NWRK, slow)) late_rows([](bool, int) {});
        STAMP(19);
        const int fl = 16 * (b & 1) + ((tid >> 2) & 15), fc = 16 * (b >> 1) + (fl >> 2) + 8 * ((tid >> 1) & 1), fsl = 2 * (fl & 3) + (tid & 1);
        const uint32_t kk = lds32(s_key + fsl * 4);
        const uint32_t* fsrc = p.s->rows + ((kk & 256u) ? 2 * NCTA + fsl : (kk & 255u)) * DM + (fc >> 1);
        uint32_t hw = 1u, uw = 1u;
        if (b < 72) { uw = ld_poll32(fsrc); hw = ld_poll32(fsrc + 288); }
        if (b < 72) {
            it = 0;
            while (!hw || !uw) { uw = ld_poll32(fsrc); hw = ld_poll32(fsrc + 288); if (++it > SPIN_LIMIT) TRAP(); }
            const int row = (kk >> 9) & 15, ftok = 8 * (kk & 252u) + (kk & 2u) + TOKEN_OF(row & 7) + (row & 8);
            const unsigned k16 = (kk >> 15) & 0xffffu;
            const unsigned bits = (k16 & 0x8000u) ? (k16 & 0x7fffu) : (~k16 & 0xffffu);
            const float rs = 512.0f * rbf(__fdividef(1.0f, 1.0f + __expf(-__uint_as_float(bits << 16))));
            bf16* const op = p.out + (unsigned)(ftok * DM + fc);
            const float uv = (fc & 1) ? bf_hi(uw) : bf_lo(uw), hv = (fc & 1) ? bf_hi(hw) : bf_lo(hw);
            const uint32_t a = sb + SM_FIN + (tid - 576) * 80;
            sts128(a + 64, __float_as_uint(rs), __float_as_uint(uv), __float_as_uint(hv), (uint32_t)(size_t)op ^ (uint32_t)((size_t)op >> 32));
            bar_sync(14, 576);
            const uint4 p0 = lds128(a), p1 = lds128(a + 16), p2 = lds128(a + 32), p3 = lds128(a + 48);
#define F4(p) ((__uint_as_float(p.x) + __uint_as_float(p.y)) + (__uint_as_float(p.z) + __uint_as_float(p.w)))
            const float v0 = F4(p0), v1 = F4(p1), v2 = F4(p2), v3 = F4(p3);
#undef F4
            const float y3 = rbf(rbf((v0 + v1) + (v2 + v3)) * rs);
            asm volatile("st.global.u16 [%0], %1;\n" ::"l"(op), "h"((unsigned short)pack_bf16(hv + rbf(uv + y3), 0.f)) : "memory");
        }
        if (b == 0 && tid >= 632) *reinterpret_cast<volatile unsigned*>(p.s->hint + (tid & 7) * 32 + 1) = lds32(s_cnt + 4) + 1u;
    } else {
        uint32_t H[2][4], U2[2][4], WA[9][4], WD[18], WE[18];
        const int fkh = warp >= 9, fmt = warp - 9 * fkh;
        auto load_wa = [&](auto k0, auto k1) {
            if (k0.value >= k1.value) return;
            if (k0.value == 0) mbar_wait(bar_w);
            const int mi = lane >> 3, rr = lane & 7;
            const int row = fkh * 144 + rr + 8 * (mi >> 1);
            const uint32_t aad = sb + (fmt < 8 ? SM_WG + (mi & 1) * (SM_WU - SM_WG) + row * 128 + (fmt ^ rr) * 16 : SM_WR + (mi & 1) * 4608 + row * 16), ks = fmt < 8 ? 2048 : 256;
#pragma unroll
            for (int k = k0.value; k < k1.value; k++) ldsm_x4_t(WA[k][0], WA[k][1], WA[k][2], WA[k][3], aad + k * ks);
        };
        auto load_wd = [&](uint32_t (&WD)[18], int tile) {
            mbar_wait(bar_d);
            if (tile & 16) mbar_wait(bar_d + 16);
            const int mi = lane >> 3, rr = lane & 7;
            const uint32_t base = sb + SM_WD + rr * 128 + (((2 * tile + (mi & 1)) & 7) ^ rr) * 16;
#pragma unroll
            for (int k = 0; k < 4; k++) ldsm_x4_t(WD[4 * k], WD[4 * k + 1], WD[4 * k + 2], WD[4 * k + 3], base + (tile >> 2) * 8192 + (k * 16 + 8 * (mi >> 1)) * 128);
            ldsm_x2_t(WD[16], WD[17], base + 40960 + (tile >> 2) * 1024);
        };
        auto publish = [&](bool hi, int slot) {
            uint4* rowp = reinterpret_cast<uint4*>(p.s->rows) + slot * 144 + warp * 4 + t;
            stg128(rowp, nzw(hi ? U2[1][0] : U2[0][0]), nzw(hi ? U2[1][1] : U2[0][1]), nzw(hi ? U2[1][2] : U2[0][2]), nzw(hi ? U2[1][3] : U2[0][3]));
            stg128(rowp + 72, nzw(hi ? H[1][0] : H[0][0]), nzw(hi ? H[1][1] : H[0][1]), nzw(hi ? H[1][2] : H[0][2]), nzw(hi ? H[1][3] : H[0][3]));
        };
        uint4 wr = make_uint4(0x3f803f80u, 0x3f803f80u, 0x3f803f80u, 0x3f803f80u);
        {
            uint2 yv[4];
#pragma unroll
            for (int k = 0; k < 4; k++) yv[k] = ld_poll64(ys + k * 128);
            if (g == 0) wr = ldg128(p.wr + 32 * warp + 8 * t);
            const uint4 x0 = lds128(sb + SM_XT + warp * 1024 + lane * 16), x1 = lds128(sb + SM_XT + warp * 1024 + 512 + lane * 16);
            load_wa(IC<0>(), IC<WA0>());
            int it = 0;
            while (!__all_sync(0xffffffffu, yv[0].x && yv[1].x && yv[2].x && yv[3].x)) {
#pragma unroll
                for (int k = 0; k < 4; k++) yv[k] = ld_poll64(ys + k * 128);
                if (++it > SPIN_LIMIT) TRAP();
            }
            STAMP(12);
            const uint32_t Z[2][4] = {{x0.x, x0.y, x0.z, x0.w}, {x1.x, x1.y, x1.z, x1.w}};
#pragma unroll
            for (int k = 0; k < 4; k++) {
                H[0][k] = hadd2_bf(Z[0][k], movm(yv[k].x));
                H[1][k] = hadd2_bf(Z[1][k], movm(yv[k].y));
            }
            const uint32_t bw[4] = {wr.x, wr.y, wr.z, wr.w};
            ln_partial<4>(H, bw, sb + SM_LNP, warp, g, t);
        }
        bar_arrive(8, 640);
        WPOINT(16, warp - 12);
        load_wa(IC<WA0>(), IC<WA1>());
        STAMP(13);
        bar_sync(13, 608);
        STAMP(14);
#pragma unroll
        for (int hf = 0; hf < 2; hf++) {
            const uint2 st = lds64(s_stat + (g + 8 * hf) * 8);
#pragma unroll
            for (int k = 0; k < 4; k++) U2[hf][k] = ln_apply(H[hf][k], st);
        }
        {
            float cs[4] = {0.f, 0.f, 0.f, 0.f}, ct[4] = {0.f, 0.f, 0.f, 0.f};
            mma_bf16(cs, U2[0][0], U2[1][0], U2[0][1], U2[1][1], wr.x, wr.y);
            mma_bf16(ct, U2[0][2], U2[1][2], U2[0][3], U2[1][3], wr.z, wr.w);
            if (t == 0) { stsf(sb + SM_LNP + ((32 + g) * 20 + warp) * 4, cs[0] + ct[0]); stsf(sb + SM_LNP + ((40 + g) * 20 + warp) * 4, cs[2] + ct[2]); }
            bar_arrive(10, 640);
        }
        load_wa(IC<WA1>(), IC<WA2>());
        bar_sync(11, 608);
        {
            const uint32_t rk[2] = {lds32(s_wm + g * 4), lds32(s_wm + 32 + g * 4)};
            uint32_t lo = min(rk[0], rk[1]), hi = max(rk[0], rk[1]);
#pragma unroll 1
            while (lo < 2) { publish(lo == rk[1], 2 * b + lo); lo = hi; hi = 16; }
        }
        load_wa(IC<WA2>(), IC<WA3>());
        load_wa(IC<WA3>(), IC<9>());
#pragma unroll
        for (int hf = 0; hf < 2; hf++)
            sts128(sb + SM_OUT + (g + 8 * hf) * OUT_PITCH + warp * 64 + t * 16,
                   hadd2_bf(H[hf][0], U2[hf][0]), hadd2_bf(H[hf][1], U2[hf][1]), hadd2_bf(H[hf][2], U2[hf][2]), hadd2_bf(H[hf][3], U2[hf][3]));
        fence_async();
        WPOINT(17, warp - 16);
        if ((WDAT == 0 || (WDAT == 2 && fkh)) && (warp < 16 || !odd)) load_wd(WD, warp);
        const uint32_t bad = pin(sb + SM_XS + (lane & 7) * XS_PITCH + (fkh * 144 + 8 * (lane >> 3)) * 2, zr), ex = pin(sb + SM_EX + warp * 512 + lane * 16, zr);
        uint32_t* pp = pin(p.s->part + ((size_t)(2 * (20 * odd + warp) + (lane >> 4)) * 64 + P) * 32 + (lane & 15) * 2, zr);
        bar_sync(12, 608);
        const bool routed = __any_sync(0xffffffffu, (lds32(s_key + 32 + (lane & 7) * 4) & 0x1efeu) == (uint32_t)((warp << 9) | 2 * b));
        auto store_row = [&]() { if (warp < 16 && elect_one()) bulk_s2g(p.out + (size_t)(32 * P + 2 * odd + TOKEN_OF(warp & 7) + (warp & 8)) * DM, sb + SM_OUT + warp * OUT_PITCH, DM * 2); };
        if (!routed) store_row();
        WPOINT(18, warp - 16);
        STAMP(15);
        if (bar_or(0, NWRK, false)) {
            if (routed) store_row();
            asm volatile("cp.async.bulk.wait_group 0;\n" ::: "memory");
            late_rows(publish);
        }
        STAMP(19);
        float gp[4];
        {
            float c4[3][4];
#pragma unroll
            for (int i = 0; i < 3; i++)
#pragma unroll
                for (int j = 0; j < 4; j++) c4[i][j] = 0.f;
#pragma unroll
            for (int k = 0; k < 10; k += 2) {
                uint32_t b0, b1, b2, b3;
                ldsm_x4(b0, b1, b2, b3, bad + k * 32);
                mma_bf16(c4[k % 3], WA[k][0], WA[k][1], WA[k][2], WA[k][3], b0, b1);
                if (k < 8) mma_bf16(c4[(k + 1) % 3], WA[k + 1][0], WA[k + 1][1], WA[k + 1][2], WA[k + 1][3], b2, b3);
            }
#pragma unroll
            for (int j = 0; j < 4; j++) gp[j] = c4[0][j] + (c4[1][j] + c4[2][j]);
            if (warp >= 9) {
                sts128f(ex, gp);
                bar_arrive(6, 576);
            } else {
                bar_sync(6, 576);
                const uint4 o = lds128(ex + 4608);
                gp[0] += __uint_as_float(o.x); gp[1] += __uint_as_float(o.y); gp[2] += __uint_as_float(o.z); gp[3] += __uint_as_float(o.w);
                asm volatile("st.async.shared::cluster.mbarrier::complete_tx::bytes.v4.b32 [%0], {%1,%2,%3,%4}, [%5];\n"
                             ::"r"(ex ^ 0x1000000u), "r"(__float_as_uint(gp[0])), "r"(__float_as_uint(gp[1])), "r"(__float_as_uint(gp[2])), "r"(__float_as_uint(gp[3])), "r"(bar_g ^ 0x1000000u) : "memory");
                if (WDAT == 2) load_wd(WD, warp);
            }
            if (WDAT == 1 && (warp < 16 || !odd)) load_wd(WD, warp);
            if (warp >= 16 && !odd) load_wd(WE, warp + 2);
        }
        STAMP(20);
        if (warp < 9) {
            mbar_wait(bar_g);
            const uint4 u = lds128(ex);
            const uint32_t G = pack_bf16(gp[0] + __uint_as_float(u.x), gp[1] + __uint_as_float(u.y)), U = pack_bf16(gp[2] + __uint_as_float(u.z), gp[3] + __uint_as_float(u.w));
            const float G0 = bf_lo(G), G1 = bf_hi(G);
            sts32(sb + SM_GU + tid * 4, hmul2_bf(pack_bf16(G0 * rcp_approx(1.0f + ex2_approx(G0 * -1.4426950408889634f)), G1 * rcp_approx(1.0f + ex2_approx(G1 * -1.4426950408889634f))), U));
        }
        bar_sync(7, 576);
        STAMP(21);
        if (warp < 16 || !odd) {
            uint32_t gb[9];
            ldsm_x4_t(gb[0], gb[1], gb[2], gb[3], sb + SM_GU + lane * 16);
            ldsm_x4_t(gb[4], gb[5], gb[6], gb[7], sb + SM_GU + 512 + lane * 16);
            ldsm_x1_t(gb[8], sb + SM_GU + 1024 + (lane & 7) * 16);
            auto down = [&](const uint32_t (&W)[18], uint32_t* dst) {
                float c4[4] = {0.f, 0.f, 0.f, 0.f}, d4[4] = {0.f, 0.f, 0.f, 0.f}, e4[4] = {0.f, 0.f, 0.f, 0.f};
                mma_bf16(c4, W[0], W[1], W[2], W[3], gb[0], gb[1]);
                mma_bf16(d4, W[4], W[5], W[6], W[7], gb[2], gb[3]);
                mma_bf16(e4, W[8], W[9], W[10], W[11], gb[4], gb[5]);
                mma_bf16_k8(c4, W[16], W[17], gb[8]);
                mma_bf16(d4, W[12], W[13], W[14], W[15], gb[6], gb[7]);
                const float v0 = (c4[0] + e4[0]) + d4[0], v1 = (c4[1] + e4[1]) + d4[1], v2 = (c4[2] + e4[2]) + d4[2], v3 = (c4[3] + e4[3]) + d4[3];
                const uint32_t e = max(max(__float_as_uint(fmaxf(fabsf(v0), fabsf(v1))), __float_as_uint(fmaxf(fabsf(v2), fabsf(v3)))), 16u << 23) >> 23;
                const float sc = __uint_as_float((245u - e) << 23);
                stg64(dst, pack_f16(v0 * sc, v1 * sc) | ((e * 0x8002000u) & 0x60006000u), pack_f16(v2 * sc, v3 * sc) | ((e * 0x800200u) & 0x60006000u));
            };
            if (warp >= 16) { down(WE, pp + 4 * 64 * 32); down(WD, pp); }
            else down(WD, pp);
        }
        asm volatile("cp.async.bulk.wait_group.read 0;\n" ::: "memory");
        STAMP(22);
        if (b < 72 && warp < 16) {
            const uint2* src = reinterpret_cast<const uint2*>(p.s->part) + (unsigned)(b * 1024 + tid);
            uint2 a, c;
            int it = 0;
            DELAY(PDEL);
            a = ld_poll64(src); c = ld_poll64(src + 512);
            while (!__all_sync(0xffffffffu, a.y && c.y)) {
                a = ld_poll64(src); c = ld_poll64(src + 512);
                if (++it > SPIN_LIMIT) TRAP();
            }
            STAMP(24);
            const float ea = __uint_as_float((((a.y & 0x60006000u) | ((a.x >> 4) & 0x06000600u)) * 0x4001u) & 0x7f800000u);
            const float ec = __uint_as_float((((c.y & 0x60006000u) | ((c.x >> 4) & 0x06000600u)) * 0x4001u) & 0x7f800000u);
            a.x &= 0x9fff9fffu; a.y &= 0x9fff9fffu; c.x &= 0x9fff9fffu; c.y &= 0x9fff9fffu;
            const float s0 = fmaf(h_lo(a.x), ea, h_lo(c.x) * ec), s1 = fmaf(h_hi(a.x), ea, h_hi(c.x) * ec), s2 = fmaf(h_lo(a.y), ea, h_lo(c.y) * ec), s3 = fmaf(h_hi(a.y), ea, h_hi(c.y) * ec);
            const bool up = lane & 16;
            const float r0 = __shfl_xor_sync(0xffffffffu, up ? s0 : s2, 16), r1 = __shfl_xor_sync(0xffffffffu, up ? s1 : s3, 16);
            const uint32_t fa = sb + SM_FIN + ((lane & 15) * 4 + (up ? 2 : 0)) * 80 + warp * 4;
            stsf(fa, (up ? s2 : s0) + r0); stsf(fa + 80, (up ? s3 : s1) + r1);
            bar_arrive(14, 576);
        }
    }
    STAMP(25);
    }
}

typedef CUresult (*PFN_tmEncode)(CUtensorMap*, CUtensorMapDataType, cuuint32_t, void*, const cuuint64_t*, const cuuint64_t*, const cuuint32_t*,
                                 const cuuint32_t*, CUtensorMapInterleave, CUtensorMapSwizzle, CUtensorMapL2promotion, CUtensorMapFloatOOBfill);

extern "C" void kernel_launch(void* const* d_in, const int* in_sizes, int n_in, void* d_out, int out_size) {
    Params p;
    p.x = (const bf16*)d_in[0];
    p.lar = (const bf16*)d_in[1];
    p.aim = (const bf16*)d_in[2];
    p.cre = (const bf16*)d_in[3];
    p.cim = (const bf16*)d_in[4];
    p.ldt = (const bf16*)d_in[5];
    p.dsk = (const bf16*)d_in[6];
    p.wr = (const bf16*)d_in[8];
    p.out = (bf16*)d_out;
    static PFN_tmEncode enc = nullptr;
    static void* scratch = nullptr;
    if (!enc) {
        cudaFuncSetAttribute(fused_kernel, cudaFuncAttributeMaxDynamicSharedMemorySize, SMEM_TOTAL);
        void* fn = nullptr;
        cudaDriverEntryPointQueryResult qr;
        cudaGetDriverEntryPoint("cuTensorMapEncodeTiled", &fn, cudaEnableDefault, &qr);
        enc = (PFN_tmEncode)fn;
        cudaGetSymbolAddress(&scratch, g_scratch);
    }
    p.s = (Scratch*)scratch;
    WMaps wm;
    CUtensorMap tm_x, tm_y, tm_z;
    const cuuint64_t dims[2] = {FF, DM}, strides[1] = {FF * 2}, rdims[3] = {FF, 144, 4}, rstrides[2] = {FF * 2, 144 * FF * 2};
    const cuuint32_t box[2] = {64, 72}, rbox[3] = {8, 144, 2}, es3[3] = {1, 1, 1};
    for (int i = 0; i < 2; i++) {
        enc(i ? &wm.u : &wm.g, CU_TENSOR_MAP_DATA_TYPE_BFLOAT16, 2, d_in[9 + i], dims, strides, box, es3, CU_TENSOR_MAP_INTERLEAVE_NONE, CU_TENSOR_MAP_SWIZZLE_128B,
            CU_TENSOR_MAP_L2_PROMOTION_NONE, CU_TENSOR_MAP_FLOAT_OOB_FILL_NONE);
        enc(i ? &wm.ur : &wm.gr, CU_TENSOR_MAP_DATA_TYPE_BFLOAT16, 3, d_in[9 + i], rdims, rstrides, rbox, es3, CU_TENSOR_MAP_INTERLEAVE_NONE, CU_TENSOR_MAP_SWIZZLE_NONE,
            CU_TENSOR_MAP_L2_PROMOTION_NONE, CU_TENSOR_MAP_FLOAT_OOB_FILL_NONE);
    }
    const cuuint64_t ddims[2] = {DM, FF}, dstrides[1] = {DM * 2}, edims[3] = {64, FF, 9}, estrides[2] = {DM * 2, 128};
    const cuuint32_t dbox[2] = {64, 64}, ebox[3] = {64, 8, 5};
    enc(&wm.d, CU_TENSOR_MAP_DATA_TYPE_BFLOAT16, 2, d_in[11], ddims, dstrides, dbox, es3, CU_TENSOR_MAP_INTERLEAVE_NONE, CU_TENSOR_MAP_SWIZZLE_128B,
        CU_TENSOR_MAP_L2_PROMOTION_NONE, CU_TENSOR_MAP_FLOAT_OOB_FILL_NONE);
    enc(&wm.dr, CU_TENSOR_MAP_DATA_TYPE_BFLOAT16, 3, d_in[11], edims, estrides, ebox, es3, CU_TENSOR_MAP_INTERLEAVE_NONE, CU_TENSOR_MAP_SWIZZLE_128B,
        CU_TENSOR_MAP_L2_PROMOTION_NONE, CU_TENSOR_MAP_FLOAT_OOB_FILL_NONE);
    const cuuint64_t xdims[3] = {DM, LSEQ / 16, 16}, xstrides[2] = {16 * DM * 2, DM * 2};
    const cuuint32_t xbox[3] = {8, LSEQ / 16, 8};
    enc(&tm_x, CU_TENSOR_MAP_DATA_TYPE_BFLOAT16, 3, d_in[0], xdims, xstrides, xbox, es3, CU_TENSOR_MAP_INTERLEAVE_NONE, CU_TENSOR_MAP_SWIZZLE_NONE,
        CU_TENSOR_MAP_L2_PROMOTION_NONE, CU_TENSOR_MAP_FLOAT_OOB_FILL_NONE);
    const cuuint64_t ydims[3] = {DM * 32, 16, 4}, ystrides[2] = {DM * 64, 16 * DM * 64};
    const cuuint32_t ybox[3] = {128, 16, 2}, zbox[3] = {32, 16, 2};
    enc(&tm_y, CU_TENSOR_MAP_DATA_TYPE_BFLOAT16, 3, p.s->y, ydims, ystrides, ybox, es3, CU_TENSOR_MAP_INTERLEAVE_NONE, CU_TENSOR_MAP_SWIZZLE_NONE,
        CU_TENSOR_MAP_L2_PROMOTION_NONE, CU_TENSOR_MAP_FLOAT_OOB_FILL_NONE);
    enc(&tm_z, CU_TENSOR_MAP_DATA_TYPE_BFLOAT16, 3, p.s->y, ydims, ystrides, zbox, es3, CU_TENSOR_MAP_INTERLEAVE_NONE, CU_TENSOR_MAP_SWIZZLE_NONE,
        CU_TENSOR_MAP_L2_PROMOTION_NONE, CU_TENSOR_MAP_FLOAT_OOB_FILL_NONE);
    fused_kernel<<<NCTA, NTHR, SMEM_TOTAL>>>(p, wm, tm_x, tm_y, tm_z);
}
```

```cpp
#include <cuda_runtime.h>
#include <cuda.h>
#include <cuda_fp16.h>
#include <cuda_bf16.h>
#include <stdint.h>

#define LSEQ 2048
#define DM 576
#define NST 128
#define FF 4608
#define NSEL 8
#define NCTA 128
#define NTHR 640
#define NWRK 640

typedef __nv_bfloat16 bf16;

#define SM_WD 0
#define SM_WG 46080
#define SM_WR 82944
#define SM_WU 92160
#define SM_ZERO 32768
#define SM_XC 16384
#define SM_TB 96000
#define SM_PL 129024
#define PL_B 10752
#define SM_XT (SM_TB + 20 * TBW)
#define SM_U (SM_XT + 18432)
#define UPAD 8
#define ULO_B ((UPAD + 128) * 16)
#define USLOT_B (2 * ULO_B)
#define SM_KW (SM_U + 5 * USLOT_B)
#define KW_B 3600
#define KW_T2 1152
#define KW_KH 656
#define KW_T3 2464
#define SM_MISC (SM_KW + 5 * KW_B)
#define SM_LNP (SM_MISC + 576)
#define SMEM_TOTAL (SM_LNP + 5120)
#define TBP 112
#define TBW (32 * TBP)
#define SM_OUT SM_PL
#define OUT_PITCH 1216
#define SM_XS (SM_PL + 19456)
#define XS_PITCH 592
#define SM_EX (SM_PL + 24320)
#define SM_KEYS (SM_KW + 5120)
#define SM_FIN SM_KW
#define SM_GU (SM_PL + 33536)

struct __align__(128) Scratch {
    unsigned hint[8 * 32];
    unsigned flag[32];
    uint32_t sc[NCTA * 64];
    uint32_t st[LSEQ * 2];
    uint32_t uT[64 * (LSEQ / 2)];
    uint32_t y[NCTA * DM * 8];
    uint32_t part[72 * 64 * 32];
    uint32_t rows[(2 * NCTA + NSEL) * DM];
};
__device__ Scratch g_scratch;
#define STAMP(i)
#define DBG(i, v)

__device__ __forceinline__ float rbf(float x) {
    uint32_t r;
    asm("cvt.rn.bf16x2.f32 %0, %1, %2;\n" : "=r"(r) : "f"(x), "f"(0.f));
    return __uint_as_float(r);
}
__device__ __forceinline__ uint32_t pack_bf16(float lo, float hi) {
    uint32_t r;
    asm("cvt.rn.bf16x2.f32 %0, %1, %2;\n" : "=r"(r) : "f"(hi), "f"(lo));
    return r;
}
__device__ __forceinline__ uint32_t pack_f16(float lo, float hi) {
    uint32_t r;
    asm("cvt.rn.f16x2.f32 %0, %1, %2;\n" : "=r"(r) : "f"(hi), "f"(lo));
    return r;
}
__device__ __forceinline__ uint32_t pack_f16_rz(float lo, float hi) {
    uint32_t r;
    asm("cvt.rz.f16x2.f32 %0, %1, %2;\n" : "=r"(r) : "f"(hi), "f"(lo));
    return r;
}
__device__ __forceinline__ float bf_lo(uint32_t w) { return __uint_as_float(w << 16); }
__device__ __forceinline__ float bf_hi(uint32_t w) { return __uint_as_float(w & 0xffff0000u); }
__device__ __forceinline__ uint32_t hadd2_bf(uint32_t a, uint32_t b) {
    __nv_bfloat162 r = __hadd2_rn(*reinterpret_cast<__nv_bfloat162*>(&a), *reinterpret_cast<__nv_bfloat162*>(&b));
    return *reinterpret_cast<uint32_t*>(&r);
}
__device__ __forceinline__ uint32_t hmul2_bf(uint32_t a, uint32_t b) {
    __nv_bfloat162 r = __hmul2_rn(*reinterpret_cast<__nv_bfloat162*>(&a), *reinterpret_cast<__nv_bfloat162*>(&b));
    return *reinterpret_cast<uint32_t*>(&r);
}
__device__ __forceinline__ uint32_t hfma2_bf(uint32_t a, uint32_t b, uint32_t c) { uint32_t r; asm("fma.rn.bf16x2 %0, %1, %2, %3;\n" : "=r"(r) : "r"(a), "r"(b), "r"(c)); return r; }
__device__ __forceinline__ uint32_t hmul2(uint32_t a, uint32_t b) { uint32_t r; asm("mul.rn.f16x2 %0, %1, %2;\n" : "=r"(r) : "r"(a), "r"(b)); return r; }
__device__ __forceinline__ uint32_t hadd2(uint32_t a, uint32_t b) { uint32_t r; asm("add.rn.f16x2 %0, %1, %2;\n" : "=r"(r) : "r"(a), "r"(b)); return r; }
__device__ __forceinline__ uint32_t nzw(uint32_t w) { return w ? w : 0x8000u; }
__device__ __forceinline__ uint32_t smem_u32(const void* p) { return (uint32_t)__cvta_generic_to_shared(p); }
__device__ __forceinline__ uint32_t lds32(uint32_t addr) {
    uint32_t v;
    asm volatile("ld.shared.u32 %0, [%1];\n" : "=r"(v) : "r"(addr) : "memory");
    return v;
}
__device__ __forceinline__ uint2 lds64(uint32_t addr) {
    uint2 v;
    asm volatile("ld.shared.v2.u32 {%0,%1}, [%2];\n" : "=r"(v.x), "=r"(v.y) : "r"(addr) : "memory");
    return v;
}
__device__ __forceinline__ uint4 lds128(uint32_t addr) {
    uint4 v;
    asm volatile("ld.shared.v4.u32 {%0,%1,%2,%3}, [%4];\n" : "=r"(v.x), "=r"(v.y), "=r"(v.z), "=r"(v.w) : "r"(addr) : "memory");
    return v;
}
__device__ __forceinline__ float ldsf(uint32_t addr) { return __uint_as_float(lds32(addr)); }
__device__ __forceinline__ void sts32(uint32_t addr, uint32_t v) { asm volatile("st.shared.u32 [%0], %1;\n" ::"r"(addr), "r"(v) : "memory"); }
__device__ __forceinline__ void stsf(uint32_t addr, float v) { sts32(addr, __float_as_uint(v)); }
__device__ __forceinline__ void sts64(uint32_t addr, uint32_t a, uint32_t b) { asm volatile("st.shared.v2.u32 [%0], {%1,%2};\n" ::"r"(addr), "r"(a), "r"(b) : "memory"); }
__device__ __forceinline__ void sts128(uint32_t addr, uint32_t a, uint32_t b, uint32_t c, uint32_t d) {
    asm volatile("st.shared.v4.u32 [%0], {%1,%2,%3,%4};\n" ::"r"(addr), "r"(a), "r"(b), "r"(c), "r"(d) : "memory");
}
__device__ __forceinline__ void sts128f(uint32_t addr, const float (&v)[4]) {
    sts128(addr, __float_as_uint(v[0]), __float_as_uint(v[1]), __float_as_uint(v[2]), __float_as_uint(v[3]));
}
__device__ __forceinline__ void ldsm_x4(uint32_t& r0, uint32_t& r1, uint32_t& r2, uint32_t& r3, uint32_t addr) {
    asm volatile("ldmatrix.sync.aligned.m8n8.x4.shared.b16 {%0,%1,%2,%3}, [%4];\n"
                 : "=r"(r0), "=r"(r1), "=r"(r2), "=r"(r3) : "r"(addr) : "memory");
}
__device__ __forceinline__ void ldsm_x4_t(uint32_t& r0, uint32_t& r1, uint32_t& r2, uint32_t& r3, uint32_t addr) {
    asm volatile("ldmatrix.sync.aligned.m8n8.x4.trans.shared.b16 {%0,%1,%2,%3}, [%4];\n"
                 : "=r"(r0), "=r"(r1), "=r"(r2), "=r"(r3) : "r"(addr) : "memory");
}
__device__ __forceinline__ void ldsm_x2_t(uint32_t& r0, uint32_t& r1, uint32_t addr) {
    asm volatile("ldmatrix.sync.aligned.m8n8.x2.trans.shared.b16 {%0,%1}, [%2];\n" : "=r"(r0), "=r"(r1) : "r"(addr) : "memory");
}
__device__ __forceinline__ void ldsm_x1_t(uint32_t& r0, uint32_t addr) {
    asm volatile("ldmatrix.sync.aligned.m8n8.x1.trans.shared.b16 {%0}, [%1];\n" : "=r"(r0) : "r"(addr) : "memory");
}
__device__ __forceinline__ uint32_t movm(uint32_t a) {
    uint32_t d;
    asm volatile("movmatrix.sync.aligned.m8n8.trans.b16 %0, %1;\n" : "=r"(d) : "r"(a));
    return d;
}
__device__ __forceinline__ void mma_f16(float (&c)[4], uint32_t a0, uint32_t a1, uint32_t a2, uint32_t a3, uint32_t b0, uint32_t b1) {
    asm volatile(
        "mma.sync.aligned.m16n8k16.row.col.f32.f16.f16.f32 {%0,%1,%2,%3}, {%4,%5,%6,%7}, {%8,%9}, {%0,%1,%2,%3};\n"
        : "+f"(c[0]), "+f"(c[1]), "+f"(c[2]), "+f"(c[3])
        : "r"(a0), "r"(a1), "r"(a2), "r"(a3), "r"(b0), "r"(b1));
}
__device__ __forceinline__ void mma_bf16(float (&c)[4], uint32_t a0, uint32_t a1, uint32_t a2, uint32_t a3, uint32_t b0, uint32_t b1) {
    asm volatile(
        "mma.sync.aligned.m16n8k16.row.col.f32.bf16.bf16.f32 {%0,%1,%2,%3}, {%4,%5,%6,%7}, {%8,%9}, {%0,%1,%2,%3};\n"
        : "+f"(c[0]), "+f"(c[1]), "+f"(c[2]), "+f"(c[3])
        : "r"(a0), "r"(a1), "r"(a2), "r"(a3), "r"(b0), "r"(b1));
}
__device__ __forceinline__ void mma_bf16_k8(float (&c)[4], uint32_t a0, uint32_t a1, uint32_t b0) {
    asm volatile("mma.sync.aligned.m16n8k8.row.col.f32.bf16.bf16.f32 {%0,%1,%2,%3}, {%4,%5}, {%6}, {%0,%1,%2,%3};\n"
        : "+f"(c[0]), "+f"(c[1]), "+f"(c[2]), "+f"(c[3]) : "r"(a0), "r"(a1), "r"(b0));
}
__device__ __forceinline__ void bar_sync(int id, int n) { asm volatile("bar.sync %0, %1;\n" ::"r"(id), "r"(n) : "memory"); }
__device__ __forceinline__ void bar_arrive(int id, int n) { asm volatile("bar.arrive %0, %1;\n" ::"r"(id), "r"(n) : "memory"); }
__device__ __forceinline__ bool bar_or(int id, int n, bool v) {
    uint32_t r;
    asm volatile("{\n.reg .pred p, q;\nsetp.ne.u32 p, %3, 0;\nbar.red.or.pred q, %1, %2, p;\nselp.u32 %0, 1, 0, q;\n}\n" : "=r"(r) : "r"(id), "r"(n), "r"((uint32_t)v) : "memory");
    return r;
}
__device__ __forceinline__ uint4 ld_poll(const void* p) {
    uint4 v;
    asm volatile("ld.relaxed.gpu.global.v4.u32 {%0,%1,%2,%3}, [%4];\n" : "=r"(v.x), "=r"(v.y), "=r"(v.z), "=r"(v.w) : "l"(p) : "memory");
    return v;
}
template <class T> __device__ __forceinline__ T* pin(T* p, uint32_t z) {
    uint32_t lo, hi;
    asm volatile("mov.b64 {%0, %1}, %2;\n" : "=r"(lo), "=r"(hi) : "l"(p));
    asm volatile("xor.b32 %0, %0, %1;\n" : "+r"(lo) : "r"(z));
    asm volatile("xor.b32 %0, %0, %1;\n" : "+r"(hi) : "r"(z));
    asm volatile("mov.b64 %0, {%1, %2};\n" : "=l"(p) : "r"(lo), "r"(hi));
    return p;
}
__device__ __forceinline__ uint32_t pin(uint32_t a, uint32_t z) { asm volatile("xor.b32 %0, %0, %1;\n" : "+r"(a) : "r"(z)); return a; }
__device__ __forceinline__ uint2 ld_poll64(const void* p) {
    uint2 v;
    asm volatile("ld.relaxed.gpu.global.v2.u32 {%0,%1}, [%2];\n" : "=r"(v.x), "=r"(v.y) : "l"(p) : "memory");
    return v;
}
__device__ __forceinline__ uint32_t ld_poll32(const void* p) {
    uint32_t v;
    asm volatile("ld.relaxed.gpu.global.u32 %0, [%1];\n" : "=r"(v) : "l"(p) : "memory");
    return v;
}
__device__ __forceinline__ uint4 ldg128(const void* p) {
    uint4 v;
    asm volatile("ld.global.nc.v4.u32 {%0,%1,%2,%3}, [%4];\n" : "=r"(v.x), "=r"(v.y), "=r"(v.z), "=r"(v.w) : "l"(p));
    return v;
}
__device__ __forceinline__ uint2 ldg64(const void* p) {
    uint2 v;
    asm volatile("ld.global.nc.v2.u32 {%0,%1}, [%2];\n" : "=r"(v.x), "=r"(v.y) : "l"(p));
    return v;
}
__device__ __forceinline__ uint32_t ldg16(const void* p) {
    uint32_t v;
    asm volatile("ld.global.nc.u16 %0, [%1];\n" : "=r"(v) : "l"(p));
    return v;
}
__device__ __forceinline__ void stg128(void* p, uint32_t a, uint32_t b, uint32_t c, uint32_t d) {
    asm volatile("st.global.v4.u32 [%0], {%1,%2,%3,%4};\n" ::"l"(p), "r"(a), "r"(b), "r"(c), "r"(d) : "memory");
}
__device__ __forceinline__ void stg64(void* p, uint32_t a, uint32_t b) { asm volatile("st.global.v2.u32 [%0], {%1,%2};\n" ::"l"(p), "r"(a), "r"(b) : "memory"); }
__device__ __forceinline__ void stg32(void* p, uint32_t a) { asm volatile("st.global.u32 [%0], %1;\n" ::"l"(p), "r"(a) : "memory"); }
__device__ __forceinline__ bool all_nz(const uint4& v) { return v.x && v.y && v.z && v.w; }
#define SPIN_LIMIT (1 << 21)
#define TRAP() __trap()
__device__ __forceinline__ void hint_arrive(unsigned* g_hint, int idx, int sub) {
    asm volatile("red.relaxed.gpu.global.add.u32 [%0], 1;\n" ::"l"(&g_hint[sub * 32 + idx]) : "memory");
}
__device__ __forceinline__ void hint_wait(const unsigned* g_hint, int idx, unsigned target) {
    unsigned l;
    asm volatile("mov.u32 %0, %%laneid;" : "=r"(l));
    const unsigned* c = &g_hint[(l & 7) * 32 + idx];
    int it = 0;
    while (__any_sync(0xffffffffu, (int)(ld_poll32(c) - target) < 0)) { if (++it > SPIN_LIMIT) TRAP(); }
}
__device__ __forceinline__ void mbar_init(uint32_t bar, uint32_t cnt) { asm volatile("mbarrier.init.shared::cta.b64 [%0], %1;\n" ::"r"(bar), "r"(cnt) : "memory"); }
__device__ __forceinline__ void mbar_expect(uint32_t bar, uint32_t bytes) {
    asm volatile("mbarrier.arrive.expect_tx.shared::cta.b64 _, [%0], %1;\n" ::"r"(bar), "r"(bytes) : "memory");
}
__device__ __forceinline__ void mbar_arrive(uint32_t bar) { asm volatile("mbarrier.arrive.shared::cta.b64 _, [%0];\n" ::"r"(bar) : "memory"); }
__device__ __forceinline__ void mbar_wait(uint32_t bar) {
    asm volatile(
        "{\n.reg .pred p;\n"
        "W_%=:\n"
        "mbarrier.try_wait.parity.shared::cta.b64 p, [%0], 0;\n"
        "@!p bra W_%=;\n}\n" ::"r"(bar) : "memory");
}
__device__ __forceinline__ void bulk_s2g(void* dst, uint32_t src, uint32_t bytes) {
    asm volatile("cp.async.bulk.global.shared::cta.bulk_group [%0], [%1], %2;\ncp.async.bulk.commit_group;\n" ::"l"(dst), "r"(src), "r"(bytes) : "memory");
}
__device__ __forceinline__ void tma_2d(uint32_t dst, const CUtensorMap* tm, int c0, int c1, uint32_t bar) {
    asm volatile("cp.async.bulk.tensor.2d.shared::cluster.global.mbarrier::complete_tx::bytes [%0], [%1, {%3, %4}], [%2];\n"
                 ::"r"(dst), "l"(tm), "r"(bar), "r"(c0), "r"(c1) : "memory");
}
__device__ __forceinline__ void tma_3d(uint32_t dst, const CUtensorMap* tm, int c0, int c1, int c2, uint32_t bar) {
    asm volatile("cp.async.bulk.tensor.3d.shared::cluster.global.mbarrier::complete_tx::bytes [%0], [%1, {%3, %4, %5}], [%2];\n"
                 ::"r"(dst), "l"(tm), "r"(bar), "r"(c0), "r"(c1), "r"(c2) : "memory");
}
__device__ __forceinline__ void tma_st_3d(const CUtensorMap* tm, uint32_t src, int c0, int c1, int c2) {
    asm volatile("cp.async.bulk.tensor.3d.global.shared::cta.bulk_group [%0, {%2, %3, %4}], [%1];\ncp.async.bulk.commit_group;\n"
                 ::"l"(tm), "r"(src), "r"(c0), "r"(c1), "r"(c2) : "memory");
}
__device__ __forceinline__ bool elect_one() {
    uint32_t r;
    asm volatile("{\n.reg .pred p;\nelect.sync _|p, 0xffffffff;\nselp.u32 %0, 1, 0, p;\n}\n" : "=r"(r));
    return r;
}
__device__ __forceinline__ void fence_async() { asm volatile("fence.proxy.async.shared::cta;\n" ::: "memory"); }

__device__ __forceinline__ float2 cmul(float2 a, float2 b) {
    return make_float2(fmaf(a.x, b.x, -a.y * b.y), fmaf(a.x, b.y, a.y * b.x));
}
__device__ __forceinline__ float2 csq(float2 a) {
    float p = a.x * a.y;
    return make_float2(fmaf(a.x, a.x, -a.y * a.y), p + p);
}
__device__ __forceinline__ float2 cexp_e(float lr2, float rh, float rl, float e) {
    float m;
    asm("ex2.approx.ftz.f32 %0, %1;\n" : "=f"(m) : "f"(lr2 * e));
    const float a = rh * e;
    const float r = fmaf(rl, e, a - rintf(a)) * 6.283185307179586f;
    return make_float2(m * __cosf(r), m * __sinf(r));
}
__device__ __forceinline__ float rcp_approx(float x) { float r; asm("rcp.approx.ftz.f32 %0, %1;\n" : "=f"(r) : "f"(x)); return r; }
__device__ __forceinline__ float ex2_approx(float x) { float r; asm("ex2.approx.ftz.f32 %0, %1;\n" : "=f"(r) : "f"(x)); return r; }
__device__ __forceinline__ float sqrt_approx(float x) { float r; asm("sqrt.approx.ftz.f32 %0, %1;\n" : "=f"(r) : "f"(x)); return r; }

__device__ __forceinline__ void wg_fence() { asm volatile("wgmma.fence.sync.aligned;\n" ::: "memory"); }
__device__ __forceinline__ void wg_commit() { asm volatile("wgmma.commit_group.sync.aligned;\n" ::: "memory"); }
__device__ __forceinline__ void wg_wait0() { asm volatile("wgmma.wait_group.sync.aligned 0;\n" ::: "memory"); }
template <int T0, int NT> __device__ __forceinline__ void wg_h(uint32_t (&acc)[32], const uint32_t (&a)[4], uint64_t desc);
template <> __device__ __forceinline__ void wg_h<0, 16>(uint32_t (&acc)[32], const uint32_t (&a)[4], uint64_t desc) {
    asm volatile("wgmma.mma_async.sync.aligned.m64n128k16.f16.f16.f16 {%0,%1,%2,%3,%4,%5,%6,%7,%8,%9,%10,%11,%12,%13,%14,%15,%16,%17,%18,%19,%20,%21,%22,%23,%24,%25,%26,%27,%28,%29,%30,%31}, {%32,%33,%34,%35}, %36, 1, 1, 1, 0;\n"
                 : "+r"(acc[0]), "+r"(acc[1]), "+r"(acc[2]), "+r"(acc[3]), "+r"(acc[4]), "+r"(acc[5]), "+r"(acc[6]), "+r"(acc[7]), "+r"(acc[8]), "+r"(acc[9]), "+r"(acc[10]), "+r"(acc[11]), "+r"(acc[12]), "+r"(acc[13]), "+r"(acc[14]), "+r"(acc[15]), "+r"(acc[16]), "+r"(acc[17]), "+r"(acc[18]), "+r"(acc[19]), "+r"(acc[20]), "+r"(acc[21]), "+r"(acc[22]), "+r"(acc[23]), "+r"(acc[24]), "+r"(acc[25]), "+r"(acc[26]), "+r"(acc[27]), "+r"(acc[28]), "+r"(acc[29]), "+r"(acc[30]), "+r"(acc[31])
                 : "r"(a[0]), "r"(a[1]), "r"(a[2]), "r"(a[3]), "l"(desc));
}
template <> __device__ __forceinline__ void wg_h<4, 4>(uint32_t (&acc)[32], const uint32_t (&a)[4], uint64_t desc) {
    asm volatile("wgmma.mma_async.sync.aligned.m64n32k16.f16.f16.f16 {%0,%1,%2,%3,%4,%5,%6,%7}, {%8,%9,%10,%11}, %12, 1, 1, 1, 0;\n"
                 : "+r"(acc[8]), "+r"(acc[9]), "+r"(acc[10]), "+r"(acc[11]), "+r"(acc[12]), "+r"(acc[13]), "+r"(acc[14]), "+r"(acc[15])
                 : "r"(a[0]), "r"(a[1]), "r"(a[2]), "r"(a[3]), "l"(desc));
}
template <> __device__ __forceinline__ void wg_h<8, 4>(uint32_t (&acc)[32], const uint32_t (&a)[4], uint64_t desc) {
    asm volatile("wgmma.mma_async.sync.aligned.m64n32k16.f16.f16.f16 {%0,%1,%2,%3,%4,%5,%6,%7}, {%8,%9,%10,%11}, %12, 1, 1, 1, 0;\n"
                 : "+r"(acc[16]), "+r"(acc[17]), "+r"(acc[18]), "+r"(acc[19]), "+r"(acc[20]), "+r"(acc[21]), "+r"(acc[22]), "+r"(acc[23])
                 : "r"(a[0]), "r"(a[1]), "r"(a[2]), "r"(a[3]), "l"(desc));
}
template <> __device__ __forceinline__ void wg_h<12, 4>(uint32_t (&acc)[32], const uint32_t (&a)[4], uint64_t desc) {
    asm volatile("wgmma.mma_async.sync.aligned.m64n32k16.f16.f16.f16 {%0,%1,%2,%3,%4,%5,%6,%7}, {%8,%9,%10,%11}, %12, 1, 1, 1, 0;\n"
                 : "+r"(acc[24]), "+r"(acc[25]), "+r"(acc[26]), "+r"(acc[27]), "+r"(acc[28]), "+r"(acc[29]), "+r"(acc[30]), "+r"(acc[31])
                 : "r"(a[0]), "r"(a[1]), "r"(a[2]), "r"(a[3]), "l"(desc));
}
template <> __device__ __forceinline__ void wg_h<0, 8>(uint32_t (&acc)[32], const uint32_t (&a)[4], uint64_t desc) {
    asm volatile("wgmma.mma_async.sync.aligned.m64n64k16.f16.f16.f16 {%0,%1,%2,%3,%4,%5,%6,%7,%8,%9,%10,%11,%12,%13,%14,%15}, {%16,%17,%18,%19}, %20, 1, 1, 1, 0;\n"
                 : "+r"(acc[0]), "+r"(acc[1]), "+r"(acc[2]), "+r"(acc[3]), "+r"(acc[4]), "+r"(acc[5]), "+r"(acc[6]), "+r"(acc[7]), "+r"(acc[8]), "+r"(acc[9]), "+r"(acc[10]), "+r"(acc[11]), "+r"(acc[12]), "+r"(acc[13]), "+r"(acc[14]), "+r"(acc[15])
                 : "r"(a[0]), "r"(a[1]), "r"(a[2]), "r"(a[3]), "l"(desc));
}
template <> __device__ __forceinline__ void wg_h<4, 12>(uint32_t (&acc)[32], const uint32_t (&a)[4], uint64_t desc) {
    asm volatile("wgmma.mma_async.sync.aligned.m64n96k16.f16.f16.f16 {%0,%1,%2,%3,%4,%5,%6,%7,%8,%9,%10,%11,%12,%13,%14,%15,%16,%17,%18,%19,%20,%21,%22,%23}, {%24,%25,%26,%27}, %28, 1, 1, 1, 0;\n"
                 : "+r"(acc[8]), "+r"(acc[9]), "+r"(acc[10]), "+r"(acc[11]), "+r"(acc[12]), "+r"(acc[13]), "+r"(acc[14]), "+r"(acc[15]), "+r"(acc[16]), "+r"(acc[17]), "+r"(acc[18]), "+r"(acc[19]), "+r"(acc[20]), "+r"(acc[21]), "+r"(acc[22]), "+r"(acc[23]), "+r"(acc[24]), "+r"(acc[25]), "+r"(acc[26]), "+r"(acc[27]), "+r"(acc[28]), "+r"(acc[29]), "+r"(acc[30]), "+r"(acc[31])
                 : "r"(a[0]), "r"(a[1]), "r"(a[2]), "r"(a[3]), "l"(desc));
}

#define PBYTES 4608
#define DELAY(n) do { if (n) { const unsigned c0_ = clock32(); while ((int)(clock32() - c0_) < (n)) {} } } while (0)
#define KDEL 300
#define PDEL 300
#define CST(i) do { if ((warp & 3) == 0 && lane_v() == 0) { unsigned t_; asm volatile("mov.u32 %0, %%globaltimer_lo;" : "=r"(t_) :: "memory"); sts32(sb + SMEM_TOTAL - 768 + (warp >> 2) * 128 + (i) * 4, t_); } } while (0)
#define TP0 5000
#define TP4 5800
#define KDEL2 300
#define WSP 450
#define WS0 0
#define HINTW 10
#define WAS 0x0005
#define WA0 (WAS >> 12)
#define WA1 ((WAS >> 8) & 15)
#define WA2 ((WAS >> 4) & 15)
#define WA3 (WAS & 15)
#define WDAT 1
#define PAUSE 2
#define PCNT (32 + ((PAUSE & 1) ? 288 : 0) + ((PAUSE & 6) ? 320 : 64))
#define LNAT 2
#define UW 8
#define FINAT 3
#define UAT 2
#define TOKEN_OF(g) (16 * ((g) & 1) + ((g) >> 2) + 2 * ((g) & 2))
#define HI2(a, b) (pack_f16_rz(__uint_as_float(a), __uint_as_float(b)) & 0xfff8fff8u)
struct Params {
    const bf16 *x, *lar, *aim, *cre, *cim, *ldt, *dsk;
    Scratch* s;
    const bf16* wr;
    bf16* out;
};

template <int NK>
__device__ __forceinline__ void ln_partial(const uint32_t (&H)[2][NK], const uint32_t (&bw)[NK], uint32_t lp, int warp, int g, int t) {
    float cs[4] = {0.f, 0.f, 0.f, 0.f}, cl[4] = {0.f, 0.f, 0.f, 0.f}, ch[4] = {0.f, 0.f, 0.f, 0.f};
#pragma unroll
    for (int k = 0; k < NK; k += 2) {
        uint32_t a0, a1, a2, a3;
        asm volatile("prmt.b32 %0, %4, %4, %8;\nprmt.b32 %1, %5, %5, %8;\nprmt.b32 %2, %6, %6, %8;\nprmt.b32 %3, %7, %7, %8;\n"
                     : "=r"(a0), "=r"(a1), "=r"(a2), "=r"(a3) : "r"(H[0][k]), "r"(H[1][k]), "r"(H[0][k + 1]), "r"(H[1][k + 1]), "r"(0x3210u + (warp >> 8)));
        mma_bf16(cl, a0, a1, a2, a3, H[0][k], H[0][k + 1]);
        mma_bf16(ch, a0, a1, a2, a3, H[1][k], H[1][k + 1]);
        mma_bf16(cs, a0, a1, a2, a3, bw[k], bw[k + 1]);
    }
    const uint32_t a = lp + (g * 20 + warp) * 4;
    if (t == 0) {
        stsf(a, cs[1]); stsf(a + 8 * 80, cs[3]);
        if (NK == 4) { stsf(a + 48 * 80, cs[0]); stsf(a + 56 * 80, cs[2]); }
    }
    if (t == (g >> 1)) { stsf(a + 16 * 80, (g & 1) ? cl[1] : cl[0]); stsf(a + 24 * 80, (g & 1) ? ch[3] : ch[2]); }
}
__device__ __forceinline__ float sum18(uint32_t a) {
    const uint4 p = lds128(a), q = lds128(a + 16), r = lds128(a + 32), s = lds128(a + 48);
    const uint2 u = lds64(a + 64);
#define F(x) __uint_as_float(x)
    return (((F(p.x) + F(p.y)) + (F(p.z) + F(p.w))) + ((F(q.x) + F(q.y)) + (F(q.z) + F(q.w)))) +
           (((F(r.x) + F(r.y)) + (F(r.z) + F(r.w))) + ((F(s.x) + F(s.y)) + (F(s.z) + F(s.w))) + (F(u.x) + F(u.y)));
#undef F
}
__device__ __forceinline__ float sum9(uint32_t a) {
    const uint4 p = lds128(a), q = lds128(a + 16);
#define F(x) __uint_as_float(x)
    return (((F(p.x) + F(p.y)) + (F(p.z) + F(p.w))) + ((F(q.x) + F(q.y)) + (F(q.z) + F(q.w)))) + ldsf(a + 32);
#undef F
}
template <int N>
__device__ __forceinline__ void ln_finish(uint32_t lp, int lane, float& mb, float& rc) {
    const float v = N == 9 ? sum9(lp + lane * 80) : sum18(lp + lane * 80);
    const float o = __shfl_xor_sync(0xffffffffu, v, 16);
    const float m0 = v * (1.0f / 576.0f);
    const float mean = fmaf(fmaf(-m0, 576.0f, v), 1.0f / 576.0f, m0);
    const float var = fmaxf(fmaf(o, 1.0f / 576.0f, -(mean * mean)), 0.f);
    mb = rbf(mean);
    rc = rcp_approx(rbf(sqrt_approx(rbf(rbf(var) + 1e-5f))));
}
__device__ __forceinline__ uint32_t ln_apply(uint32_t w, const uint2& st) {
    uint32_t r;
    asm("{\n.reg .b16 m, t, h, l;\n.reg .b32 mm, hh, ll, d, e;\nmov.b32 {m, t}, %2;\nmov.b32 {h, l}, %3;\nmov.b32 mm, {m, m};\nmov.b32 hh, {h, h};\nmov.b32 ll, {l, l};\n"
        "sub.rn.bf16x2 d, %1, mm;\nmul.rn.bf16x2 e, d, ll;\nfma.rn.bf16x2 %0, d, hh, e;\n}\n" : "=r"(r) : "r"(w), "r"(st.x), "r"(st.y));
    return r;
}
__device__ __forceinline__ void stat_store(uint32_t a, float mb, float rc, uint32_t extra) {
    const float rh = rbf(rc);
    sts64(a, (__float_as_uint(mb) >> 16) | (extra << 16), pack_bf16(rh, rc - rh));
}

__device__ __forceinline__ void hcmul(uint32_t re, uint32_t im, uint32_t z, uint32_t& ore, uint32_t& oim) {
    asm("{\n.reg .b16 x, y;\n.reg .b32 xx, yy, ny, a, b;\nmov.b32 {x, y}, %4;\nmov.b32 xx, {x, x};\nmov.b32 yy, {y, y};\nneg.f16x2 ny, yy;\n"
        "mul.rn.f16x2 a, %2, xx;\nfma.rn.f16x2 %0, %3, ny, a;\nmul.rn.f16x2 b, %3, xx;\nfma.rn.f16x2 %1, %2, yy, b;\n}\n" : "=&r"(ore), "=r"(oim) : "r"(re), "r"(im), "r"(z));
}
__device__ __forceinline__ void hcmul(uint32_t re, uint32_t im, uint32_t zx, uint32_t zy, uint32_t& ore, uint32_t& oim) {
    asm("{\n.reg .b32 ny, a, b;\nneg.f16x2 ny, %5;\n"
        "mul.rn.f16x2 a, %2, %4;\nfma.rn.f16x2 %0, %3, ny, a;\nmul.rn.f16x2 b, %3, %4;\nfma.rn.f16x2 %1, %2, %5, b;\n}\n" : "=&r"(ore), "=r"(oim) : "r"(re), "r"(im), "r"(zx), "r"(zy));
}

struct KGen {
    uint32_t Af[4][4];
    float2 z1, z8, z64, z128, T[9];
    uint32_t zw;
};
__device__ __forceinline__ void kgen_setup(KGen& k, uint32_t pa, float dt) {
    const float A = rbf(expf(bf_lo(pa)));
    const float lr2 = -(A * dt) * 1.4426950408889634f;
    const float li = bf_hi(pa) * dt;
    const float rh = li * 0.15915494309189535f;
    const float rl = fmaf(li, 6.4206382986e-9f, fmaf(li, 0.15915494309189535f, -rh));
    k.z1 = cexp_e(lr2, rh, rl, 1.0f);
    k.z8 = cexp_e(lr2, rh, rl, 8.0f);
    k.z64 = cexp_e(lr2, rh, rl, 64.0f);
}
__device__ __forceinline__ void kgen_rows(KGen& k, uint32_t tb, int lane) {
    const float2 z8 = k.z8, z64 = k.z64;
    const uint32_t row = tb + lane * TBP;
    k.z128 = csq(z64);
    const float2 z16 = csq(z8), z32 = csq(z16), z48 = cmul(z32, z16), z80 = cmul(z64, z16), z96 = cmul(z64, z32), z112 = cmul(z64, z48);
    uint32_t re[4], im[4], a[4], b[4];
    re[0] = pack_f16(1.0f, z16.x); im[0] = pack_f16(0.0f, z16.y);
    re[1] = pack_f16(z32.x, z48.x); im[1] = pack_f16(z32.y, z48.y);
    re[2] = pack_f16(z64.x, z80.x); im[2] = pack_f16(z64.y, z80.y);
    re[3] = pack_f16(z96.x, z112.x); im[3] = pack_f16(z96.y, z112.y);
    sts128(row, re[0], re[1], re[2], re[3]);
    sts128(row + 32, im[0], im[1], im[2], im[3]);
    const uint32_t zz = pack_f16(z8.x, z8.y);
#pragma unroll
    for (int j = 0; j < 4; j++) hcmul(re[j], im[j], zz, a[j], b[j]);
    sts128(row + 16, a[0], a[1], a[2], a[3]);
    sts128(row + 48, b[0], b[1], b[2], b[3]);
    __syncwarp();
    const int mi = lane >> 3;
    const uint32_t ad = tb + (lane & 7) * TBP + mi * 16;
#pragma unroll
    for (int ks = 0; ks < 4; ks++) ldsm_x4_t(k.Af[ks][0], k.Af[ks][1], k.Af[ks][2], k.Af[ks][3], ad + ks * 8 * TBP);
}
__device__ __forceinline__ void kgen_chain(KGen& k, uint32_t pc, float cs) {
    k.T[0] = make_float2(bf_lo(pc) * cs, -bf_hi(pc) * cs);
    const float2 y1 = make_float2(k.z1.x, -k.z1.y);
#pragma unroll
    for (int c = 1; c < 8; c++) k.T[c] = cmul(k.T[c - 1], y1);
    k.T[8] = cmul(k.T[0], make_float2(k.z8.x, -k.z8.y));
}
__device__ __forceinline__ void kgen_cols(KGen& k, uint32_t tb, int lane) {
    const uint32_t row = tb + lane * TBP;
    const float2 (&T)[9] = k.T;
    const uint32_t zv = pack_f16(k.z128.x, k.z128.y), zo = __shfl_xor_sync(0xffffffffu, zv, 1);
    k.zw = (lane & 1) ? __byte_perm(zo, zv, 0x7632) : __byte_perm(zv, zo, 0x5410);
    const float2 y256 = csq(make_float2(k.z128.x, -k.z128.y)), y512 = csq(y256), y768 = cmul(y512, y256), y1024 = csq(y512);
    const float2 c1032 = cmul(T[8], y1024);
    const uint32_t r04 = pack_f16(T[0].x, T[4].x), i04 = pack_f16(T[0].y, T[4].y), r26 = pack_f16(T[2].x, T[6].x), i26 = pack_f16(T[2].y, T[6].y);
    const uint32_t r48 = pack_f16(T[4].x, T[8].x), i48 = pack_f16(T[4].y, T[8].y);
    __syncwarp();
    sts128(row, r04, pack_f16(T[1].x, T[5].x), r26, pack_f16(T[3].x, T[7].x));
    sts128(row + 16, i04, pack_f16(T[1].y, T[5].y), i26, pack_f16(T[3].y, T[7].y));
    uint32_t a[4], b[4];
    {
        const uint32_t zz = pack_f16(y256.x, y256.y);
        hcmul(r04, i04, zz, a[0], b[0]);
        hcmul(r26, i26, zz, a[2], b[2]);
        hcmul(r48, i48, zz, a[3], b[3]);
    }
    sts128(row + 32, a[0], a[0], a[2], a[3]);
    sts128(row + 48, b[0], b[0], b[2], b[3]);
    {
        hcmul(r48, i48, pack_f16(y512.x, y512.y), a[0], b[0]);
        hcmul(r48, i48, pack_f16(y768.x, y768.y), a[1], b[1]);
        const uint32_t zz = pack_f16(c1032.x, c1032.y);
        hcmul(pack_f16(1.0f, y256.x), pack_f16(0.0f, y256.y), zz, a[2], b[2]);
        hcmul(pack_f16(y512.x, y768.x), pack_f16(y512.y, y768.y), zz, a[3], b[3]);
    }
    sts128(row + 64, a[0], a[1], a[2], a[3]);
    sts128(row + 80, b[0], b[1], b[2], b[3]);
}
__device__ __forceinline__ void kgen_mma(const KGen& k, uint32_t tb, int lane) {
    const int t = lane & 3;
    const uint32_t zw = k.zw;
    uint32_t zx[4], zy[4];
#pragma unroll
    for (int ks = 0; ks < 4; ks++) { zx[ks] = __shfl_sync(0xffffffffu, zw, 8 * ks + 2 * t); zy[ks] = __shfl_sync(0xffffffffu, zw, 8 * ks + 2 * t + 1); }
    __syncwarp();
    float acc[2][3][4];
#pragma unroll
    for (int i = 0; i < 6; i++)
#pragma unroll
        for (int j = 0; j < 4; j++) acc[i / 3][i % 3][j] = 0.f;
    {
        const int mi = lane >> 3;
        const uint32_t bd = tb + ((lane & 7) + 8 * (mi >> 1)) * TBP + (mi & 1) * 16;
#pragma unroll
        for (int kp = 0; kp < 2; kp++) {
            uint32_t b[3][4];
#pragma unroll
            for (int j = 0; j < 3; j++) ldsm_x4_t(b[j][0], b[j][1], b[j][2], b[j][3], bd + kp * 16 * TBP + j * 32);
#pragma unroll
            for (int h = 0; h < 2; h++) {
                const int ks = 2 * kp + h;
                uint32_t d[4];
                hcmul(k.Af[ks][0], k.Af[ks][2], zx[ks], zy[ks], d[0], d[2]);
                hcmul(k.Af[ks][1], k.Af[ks][3], zx[ks], zy[ks], d[1], d[3]);
#pragma unroll
                for (int j = 0; j < 3; j++) {
                    mma_f16(acc[0][j], k.Af[ks][0], k.Af[ks][1], k.Af[ks][2], k.Af[ks][3], b[j][2 * h], b[j][2 * h + 1]);
                    mma_f16(acc[1][j], d[0], d[1], d[2], d[3], b[j][2 * h], b[j][2 * h + 1]);
                }
            }
        }
    }
    __syncwarp();
#pragma unroll
    for (int h = 0; h < 2; h++) {
        sts64(tb + h * 256 + lane * 8, pack_f16(acc[h][0][0], acc[h][0][1]), pack_f16(acc[h][0][2], acc[h][0][3]));
        sts64(tb + 512 + h * 256 + lane * 8, pack_f16(acc[h][1][0], acc[h][1][1]), pack_f16(acc[h][1][2], acc[h][1][3]));
        sts32(tb + 1024 + h * 256 + lane * 4, pack_f16(acc[h][2][0], t < 2 ? acc[h][2][1] : acc[h][2][2]));
        sts32(tb + 1152 + h * 256 + lane * 4, pack_f16(t < 2 ? acc[h][2][2] : acc[h][2][1], acc[h][2][3]));
    }
}
__device__ __forceinline__ uint32_t table_buf(uint32_t sb, int warp) { return sb + SM_TB + warp * TBW; }

__device__ __forceinline__ void kgen_combine(uint32_t sb, int warp, int lane, uint32_t kw, uint32_t ao) {
    const int wq = warp & 3;
    const uint32_t a = table_buf(sb, warp & ~3) + wq * 256 + lane * 8, c = table_buf(sb, warp & ~3) + 1024 + wq * 128 + lane * 4;
    const int t = lane & 3;
    const uint32_t o0 = (t < 2 ? KW_T2 + KW_KH + 16 + t * 256 - (wq & 1) * KW_KH : KW_T3 + 16 - 1024 + t * 512 + (wq & 1) * 256) + (lane >> 2) * 16;
    const uint4 o = make_uint4(o0 + t * 36, o0 + (t ^ 1) * 36, o0 + (t ^ 2) * 36, o0 + (t ^ 3) * 36);
    const uint2 u = lds64(a), v = lds64(a + TBW), w = lds64(a + 2 * TBW), x = lds64(a + 3 * TBW);
    const uint32_t kt = hadd2(hadd2(lds32(c), lds32(c + TBW)), hadd2(lds32(c + 2 * TBW), lds32(c + 3 * TBW)));
    const uint32_t k23 = hadd2(hadd2(u.y, v.y), hadd2(w.y, x.y));
    sts64(kw + wq * 64 + ao, hadd2(hadd2(u.x, v.x), hadd2(w.x, x.x)), k23);
    const uint32_t d = kw + (wq >> 1) * 128;
    const uint32_t kh = hmul2(kt, 0x38003800u);
    sts32(d + o.x, kh); sts32(d + o.y, kh); sts32(d + o.z, kh); sts32(d + o.w, kh);
    if (wq == 3) {
        if (lane == 31) { sts32(kw + 264, k23 >> 16); sts32(kw + 288 + 264, k23 >> 16); sts32(kw + 576 + 264, k23 >> 16); }
        if (lane == 29) { sts32(kw + 864 + 280, kt >> 16); sts32(kw + 280, kt & 0xffff0000u); }
    }
}

__device__ __forceinline__ int c_exponent(const uint2& r, const uint2& i) {
    uint32_t mx = __vmaxu2(__vmaxu2(r.x & 0x7fff7fffu, r.y & 0x7fff7fffu), __vmaxu2(i.x & 0x7fff7fffu, i.y & 0x7fff7fffu));
    mx = __reduce_max_sync(0xffffffffu, max(mx & 0xffffu, mx >> 16));
    return min(max((int)(mx >> 7), 4), 240);
}

__device__ __forceinline__ int warp_v() { int l; asm volatile("mov.u32 %0, %%tid.x;" : "=r"(l)); return __shfl_sync(0xffffffffu, l >> 5, 0); }
__device__ __forceinline__ int lane_v() { int l; asm volatile("mov.u32 %0, %%laneid;" : "=r"(l)); return l; }
__device__ __forceinline__ unsigned clock32() { unsigned c; asm volatile("mov.u32 %0, %%clock;" : "=r"(c)); return c; }
__device__ __forceinline__ uint32_t prmt(uint32_t a, uint32_t b, uint32_t s) { uint32_t d; asm("prmt.b32 %0, %1, %2, %3;\n" : "=r"(d) : "r"(a), "r"(b), "r"(s)); return d; }
__device__ __forceinline__ uint32_t prmt_v(uint32_t a, uint32_t b, uint32_t s) { uint32_t d; asm volatile("prmt.b32 %0, %1, %2, %3;\n" : "=r"(d) : "r"(a), "r"(b), "r"(s)); return d; }
__device__ __forceinline__ void mmah16(uint32_t& d0, uint32_t& d1, uint32_t a0, uint32_t a1, uint32_t a2, uint32_t a3, uint32_t b0, uint32_t b1, uint32_t c0, uint32_t c1) {
    asm volatile("mma.sync.aligned.m16n8k16.row.col.f16.f16.f16.f16 {%0,%1}, {%2,%3,%4,%5}, {%6,%7}, {%8,%9};\n"
                 : "=r"(d0), "=r"(d1) : "r"(a0), "r"(a1), "r"(a2), "r"(a3), "r"(b0), "r"(b1), "r"(c0), "r"(c1));
}
__device__ __forceinline__ void mmah8(uint32_t& d0, uint32_t& d1, uint32_t a0, uint32_t a1, uint32_t b0, uint32_t c0, uint32_t c1) {
    asm volatile("mma.sync.aligned.m16n8k8.row.col.f16.f16.f16.f16 {%0,%1}, {%2,%3}, {%4}, {%5,%6};\n"
                 : "=r"(d0), "=r"(d1) : "r"(a0), "r"(a1), "r"(b0), "r"(c0), "r"(c1));
}
template <int A = 8, int B = 32>
__device__ __forceinline__ void conv_rename(uint32_t (&acc)[32]) {
#pragma unroll
    for (int i = A; i < B; i++) { uint32_t v; asm volatile("mov.b32 %0, %1;\n" : "=r"(v) : "r"(acc[i])); acc[i] = v; }
}
__host__ __device__ constexpr uint32_t band_bits(int hw, int sh) {
    uint32_t c = 0;
    for (int s = 0; s <= 10; s++)
        for (int e = 0; e < 2; e++) {
            const int v = s - 3 + sh - 4 * e;
            if (v <= hw && v >= -hw) c |= 1u << (14 + 16 * e - s);
        }
    return c;
}
template <int HW, int SH, int J> __device__ __forceinline__ uint32_t band(uint32_t p2) {
    uint32_t d;
    asm volatile("{\n.reg .b32 t;\nmul.lo.u32 t, %1, %2;\nand.b32 %0, t, 0x40004000;\n}\n" : "=r"(d) : "r"(p2), "n"(band_bits(HW, SH) | J));
    return d;
}
__device__ __forceinline__ void band_quads(uint4 (&b)[3], uint32_t p2, uint32_t pm) {
    b[0] = make_uint4(band<2, 4, 1>(pm), band<1, 4, 1>(p2), band<2, -4, 1>(pm), band<1, -4, 1>(p2));
    b[1] = make_uint4(band<4, 4, 1>(pm), band<3, 4, 1>(pm), band<4, -4, 1>(pm), band<3, -4, 1>(pm));
    b[2] = make_uint4(band<2, 4, 2>(pm), band<4, 4, 2>(pm), band<2, -4, 2>(pm), band<4, -4, 2>(pm));
}
__device__ __forceinline__ uint2 run_sums(const uint4& a, uint32_t b0, uint32_t b1) {
    uint2 d;
    mmah16(d.x, d.y, a.x, a.y, a.z, a.w, b0, b1, 0u, 0u);
    return d;
}
__device__ __forceinline__ float h_lo(uint32_t w) { return __half2float(__ushort_as_half((unsigned short)(w & 0xffffu))); }
__device__ __forceinline__ float h_hi(uint32_t w) { return __half2float(__ushort_as_half((unsigned short)(w >> 16))); }
__device__ __forceinline__ uint64_t smem_desc(uint32_t sb, uint32_t o16, uint32_t lbo) {
    uint64_t d;
    asm("mov.b64 %0, {%1, %2};" : "=l"(d) : "r"(((sb & 0x3FFFF) >> 4) + o16 + (lbo << 12)), "r"(8));
    return d;
}
template <int I> struct IC { static constexpr int value = I; };

#define STG3 1
struct Conv {
    uint32_t q2[3][2][4];
    uint32_t q3[2][4];
    uint32_t r[18];
};
struct ConvPre {
    uint32_t a[5], b[5];
    uint32_t t[4];
};
__device__ __forceinline__ void conv_pre(ConvPre& e, uint32_t ka, uint32_t ks, uint32_t sel) {
    const uint4 r = lds128(ka + 256), s = lds128(ka + 272);
    ldsm_x4(e.t[0], e.t[1], e.t[2], e.t[3], ks);
    const uint32_t sw = sel ^ 0x4444u;
    e.a[0] = prmt(r.y, r.z, sel); e.a[1] = prmt(r.w, r.z, sw); e.a[2] = prmt(r.x, r.y, sel); e.a[3] = prmt(r.z, r.y, sw); e.a[4] = prmt(r.z, r.w, sel);
    e.b[0] = prmt(s.y, s.z, sel); e.b[1] = prmt(s.w, s.z, sw); e.b[2] = prmt(s.x, s.y, sel); e.b[3] = prmt(s.z, s.y, sw); e.b[4] = prmt(s.z, s.w, sel);
}
__device__ __forceinline__ void conv_sums(Conv& c, uint32_t (&acc)[32], const ConvPre& e, uint32_t a0, uint32_t a1, const uint4 (&bd)[3], uint32_t ka, uint32_t sel, int wq, bool odd) {
#pragma unroll
    for (int i = 0; i < 32; i++) acc[i] = 0u;
    uint32_t un[4], vn[4];
    ldsm_x4(un[0], un[1], un[2], un[3], a1);
    ldsm_x4(vn[0], vn[1], vn[2], vn[3], a0);
#pragma unroll
    for (int q = 0; q < 3; q++) {
        const uint32_t u[4] = {un[0], un[1], un[2], un[3]}, v[4] = {vn[0], vn[1], vn[2], vn[3]};
        if (STG3 && q && sel == 0u) {
            sts128(ka, c.q3[q - 1][0], c.q3[q - 1][1], c.q3[q - 1][2], c.q3[q - 1][3]);
            sts64(ka, acc[8 * q], acc[8 * q + 8]);
        }
        if (q < 2) {
            ldsm_x4(un[0], un[1], un[2], un[3], a1 + q * 512 + 512);
            ldsm_x4(vn[0], vn[1], vn[2], vn[3], a0 + q * 512 + 512);
        } else if (STG3 == 2) {
            const uint32_t a = ka + wq * 64;
#pragma unroll
            for (int i = 0; i < 4; i++) { const uint4 v = lds128(a + i * 16); c.r[4 * i] = v.x; c.r[4 * i + 1] = v.y; c.r[4 * i + 2] = v.z; c.r[4 * i + 3] = v.w; }
            const uint2 v = lds64(a + 64);
            c.r[16] = v.x; c.r[17] = v.y;
            if (sel == 1u) sts32(ka, 0u);
        }
        mmah8(acc[8 * q + 8], acc[8 * q + 9], e.a[4], 0u, u[1], acc[8 * q + 8], acc[8 * q + 9]);
        mmah16(acc[8 * q + 8], acc[8 * q + 9], e.a[0], e.a[1], e.a[2], e.a[3], u[2], u[3], acc[8 * q + 8], acc[8 * q + 9]);
        const uint2 z0 = run_sums(bd[2], v[0], v[1]);
        if (q < 2) {
            mmah8(acc[8 * q + 16], acc[8 * q + 17], e.b[4], 0u, u[1], 0u, 0u);
            mmah16(acc[8 * q + 16], acc[8 * q + 17], e.b[0], e.b[1], e.b[2], e.b[3], u[2], u[3], acc[8 * q + 16], acc[8 * q + 17]);
            const uint2 y1 = run_sums(bd[1], u[0], u[1]), y2 = run_sums(bd[1], v[2], v[3]), y3 = run_sums(bd[1], u[2], u[3]);
            const uint32_t n0 = odd ? y1.x : z0.y, n1 = odd ? y2.x : y1.x, s1 = odd ? y2.y : y1.y, s2 = odd ? y3.y : y2.y;
            c.q3[q][0] = prmt(s1, n0, 0x7632u); c.q3[q][1] = prmt(s2, n1, 0x7632u);
            c.q3[q][2] = prmt(s1, n0, 0x5410u); c.q3[q][3] = prmt(s2, n1, 0x5410u);
        }
        const uint2 x1 = run_sums(bd[0], u[0], u[1]), x2 = run_sums(bd[0], v[2], v[3]), x3 = run_sums(bd[0], u[2], u[3]);
        const uint32_t f0 = odd ? x1.x : z0.x, f1 = odd ? x2.x : x1.x, f2 = odd ? x3.x : x2.x;
#pragma unroll
        for (int h = 0; h < 2; h++) {
            const uint32_t s = h ? 0x7632u : 0x5410u;
            c.q2[q][h][0] = prmt(x1.y, f0, s); c.q2[q][h][1] = prmt(x2.y, f1, s);
            c.q2[q][h][2] = prmt(f1, x2.y, s ^ 0x4444u); c.q2[q][h][3] = prmt(x3.y, f2, s);
            if (q < 2) mmah16(acc[8 * q + 16], acc[8 * q + 17], c.q2[q][h][0], c.q2[q][h][1], c.q2[q][h][2], c.q2[q][h][3], e.t[2 * h], e.t[2 * h + 1], acc[8 * q + 16], acc[8 * q + 17]);
        }
    }
    if (STG3 != 2) {
        const uint32_t a = ka + wq * 64;
#pragma unroll
        for (int i = 0; i < 4; i++) { const uint4 v = lds128(a + i * 16); c.r[4 * i] = v.x; c.r[4 * i + 1] = v.y; c.r[4 * i + 2] = v.z; c.r[4 * i + 3] = v.w; }
        const uint2 v = lds64(a + 64);
        c.r[16] = v.x; c.r[17] = v.y;
    }
    if (sel == 0u) {
#pragma unroll
        for (int i = 0; i < 6; i++) sts128(ka + i * 16, c.q2[i >> 1][i & 1][0], c.q2[i >> 1][i & 1][1], c.q2[i >> 1][i & 1][2], c.q2[i >> 1][i & 1][3]);
#pragma unroll
        for (int i = 0; i < 2; i++) sts128(ka + i * 16, c.q3[i][0], c.q3[i][1], c.q3[i][2], c.q3[i][3]);
#pragma unroll
        for (int i = 1; i < 4; i++) sts64(ka + i * 16, acc[8 * i], acc[8 * i + 1]);
    }
    conv_rename(acc);
}
#define SPACE 100
#define SPN 3
#define O4 4
#define B2L 1
#define GATE 2
#define HAND 2
#define GA 6
#define GB 4
template <int TA, int TB, int IA, class FG>
__device__ __forceinline__ void conv_tail(uint32_t (&acc)[32], const uint32_t (&a)[8][4], uint32_t sb, unsigned char* gy0, int warp, size_t ycopy, FG fg) {
    const int wg = warp >> 2, wq = warp & 3, ord = TA == 0 && TB == 16 ? 3 - wg + (3 - wg >= O4) : O4;
    const uint32_t ub = sb + SM_U + wg * USLOT_B + UPAD * 16, turn = sb + SM_MISC + 376 + ord * 8, sfs = sb + SM_MISC + 256 + wg * 8;
    const uint32_t du = wg * (USLOT_B / 16) + (SM_U / 16 + UPAD + TA * 8);
    uint32_t ud[8], fs;
    auto skip = [&]() {
        const int lane = lane_v();
        const uint32_t ua = ub + ((lane >> 3) & 1) * ULO_B + (8 * wq + (lane & 7)) * 16 + (lane >> 4) * 512;
        if (IA == 0) ldsm_x4_t(ud[0], ud[1], ud[2], ud[3], ua);
        if (TB == 16) ldsm_x4_t(ud[4], ud[5], ud[6], ud[7], ua + 1024);
        const uint2 fd = lds64(sfs);
        fs = fd.x;
        const float dsk = __uint_as_float(fd.y);
#pragma unroll
        for (int i = 2 * IA; i < TB / 2; i++) ud[i] = pack_bf16(h_lo(ud[i]) * dsk, h_hi(ud[i]) * dsk);
    };
    conv_rename<2 * TA, 2 * TB>(acc);
    if (__builtin_expect(ord != 0, 0)) {
        skip();
        mbar_wait(turn);
    } else if (B2L) {
        bar_sync(0, NWRK);
    }
    if (O4 < 4 || (TA == 0 && TB == 16)) asm volatile("{\n.reg .pred p;\nelect.sync _|p, 0xffffffff;\n@p mbarrier.arrive.shared::cta.b64 _, [%0];\n}\n" ::"r"(turn + 48) : "memory");
    fg(IC<8>());
    wg_fence();
#pragma unroll
    for (int m = 7; m >= 0; m--) {
        wg_h<TA, TB - TA>(acc, a[m], smem_desc(sb, du - m, ULO_B));
        if (m == GA || m == GB || m == HAND) wg_commit();
        if (m == GB) asm volatile("wgmma.wait_group.sync.aligned 1;\n" ::: "memory");
    }
    wg_commit();
    if (O4 < 4 || (TA == 0 && TB == 16)) {
        asm volatile("wgmma.wait_group.sync.aligned 1;\n" ::: "memory");
        asm volatile("{\n.reg .pred p;\nelect.sync _|p, 0xffffffff;\n@p mbarrier.arrive.shared::cta.b64 _, [%0];\n}\n" ::"r"(turn + 8) : "memory");
    }
    __syncwarp();
    fg(IC<3>());
    if (!ord) skip();
    fg(IC<4>());
    const int lane = lane_v();
    const uint32_t lp = sb + SM_PL + (ord >= 3 ? ord - 3 : ord) * PL_B + lane * 8;
    unsigned char* gy = gy0 + ((4 * wq + (lane & 3)) * DM + (TA == 0 && TB == 16 ? 4 * blockIdx.x + wg : 512 + (blockIdx.x >> 1))) * 64 + (lane >> 2) * 8;
    const uint32_t st = lp + (wq * 12 - ((wq * (wq - 1)) >> 1)) * 256;
    uint32_t ld[3];
#pragma unroll
    for (int s = 1; s < 4; s++) {
        const int w = (wq - s) & 3;
        ld[s - 1] = lp + (w * 12 - ((w * (w - 1)) >> 1) + s - 1 - (wq < s ? 3 : 0)) * 256;
    }
    const uint32_t one = 1u + (warp >> 8);
    if (one == 0u) stg64(gy, ld[0], ld[1]);
    if (ord >= 3) bar_sync(9 + ord, 256);
    wg_wait0();
    fg(IC<6>());
#pragma unroll
    for (int j = TA; j < TB; j++)
        if ((j & 3) && j + 3 >= 4 * IA && (j + 3 < TB || j + wq < TB)) sts64(st + (j - 1 - (j >> 2)) * 256, acc[2 * j], acc[2 * j + 1]);
    bar_sync(1 + wg, 128);
    fg(IC<7>());
    uint2 v[4][3];
#pragma unroll
    for (int i = IA; i < TB / 4; i++)
#pragma unroll
        for (int s = 0; s < 3; s++) {
            if (i == 0) { v[i][s] = make_uint2(0u, 0u); if (wq > s) v[i][s] = lds64(ld[s]); }
            else v[i][s] = lds64(ld[s] + i * 768);
        }
    fg(IC<5>());
#pragma unroll
    for (int i = IA; i < TB / 4; i++) {
        const uint32_t x0 = hadd2(v[i][0].x, acc[8 * i]), x1 = hadd2(v[i][1].x, v[i][2].x), y0 = hadd2(v[i][0].y, acc[8 * i + 1]), y1 = hadd2(v[i][1].y, v[i][2].y);
        const uint32_t lo = pack_bf16(h_lo(x0) + h_lo(x1), h_hi(x0) + h_hi(x1)), hi = pack_bf16(h_lo(y0) + h_lo(y1), h_hi(y0) + h_hi(y1));
        ud[2 * i] = max(hfma2_bf(lo, fs, ud[2 * i]), one); ud[2 * i + 1] = hfma2_bf(hi, fs, ud[2 * i + 1]);
    }
    if (SPACE && TA == 0 && TB == 16 && ord < SPN) {
#pragma unroll
        for (int i = 0; i < 4; i++) {
            stg64(gy + i * 16 * DM * 64, ud[2 * i], ud[2 * i + 1]);
            if (i < 3) { const unsigned c0 = clock32(); while (clock32() - c0 < SPACE) {} }
        }
    } else {
#pragma unroll
        for (int i = IA; i < TB / 4; i++) stg64(gy + i * 16 * DM * 64, ud[2 * i], ud[2 * i + 1]);
    }
    if (ord < 2) bar_arrive(12 + ord, 256);
}
template <int M0, int M1>
__device__ __forceinline__ void conv_frags(uint32_t (&a)[8][4], const uint32_t (&r)[18], uint32_t sel, uint32_t dep, int warp) {
    const uint32_t s = prmt_v(sel, dep, 0x3210u + (warp >> 8)), sw = s ^ 0x4444u;
#pragma unroll
    for (int m = M0; m < M1; m++) {
        a[m][0] = prmt_v(r[2 * m + 1], r[2 * m + 2], s); a[m][1] = prmt_v(r[2 * m + 2], r[2 * m + 3], s);
        a[m][2] = prmt_v(r[2 * m + 1], r[2 * m], sw); a[m][3] = prmt_v(r[2 * m + 2], r[2 * m + 1], sw);
    }
}
template <class FG>
__device__ __forceinline__ void conv_main(const Conv& c, uint32_t (&acc)[32], uint32_t sb, uint32_t sel, unsigned char* gy, int warp, size_t ycopy, FG fg) {
    const uint32_t kw = (warp >> 2) * (KW_B / 16) + SM_KW / 16;
    const uint64_t d2 = smem_desc(sb, kw + KW_T2 / 16, KW_KH), d2b = smem_desc(sb, kw + KW_T2 / 16 + 1, KW_KH), d3 = smem_desc(sb, kw + KW_T3 / 16, 16), d3b = smem_desc(sb, kw + KW_T3 / 16 + 32, 16);
    uint32_t a[8][4];
    {
        const int ord = warp < 16 ? 3 - (warp >> 2) + (3 - (warp >> 2) >= O4) : O4;
        if (__builtin_expect(ord >= GATE, 0)) {
            fg(IC<1>());
            mbar_wait(sb + SM_MISC + 376 + 48 + (ord - GATE) * 8);
        }
    }
    wg_fence();
    wg_h<12, 4>(acc, c.q3[0], d3b); wg_h<8, 4>(acc, c.q3[0], d3); wg_h<4, 4>(acc, c.q2[0][0], d2b);
    wg_h<12, 4>(acc, c.q3[1], d3); wg_h<8, 4>(acc, c.q2[1][0], d2b);
    wg_h<12, 4>(acc, c.q2[2][0], d2b); wg_h<4, 4>(acc, c.q2[0][1], d2); wg_h<8, 4>(acc, c.q2[1][1], d2);
    wg_h<12, 4>(acc, c.q2[2][1], d2);
    wg_commit(); __syncwarp();
    fg(IC<0>());
    wg_wait0();
    conv_frags<0, 8>(a, c.r, sel, acc[16], warp);
    fg(IC<2>());
    if (warp >= 16) {
        if (blockIdx.x & 1) conv_tail<4, 16, 2>(acc, a, sb, gy, warp, ycopy, fg);
        else conv_tail<0, 8, 0>(acc, a, sb, gy, warp, ycopy, fg);
    } else {
        conv_tail<0, 16, 0>(acc, a, sb, gy, warp, ycopy, fg);
    }
}
#define CONV_LT6 const int dd = (lane >> 3) + (lane & 4) - (lane & 3); \
        const uint4 lt6 = make_uint4(prmt_v((dd & 3) * 288, 0u, idn), prmt_v(0x3254u + (dd >> 2) * 0x2222u, 0u, idn), \
            prmt_v(UPAD * 16 + (lane & 7) * 16 + ((lane >> 3) & 1) * (16 - ULO_B) + ULO_B - 32 + (lane & 16), 0u, idn), prmt_v(UPAD * 16 + (lane & 7) * 16 + ((lane >> 3) & 1) * ULO_B - 16 + (lane & 16), 0u, idn));
#define CONV_PRE \
        CONV_LT6 \
        const uint32_t ka = kw + lt6.x, sel = lt6.y, ks = kw + lt7.x; \
        const uint32_t ca0 = sb + SM_U + wg * USLOT_B + (warp & 3) * 128 + lt6.z, ca1 = sb + SM_U + wg * USLOT_B + (warp & 3) * 128 + lt6.w; \
        uint4 bd[3]; \
        band_quads(bd, lt7.w, (lane & 4) ? lt7.w >> 4 : lt7.w << 4);
#define CONV_PRE2 ConvPre ce_; conv_pre(ce_, ka, ks, sel);
#define CONV_BODY \
        Conv c; \
        uint32_t acc[32]; \
        conv_sums(c, acc, ce_, ca0, ca1, bd, ka, sel, warp & 3, lane & 4);
#define WS a_b_0_1_2_34_x__y567____c____de_r_
#define WS_STR2(x) #x
#define WS_STR(x) WS_STR2(x)
__device__ constexpr char wunit(int pt, int k) {
    constexpr char t[] = WS_STR(WS);
    int i = 0;
    for (; pt > 0 && t[i]; i++) pt -= t[i] == '_';
    for (; k > 0 && t[i] && t[i] != '_'; i++) k--;
    return t[i] == '_' ? 0 : t[i];
}
__device__ constexpr bool wsched_ok() {
    int seen = 0;
    for (int p = 0; p < 21; p++)
        for (int k = 0; wunit(p, k); k++) {
            const char c = wunit(p, k);
            const int bit = 1 << (c == 'r' ? 13 : c >= 'x' ? c - 'x' + 14 : c >= 'a' ? c - 'a' + 8 : c - '0');
            if ((seen & bit) || k >= (p < 16 ? 4 : 2) || (p < 5 && c >= '4' && c <= '7') || (p < 6 && (c == 'c' || c == 'd')) || (p < 16 && c == 'e')) return false;
            seen |= bit;
        }
    return seen == 0xffff;
}
struct WMaps { CUtensorMap g, u, gr, ur, d, dr; };
static_assert(GATE <= 2 && O4 >= 2, "resets");
static_assert(wsched_ok(), "weight schedule");
template <int PT, int K>
__device__ __forceinline__ void weight_units(uint32_t sb, const WMaps& m, int w) {
    constexpr char U = wunit(PT, K);
    if constexpr (U != 0) {
        if (w == K && elect_one()) {
            if (PT == 8) DELAY(K * WSP + WS0);
            const int P = blockIdx.x >> 1, odd = blockIdx.x & 1;
            constexpr int bar = SM_MISC + (U == 'e' ? 352 : U >= 'a' && U <= 'r' ? 336 : 328);
            if constexpr (U == 'e') { if (!odd) tma_2d(sb + SM_WD + 4 * 8192, &m.d, 256, 64 * P, sb + bar); }
            else if constexpr (U == 'r') tma_3d(sb + SM_WD + 40960, &m.dr, 0, 4096 + 8 * P, 5 * odd, sb + bar);
            else if constexpr (U >= 'x') tma_3d(sb + SM_WR + (U - 'x') * 4608, U == 'x' ? &m.gr : &m.ur, 4096 + 8 * P, 0, 2 * odd, sb + bar);
            else if constexpr (U >= 'a') tma_2d(sb + SM_WD + (U - 'a') * 8192, &m.d, 320 * odd + 64 * (U - 'a'), 64 * P, sb + bar);
            else tma_2d(sb + (U < '4' ? SM_WG : SM_WU) + (U & 3) * 9216, U < '4' ? &m.g : &m.u, 64 * P, 288 * odd + (U & 3) * 72, sb + bar);
        }
        weight_units<PT, K + 1>(sb, m, w);
    }
}
#define WPOINT(i, w) do { weight_units<i, 0>(sb, wm, w); } while (0)

__global__ void __launch_bounds__(NTHR, 1) __cluster_dims__(2, 1, 1)
fused_kernel(const Params p, const __grid_constant__ WMaps wm, const __grid_constant__ CUtensorMap tm_x,
             const __grid_constant__ CUtensorMap tm_y, const __grid_constant__ CUtensorMap tm_z) {
    extern __shared__ __align__(1024) unsigned char smem[];
    const uint32_t sb = smem_u32(smem);
    const int tid = threadIdx.x, warp = __shfl_sync(0xffffffffu, tid >> 5, 0), lane = tid & 31;
    const int b = blockIdx.x, P = b >> 1, odd = b & 1;
    const int g = lane >> 2, t = lane & 3;
    const int wg = warp >> 2, t128 = tid & 127;
    const uint32_t s_stat = sb + SM_MISC;
    const uint32_t s_key = sb + SM_MISC + 128;
    const uint32_t s_wm = sb + SM_MISC + 256;
    const uint32_t s_k16 = sb + SM_MISC + 192;
    const uint32_t s_fs = sb + SM_MISC + 256;
    const uint32_t s_cnt = sb + SM_MISC + 320;
    const uint32_t bar_w = sb + SM_MISC + 328, bar_d = bar_w + 8, bar_g = bar_w + 16, bar_r = bar_w + 32, bar_h = bar_w + 40, bar_x = bar_w + 48;
    STAMP(0);

    const unsigned tk0 = clock32();
    const bool lnw = (unsigned)(warp - 10) < 9u;
    const unsigned pm = tid + (tid < 512 ? 512 * b : 65024 + 128 * P), pq = (pm & ~127u) + 4 * lane;
    uint32_t pl = ldg16(p.lar + pm), ldt = ldg16(p.ldt + (pm >> 7));
    const uint32_t pa2 = ldg16(p.aim + pm), pc = ldg16(p.cre + pm), pi = ldg16(p.cim + pm);
    const uint2 call_re = ldg64(p.cre + pq), call_im = ldg64(p.cim + pq);
    const uint32_t dskl = ldg16(p.dsk + (pm >> 7));
    const uint32_t ep = ld_poll32(p.s->hint + (b & 7) * 32 + 1 + (lane >> 5));
    if ((unsigned)(tid - 320) < 288u) {
        const bf16* xp = p.x + (unsigned)((32 * P + 2 * odd + TOKEN_OF(g)) * DM + ((tid - 320) & ~31) + 8 * t);
        const uint32_t xt = sb + SM_XT + ((tid - 320) & ~31) * 32 + lane * 16;
        asm volatile("cp.async.cg.shared.global [%0], [%1], 16;\ncp.async.cg.shared.global [%0 + 512], [%1 + 9216], 16;\n"
                     "cp.async.cg.shared.global [%0 + 9216], [%1 + 576], 16;\ncp.async.cg.shared.global [%0 + 9728], [%1 + 9792], 16;\n" ::"r"(xt), "l"(xp) : "memory");
    }
    uint32_t* const std_ = p.s->st + ((lane & 12) * 128 + odd * 256 + 4 * P + 2 * (lane & 1) + ((lane >> 1) & 1)) * 2;
    unsigned char* const ud = reinterpret_cast<unsigned char*>(p.s->uT) + (32 * (warp - UW) + 8 * (g >> 1) + (g & 1)) * 4096 + b * 32 + t * 8;
    if (warp == 0) {
        if (lane == 0) {
            mbar_init(bar_x, 1); mbar_init(bar_w, 1); mbar_init(bar_d, 1); mbar_init(bar_d + 16, 1); mbar_init(bar_g, 1); mbar_init(bar_h, 3); mbar_init(bar_r, 1);
            #pragma unroll
            for (int i = 1; i < 11; i++) mbar_init(bar_x + 8 * i, 4);
            asm volatile("fence.mbarrier_init.release.cluster;\n" ::: "memory");
            mbar_expect(bar_x, 16384); mbar_expect(bar_r, 8192);
            mbar_expect(bar_w, 2 * 41472); mbar_expect(bar_d, 32768 + 5120); mbar_expect(bar_d + 16, 8192); mbar_expect(bar_g, 9 * 512);
        }
        __syncwarp();
        bar_arrive(0, NWRK);
    }
    if (warp == 0 && elect_one()) tma_3d(sb + SM_XC, &tm_x, 8 * P, 0, 8 * odd, bar_x);
    asm volatile("barrier.cluster.arrive.relaxed.aligned;\n" ::: "memory");
    const uint32_t kw = sb + SM_KW + wg * KW_B;
    if (t128 < 2 * UPAD) sts128(sb + SM_U + wg * USLOT_B + (t128 & 1) * ULO_B + (t128 >> 1) * 16, 0u, 0u, 0u, 0u);
    sts128(kw + t128 * 16, 0u, 0u, 0u, 0u);
    if (t128 < KW_B / 16 - 128) sts128(kw + 2048 + t128 * 16, 0u, 0u, 0u, 0u);
    if (tid < 128) {
#pragma unroll
        for (int i = 0; i < 4; i++) sts128(sb + SM_ZERO + i * 2048 + tid * 16, 0u, 0u, 0u, 0u);
    }
    if (warp != 0) bar_sync(0, NWRK);
    STAMP(1);
    if (warp == 19 || warp == UW || warp == UW + 1) {
        if (warp == 19) {
            if (lane < 16) stg64(std_, 0u, 0u);
            if (lane < 9) asm volatile("prefetch.global.L2 [%0];\n" ::"l"(p.wr + lane * 64));
        } else {
#pragma unroll
            for (int k = 0; k < 4; k++) stg64(ud + k * 8192, 0u, 0u);
        }
    }
    uint32_t X[2][8];
    auto partial = [&]() {
        const uint32_t xt = sb + SM_XT + (warp - 10) * 1024 + lane * 16;
        asm volatile("cp.async.wait_all;\n" ::: "memory");
        STAMP(23);
        const uint4 a = lds128(xt), c = lds128(xt + 512), d = lds128(xt + 9216), e = lds128(xt + 9728);
        X[0][0] = a.x; X[0][1] = a.y; X[0][2] = a.z; X[0][3] = a.w; X[0][4] = d.x; X[0][5] = d.y; X[0][6] = d.z; X[0][7] = d.w;
        X[1][0] = c.x; X[1][1] = c.y; X[1][2] = c.z; X[1][3] = c.w; X[1][4] = e.x; X[1][5] = e.y; X[1][6] = e.z; X[1][7] = e.w;
        const uint32_t one[8] = {0x3f803f80u, 0x3f803f80u, 0x3f803f80u, 0x3f803f80u, 0x3f803f80u, 0x3f803f80u, 0x3f803f80u, 0x3f803f80u};
        ln_partial<8>(X, one, sb + SM_LNP, warp - 10, g, t);
        bar_arrive(6, 320);
        if (PAUSE & 1) bar_sync(7, PCNT);
    };
    if (LNAT == 0 && lnw) {
        partial();
        pl = prmt_v(pl, X[0][0], 0x3210u + (warp >> 8)); ldt = prmt_v(ldt, X[0][0], 0x3210u + (warp >> 8));
    }
    auto finish = [&]() {
        bar_sync(6, 320);
        float mb, rc;
        ln_finish<9>(sb + SM_LNP, lane, mb, rc);
        const float rh = rbf(rc);
        const uint32_t s0 = (__float_as_uint(mb) >> 16) | (((ep & 0x7fffu) + 1u) << 16), s1 = pack_bf16(rh, rc - rh);
        if (lane < 16) { stg64(std_, s0, s1); sts64(s_stat + lane * 8, s0, s1); }
        if (lane == 16) sts32(s_cnt + 4, ep);
        bar_arrive(7, PCNT);
        STAMP(28);
    };
    auto upub = [&]() {
        if (!(PAUSE & 6)) bar_sync(7, PCNT);
        const uint32_t utag = ((ep & 3u) + 1u) * 0x10001u;
        uint32_t U[2][4];
#pragma unroll
        for (int hf = 0; hf < 2; hf++) {
            const uint2 st = lds64(s_stat + (g + 8 * hf) * 8);
            const uint4 xv = lds128(sb + SM_XT + (16 + warp - UW) * 1024 + hf * 512 + lane * 16);
            const uint32_t xs[4] = {xv.x, xv.y, xv.z, xv.w};
#pragma unroll
            for (int k = 0; k < 4; k++) {
                const uint32_t u = ln_apply(xs[k], st);
                U[hf][k] = movm((pack_f16_rz(bf_lo(u), __uint_as_float(u)) & 0xfff8fff8u) | utag);
            }
        }
#pragma unroll
        for (int k = 0; k < 4; k++) stg64(ud + k * 8192, U[0][k], U[1][k]);
    };
    if (FINAT == 0 && warp == 19) finish();
    const uint32_t tb = table_buf(sb, warp);
    const float dt = rbf(expf(bf_lo(ldt)));
    KGen kg;
    kgen_setup(kg, pl | (pa2 << 16), dt);
    if (LNAT == 1 && lnw) {
        partial();
        kg.z8.x = __uint_as_float(prmt_v(__float_as_uint(kg.z8.x), X[0][0], 0x3210u + (warp >> 8)));
        kg.z1.x = __uint_as_float(prmt_v(__float_as_uint(kg.z1.x), X[0][0], 0x3210u + (warp >> 8)));
    }
    if (FINAT == 1 && warp == 19) finish();
    if (UAT == 0 && (warp == UW || warp == UW + 1)) upub();
    kgen_rows(kg, tb, lane);
    if (wg == 0) fence_async();
    if (LNAT == 2 && lnw) {
        partial();
        kg.z128.x = __uint_as_float(prmt_v(__float_as_uint(kg.z128.x), X[0][0], 0x3210u + (warp >> 8)));
        kg.z1.x = __uint_as_float(prmt_v(__float_as_uint(kg.z1.x), X[0][0], 0x3210u + (warp >> 8)));
    }
    if (FINAT == 2 && warp == 19) finish();
    if (UAT == 1 && (warp == UW || warp == UW + 1)) upub();
    STAMP(2);
    WPOINT(0, warp - 4);
    const int ce = c_exponent(call_re, call_im);
    if (t128 == 0) sts64(s_fs + wg * 8, (uint32_t)min(max(ce + (int)(__float_as_uint(dt) >> 23) - 116, 0), 254) * 0x800080u, dskl << 16);
    kgen_chain(kg, pc | (pi << 16), __uint_as_float(((uint32_t)(244 - ce) << 23) | (__float_as_uint(dt) & 0x7fffffu)));
    if ((PAUSE & 4) && warp < 10) bar_sync(7, PCNT);
    if (UAT == 4 && (warp == UW || warp == UW + 1)) upub();
    STAMP(3);
    WPOINT(1, warp - 6);
    kgen_cols(kg, tb, lane);
    if (LNAT == 3 && lnw) partial();
    if (FINAT == 3 && warp == 19) finish();
    if ((PAUSE & 2) && warp < 10) bar_sync(7, PCNT);
    if (UAT == 2 && (warp == UW || warp == UW + 1)) upub();
    STAMP(4);
    WPOINT(2, warp - 8);
    const uint4* usrc = wg < 4 ? reinterpret_cast<const uint4*>(p.s->st) + odd * 512 + (lane & 1) * 128 + 16 * (warp & 7) + (lane >> 1)
                               : reinterpret_cast<const uint4*>(p.s->uT) + P * 256 + 2 * t128;
    const int ustep = wg < 4 ? 256 : 1;
    uint4 uv0, uv1;
    kgen_mma(kg, tb, lane);
    if (UAT == 3 && (warp == UW || warp == UW + 1)) upub();
    STAMP(26);
    WPOINT(3, warp - 5);
    const uint32_t idn = 0x3210u + (warp >> 8);
    uint4 lt7 = make_uint4(prmt_v(KW_T2 + ((lane >> 3) & 1) * KW_KH + (33 + (lane & 7)) * 16 - (lane & 16), 0u, idn), t * 288 + g * 8 + 8, (lane & 1) * 4096 + (lane >> 1) * 16,
                                 prmt_v(8u << ((lane >> 3) + (lane & 4)) >> (lane & 3), 0u, idn));
    asm volatile("barrier.cluster.wait.acquire.aligned;\n" ::: "memory");
    const bool pe = (int)(clock32() - tk0) >= (wg < 4 ? TP0 : TP4);
    if (pe) { uv0 = ld_poll(usrc); uv1 = ld_poll(usrc + ustep); }
    bar_sync(1 + wg, 128);
    kgen_combine(sb, warp, lane, kw, lt7.y);
    if (warp < 3 || warp > 6) bar_arrive(14, NWRK);
    STAMP(5);
    WPOINT(4, warp - 7);
    if (!pe) {
        while ((int)(clock32() - tk0) < (wg < 4 ? TP0 : TP4)) {}
        uv0 = ld_poll(usrc); uv1 = ld_poll(usrc + ustep);
    }
    if (wg < 4) {
        mbar_wait(bar_x);
        const bool far = warp < 8;
        const uint32_t xa = sb + SM_XC + (warp & 7) * 256 + (odd ^ far) * 8 + lt7.z;
        uint2 xv[4] = {lds64(xa), lds64(xa + 8192), lds64(xa + 2048), lds64(xa + 10240)};
        const uint32_t tag = ((ep & 0x7fffu) + 1u) << 16;
        int it = 0;
        while (true) {
            const bool bad = (((uv0.x ^ tag) | (uv0.z ^ tag)) | ((uv1.x ^ tag) | (uv1.z ^ tag))) >> 16;
            if (!__any_sync(0xffffffffu, bad)) break;
            if (++it > SPIN_LIMIT) TRAP();
            if (bad) { uv0 = ld_poll(usrc); uv1 = ld_poll(usrc + 256); }
        }
        STAMP(6);
        DBG(wg, it);
        const uint2 st[4] = {make_uint2(uv0.x, uv0.y), make_uint2(uv0.z, uv0.w), make_uint2(uv1.x, uv1.y), make_uint2(uv1.z, uv1.w)};
#pragma unroll
        for (int i = 0; i < 4; i++) {
            xv[i].x = ln_apply(xv[i].x, st[i]);
            xv[i].y = ln_apply(xv[i].y, st[i]);
        }
        const uint32_t ub = sb + SM_U + UPAD * 16 + odd * ULO_B + (warp & 7) * 256 + lane * 8;
        const uint32_t w[4][2] = {{pack_f16(bf_lo(xv[0].x), bf_lo(xv[1].x)), pack_f16(bf_lo(xv[2].x), bf_lo(xv[3].x))}, {HI2(xv[0].x, xv[1].x), HI2(xv[2].x, xv[3].x)},
                                  {pack_f16(bf_lo(xv[0].y), bf_lo(xv[1].y)), pack_f16(bf_lo(xv[2].y), bf_lo(xv[3].y))}, {HI2(xv[0].y, xv[1].y), HI2(xv[2].y, xv[3].y)}};
#pragma unroll
        for (int i = 0; i < 4; i++) {
            if (far) asm volatile("st.async.shared::cluster.mbarrier::complete_tx::bytes.v2.b32 [%0], {%1,%2}, [%3];\n" ::"r"((ub ^ 0x1000000u) + i * USLOT_B), "r"(w[i][0]), "r"(w[i][1]), "r"(bar_r ^ 0x1000000u) : "memory");
            else sts64(ub + i * USLOT_B, w[i][0], w[i][1]);
        }
    } else {
        const uint32_t utag = ((ep & 3u) + 1u) * 0x10001u;
        int it = 0;
        while (true) {
            const bool bad = (((uv0.x ^ utag) | (uv0.y ^ utag) | (uv0.z ^ utag) | (uv0.w ^ utag)) | ((uv1.x ^ utag) | (uv1.y ^ utag) | (uv1.z ^ utag) | (uv1.w ^ utag))) & 0x70007u;
            if (!__any_sync(0xffffffffu, bad)) break;
            if (++it > SPIN_LIMIT) TRAP();
            if (bad) { uv0 = ld_poll(usrc); uv1 = ld_poll(usrc + 1); }
        }
        STAMP(6);
        DBG(4, it);
        const uint32_t ub = sb + SM_U + UPAD * 16 + 4 * USLOT_B + (t128 >> 1) * 32 + (t128 & 1) * 8;
        sts64(ub, prmt(uv0.x, uv0.z, 0x5410u) ^ utag, prmt(uv1.x, uv1.z, 0x5410u) ^ utag);
        sts64(ub + 16, prmt(uv0.x, uv0.z, 0x7632u) ^ utag, prmt(uv1.x, uv1.z, 0x7632u) ^ utag);
        sts64(ub + ULO_B, prmt(uv0.y, uv0.w, 0x5410u) ^ utag, prmt(uv1.y, uv1.w, 0x5410u) ^ utag);
        sts64(ub + ULO_B + 16, prmt(uv0.y, uv0.w, 0x7632u) ^ utag, prmt(uv1.y, uv1.w, 0x7632u) ^ utag);
    }
    lt7.w = prmt_v(lt7.w, uv0.x, idn);
    CONV_PRE
    if (warp < 3 && elect_one()) tma_st_3d(warp < 2 ? &tm_y : &tm_z, sb + SM_ZERO, warp < 2 ? 128 * b : 32 * (512 + P), 0, 2 * (warp < 2 ? warp : odd));
    if (warp >= 3 && warp <= 6) {
        bar_sync(14, NWRK);
        WPOINT(5, warp - 3);
    }
    bar_sync(1 + wg, 128);
    CONV_PRE2
    mbar_wait(bar_r);
    fence_async();
    bar_sync(0, NWRK);
    STAMP(7);
    uint32_t hv0 = 0;
    {
        WPOINT(6, 19 - warp);
        CONV_BODY
        WPOINT(7, 19 - warp);
        if (!B2L) bar_sync(0, NWRK); else if (wg != 3) bar_arrive(0, NWRK);
        STAMP(8);
        size_t ycopy = 0;
        auto hook = [&](auto gi) {
                     constexpr int G = decltype(gi)::value;
                     if (G == 4 && warp == HINTW) hv0 = ld_poll32(p.s->hint + (lane_v() & 7) * 32);
                     if (G == 4) mbar_wait(bar_h);
                     if (G == 2) WPOINT(9, warp - 16);
                     if (G == 3) { WPOINT(10, warp - 12); WPOINT(12, warp - 8); WPOINT(14, warp - 4); }
                     if (G == 5) { WPOINT(11, warp - 13); WPOINT(13, warp - 9); WPOINT(15, warp - 5); }
                     if (G == 1 && warp >= 17 && elect_one())
                         bulk_s2g(warp == 17 ? p.s->part + b * (PBYTES / 4) : warp == 18 ? p.s->rows + b * 1152 : p.s->sc + b * 64, sb + SM_ZERO, warp == 17 ? PBYTES : warp == 18 ? 4608 : 160);
                     if (G == 4 && warp >= 17 && elect_one()) {
                         asm volatile("cp.async.bulk.wait_group 0;\n" ::: "memory");
                         hint_arrive(p.s->hint, 2, b & 7);
                     }
                     if (G == 1 && warp < 3) {
                         if (elect_one()) {
                             asm volatile("cp.async.bulk.wait_group 0;\n" ::: "memory");
                             mbar_arrive(bar_h);
                             hint_arrive(p.s->hint, 0, b & 7);
                         }
                         __syncwarp();
                         STAMP(17);
                     }
                     if (G == 1) WPOINT(8, warp - 16);
                 };
        conv_main(c, acc, sb, sel, reinterpret_cast<unsigned char*>(p.s->y), warp, ycopy, hook);
        STAMP(10);
    }
    {
    const int warp = warp_v(), lane = lane_v(), tid = 32 * warp + lane, g = lane >> 2, t = lane & 3;
    if (warp == HINTW) {
        const uint32_t target = (lds32(s_cnt + 4) + 1u) * 48u;
        if (__any_sync(0xffffffffu, (int)(hv0 - target) < 0)) hint_wait(p.s->hint, 0, target);
    }
    const unsigned char* ys = reinterpret_cast<const unsigned char*>(p.s->y) + ((size_t)P * DM + 32 * warp + 8 * (g >> 1) + (g & 1)) * 64 + odd * 32 + t * 8;
    STAMP(27);
    bar_sync(0, NWRK);
    STAMP(11);
    const uint32_t zr = warp >> 8;
    auto late_rows = [&](auto pub) {
        const uint32_t k = lds32(s_key + (lane & 7) * 4), ep = lds32(s_cnt + 4);
        const bool late = k & 256u, mine = late && ((k & 255u) >> 1) == (uint32_t)b;
        uint32_t todo = __ballot_sync(0xffffffffu, mine) & 0xffu;
        if (todo) {
#pragma unroll 1
            while (todo) {
                const int s = __ffs(todo) - 1, row = (__shfl_sync(0xffffffffu, k, s) >> 9) & 15;
                todo &= todo - 1;
                if ((row & 7) == g) pub(row & 8, 2 * NCTA + s);
            }
            __threadfence();
            bar_sync(0, NWRK);
            if (tid < NSEL && mine) *reinterpret_cast<volatile unsigned*>(p.s->flag + tid) = ep + 1u;
        }
        int it = 0;
        if (__any_sync(0xffffffffu, late)) {
            while (__any_sync(0xffffffffu, late && ld_poll32(p.s->flag + (lane & 7)) != ep + 1u)) { if (++it > SPIN_LIMIT) TRAP(); }
            __threadfence();
        }
        const int gs = tid / 36;
        const uint4* src = reinterpret_cast<const uint4*>(p.s->rows) + __shfl_sync(0xffffffffu, late ? 2 * NCTA + (lane & 7) : (k & 255u), gs & 7) * 144 + 36 * odd + (tid - gs * 36);
        if (tid < 288) {
            uint4 v0;
            do { v0 = ld_poll(src); if (++it > SPIN_LIMIT) TRAP(); } while (!v0.x);
            sts128(sb + SM_XS + gs * XS_PITCH + (tid - gs * 36) * 16, v0.x, v0.y, v0.z, v0.w);
        }
        __syncwarp();
    };
    if (warp >= 18) {
        uint32_t* const kp = pin(p.s->sc + 64 * b + 32 * (19 - warp), zr);
        const uint32_t kid = pin(0xc0000000u | ((lane & 15) << 9) | 2 * b, zr), ka = pin(s_k16 + (warp & 1) * 288 + (lane & 15) * 4, zr), kb = pin(s_k16 + (warp & 1) * 288 + (lane & 16) * 2, zr);
        const uint4* ksrc = pin(reinterpret_cast<const uint4*>(p.s->sc) + 8 * (19 - warp) + 16 * lane, zr);
        const uint4* rsrc = pin(reinterpret_cast<const uint4*>(p.s->rows) + 36 * odd + t, zr);
        uint32_t bits, early = 0;
        if (warp == 18) {
            weight_units<20, 0>(sb, wm, 0); weight_units<20, 1>(sb, wm, 1);
            bar_sync(8, 640);
            float mb, rc;
            ln_finish<18>(sb + SM_LNP, lane, mb, rc);
            if (lane < 16) stat_store(s_stat + lane * 8, mb, rc, 0u);
            bar_arrive(13, 608);
            bar_sync(10, 640);
            early = lds32(s_wm + (lane & 15) * 4);
            bits = pack_bf16(0.f, sum18(sb + SM_LNP + (32 + (lane & 15)) * 80));
        } else {
            float sw = 0.f;
#pragma unroll
            for (int i = 0; i < 9; i++) { const uint32_t w = reinterpret_cast<const uint32_t*>(p.wr)[32 * i + lane]; sw += bf_lo(w) + bf_hi(w); }
#pragma unroll
            for (int i = 16; i; i >>= 1) sw += __shfl_xor_sync(0xffffffffu, sw, i);
            early = ld_poll32(p.s->hint + (lane & 7) * 32 + 2);
            if (zr) stsf(sb, sw);
            bar_sync(8, 640);
            const float v = sum18(sb + SM_LNP + lane * 80), hw = sum18(sb + SM_LNP + (48 + (lane & 15)) * 80);
            const float o = __shfl_xor_sync(0xffffffffu, v, 16), mean = (lane < 16 ? v : o) * (1.0f / 576.0f);
            const float var = fmaxf(fmaf(lane < 16 ? o : v, 1.0f / 576.0f, -(mean * mean)), 0.f);
            bits = __float_as_uint(fmaf(-rbf(mean), sw, hw) * rcp_approx(rbf(sqrt_approx(rbf(rbf(var) + 1e-5f)))));
        }
        {
            const uint32_t me = (((bits ^ ((uint32_t)((int)bits >> 31) & 0x7fffffffu)) >> 1) & 0x7fffe000u) ^ kid;
            sts32(ka, me);
            __syncwarp();
            const uint4 v = lds128(kb), w = lds128(kb + 16);
#define GT(x) ((me - (x)) >> 31)
            uint32_t rank = pin(GT(v.x) + GT(v.y) + GT(v.z), zr) + pin(GT(v.w) + GT(w.x) + GT(w.y), zr) + pin(GT(w.z) + GT(w.w), zr);
#undef GT
            rank += __shfl_xor_sync(0xffffffffu, rank, 16);
            const uint32_t sl = warp == 18 ? early : rank;
            if (lane < 16 && rank < 8) stg32(kp + rank, me + (sl < 2 ? sl : 256u));
            if (warp == 19) {
                sts32(s_wm + (lane & 15) * 4, rank);
                const uint32_t target = (lds32(s_cnt + 4) + 1u) * 48u;
                if (__any_sync(0xffffffffu, (int)(early - target) < 0)) hint_wait(p.s->hint, 2, target);
                bar_arrive(10, 640); bar_arrive(11, 608);
            }
        }
        bool slow;
        int it = 0;
        uint4 q[4];
        STAMP(13);
        DELAY(warp == 19 ? KDEL : KDEL2);
#pragma unroll
        for (int i = 0; i < 4; i++) q[i] = ld_poll(ksrc + 512 * i);
        while (true) {
            uint32_t a[4];
#pragma unroll
            for (int i = 0; i < 4; i++) a[i] = q[i].x & q[i].y & q[i].z & q[i].w;
            if (__all_sync(0xffffffffu, a[0] & a[1] & a[2] & a[3])) break;
#pragma unroll
            for (int i = 0; i < 4; i++)
                if (!a[i]) q[i] = ld_poll(ksrc + 512 * i);
            if (++it > SPIN_LIMIT) TRAP();
        }
        STAMP(16);
        if (warp == 18) {
            const uint32_t kt = sb + SM_KEYS;
#pragma unroll
            for (int i = 0; i < 4; i++) sts128(kt + i * 512 + lane * 16, q[i].x, q[i].y, q[i].z, q[i].w);
            bar_sync(15, 64);
            const uint32_t c = lds32(s_key + 32 + g * 4), e = lds32(kt + (c & 254u) * 8 + t * 4);
            const bool hit = ((e ^ c) & 0x1fffu) == 0u && !(c & 256u);
            if (hit) sts32(s_key + g * 4, e);
            const uint32_t lo = __reduce_min_sync(0xffffffffu, hit ? e : 0xffffffffu) | 0x1fffu;
#define GT(x) ((lo - (x)) >> 31)
            uint32_t n = hit ? 256u - GT(e) : 0u;
#pragma unroll
            for (int i = 0; i < 4; i++) n += pin(GT(q[i].x) + GT(q[i].y) + GT(q[i].z) + GT(q[i].w), zr) << 12;
#undef GT
            n = __reduce_add_sync(0xffffffffu, n);
            slow = (n >> 12) + (n & 4095u) != 2048u || (n & 4095u) <= 2040u;
            if (slow) {
                uint4 r[4];
                it = 0;
                while (true) {
#pragma unroll
                    for (int i = 0; i < 4; i++) r[i] = ld_poll(ksrc + 512 * i + 1);
                    if (__all_sync(0xffffffffu, all_nz(r[0]) && all_nz(r[1]) && all_nz(r[2]) && all_nz(r[3]))) break;
                    if (++it > SPIN_LIMIT) TRAP();
                }
                uint32_t m = 0u;
#pragma unroll 1
                for (int s = 0; s < 8; s++) {
                    uint32_t x = 0;
#pragma unroll
                    for (int i = 0; i < 4; i++) {
                        x = max(max(max(x, q[i].x - m), max(q[i].y - m, q[i].z - m)), q[i].w - m);
                        x = max(max(max(x, r[i].x - m), max(r[i].y - m, r[i].z - m)), r[i].w - m);
                    }
                    m += __reduce_max_sync(0xffffffffu, x);
                    if (lane == 0) sts32(s_key + s * 4, m);
                }
            }
            DBG(7, slow);
        } else {
            auto merge = [](const uint4& x, const uint4& y) {
                const uint32_t a = max(x.x, y.w), c = max(x.y, y.z), d = max(x.z, y.y), e = max(x.w, y.x);
                const uint32_t a2 = max(a, d), d2 = min(a, d), c2 = max(c, e), e2 = min(c, e);
                return make_uint4(max(a2, c2), min(a2, c2), max(d2, e2), min(d2, e2));
            };
            uint4 h = merge(merge(q[0], q[1]), merge(q[2], q[3]));
            uint4 v[9];
            uint32_t key = 0;
#pragma unroll
            for (int s = 0; s < 8; s++) {
                const uint32_t m = __reduce_max_sync(0xffffffffu, h.x);
                const bool w = h.x == m;
                h.x = w ? h.y : h.x; h.y = w ? h.z : h.y; h.z = w ? h.w : h.z; h.w = w ? 0u : h.w;
                if (g == s) key = m;
            }
            rsrc += (key & 255u) * 144;
#pragma unroll
            for (int j = 0; j < 9; j++) v[j] = ld_poll(rsrc + 4 * j);
            const uint32_t xsa = sb + SM_XS + g * XS_PITCH + t * 16;
            sts32(s_key + 32 + g * 4, key);
            sts32(xsa, 0u);
            bar_arrive(15, 64);
            bar_arrive(12, 608);
            STAMP(18);
#pragma unroll
            for (int j = 0; j < 9; j++) sts128(xsa + j * 64, v[j].x, v[j].y, v[j].z, v[j].w);
            slow = min(min(min(min(v[0].x, v[1].x), v[2].x), min(min(v[3].x, v[4].x), v[5].x)), min(min(v[6].x, v[7].x), v[8].x)) == 0u;
        }
        if (bar_or(0, NWRK, slow)) { late_rows([](bool, int) {}); bar_or(0, NWRK, false); }
        STAMP(19);
        const int fl = 16 * (b & 1) + ((tid >> 2) & 15), fc = 16 * (b >> 1) + (fl >> 2) + 8 * ((tid >> 1) & 1), fsl = 2 * (fl & 3) + (tid & 1);
        const uint32_t kk = lds32(s_key + fsl * 4);
        const uint32_t* fsrc = p.s->rows + ((kk & 256u) ? 2 * NCTA + fsl : (kk & 255u)) * DM + (fc >> 1);
        uint32_t hw = 1u, uw = 1u;
        if (b < 72) { uw = ld_poll32(fsrc); hw = ld_poll32(fsrc + 288); }
        if (b < 72) {
            it = 0;
            while (!hw || !uw) { uw = ld_poll32(fsrc); hw = ld_poll32(fsrc + 288); if (++it > SPIN_LIMIT) TRAP(); }
            const int row = (kk >> 9) & 15, ftok = 8 * (kk & 252u) + (kk & 2u) + TOKEN_OF(row & 7) + (row & 8);
            const unsigned k16 = (kk >> 15) & 0xffffu;
            const unsigned bits = (k16 & 0x8000u) ? (k16 & 0x7fffu) : (~k16 & 0xffffu);
            const float rs = 512.0f * rbf(__fdividef(1.0f, 1.0f + __expf(-__uint_as_float(bits << 16))));
            bf16* const op = p.out + (unsigned)(ftok * DM + fc);
            const float uv = (fc & 1) ? bf_hi(uw) : bf_lo(uw), hv = (fc & 1) ? bf_hi(hw) : bf_lo(hw);
            const uint32_t a = sb + SM_FIN + (tid - 576) * 80;
            sts128(a + 64, __float_as_uint(rs), __float_as_uint(uv), __float_as_uint(hv), (uint32_t)(size_t)op ^ (uint32_t)((size_t)op >> 32));
            bar_sync(14, 576);
            const uint4 p0 = lds128(a), p1 = lds128(a + 16), p2 = lds128(a + 32), p3 = lds128(a + 48);
#define F4(p) ((__uint_as_float(p.x) + __uint_as_float(p.y)) + (__uint_as_float(p.z) + __uint_as_float(p.w)))
            const float v0 = F4(p0), v1 = F4(p1), v2 = F4(p2), v3 = F4(p3);
#undef F4
            const float y3 = rbf(rbf((v0 + v1) + (v2 + v3)) * rs);
            asm volatile("st.global.u16 [%0], %1;\n" ::"l"(op), "h"((unsigned short)pack_bf16(hv + rbf(uv + y3), 0.f)) : "memory");
        }
        if (b == 0 && tid >= 632) *reinterpret_cast<volatile unsigned*>(p.s->hint + (tid & 7) * 32 + 1) = lds32(s_cnt + 4) + 1u;
    } else {
        uint32_t H[2][4], U2[2][4], WA[9][4], WD[18], WE[18];
        const int fkh = warp >= 9, fmt = warp - 9 * fkh;
        auto load_wa = [&](auto k0, auto k1) {
            if (k0.value >= k1.value) return;
            if (k0.value == 0) mbar_wait(bar_w);
            const int mi = lane >> 3, rr = lane & 7;
            const int row = fkh * 144 + rr + 8 * (mi >> 1);
            const uint32_t aad = sb + (fmt < 8 ? SM_WG + (mi & 1) * (SM_WU - SM_WG) + row * 128 + (fmt ^ rr) * 16 : SM_WR + (mi & 1) * 4608 + row * 16), ks = fmt < 8 ? 2048 : 256;
#pragma unroll
            for (int k = k0.value; k < k1.value; k++) ldsm_x4_t(WA[k][0], WA[k][1], WA[k][2], WA[k][3], aad + k * ks);
        };
        auto load_wd = [&](uint32_t (&WD)[18], int tile) {
            mbar_wait(bar_d);
            if (tile & 16) mbar_wait(bar_d + 16);
            const int mi = lane >> 3, rr = lane & 7;
            const uint32_t base = sb + SM_WD + rr * 128 + (((2 * tile + (mi & 1)) & 7) ^ rr) * 16;
#pragma unroll
            for (int k = 0; k < 4; k++) ldsm_x4_t(WD[4 * k], WD[4 * k + 1], WD[4 * k + 2], WD[4 * k + 3], base + (tile >> 2) * 8192 + (k * 16 + 8 * (mi >> 1)) * 128);
            ldsm_x2_t(WD[16], WD[17], base + 40960 + (tile >> 2) * 1024);
        };
        auto publish = [&](bool hi, int slot) {
            uint4* rowp = reinterpret_cast<uint4*>(p.s->rows) + slot * 144 + warp * 4 + t;
            stg128(rowp, nzw(hi ? U2[1][0] : U2[0][0]), nzw(hi ? U2[1][1] : U2[0][1]), nzw(hi ? U2[1][2] : U2[0][2]), nzw(hi ? U2[1][3] : U2[0][3]));
            stg128(rowp + 72, nzw(hi ? H[1][0] : H[0][0]), nzw(hi ? H[1][1] : H[0][1]), nzw(hi ? H[1][2] : H[0][2]), nzw(hi ? H[1][3] : H[0][3]));
        };
        uint4 wr = make_uint4(0x3f803f80u, 0x3f803f80u, 0x3f803f80u, 0x3f803f80u);
        {
            uint2 yv[4];
#pragma unroll
            for (int k = 0; k < 4; k++) yv[k] = ld_poll64(ys + k * 128);
            if (g == 0) wr = ldg128(p.wr + 32 * warp + 8 * t);
            const uint4 x0 = lds128(sb + SM_XT + warp * 1024 + lane * 16), x1 = lds128(sb + SM_XT + warp * 1024 + 512 + lane * 16);
            load_wa(IC<0>(), IC<WA0>());
            int it = 0;
            while (!__all_sync(0xffffffffu, yv[0].x && yv[1].x && yv[2].x && yv[3].x)) {
#pragma unroll
                for (int k = 0; k < 4; k++) yv[k] = ld_poll64(ys + k * 128);
                if (++it > SPIN_LIMIT) TRAP();
            }
            STAMP(12);
            const uint32_t Z[2][4] = {{x0.x, x0.y, x0.z, x0.w}, {x1.x, x1.y, x1.z, x1.w}};
#pragma unroll
            for (int k = 0; k < 4; k++) {
                H[0][k] = hadd2_bf(Z[0][k], movm(yv[k].x));
                H[1][k] = hadd2_bf(Z[1][k], movm(yv[k].y));
            }
            const uint32_t bw[4] = {wr.x, wr.y, wr.z, wr.w};
            ln_partial<4>(H, bw, sb + SM_LNP, warp, g, t);
        }
        bar_arrive(8, 640);
        WPOINT(16, warp - 12);
        load_wa(IC<WA0>(), IC<WA1>());
        STAMP(13);
        bar_sync(13, 608);
        STAMP(14);
#pragma unroll
        for (int hf = 0; hf < 2; hf++) {
            const uint2 st = lds64(s_stat + (g + 8 * hf) * 8);
#pragma unroll
            for (int k = 0; k < 4; k++) U2[hf][k] = ln_apply(H[hf][k], st);
        }
        {
            float cs[4] = {0.f, 0.f, 0.f, 0.f}, ct[4] = {0.f, 0.f, 0.f, 0.f};
            mma_bf16(cs, U2[0][0], U2[1][0], U2[0][1], U2[1][1], wr.x, wr.y);
            mma_bf16(ct, U2[0][2], U2[1][2], U2[0][3], U2[1][3], wr.z, wr.w);
            if (t == 0) { stsf(sb + SM_LNP + ((32 + g) * 20 + warp) * 4, cs[0] + ct[0]); stsf(sb + SM_LNP + ((40 + g) * 20 + warp) * 4, cs[2] + ct[2]); }
            bar_arrive(10, 640);
        }
        load_wa(IC<WA1>(), IC<WA2>());
        bar_sync(11, 608);
        {
            const uint32_t rk[2] = {lds32(s_wm + g * 4), lds32(s_wm + 32 + g * 4)};
            uint32_t lo = min(rk[0], rk[1]), hi = max(rk[0], rk[1]);
#pragma unroll 1
            while (lo < 2) { publish(lo == rk[1], 2 * b + lo); lo = hi; hi = 16; }
        }
        load_wa(IC<WA2>(), IC<WA3>());
        load_wa(IC<WA3>(), IC<9>());
#pragma unroll
        for (int hf = 0; hf < 2; hf++)
            sts128(sb + SM_OUT + (g + 8 * hf) * OUT_PITCH + warp * 64 + t * 16,
                   hadd2_bf(H[hf][0], U2[hf][0]), hadd2_bf(H[hf][1], U2[hf][1]), hadd2_bf(H[hf][2], U2[hf][2]), hadd2_bf(H[hf][3], U2[hf][3]));
        fence_async();
        WPOINT(17, warp - 16);
        if ((WDAT == 0 || (WDAT == 2 && fkh)) && (warp < 16 || !odd)) load_wd(WD, warp);
        const uint32_t bad = pin(sb + SM_XS + (lane & 7) * XS_PITCH + (fkh * 144 + 8 * (lane >> 3)) * 2, zr), ex = pin(sb + SM_EX + warp * 512 + lane * 16, zr);
        uint32_t* pp = pin(p.s->part + ((size_t)(2 * (20 * odd + warp) + (lane >> 4)) * 64 + P) * 32 + (lane & 15) * 2, zr);
        bar_sync(12, 608);
        const bool routed = __any_sync(0xffffffffu, (lds32(s_key + 32 + (lane & 7) * 4) & 0x1efeu) == (uint32_t)((warp << 9) | 2 * b));
        auto store_row = [&]() { if (warp < 16 && elect_one()) bulk_s2g(p.out + (size_t)(32 * P + 2 * odd + TOKEN_OF(warp & 7) + (warp & 8)) * DM, sb + SM_OUT + warp * OUT_PITCH, DM * 2); };
        if (!routed) store_row();
        WPOINT(18, warp - 16);
        STAMP(15);
        bool again = zr;
#pragma unroll 1
        do {
            if (again) {
                if (routed) store_row();
                asm volatile("cp.async.bulk.wait_group 0;\n" ::: "memory");
                late_rows(publish);
            }
            again = bar_or(0, NWRK, false);
        } while (again);
        STAMP(19);
        float gp[4];
        {
            float c4[3][4];
#pragma unroll
            for (int i = 0; i < 3; i++)
#pragma unroll
                for (int j = 0; j < 4; j++) c4[i][j] = 0.f;
#pragma unroll
            for (int k = 0; k < 10; k += 2) {
                uint32_t b0, b1, b2, b3;
                ldsm_x4(b0, b1, b2, b3, bad + k * 32);
                mma_bf16(c4[k % 3], WA[k][0], WA[k][1], WA[k][2], WA[k][3], b0, b1);
                if (k < 8) mma_bf16(c4[(k + 1) % 3], WA[k + 1][0], WA[k + 1][1], WA[k + 1][2], WA[k + 1][3], b2, b3);
            }
#pragma unroll
            for (int j = 0; j < 4; j++) gp[j] = c4[0][j] + (c4[1][j] + c4[2][j]);
            if (warp >= 9) {
                sts128f(ex, gp);
                bar_arrive(6, 576);
            } else {
                bar_sync(6, 576);
                const uint4 o = lds128(ex + 4608);
                gp[0] += __uint_as_float(o.x); gp[1] += __uint_as_float(o.y); gp[2] += __uint_as_float(o.z); gp[3] += __uint_as_float(o.w);
                asm volatile("st.async.shared::cluster.mbarrier::complete_tx::bytes.v4.b32 [%0], {%1,%2,%3,%4}, [%5];\n"
                             ::"r"(ex ^ 0x1000000u), "r"(__float_as_uint(gp[0])), "r"(__float_as_uint(gp[1])), "r"(__float_as_uint(gp[2])), "r"(__float_as_uint(gp[3])), "r"(bar_g ^ 0x1000000u) : "memory");
                if (WDAT == 2) load_wd(WD, warp);
            }
            if (WDAT == 1 && (warp < 16 || !odd)) load_wd(WD, warp);
            if (warp >= 16 && !odd) load_wd(WE, warp + 2);
        }
        STAMP(20);
        if (warp < 9) {
            mbar_wait(bar_g);
            const uint4 u = lds128(ex);
            const uint32_t G = pack_bf16(gp[0] + __uint_as_float(u.x), gp[1] + __uint_as_float(u.y)), U = pack_bf16(gp[2] + __uint_as_float(u.z), gp[3] + __uint_as_float(u.w));
            const float G0 = bf_lo(G), G1 = bf_hi(G);
            sts32(sb + SM_GU + tid * 4, hmul2_bf(pack_bf16(G0 * rcp_approx(1.0f + ex2_approx(G0 * -1.4426950408889634f)), G1 * rcp_approx(1.0f + ex2_approx(G1 * -1.4426950408889634f))), U));
        }
        bar_sync(7, 576);
        STAMP(21);
        if (warp < 16 || !odd) {
            uint32_t gb[9];
            ldsm_x4_t(gb[0], gb[1], gb[2], gb[3], sb + SM_GU + lane * 16);
            ldsm_x4_t(gb[4], gb[5], gb[6], gb[7], sb + SM_GU + 512 + lane * 16);
            ldsm_x1_t(gb[8], sb + SM_GU + 1024 + (lane & 7) * 16);
            auto down = [&](const uint32_t (&W)[18], uint32_t* dst) {
                float c4[4] = {0.f, 0.f, 0.f, 0.f}, d4[4] = {0.f, 0.f, 0.f, 0.f}, e4[4] = {0.f, 0.f, 0.f, 0.f};
                mma_bf16(c4, W[0], W[1], W[2], W[3], gb[0], gb[1]);
                mma_bf16(d4, W[4], W[5], W[6], W[7], gb[2], gb[3]);
                mma_bf16(e4, W[8], W[9], W[10], W[11], gb[4], gb[5]);
                mma_bf16_k8(c4, W[16], W[17], gb[8]);
                mma_bf16(d4, W[12], W[13], W[14], W[15], gb[6], gb[7]);
                const float v0 = (c4[0] + e4[0]) + d4[0], v1 = (c4[1] + e4[1]) + d4[1], v2 = (c4[2] + e4[2]) + d4[2], v3 = (c4[3] + e4[3]) + d4[3];
                const uint32_t e = max(max(__float_as_uint(fmaxf(fabsf(v0), fabsf(v1))), __float_as_uint(fmaxf(fabsf(v2), fabsf(v3)))), 16u << 23) >> 23;
                const float sc = __uint_as_float((245u - e) << 23);
                stg64(dst, pack_f16(v0 * sc, v1 * sc) | ((e * 0x8002000u) & 0x60006000u), pack_f16(v2 * sc, v3 * sc) | ((e * 0x800200u) & 0x60006000u));
            };
            if (warp >= 16) { down(WE, pp + 4 * 64 * 32); down(WD, pp); }
            else down(WD, pp);
        }
        asm volatile("cp.async.bulk.wait_group.read 0;\n" ::: "memory");
        STAMP(22);
        if (b < 72 && warp < 16) {
            const uint2* src = reinterpret_cast<const uint2*>(p.s->part) + (unsigned)(b * 1024 + tid);
            uint2 a, c;
            int it = 0;
            DELAY(PDEL);
            a = ld_poll64(src); c = ld_poll64(src + 512);
            while (!__all_sync(0xffffffffu, a.y && c.y)) {
                a = ld_poll64(src); c = ld_poll64(src + 512);
                if (++it > SPIN_LIMIT) TRAP();
            }
            STAMP(24);
            const float ea = __uint_as_float((((a.y & 0x60006000u) | ((a.x >> 4) & 0x06000600u)) * 0x4001u) & 0x7f800000u);
            const float ec = __uint_as_float((((c.y & 0x60006000u) | ((c.x >> 4) & 0x06000600u)) * 0x4001u) & 0x7f800000u);
            a.x &= 0x9fff9fffu; a.y &= 0x9fff9fffu; c.x &= 0x9fff9fffu; c.y &= 0x9fff9fffu;
            const float s0 = fmaf(h_lo(a.x), ea, h_lo(c.x) * ec), s1 = fmaf(h_hi(a.x), ea, h_hi(c.x) * ec), s2 = fmaf(h_lo(a.y), ea, h_lo(c.y) * ec), s3 = fmaf(h_hi(a.y), ea, h_hi(c.y) * ec);
            const bool up = lane & 16;
            const float r0 = __shfl_xor_sync(0xffffffffu, up ? s0 : s2, 16), r1 = __shfl_xor_sync(0xffffffffu, up ? s1 : s3, 16);
            const uint32_t fa = sb + SM_FIN + ((lane & 15) * 4 + (up ? 2 : 0)) * 80 + warp * 4;
            stsf(fa, (up ? s2 : s0) + r0); stsf(fa + 80, (up ? s3 : s1) + r1);
            bar_arrive(14, 576);
        }
    }
    STAMP(25);
    }
}

typedef CUresult (*PFN_tmEncode)(CUtensorMap*, CUtensorMapDataType, cuuint32_t, void*, const cuuint64_t*, const cuuint64_t*, const cuuint32_t*,
                                 const cuuint32_t*, CUtensorMapInterleave, CUtensorMapSwizzle, CUtensorMapL2promotion, CUtensorMapFloatOOBfill);

extern "C" void kernel_launch(void* const* d_in, const int* in_sizes, int n_in, void* d_out, int out_size) {
    Params p;
    p.x = (const bf16*)d_in[0];
    p.lar = (const bf16*)d_in[1];
    p.aim = (const bf16*)d_in[2];
    p.cre = (const bf16*)d_in[3];
    p.cim = (const bf16*)d_in[4];
    p.ldt = (const bf16*)d_in[5];
    p.dsk = (const bf16*)d_in[6];
    p.wr = (const bf16*)d_in[8];
    p.out = (bf16*)d_out;
    static PFN_tmEncode enc = nullptr;
    static void* scratch = nullptr;
    if (!enc) {
        cudaFuncSetAttribute(fused_kernel, cudaFuncAttributeMaxDynamicSharedMemorySize, SMEM_TOTAL);
        void* fn = nullptr;
        cudaDriverEntryPointQueryResult qr;
        cudaGetDriverEntryPoint("cuTensorMapEncodeTiled", &fn, cudaEnableDefault, &qr);
        enc = (PFN_tmEncode)fn;
        cudaGetSymbolAddress(&scratch, g_scratch);
    }
    p.s = (Scratch*)scratch;
    WMaps wm;
    CUtensorMap tm_x, tm_y, tm_z;
    const cuuint64_t dims[2] = {FF, DM}, strides[1] = {FF * 2}, rdims[3] = {FF, 144, 4}, rstrides[2] = {FF * 2, 144 * FF * 2};
    const cuuint32_t box[2] = {64, 72}, rbox[3] = {8, 144, 2}, es3[3] = {1, 1, 1};
    for (int i = 0; i < 2; i++) {
        enc(i ? &wm.u : &wm.g, CU_TENSOR_MAP_DATA_TYPE_BFLOAT16, 2, d_in[9 + i], dims, strides, box, es3, CU_TENSOR_MAP_INTERLEAVE_NONE, CU_TENSOR_MAP_SWIZZLE_128B,
            CU_TENSOR_MAP_L2_PROMOTION_NONE, CU_TENSOR_MAP_FLOAT_OOB_FILL_NONE);
        enc(i ? &wm.ur : &wm.gr, CU_TENSOR_MAP_DATA_TYPE_BFLOAT16, 3, d_in[9 + i], rdims, rstrides, rbox, es3, CU_TENSOR_MAP_INTERLEAVE_NONE, CU_TENSOR_MAP_SWIZZLE_NONE,
            CU_TENSOR_MAP_L2_PROMOTION_NONE, CU_TENSOR_MAP_FLOAT_OOB_FILL_NONE);
    }
    const cuuint64_t ddims[2] = {DM, FF}, dstrides[1] = {DM * 2}, edims[3] = {64, FF, 9}, estrides[2] = {DM * 2, 128};
    const cuuint32_t dbox[2] = {64, 64}, ebox[3] = {64, 8, 5};
    enc(&wm.d, CU_TENSOR_MAP_DATA_TYPE_BFLOAT16, 2, d_in[11], ddims, dstrides, dbox, es3, CU_TENSOR_MAP_INTERLEAVE_NONE, CU_TENSOR_MAP_SWIZZLE_128B,
        CU_TENSOR_MAP_L2_PROMOTION_NONE, CU_TENSOR_MAP_FLOAT_OOB_FILL_NONE);
    enc(&wm.dr, CU_TENSOR_MAP_DATA_TYPE_BFLOAT16, 3, d_in[11], edims, estrides, ebox, es3, CU_TENSOR_MAP_INTERLEAVE_NONE, CU_TENSOR_MAP_SWIZZLE_128B,
        CU_TENSOR_MAP_L2_PROMOTION_NONE, CU_TENSOR_MAP_FLOAT_OOB_FILL_NONE);
    const cuuint64_t xdims[3] = {DM, LSEQ / 16, 16}, xstrides[2] = {16 * DM * 2, DM * 2};
    const cuuint32_t xbox[3] = {8, LSEQ / 16, 8};
    enc(&tm_x, CU_TENSOR_MAP_DATA_TYPE_BFLOAT16, 3, d_in[0], xdims, xstrides, xbox, es3, CU_TENSOR_MAP_INTERLEAVE_NONE, CU_TENSOR_MAP_SWIZZLE_NONE,
        CU_TENSOR_MAP_L2_PROMOTION_NONE, CU_TENSOR_MAP_FLOAT_OOB_FILL_NONE);
    const cuuint64_t ydims[3] = {DM * 32, 16, 4}, ystrides[2] = {DM * 64, 16 * DM * 64};
    const cuuint32_t ybox[3] = {128, 16, 2}, zbox[3] = {32, 16, 2};
    enc(&tm_y, CU_TENSOR_MAP_DATA_TYPE_BFLOAT16, 3, p.s->y, ydims, ystrides, ybox, es3, CU_TENSOR_MAP_INTERLEAVE_NONE, CU_TENSOR_MAP_SWIZZLE_NONE,
        CU_TENSOR_MAP_L2_PROMOTION_NONE, CU_TENSOR_MAP_FLOAT_OOB_FILL_NONE);
    enc(&tm_z, CU_TENSOR_MAP_DATA_TYPE_BFLOAT16, 3, p.s->y, ydims, ystrides, zbox, es3, CU_TENSOR_MAP_INTERLEAVE_NONE, CU_TENSOR_MAP_SWIZZLE_NONE,
        CU_TENSOR_MAP_L2_PROMOTION_NONE, CU_TENSOR_MAP_FLOAT_OOB_FILL_NONE);
    fused_kernel<<<NCTA, NTHR, SMEM_TOTAL>>>(p, wm, tm_x, tm_y, tm_z);
}
```

```cpp
#include <cuda_runtime.h>
#include <cuda.h>
#include <cuda_fp16.h>
#include <cuda_bf16.h>
#include <stdint.h>

#define LSEQ 2048
#define DM 576
#define NST 128
#define FF 4608
#define NSEL 8
#define NCTA 128
#define NTHR 640
#define NWRK 640

typedef __nv_bfloat16 bf16;

#define SM_WD 0
#define SM_WG 46080
#define SM_WR 82944
#define SM_WU 92160
#define SM_ZERO 32768
#define SM_XC 16384
#define SM_TB 96000
#define SM_PL 129024
#define PL_B 10752
#define SM_XT (SM_TB + 20 * TBW)
#define SM_U (SM_XT + 18432)
#define UPAD 8
#define ULO_B ((UPAD + 128) * 16)
#define USLOT_B (2 * ULO_B)
#define SM_KW (SM_U + 5 * USLOT_B)
#define KW_B 3600
#define KW_T2 1152
#define KW_KH 656
#define KW_T3 2464
#define SM_MISC (SM_KW + 5 * KW_B)
#define SM_LNP (SM_MISC + 576)
#define SMEM_TOTAL (SM_LNP + 5120)
#define TBP 112
#define TBW (32 * TBP)
#define SM_OUT SM_PL
#define OUT_PITCH 1216
#define SM_XS (SM_PL + 19456)
#define XS_PITCH 592
#define SM_EX (SM_PL + 24320)
#define SM_KEYS (SM_KW + 5120)
#define SM_FIN SM_KW
#define SM_GU (SM_PL + 33536)

struct __align__(128) Scratch {
    unsigned hint[8 * 32];
    unsigned flag[32];
    uint32_t sc[NCTA * 64];
    uint32_t st[LSEQ * 2];
    uint32_t uT[64 * (LSEQ / 2)];
    uint32_t y[NCTA * DM * 8];
    uint32_t part[72 * 64 * 32];
    uint32_t rows[(2 * NCTA + NSEL) * DM];
};
__device__ Scratch g_scratch;
#define STAMP(i)
#define DBG(i, v)

__device__ __forceinline__ float rbf(float x) {
    uint32_t r;
    asm("cvt.rn.bf16x2.f32 %0, %1, %2;\n" : "=r"(r) : "f"(x), "f"(0.f));
    return __uint_as_float(r);
}
__device__ __forceinline__ uint32_t pack_bf16(float lo, float hi) {
    uint32_t r;
    asm("cvt.rn.bf16x2.f32 %0, %1, %2;\n" : "=r"(r) : "f"(hi), "f"(lo));
    return r;
}
__device__ __forceinline__ uint32_t pack_f16(float lo, float hi) {
    uint32_t r;
    asm("cvt.rn.f16x2.f32 %0, %1, %2;\n" : "=r"(r) : "f"(hi), "f"(lo));
    return r;
}
__device__ __forceinline__ uint32_t pack_f16_rz(float lo, float hi) {
    uint32_t r;
    asm("cvt.rz.f16x2.f32 %0, %1, %2;\n" : "=r"(r) : "f"(hi), "f"(lo));
    return r;
}
__device__ __forceinline__ float bf_lo(uint32_t w) { return __uint_as_float(w << 16); }
__device__ __forceinline__ float bf_hi(uint32_t w) { return __uint_as_float(w & 0xffff0000u); }
__device__ __forceinline__ uint32_t hadd2_bf(uint32_t a, uint32_t b) {
    __nv_bfloat162 r = __hadd2_rn(*reinterpret_cast<__nv_bfloat162*>(&a), *reinterpret_cast<__nv_bfloat162*>(&b));
    return *reinterpret_cast<uint32_t*>(&r);
}
__device__ __forceinline__ uint32_t hmul2_bf(uint32_t a, uint32_t b) {
    __nv_bfloat162 r = __hmul2_rn(*reinterpret_cast<__nv_bfloat162*>(&a), *reinterpret_cast<__nv_bfloat162*>(&b));
    return *reinterpret_cast<uint32_t*>(&r);
}
__device__ __forceinline__ uint32_t hfma2_bf(uint32_t a, uint32_t b, uint32_t c) { uint32_t r; asm("fma.rn.bf16x2 %0, %1, %2, %3;\n" : "=r"(r) : "r"(a), "r"(b), "r"(c)); return r; }
__device__ __forceinline__ uint32_t hmul2(uint32_t a, uint32_t b) { uint32_t r; asm("mul.rn.f16x2 %0, %1, %2;\n" : "=r"(r) : "r"(a), "r"(b)); return r; }
__device__ __forceinline__ uint32_t hadd2(uint32_t a, uint32_t b) { uint32_t r; asm("add.rn.f16x2 %0, %1, %2;\n" : "=r"(r) : "r"(a), "r"(b)); return r; }
__device__ __forceinline__ uint32_t nzw(uint32_t w) { return w ? w : 0x8000u; }
__device__ __forceinline__ uint32_t smem_u32(const void* p) { return (uint32_t)__cvta_generic_to_shared(p); }
__device__ __forceinline__ uint32_t lds32(uint32_t addr) {
    uint32_t v;
    asm volatile("ld.shared.u32 %0, [%1];\n" : "=r"(v) : "r"(addr) : "memory");
    return v;
}
__device__ __forceinline__ uint2 lds64(uint32_t addr) {
    uint2 v;
    asm volatile("ld.shared.v2.u32 {%0,%1}, [%2];\n" : "=r"(v.x), "=r"(v.y) : "r"(addr) : "memory");
    return v;
}
__device__ __forceinline__ uint4 lds128(uint32_t addr) {
    uint4 v;
    asm volatile("ld.shared.v4.u32 {%0,%1,%2,%3}, [%4];\n" : "=r"(v.x), "=r"(v.y), "=r"(v.z), "=r"(v.w) : "r"(addr) : "memory");
    return v;
}
__device__ __forceinline__ float ldsf(uint32_t addr) { return __uint_as_float(lds32(addr)); }
__device__ __forceinline__ void sts32(uint32_t addr, uint32_t v) { asm volatile("st.shared.u32 [%0], %1;\n" ::"r"(addr), "r"(v) : "memory"); }
__device__ __forceinline__ void stsf(uint32_t addr, float v) { sts32(addr, __float_as_uint(v)); }
__device__ __forceinline__ void sts64(uint32_t addr, uint32_t a, uint32_t b) { asm volatile("st.shared.v2.u32 [%0], {%1,%2};\n" ::"r"(addr), "r"(a), "r"(b) : "memory"); }
__device__ __forceinline__ void sts128(uint32_t addr, uint32_t a, uint32_t b, uint32_t c, uint32_t d) {
    asm volatile("st.shared.v4.u32 [%0], {%1,%2,%3,%4};\n" ::"r"(addr), "r"(a), "r"(b), "r"(c), "r"(d) : "memory");
}
__device__ __forceinline__ void sts128f(uint32_t addr, const float (&v)[4]) {
    sts128(addr, __float_as_uint(v[0]), __float_as_uint(v[1]), __float_as_uint(v[2]), __float_as_uint(v[3]));
}
__device__ __forceinline__ void ldsm_x4(uint32_t& r0, uint32_t& r1, uint32_t& r2, uint32_t& r3, uint32_t addr) {
    asm volatile("ldmatrix.sync.aligned.m8n8.x4.shared.b16 {%0,%1,%2,%3}, [%4];\n"
                 : "=r"(r0), "=r"(r1), "=r"(r2), "=r"(r3) : "r"(addr) : "memory");
}
__device__ __forceinline__ void ldsm_x4_t(uint32_t& r0, uint32_t& r1, uint32_t& r2, uint32_t& r3, uint32_t addr) {
    asm volatile("ldmatrix.sync.aligned.m8n8.x4.trans.shared.b16 {%0,%1,%2,%3}, [%4];\n"
                 : "=r"(r0), "=r"(r1), "=r"(r2), "=r"(r3) : "r"(addr) : "memory");
}
__device__ __forceinline__ void ldsm_x2_t(uint32_t& r0, uint32_t& r1, uint32_t addr) {
    asm volatile("ldmatrix.sync.aligned.m8n8.x2.trans.shared.b16 {%0,%1}, [%2];\n" : "=r"(r0), "=r"(r1) : "r"(addr) : "memory");
}
__device__ __forceinline__ void ldsm_x1_t(uint32_t& r0, uint32_t addr) {
    asm volatile("ldmatrix.sync.aligned.m8n8.x1.trans.shared.b16 {%0}, [%1];\n" : "=r"(r0) : "r"(addr) : "memory");
}
__device__ __forceinline__ uint32_t movm(uint32_t a) {
    uint32_t d;
    asm volatile("movmatrix.sync.aligned.m8n8.trans.b16 %0, %1;\n" : "=r"(d) : "r"(a));
    return d;
}
__device__ __forceinline__ void mma_f16(float (&c)[4], uint32_t a0, uint32_t a1, uint32_t a2, uint32_t a3, uint32_t b0, uint32_t b1) {
    asm volatile(
        "mma.sync.aligned.m16n8k16.row.col.f32.f16.f16.f32 {%0,%1,%2,%3}, {%4,%5,%6,%7}, {%8,%9}, {%0,%1,%2,%3};\n"
        : "+f"(c[0]), "+f"(c[1]), "+f"(c[2]), "+f"(c[3])
        : "r"(a0), "r"(a1), "r"(a2), "r"(a3), "r"(b0), "r"(b1));
}
__device__ __forceinline__ void mma_bf16(float (&c)[4], uint32_t a0, uint32_t a1, uint32_t a2, uint32_t a3, uint32_t b0, uint32_t b1) {
    asm volatile(
        "mma.sync.aligned.m16n8k16.row.col.f32.bf16.bf16.f32 {%0,%1,%2,%3}, {%4,%5,%6,%7}, {%8,%9}, {%0,%1,%2,%3};\n"
        : "+f"(c[0]), "+f"(c[1]), "+f"(c[2]), "+f"(c[3])
        : "r"(a0), "r"(a1), "r"(a2), "r"(a3), "r"(b0), "r"(b1));
}
__device__ __forceinline__ void mma_bf16_k8(float (&c)[4], uint32_t a0, uint32_t a1, uint32_t b0) {
    asm volatile("mma.sync.aligned.m16n8k8.row.col.f32.bf16.bf16.f32 {%0,%1,%2,%3}, {%4,%5}, {%6}, {%0,%1,%2,%3};\n"
        : "+f"(c[0]), "+f"(c[1]), "+f"(c[2]), "+f"(c[3]) : "r"(a0), "r"(a1), "r"(b0));
}
__device__ __forceinline__ void bar_sync(int id, int n) { asm volatile("bar.sync %0, %1;\n" ::"r"(id), "r"(n) : "memory"); }
__device__ __forceinline__ void bar_arrive(int id, int n) { asm volatile("bar.arrive %0, %1;\n" ::"r"(id), "r"(n) : "memory"); }
__device__ __forceinline__ bool bar_or(int id, int n, bool v) {
    uint32_t r;
    asm volatile("{\n.reg .pred p, q;\nsetp.ne.u32 p, %3, 0;\nbar.red.or.pred q, %1, %2, p;\nselp.u32 %0, 1, 0, q;\n}\n" : "=r"(r) : "r"(id), "r"(n), "r"((uint32_t)v) : "memory");
    return r;
}
__device__ __forceinline__ uint4 ld_poll(const void* p) {
    uint4 v;
    asm volatile("ld.relaxed.gpu.global.v4.u32 {%0,%1,%2,%3}, [%4];\n" : "=r"(v.x), "=r"(v.y), "=r"(v.z), "=r"(v.w) : "l"(p) : "memory");
    return v;
}
template <class T> __device__ __forceinline__ T* pin(T* p, uint32_t z) {
    uint32_t lo, hi;
    asm volatile("mov.b64 {%0, %1}, %2;\n" : "=r"(lo), "=r"(hi) : "l"(p));
    asm volatile("xor.b32 %0, %0, %1;\n" : "+r"(lo) : "r"(z));
    asm volatile("xor.b32 %0, %0, %1;\n" : "+r"(hi) : "r"(z));
    asm volatile("mov.b64 %0, {%1, %2};\n" : "=l"(p) : "r"(lo), "r"(hi));
    return p;
}
__device__ __forceinline__ uint32_t pin(uint32_t a, uint32_t z) { asm volatile("xor.b32 %0, %0, %1;\n" : "+r"(a) : "r"(z)); return a; }
__device__ __forceinline__ uint2 ld_poll64(const void* p) {
    uint2 v;
    asm volatile("ld.relaxed.gpu.global.v2.u32 {%0,%1}, [%2];\n" : "=r"(v.x), "=r"(v.y) : "l"(p) : "memory");
    return v;
}
__device__ __forceinline__ uint32_t ld_poll32(const void* p) {
    uint32_t v;
    asm volatile("ld.relaxed.gpu.global.u32 %0, [%1];\n" : "=r"(v) : "l"(p) : "memory");
    return v;
}
__device__ __forceinline__ uint4 ldg128(const void* p) {
    uint4 v;
    asm volatile("ld.global.nc.v4.u32 {%0,%1,%2,%3}, [%4];\n" : "=r"(v.x), "=r"(v.y), "=r"(v.z), "=r"(v.w) : "l"(p));
    return v;
}
__device__ __forceinline__ uint2 ldg64(const void* p) {
    uint2 v;
    asm volatile("ld.global.nc.v2.u32 {%0,%1}, [%2];\n" : "=r"(v.x), "=r"(v.y) : "l"(p));
    return v;
}
__device__ __forceinline__ uint32_t ldg16(const void* p) {
    uint32_t v;
    asm volatile("ld.global.nc.u16 %0, [%1];\n" : "=r"(v) : "l"(p));
    return v;
}
__device__ __forceinline__ void stg128(void* p, uint32_t a, uint32_t b, uint32_t c, uint32_t d) {
    asm volatile("st.global.v4.u32 [%0], {%1,%2,%3,%4};\n" ::"l"(p), "r"(a), "r"(b), "r"(c), "r"(d) : "memory");
}
__device__ __forceinline__ void stg64(void* p, uint32_t a, uint32_t b) { asm volatile("st.global.v2.u32 [%0], {%1,%2};\n" ::"l"(p), "r"(a), "r"(b) : "memory"); }
__device__ __forceinline__ void stg32(void* p, uint32_t a) { asm volatile("st.global.u32 [%0], %1;\n" ::"l"(p), "r"(a) : "memory"); }
__device__ __forceinline__ bool all_nz(const uint4& v) { return v.x && v.y && v.z && v.w; }
#define SPIN_LIMIT (1 << 21)
#define TRAP() __trap()
__device__ __forceinline__ void hint_arrive(unsigned* g_hint, int idx, int sub) {
    asm volatile("red.relaxed.gpu.global.add.u32 [%0], 1;\n" ::"l"(&g_hint[sub * 32 + idx]) : "memory");
}
__device__ __forceinline__ void hint_wait(const unsigned* g_hint, int idx, unsigned target) {
    unsigned l;
    asm volatile("mov.u32 %0, %%laneid;" : "=r"(l));
    const unsigned* c = &g_hint[(l & 7) * 32 + idx];
    int it = 0;
    while (__any_sync(0xffffffffu, (int)(ld_poll32(c) - target) < 0)) { if (++it > SPIN_LIMIT) TRAP(); }
}
__device__ __forceinline__ void mbar_init(uint32_t bar, uint32_t cnt) { asm volatile("mbarrier.init.shared::cta.b64 [%0], %1;\n" ::"r"(bar), "r"(cnt) : "memory"); }
__device__ __forceinline__ void mbar_expect(uint32_t bar, uint32_t bytes) {
    asm volatile("mbarrier.arrive.expect_tx.shared::cta.b64 _, [%0], %1;\n" ::"r"(bar), "r"(bytes) : "memory");
}
__device__ __forceinline__ void mbar_arrive(uint32_t bar) { asm volatile("mbarrier.arrive.shared::cta.b64 _, [%0];\n" ::"r"(bar) : "memory"); }
__device__ __forceinline__ void mbar_wait(uint32_t bar) {
    asm volatile(
        "{\n.reg .pred p;\n"
        "W_%=:\n"
        "mbarrier.try_wait.parity.shared::cta.b64 p, [%0], 0;\n"
        "@!p bra W_%=;\n}\n" ::"r"(bar) : "memory");
}
__device__ __forceinline__ void bulk_s2g(void* dst, uint32_t src, uint32_t bytes) {
    asm volatile("cp.async.bulk.global.shared::cta.bulk_group [%0], [%1], %2;\ncp.async.bulk.commit_group;\n" ::"l"(dst), "r"(src), "r"(bytes) : "memory");
}
__device__ __forceinline__ void tma_2d(uint32_t dst, const CUtensorMap* tm, int c0, int c1, uint32_t bar) {
    asm volatile("cp.async.bulk.tensor.2d.shared::cluster.global.mbarrier::complete_tx::bytes [%0], [%1, {%3, %4}], [%2];\n"
                 ::"r"(dst), "l"(tm), "r"(bar), "r"(c0), "r"(c1) : "memory");
}
__device__ __forceinline__ void tma_3d(uint32_t dst, const CUtensorMap* tm, int c0, int c1, int c2, uint32_t bar) {
    asm volatile("cp.async.bulk.tensor.3d.shared::cluster.global.mbarrier::complete_tx::bytes [%0], [%1, {%3, %4, %5}], [%2];\n"
                 ::"r"(dst), "l"(tm), "r"(bar), "r"(c0), "r"(c1), "r"(c2) : "memory");
}
__device__ __forceinline__ void tma_st_3d(const CUtensorMap* tm, uint32_t src, int c0, int c1, int c2) {
    asm volatile("cp.async.bulk.tensor.3d.global.shared::cta.bulk_group [%0, {%2, %3, %4}], [%1];\ncp.async.bulk.commit_group;\n"
                 ::"l"(tm), "r"(src), "r"(c0), "r"(c1), "r"(c2) : "memory");
}
__device__ __forceinline__ bool elect_one() {
    uint32_t r;
    asm volatile("{\n.reg .pred p;\nelect.sync _|p, 0xffffffff;\nselp.u32 %0, 1, 0, p;\n}\n" : "=r"(r));
    return r;
}
__device__ __forceinline__ void fence_async() { asm volatile("fence.proxy.async.shared::cta;\n" ::: "memory"); }

__device__ __forceinline__ float2 cmul(float2 a, float2 b) {
    return make_float2(fmaf(a.x, b.x, -a.y * b.y), fmaf(a.x, b.y, a.y * b.x));
}
__device__ __forceinline__ float2 csq(float2 a) {
    float p = a.x * a.y;
    return make_float2(fmaf(a.x, a.x, -a.y * a.y), p + p);
}
__device__ __forceinline__ float2 cexp_e(float lr2, float rh, float rl, float e) {
    float m;
    asm("ex2.approx.ftz.f32 %0, %1;\n" : "=f"(m) : "f"(lr2 * e));
    const float a = rh * e;
    const float r = fmaf(rl, e, a - rintf(a)) * 6.283185307179586f;
    return make_float2(m * __cosf(r), m * __sinf(r));
}
__device__ __forceinline__ float rcp_approx(float x) { float r; asm("rcp.approx.ftz.f32 %0, %1;\n" : "=f"(r) : "f"(x)); return r; }
__device__ __forceinline__ float ex2_approx(float x) { float r; asm("ex2.approx.ftz.f32 %0, %1;\n" : "=f"(r) : "f"(x)); return r; }
__device__ __forceinline__ float sqrt_approx(float x) { float r; asm("sqrt.approx.ftz.f32 %0, %1;\n" : "=f"(r) : "f"(x)); return r; }

__device__ __forceinline__ void wg_fence() { asm volatile("wgmma.fence.sync.aligned;\n" ::: "memory"); }
__device__ __forceinline__ void wg_commit() { asm volatile("wgmma.commit_group.sync.aligned;\n" ::: "memory"); }
__device__ __forceinline__ void wg_wait0() { asm volatile("wgmma.wait_group.sync.aligned 0;\n" ::: "memory"); }
template <int T0, int NT> __device__ __forceinline__ void wg_h(uint32_t (&acc)[32], const uint32_t (&a)[4], uint64_t desc);
template <> __device__ __forceinline__ void wg_h<0, 16>(uint32_t (&acc)[32], const uint32_t (&a)[4], uint64_t desc) {
    asm volatile("wgmma.mma_async.sync.aligned.m64n128k16.f16.f16.f16 {%0,%1,%2,%3,%4,%5,%6,%7,%8,%9,%10,%11,%12,%13,%14,%15,%16,%17,%18,%19,%20,%21,%22,%23,%24,%25,%26,%27,%28,%29,%30,%31}, {%32,%33,%34,%35}, %36, 1, 1, 1, 0;\n"
                 : "+r"(acc[0]), "+r"(acc[1]), "+r"(acc[2]), "+r"(acc[3]), "+r"(acc[4]), "+r"(acc[5]), "+r"(acc[6]), "+r"(acc[7]), "+r"(acc[8]), "+r"(acc[9]), "+r"(acc[10]), "+r"(acc[11]), "+r"(acc[12]), "+r"(acc[13]), "+r"(acc[14]), "+r"(acc[15]), "+r"(acc[16]), "+r"(acc[17]), "+r"(acc[18]), "+r"(acc[19]), "+r"(acc[20]), "+r"(acc[21]), "+r"(acc[22]), "+r"(acc[23]), "+r"(acc[24]), "+r"(acc[25]), "+r"(acc[26]), "+r"(acc[27]), "+r"(acc[28]), "+r"(acc[29]), "+r"(acc[30]), "+r"(acc[31])
                 : "r"(a[0]), "r"(a[1]), "r"(a[2]), "r"(a[3]), "l"(desc));
}
template <> __device__ __forceinline__ void wg_h<4, 4>(uint32_t (&acc)[32], const uint32_t (&a)[4], uint64_t desc) {
    asm volatile("wgmma.mma_async.sync.aligned.m64n32k16.f16.f16.f16 {%0,%1,%2,%3,%4,%5,%6,%7}, {%8,%9,%10,%11}, %12, 1, 1, 1, 0;\n"
                 : "+r"(acc[8]), "+r"(acc[9]), "+r"(acc[10]), "+r"(acc[11]), "+r"(acc[12]), "+r"(acc[13]), "+r"(acc[14]), "+r"(acc[15])
                 : "r"(a[0]), "r"(a[1]), "r"(a[2]), "r"(a[3]), "l"(desc));
}
template <> __device__ __forceinline__ void wg_h<8, 4>(uint32_t (&acc)[32], const uint32_t (&a)[4], uint64_t desc) {
    asm volatile("wgmma.mma_async.sync.aligned.m64n32k16.f16.f16.f16 {%0,%1,%2,%3,%4,%5,%6,%7}, {%8,%9,%10,%11}, %12, 1, 1, 1, 0;\n"
                 : "+r"(acc[16]), "+r"(acc[17]), "+r"(acc[18]), "+r"(acc[19]), "+r"(acc[20]), "+r"(acc[21]), "+r"(acc[22]), "+r"(acc[23])
                 : "r"(a[0]), "r"(a[1]), "r"(a[2]), "r"(a[3]), "l"(desc));
}
template <> __device__ __forceinline__ void wg_h<12, 4>(uint32_t (&acc)[32], const uint32_t (&a)[4], uint64_t desc) {
    asm volatile("wgmma.mma_async.sync.aligned.m64n32k16.f16.f16.f16 {%0,%1,%2,%3,%4,%5,%6,%7}, {%8,%9,%10,%11}, %12, 1, 1, 1, 0;\n"
                 : "+r"(acc[24]), "+r"(acc[25]), "+r"(acc[26]), "+r"(acc[27]), "+r"(acc[28]), "+r"(acc[29]), "+r"(acc[30]), "+r"(acc[31])
                 : "r"(a[0]), "r"(a[1]), "r"(a[2]), "r"(a[3]), "l"(desc));
}
template <> __device__ __forceinline__ void wg_h<0, 8>(uint32_t (&acc)[32], const uint32_t (&a)[4], uint64_t desc) {
    asm volatile("wgmma.mma_async.sync.aligned.m64n64k16.f16.f16.f16 {%0,%1,%2,%3,%4,%5,%6,%7,%8,%9,%10,%11,%12,%13,%14,%15}, {%16,%17,%18,%19}, %20, 1, 1, 1, 0;\n"
                 : "+r"(acc[0]), "+r"(acc[1]), "+r"(acc[2]), "+r"(acc[3]), "+r"(acc[4]), "+r"(acc[5]), "+r"(acc[6]), "+r"(acc[7]), "+r"(acc[8]), "+r"(acc[9]), "+r"(acc[10]), "+r"(acc[11]), "+r"(acc[12]), "+r"(acc[13]), "+r"(acc[14]), "+r"(acc[15])
                 : "r"(a[0]), "r"(a[1]), "r"(a[2]), "r"(a[3]), "l"(desc));
}
template <> __device__ __forceinline__ void wg_h<4, 12>(uint32_t (&acc)[32], const uint32_t (&a)[4], uint64_t desc) {
    asm volatile("wgmma.mma_async.sync.aligned.m64n96k16.f16.f16.f16 {%0,%1,%2,%3,%4,%5,%6,%7,%8,%9,%10,%11,%12,%13,%14,%15,%16,%17,%18,%19,%20,%21,%22,%23}, {%24,%25,%26,%27}, %28, 1, 1, 1, 0;\n"
                 : "+r"(acc[8]), "+r"(acc[9]), "+r"(acc[10]), "+r"(acc[11]), "+r"(acc[12]), "+r"(acc[13]), "+r"(acc[14]), "+r"(acc[15]), "+r"(acc[16]), "+r"(acc[17]), "+r"(acc[18]), "+r"(acc[19]), "+r"(acc[20]), "+r"(acc[21]), "+r"(acc[22]), "+r"(acc[23]), "+r"(acc[24]), "+r"(acc[25]), "+r"(acc[26]), "+r"(acc[27]), "+r"(acc[28]), "+r"(acc[29]), "+r"(acc[30]), "+r"(acc[31])
                 : "r"(a[0]), "r"(a[1]), "r"(a[2]), "r"(a[3]), "l"(desc));
}

#define PBYTES 4608
#define DELAY(n) do { if (n) { const unsigned c0_ = clock32(); while ((int)(clock32() - c0_) < (n)) {} } } while (0)
#define KDEL 400
#define PDEL 300
#define CST(i) do { if ((warp & 3) == 0 && lane_v() == 0) { unsigned t_; asm volatile("mov.u32 %0, %%globaltimer_lo;" : "=r"(t_) :: "memory"); sts32(sb + SMEM_TOTAL - 768 + (warp >> 2) * 128 + (i) * 4, t_); } } while (0)
#define TP0 5000
#define TP4 5800
#define KDEL2 300
#define WSP 450
#define WS0 0
#define HINTW 10
#define WAS 0x0005
#define WA0 (WAS >> 12)
#define WA1 ((WAS >> 8) & 15)
#define WA2 ((WAS >> 4) & 15)
#define WA3 (WAS & 15)
#define WDAT 1
#define PAUSE 2
#define PCNT (32 + ((PAUSE & 1) ? 288 : 0) + ((PAUSE & 6) ? 320 : 64))
#define LNAT 2
#define UW 8
#define FINAT 3
#define UAT 2
#define TOKEN_OF(g) (16 * ((g) & 1) + ((g) >> 2) + 2 * ((g) & 2))
#define HI2(a, b) (pack_f16_rz(__uint_as_float(a), __uint_as_float(b)) & 0xfff8fff8u)
struct Params {
    const bf16 *x, *lar, *aim, *cre, *cim, *ldt, *dsk;
    Scratch* s;
    const bf16* wr;
    bf16* out;
};

template <int NK>
__device__ __forceinline__ void ln_partial(const uint32_t (&H)[2][NK], const uint32_t (&bw)[NK], uint32_t lp, int warp, int g, int t) {
    float cs[4] = {0.f, 0.f, 0.f, 0.f}, cl[4] = {0.f, 0.f, 0.f, 0.f}, ch[4] = {0.f, 0.f, 0.f, 0.f};
#pragma unroll
    for (int k = 0; k < NK; k += 2) {
        uint32_t a0, a1, a2, a3;
        asm volatile("prmt.b32 %0, %4, %4, %8;\nprmt.b32 %1, %5, %5, %8;\nprmt.b32 %2, %6, %6, %8;\nprmt.b32 %3, %7, %7, %8;\n"
                     : "=r"(a0), "=r"(a1), "=r"(a2), "=r"(a3) : "r"(H[0][k]), "r"(H[1][k]), "r"(H[0][k + 1]), "r"(H[1][k + 1]), "r"(0x3210u + (warp >> 8)));
        mma_bf16(cl, a0, a1, a2, a3, H[0][k], H[0][k + 1]);
        mma_bf16(ch, a0, a1, a2, a3, H[1][k], H[1][k + 1]);
        mma_bf16(cs, a0, a1, a2, a3, bw[k], bw[k + 1]);
    }
    const uint32_t a = lp + (g * 20 + warp) * 4;
    if (t == 0) {
        stsf(a, cs[1]); stsf(a + 8 * 80, cs[3]);
        if (NK == 4) { stsf(a + 48 * 80, cs[0]); stsf(a + 56 * 80, cs[2]); }
    }
    if (t == (g >> 1)) { stsf(a + 16 * 80, (g & 1) ? cl[1] : cl[0]); stsf(a + 24 * 80, (g & 1) ? ch[3] : ch[2]); }
}
__device__ __forceinline__ float sum18(uint32_t a) {
    const uint4 p = lds128(a), q = lds128(a + 16), r = lds128(a + 32), s = lds128(a + 48);
    const uint2 u = lds64(a + 64);
#define F(x) __uint_as_float(x)
    return (((F(p.x) + F(p.y)) + (F(p.z) + F(p.w))) + ((F(q.x) + F(q.y)) + (F(q.z) + F(q.w)))) +
           (((F(r.x) + F(r.y)) + (F(r.z) + F(r.w))) + ((F(s.x) + F(s.y)) + (F(s.z) + F(s.w))) + (F(u.x) + F(u.y)));
#undef F
}
__device__ __forceinline__ float sum9(uint32_t a) {
    const uint4 p = lds128(a), q = lds128(a + 16);
#define F(x) __uint_as_float(x)
    return (((F(p.x) + F(p.y)) + (F(p.z) + F(p.w))) + ((F(q.x) + F(q.y)) + (F(q.z) + F(q.w)))) + ldsf(a + 32);
#undef F
}
template <int N>
__device__ __forceinline__ void ln_finish(uint32_t lp, int lane, float& mb, float& rc) {
    const float v = N == 9 ? sum9(lp + lane * 80) : sum18(lp + lane * 80);
    const float o = __shfl_xor_sync(0xffffffffu, v, 16);
    const float m0 = v * (1.0f / 576.0f);
    const float mean = fmaf(fmaf(-m0, 576.0f, v), 1.0f / 576.0f, m0);
    const float var = fmaxf(fmaf(o, 1.0f / 576.0f, -(mean * mean)), 0.f);
    mb = rbf(mean);
    rc = rcp_approx(rbf(sqrt_approx(rbf(rbf(var) + 1e-5f))));
}
__device__ __forceinline__ uint32_t ln_apply(uint32_t w, const uint2& st) {
    uint32_t r;
    asm("{\n.reg .b16 m, t, h, l;\n.reg .b32 mm, hh, ll, d, e;\nmov.b32 {m, t}, %2;\nmov.b32 {h, l}, %3;\nmov.b32 mm, {m, m};\nmov.b32 hh, {h, h};\nmov.b32 ll, {l, l};\n"
        "sub.rn.bf16x2 d, %1, mm;\nmul.rn.bf16x2 e, d, ll;\nfma.rn.bf16x2 %0, d, hh, e;\n}\n" : "=r"(r) : "r"(w), "r"(st.x), "r"(st.y));
    return r;
}
__device__ __forceinline__ void stat_store(uint32_t a, float mb, float rc, uint32_t extra) {
    const float rh = rbf(rc);
    sts64(a, (__float_as_uint(mb) >> 16) | (extra << 16), pack_bf16(rh, rc - rh));
}

__device__ __forceinline__ void hcmul(uint32_t re, uint32_t im, uint32_t z, uint32_t& ore, uint32_t& oim) {
    asm("{\n.reg .b16 x, y;\n.reg .b32 xx, yy, ny, a, b;\nmov.b32 {x, y}, %4;\nmov.b32 xx, {x, x};\nmov.b32 yy, {y, y};\nneg.f16x2 ny, yy;\n"
        "mul.rn.f16x2 a, %2, xx;\nfma.rn.f16x2 %0, %3, ny, a;\nmul.rn.f16x2 b, %3, xx;\nfma.rn.f16x2 %1, %2, yy, b;\n}\n" : "=&r"(ore), "=r"(oim) : "r"(re), "r"(im), "r"(z));
}
__device__ __forceinline__ void hcmul(uint32_t re, uint32_t im, uint32_t zx, uint32_t zy, uint32_t& ore, uint32_t& oim) {
    asm("{\n.reg .b32 ny, a, b;\nneg.f16x2 ny, %5;\n"
        "mul.rn.f16x2 a, %2, %4;\nfma.rn.f16x2 %0, %3, ny, a;\nmul.rn.f16x2 b, %3, %4;\nfma.rn.f16x2 %1, %2, %5, b;\n}\n" : "=&r"(ore), "=r"(oim) : "r"(re), "r"(im), "r"(zx), "r"(zy));
}

struct KGen {
    uint32_t Af[4][4];
    float2 z1, z8, z64, z128, T[9];
    uint32_t zw;
};
__device__ __forceinline__ void kgen_setup(KGen& k, uint32_t pa, float dt) {
    const float A = rbf(expf(bf_lo(pa)));
    const float lr2 = -(A * dt) * 1.4426950408889634f;
    const float li = bf_hi(pa) * dt;
    const float rh = li * 0.15915494309189535f;
    const float rl = fmaf(li, 6.4206382986e-9f, fmaf(li, 0.15915494309189535f, -rh));
    k.z1 = cexp_e(lr2, rh, rl, 1.0f);
    k.z8 = cexp_e(lr2, rh, rl, 8.0f);
    k.z64 = cexp_e(lr2, rh, rl, 64.0f);
}
__device__ __forceinline__ void kgen_rows(KGen& k, uint32_t tb, int lane) {
    const float2 z8 = k.z8, z64 = k.z64;
    const uint32_t row = tb + lane * TBP;
    k.z128 = csq(z64);
    const float2 z16 = csq(z8), z32 = csq(z16), z48 = cmul(z32, z16), z80 = cmul(z64, z16), z96 = cmul(z64, z32), z112 = cmul(z64, z48);
    uint32_t re[4], im[4], a[4], b[4];
    re[0] = pack_f16(1.0f, z16.x); im[0] = pack_f16(0.0f, z16.y);
    re[1] = pack_f16(z32.x, z48.x); im[1] = pack_f16(z32.y, z48.y);
    re[2] = pack_f16(z64.x, z80.x); im[2] = pack_f16(z64.y, z80.y);
    re[3] = pack_f16(z96.x, z112.x); im[3] = pack_f16(z96.y, z112.y);
    sts128(row, re[0], re[1], re[2], re[3]);
    sts128(row + 32, im[0], im[1], im[2], im[3]);
    const uint32_t zz = pack_f16(z8.x, z8.y);
#pragma unroll
    for (int j = 0; j < 4; j++) hcmul(re[j], im[j], zz, a[j], b[j]);
    sts128(row + 16, a[0], a[1], a[2], a[3]);
    sts128(row + 48, b[0], b[1], b[2], b[3]);
    __syncwarp();
    const int mi = lane >> 3;
    const uint32_t ad = tb + (lane & 7) * TBP + mi * 16;
#pragma unroll
    for (int ks = 0; ks < 4; ks++) ldsm_x4_t(k.Af[ks][0], k.Af[ks][1], k.Af[ks][2], k.Af[ks][3], ad + ks * 8 * TBP);
}
__device__ __forceinline__ void kgen_chain(KGen& k, uint32_t pc, float cs) {
    k.T[0] = make_float2(bf_lo(pc) * cs, -bf_hi(pc) * cs);
    const float2 y1 = make_float2(k.z1.x, -k.z1.y);
#pragma unroll
    for (int c = 1; c < 8; c++) k.T[c] = cmul(k.T[c - 1], y1);
    k.T[8] = cmul(k.T[0], make_float2(k.z8.x, -k.z8.y));
}
__device__ __forceinline__ void kgen_cols(KGen& k, uint32_t tb, int lane) {
    const uint32_t row = tb + lane * TBP;
    const float2 (&T)[9] = k.T;
    const uint32_t zv = pack_f16(k.z128.x, k.z128.y), zo = __shfl_xor_sync(0xffffffffu, zv, 1);
    k.zw = (lane & 1) ? __byte_perm(zo, zv, 0x7632) : __byte_perm(zv, zo, 0x5410);
    const float2 y256 = csq(make_float2(k.z128.x, -k.z128.y)), y512 = csq(y256), y768 = cmul(y512, y256), y1024 = csq(y512);
    const float2 c1032 = cmul(T[8], y1024);
    const uint32_t r04 = pack_f16(T[0].x, T[4].x), i04 = pack_f16(T[0].y, T[4].y), r26 = pack_f16(T[2].x, T[6].x), i26 = pack_f16(T[2].y, T[6].y);
    const uint32_t r48 = pack_f16(T[4].x, T[8].x), i48 = pack_f16(T[4].y, T[8].y);
    __syncwarp();
    sts128(row, r04, pack_f16(T[1].x, T[5].x), r26, pack_f16(T[3].x, T[7].x));
    sts128(row + 16, i04, pack_f16(T[1].y, T[5].y), i26, pack_f16(T[3].y, T[7].y));
    uint32_t a[4], b[4];
    {
        const uint32_t zz = pack_f16(y256.x, y256.y);
        hcmul(r04, i04, zz, a[0], b[0]);
        hcmul(r26, i26, zz, a[2], b[2]);
        hcmul(r48, i48, zz, a[3], b[3]);
    }
    sts128(row + 32, a[0], a[0], a[2], a[3]);
    sts128(row + 48, b[0], b[0], b[2], b[3]);
    {
        hcmul(r48, i48, pack_f16(y512.x, y512.y), a[0], b[0]);
        hcmul(r48, i48, pack_f16(y768.x, y768.y), a[1], b[1]);
        const uint32_t zz = pack_f16(c1032.x, c1032.y);
        hcmul(pack_f16(1.0f, y256.x), pack_f16(0.0f, y256.y), zz, a[2], b[2]);
        hcmul(pack_f16(y512.x, y768.x), pack_f16(y512.y, y768.y), zz, a[3], b[3]);
    }
    sts128(row + 64, a[0], a[1], a[2], a[3]);
    sts128(row + 80, b[0], b[1], b[2], b[3]);
}
__device__ __forceinline__ void kgen_mma(const KGen& k, uint32_t tb, int lane) {
    const int t = lane & 3;
    const uint32_t zw = k.zw;
    uint32_t zx[4], zy[4];
#pragma unroll
    for (int ks = 0; ks < 4; ks++) { zx[ks] = __shfl_sync(0xffffffffu, zw, 8 * ks + 2 * t); zy[ks] = __shfl_sync(0xffffffffu, zw, 8 * ks + 2 * t + 1); }
    __syncwarp();
    float acc[2][3][4];
#pragma unroll
    for (int i = 0; i < 6; i++)
#pragma unroll
        for (int j = 0; j < 4; j++) acc[i / 3][i % 3][j] = 0.f;
    {
        const int mi = lane >> 3;
        const uint32_t bd = tb + ((lane & 7) + 8 * (mi >> 1)) * TBP + (mi & 1) * 16;
#pragma unroll
        for (int kp = 0; kp < 2; kp++) {
            uint32_t b[3][4];
#pragma unroll
            for (int j = 0; j < 3; j++) ldsm_x4_t(b[j][0], b[j][1], b[j][2], b[j][3], bd + kp * 16 * TBP + j * 32);
#pragma unroll
            for (int h = 0; h < 2; h++) {
                const int ks = 2 * kp + h;
                uint32_t d[4];
                hcmul(k.Af[ks][0], k.Af[ks][2], zx[ks], zy[ks], d[0], d[2]);
                hcmul(k.Af[ks][1], k.Af[ks][3], zx[ks], zy[ks], d[1], d[3]);
#pragma unroll
                for (int j = 0; j < 3; j++) {
                    mma_f16(acc[0][j], k.Af[ks][0], k.Af[ks][1], k.Af[ks][2], k.Af[ks][3], b[j][2 * h], b[j][2 * h + 1]);
                    mma_f16(acc[1][j], d[0], d[1], d[2], d[3], b[j][2 * h], b[j][2 * h + 1]);
                }
            }
        }
    }
    __syncwarp();
#pragma unroll
    for (int h = 0; h < 2; h++) {
        sts64(tb + h * 256 + lane * 8, pack_f16(acc[h][0][0], acc[h][0][1]), pack_f16(acc[h][0][2], acc[h][0][3]));
        sts64(tb + 512 + h * 256 + lane * 8, pack_f16(acc[h][1][0], acc[h][1][1]), pack_f16(acc[h][1][2], acc[h][1][3]));
        sts32(tb + 1024 + h * 256 + lane * 4, pack_f16(acc[h][2][0], t < 2 ? acc[h][2][1] : acc[h][2][2]));
        sts32(tb + 1152 + h * 256 + lane * 4, pack_f16(t < 2 ? acc[h][2][2] : acc[h][2][1], acc[h][2][3]));
    }
}
__device__ __forceinline__ uint32_t table_buf(uint32_t sb, int warp) { return sb + SM_TB + warp * TBW; }

__device__ __forceinline__ void kgen_combine(uint32_t sb, int warp, int lane, uint32_t kw, uint32_t ao) {
    const int wq = warp & 3;
    const uint32_t a = table_buf(sb, warp & ~3) + wq * 256 + lane * 8, c = table_buf(sb, warp & ~3) + 1024 + wq * 128 + lane * 4;
    const int t = lane & 3;
    const uint32_t o0 = (t < 2 ? KW_T2 + KW_KH + 16 + t * 256 - (wq & 1) * KW_KH : KW_T3 + 16 - 1024 + t * 512 + (wq & 1) * 256) + (lane >> 2) * 16;
    const uint4 o = make_uint4(o0 + t * 36, o0 + (t ^ 1) * 36, o0 + (t ^ 2) * 36, o0 + (t ^ 3) * 36);
    const uint2 u = lds64(a), v = lds64(a + TBW), w = lds64(a + 2 * TBW), x = lds64(a + 3 * TBW);
    const uint32_t kt = hadd2(hadd2(lds32(c), lds32(c + TBW)), hadd2(lds32(c + 2 * TBW), lds32(c + 3 * TBW)));
    const uint32_t k23 = hadd2(hadd2(u.y, v.y), hadd2(w.y, x.y));
    sts64(kw + wq * 64 + ao, hadd2(hadd2(u.x, v.x), hadd2(w.x, x.x)), k23);
    const uint32_t d = kw + (wq >> 1) * 128;
    const uint32_t kh = hmul2(kt, 0x38003800u);
    sts32(d + o.x, kh); sts32(d + o.y, kh); sts32(d + o.z, kh); sts32(d + o.w, kh);
    if (wq == 3) {
        if (lane == 31) { sts32(kw + 264, k23 >> 16); sts32(kw + 288 + 264, k23 >> 16); sts32(kw + 576 + 264, k23 >> 16); }
        if (lane == 29) { sts32(kw + 864 + 280, kt >> 16); sts32(kw + 280, kt & 0xffff0000u); }
    }
}

__device__ __forceinline__ int c_exponent(const uint2& r, const uint2& i) {
    uint32_t mx = __vmaxu2(__vmaxu2(r.x & 0x7fff7fffu, r.y & 0x7fff7fffu), __vmaxu2(i.x & 0x7fff7fffu, i.y & 0x7fff7fffu));
    mx = __reduce_max_sync(0xffffffffu, max(mx & 0xffffu, mx >> 16));
    return min(max((int)(mx >> 7), 4), 240);
}

__device__ __forceinline__ int warp_v() { int l; asm volatile("mov.u32 %0, %%tid.x;" : "=r"(l)); return __shfl_sync(0xffffffffu, l >> 5, 0); }
__device__ __forceinline__ int lane_v() { int l; asm volatile("mov.u32 %0, %%laneid;" : "=r"(l)); return l; }
__device__ __forceinline__ unsigned clock32() { unsigned c; asm volatile("mov.u32 %0, %%clock;" : "=r"(c)); return c; }
__device__ __forceinline__ uint32_t prmt(uint32_t a, uint32_t b, uint32_t s) { uint32_t d; asm("prmt.b32 %0, %1, %2, %3;\n" : "=r"(d) : "r"(a), "r"(b), "r"(s)); return d; }
__device__ __forceinline__ uint32_t prmt_v(uint32_t a, uint32_t b, uint32_t s) { uint32_t d; asm volatile("prmt.b32 %0, %1, %2, %3;\n" : "=r"(d) : "r"(a), "r"(b), "r"(s)); return d; }
__device__ __forceinline__ void mmah16(uint32_t& d0, uint32_t& d1, uint32_t a0, uint32_t a1, uint32_t a2, uint32_t a3, uint32_t b0, uint32_t b1, uint32_t c0, uint32_t c1) {
    asm volatile("mma.sync.aligned.m16n8k16.row.col.f16.f16.f16.f16 {%0,%1}, {%2,%3,%4,%5}, {%6,%7}, {%8,%9};\n"
                 : "=r"(d0), "=r"(d1) : "r"(a0), "r"(a1), "r"(a2), "r"(a3), "r"(b0), "r"(b1), "r"(c0), "r"(c1));
}
__device__ __forceinline__ void mmah8(uint32_t& d0, uint32_t& d1, uint32_t a0, uint32_t a1, uint32_t b0, uint32_t c0, uint32_t c1) {
    asm volatile("mma.sync.aligned.m16n8k8.row.col.f16.f16.f16.f16 {%0,%1}, {%2,%3}, {%4}, {%5,%6};\n"
                 : "=r"(d0), "=r"(d1) : "r"(a0), "r"(a1), "r"(b0), "r"(c0), "r"(c1));
}
template <int A = 8, int B = 32>
__device__ __forceinline__ void conv_rename(uint32_t (&acc)[32]) {
#pragma unroll
    for (int i = A; i < B; i++) { uint32_t v; asm volatile("mov.b32 %0, %1;\n" : "=r"(v) : "r"(acc[i])); acc[i] = v; }
}
__host__ __device__ constexpr uint32_t band_bits(int hw, int sh) {
    uint32_t c = 0;
    for (int s = 0; s <= 10; s++)
        for (int e = 0; e < 2; e++) {
            const int v = s - 3 + sh - 4 * e;
            if (v <= hw && v >= -hw) c |= 1u << (14 + 16 * e - s);
        }
    return c;
}
template <int HW, int SH, int J> __device__ __forceinline__ uint32_t band(uint32_t p2) {
    uint32_t d;
    asm volatile("{\n.reg .b32 t;\nmul.lo.u32 t, %1, %2;\nand.b32 %0, t, 0x40004000;\n}\n" : "=r"(d) : "r"(p2), "n"(band_bits(HW, SH) | J));
    return d;
}
__device__ __forceinline__ void band_quads(uint4 (&b)[3], uint32_t p2, uint32_t pm) {
    b[0] = make_uint4(band<2, 4, 1>(pm), band<1, 4, 1>(p2), band<2, -4, 1>(pm), band<1, -4, 1>(p2));
    b[1] = make_uint4(band<4, 4, 1>(pm), band<3, 4, 1>(pm), band<4, -4, 1>(pm), band<3, -4, 1>(pm));
    b[2] = make_uint4(band<2, 4, 2>(pm), band<4, 4, 2>(pm), band<2, -4, 2>(pm), band<4, -4, 2>(pm));
}
__device__ __forceinline__ uint2 run_sums(const uint4& a, uint32_t b0, uint32_t b1) {
    uint2 d;
    mmah16(d.x, d.y, a.x, a.y, a.z, a.w, b0, b1, 0u, 0u);
    return d;
}
__device__ __forceinline__ float h_lo(uint32_t w) { return __half2float(__ushort_as_half((unsigned short)(w & 0xffffu))); }
__device__ __forceinline__ float h_hi(uint32_t w) { return __half2float(__ushort_as_half((unsigned short)(w >> 16))); }
__device__ __forceinline__ uint64_t smem_desc(uint32_t sb, uint32_t o16, uint32_t lbo) {
    uint64_t d;
    asm("mov.b64 %0, {%1, %2};" : "=l"(d) : "r"(((sb & 0x3FFFF) >> 4) + o16 + (lbo << 12)), "r"(8));
    return d;
}
template <int I> struct IC { static constexpr int value = I; };

#define STG3 1
struct Conv {
    uint32_t q2[3][2][4];
    uint32_t q3[2][4];
    uint32_t r[18];
};
struct ConvPre {
    uint32_t a[5], b[5];
    uint32_t t[4];
};
__device__ __forceinline__ void conv_pre(ConvPre& e, uint32_t ka, uint32_t ks, uint32_t sel) {
    const uint4 r = lds128(ka + 256), s = lds128(ka + 272);
    ldsm_x4(e.t[0], e.t[1], e.t[2], e.t[3], ks);
    const uint32_t sw = sel ^ 0x4444u;
    e.a[0] = prmt(r.y, r.z, sel); e.a[1] = prmt(r.w, r.z, sw); e.a[2] = prmt(r.x, r.y, sel); e.a[3] = prmt(r.z, r.y, sw); e.a[4] = prmt(r.z, r.w, sel);
    e.b[0] = prmt(s.y, s.z, sel); e.b[1] = prmt(s.w, s.z, sw); e.b[2] = prmt(s.x, s.y, sel); e.b[3] = prmt(s.z, s.y, sw); e.b[4] = prmt(s.z, s.w, sel);
}
__device__ __forceinline__ void conv_sums(Conv& c, uint32_t (&acc)[32], const ConvPre& e, uint32_t a0, uint32_t a1, const uint4 (&bd)[3], uint32_t ka, uint32_t sel, int wq, bool odd) {
#pragma unroll
    for (int i = 0; i < 32; i++) acc[i] = 0u;
    uint32_t un[4], vn[4];
    ldsm_x4(un[0], un[1], un[2], un[3], a1);
    ldsm_x4(vn[0], vn[1], vn[2], vn[3], a0);
#pragma unroll
    for (int q = 0; q < 3; q++) {
        const uint32_t u[4] = {un[0], un[1], un[2], un[3]}, v[4] = {vn[0], vn[1], vn[2], vn[3]};
        if (STG3 && q && sel == 0u) {
            sts128(ka, c.q3[q - 1][0], c.q3[q - 1][1], c.q3[q - 1][2], c.q3[q - 1][3]);
            sts64(ka, acc[8 * q], acc[8 * q + 8]);
        }
        if (q < 2) {
            ldsm_x4(un[0], un[1], un[2], un[3], a1 + q * 512 + 512);
            ldsm_x4(vn[0], vn[1], vn[2], vn[3], a0 + q * 512 + 512);
        } else if (STG3 == 2) {
            const uint32_t a = ka + wq * 64;
#pragma unroll
            for (int i = 0; i < 4; i++) { const uint4 v = lds128(a + i * 16); c.r[4 * i] = v.x; c.r[4 * i + 1] = v.y; c.r[4 * i + 2] = v.z; c.r[4 * i + 3] = v.w; }
            const uint2 v = lds64(a + 64);
            c.r[16] = v.x; c.r[17] = v.y;
            if (sel == 1u) sts32(ka, 0u);
        }
        mmah8(acc[8 * q + 8], acc[8 * q + 9], e.a[4], 0u, u[1], acc[8 * q + 8], acc[8 * q + 9]);
        mmah16(acc[8 * q + 8], acc[8 * q + 9], e.a[0], e.a[1], e.a[2], e.a[3], u[2], u[3], acc[8 * q + 8], acc[8 * q + 9]);
        const uint2 z0 = run_sums(bd[2], v[0], v[1]);
        if (q < 2) {
            mmah8(acc[8 * q + 16], acc[8 * q + 17], e.b[4], 0u, u[1], 0u, 0u);
            mmah16(acc[8 * q + 16], acc[8 * q + 17], e.b[0], e.b[1], e.b[2], e.b[3], u[2], u[3], acc[8 * q + 16], acc[8 * q + 17]);
            const uint2 y1 = run_sums(bd[1], u[0], u[1]), y2 = run_sums(bd[1], v[2], v[3]), y3 = run_sums(bd[1], u[2], u[3]);
            const uint32_t n0 = odd ? y1.x : z0.y, n1 = odd ? y2.x : y1.x, s1 = odd ? y2.y : y1.y, s2 = odd ? y3.y : y2.y;
            c.q3[q][0] = prmt(s1, n0, 0x7632u); c.q3[q][1] = prmt(s2, n1, 0x7632u);
            c.q3[q][2] = prmt(s1, n0, 0x5410u); c.q3[q][3] = prmt(s2, n1, 0x5410u);
        }
        const uint2 x1 = run_sums(bd[0], u[0], u[1]), x2 = run_sums(bd[0], v[2], v[3]), x3 = run_sums(bd[0], u[2], u[3]);
        const uint32_t f0 = odd ? x1.x : z0.x, f1 = odd ? x2.x : x1.x, f2 = odd ? x3.x : x2.x;
#pragma unroll
        for (int h = 0; h < 2; h++) {
            const uint32_t s = h ? 0x7632u : 0x5410u;
            c.q2[q][h][0] = prmt(x1.y, f0, s); c.q2[q][h][1] = prmt(x2.y, f1, s);
            c.q2[q][h][2] = prmt(f1, x2.y, s ^ 0x4444u); c.q2[q][h][3] = prmt(x3.y, f2, s);
            if (q < 2) mmah16(acc[8 * q + 16], acc[8 * q + 17], c.q2[q][h][0], c.q2[q][h][1], c.q2[q][h][2], c.q2[q][h][3], e.t[2 * h], e.t[2 * h + 1], acc[8 * q + 16], acc[8 * q + 17]);
        }
    }
    if (STG3 != 2) {
        const uint32_t a = ka + wq * 64;
#pragma unroll
        for (int i = 0; i < 4; i++) { const uint4 v = lds128(a + i * 16); c.r[4 * i] = v.x; c.r[4 * i + 1] = v.y; c.r[4 * i + 2] = v.z; c.r[4 * i + 3] = v.w; }
        const uint2 v = lds64(a + 64);
        c.r[16] = v.x; c.r[17] = v.y;
    }
    if (sel == 0u) {
#pragma unroll
        for (int i = 0; i < 6; i++) sts128(ka + i * 16, c.q2[i >> 1][i & 1][0], c.q2[i >> 1][i & 1][1], c.q2[i >> 1][i & 1][2], c.q2[i >> 1][i & 1][3]);
#pragma unroll
        for (int i = 0; i < 2; i++) sts128(ka + i * 16, c.q3[i][0], c.q3[i][1], c.q3[i][2], c.q3[i][3]);
#pragma unroll
        for (int i = 1; i < 4; i++) sts64(ka + i * 16, acc[8 * i], acc[8 * i + 1]);
    }
    conv_rename(acc);
}
#define SPACE 100
#define SPN 3
#define O4 4
#define B2L 1
#define GATE 2
#define HAND 2
#define GA 6
#define GB 4
template <int TA, int TB, int IA, class FG>
__device__ __forceinline__ void conv_tail(uint32_t (&acc)[32], const uint32_t (&a)[8][4], uint32_t sb, unsigned char* gy0, int warp, size_t ycopy, FG fg) {
    const int wg = warp >> 2, wq = warp & 3, ord = TA == 0 && TB == 16 ? 3 - wg + (3 - wg >= O4) : O4;
    const uint32_t ub = sb + SM_U + wg * USLOT_B + UPAD * 16, turn = sb + SM_MISC + 376 + ord * 8, sfs = sb + SM_MISC + 256 + wg * 8;
    const uint32_t du = wg * (USLOT_B / 16) + (SM_U / 16 + UPAD + TA * 8);
    uint32_t ud[8], fs;
    auto skip = [&]() {
        const int lane = lane_v();
        const uint32_t ua = ub + ((lane >> 3) & 1) * ULO_B + (8 * wq + (lane & 7)) * 16 + (lane >> 4) * 512;
        if (IA == 0) ldsm_x4_t(ud[0], ud[1], ud[2], ud[3], ua);
        if (TB == 16) ldsm_x4_t(ud[4], ud[5], ud[6], ud[7], ua + 1024);
        const uint2 fd = lds64(sfs);
        fs = fd.x;
        const float dsk = __uint_as_float(fd.y);
#pragma unroll
        for (int i = 2 * IA; i < TB / 2; i++) ud[i] = pack_bf16(h_lo(ud[i]) * dsk, h_hi(ud[i]) * dsk);
    };
    conv_rename<2 * TA, 2 * TB>(acc);
    if (__builtin_expect(ord != 0, 0)) {
        skip();
        mbar_wait(turn);
    } else if (B2L) {
        bar_sync(0, NWRK);
    }
    if (O4 < 4 || (TA == 0 && TB == 16)) asm volatile("{\n.reg .pred p;\nelect.sync _|p, 0xffffffff;\n@p mbarrier.arrive.shared::cta.b64 _, [%0];\n}\n" ::"r"(turn + 48) : "memory");
    fg(IC<8>());
    wg_fence();
#pragma unroll
    for (int m = 7; m >= 0; m--) {
        wg_h<TA, TB - TA>(acc, a[m], smem_desc(sb, du - m, ULO_B));
        if (m == GA || m == GB || m == HAND) wg_commit();
        if (m == GB) asm volatile("wgmma.wait_group.sync.aligned 1;\n" ::: "memory");
    }
    wg_commit();
    if (O4 < 4 || (TA == 0 && TB == 16)) {
        asm volatile("wgmma.wait_group.sync.aligned 1;\n" ::: "memory");
        asm volatile("{\n.reg .pred p;\nelect.sync _|p, 0xffffffff;\n@p mbarrier.arrive.shared::cta.b64 _, [%0];\n}\n" ::"r"(turn + 8) : "memory");
    }
    __syncwarp();
    fg(IC<3>());
    if (!ord) skip();
    fg(IC<4>());
    const int lane = lane_v();
    const uint32_t lp = sb + SM_PL + (ord >= 3 ? ord - 3 : ord) * PL_B + lane * 8;
    unsigned char* gy = gy0 + ((4 * wq + (lane & 3)) * DM + (TA == 0 && TB == 16 ? 4 * blockIdx.x + wg : 512 + (blockIdx.x >> 1))) * 64 + (lane >> 2) * 8;
    const uint32_t st = lp + (wq * 12 - ((wq * (wq - 1)) >> 1)) * 256;
    uint32_t ld[3];
#pragma unroll
    for (int s = 1; s < 4; s++) {
        const int w = (wq - s) & 3;
        ld[s - 1] = lp + (w * 12 - ((w * (w - 1)) >> 1) + s - 1 - (wq < s ? 3 : 0)) * 256;
    }
    const uint32_t one = 1u + (warp >> 8);
    if (one == 0u) stg64(gy, ld[0], ld[1]);
    if (ord >= 3) bar_sync(9 + ord, 256);
    wg_wait0();
    fg(IC<6>());
#pragma unroll
    for (int j = TA; j < TB; j++)
        if ((j & 3) && j + 3 >= 4 * IA && (j + 3 < TB || j + wq < TB)) sts64(st + (j - 1 - (j >> 2)) * 256, acc[2 * j], acc[2 * j + 1]);
    bar_sync(1 + wg, 128);
    fg(IC<7>());
    uint2 v[4][3];
#pragma unroll
    for (int i = IA; i < TB / 4; i++)
#pragma unroll
        for (int s = 0; s < 3; s++) {
            if (i == 0) { v[i][s] = make_uint2(0u, 0u); if (wq > s) v[i][s] = lds64(ld[s]); }
            else v[i][s] = lds64(ld[s] + i * 768);
        }
    fg(IC<5>());
#pragma unroll
    for (int i = IA; i < TB / 4; i++) {
        const uint32_t x0 = hadd2(v[i][0].x, acc[8 * i]), x1 = hadd2(v[i][1].x, v[i][2].x), y0 = hadd2(v[i][0].y, acc[8 * i + 1]), y1 = hadd2(v[i][1].y, v[i][2].y);
        const uint32_t lo = pack_bf16(h_lo(x0) + h_lo(x1), h_hi(x0) + h_hi(x1)), hi = pack_bf16(h_lo(y0) + h_lo(y1), h_hi(y0) + h_hi(y1));
        ud[2 * i] = max(hfma2_bf(lo, fs, ud[2 * i]), one); ud[2 * i + 1] = hfma2_bf(hi, fs, ud[2 * i + 1]);
    }
    if (SPACE && TA == 0 && TB == 16 && ord < SPN) {
#pragma unroll
        for (int i = 0; i < 4; i++) {
            stg64(gy + i * 16 * DM * 64, ud[2 * i], ud[2 * i + 1]);
            if (i < 3) { const unsigned c0 = clock32(); while (clock32() - c0 < SPACE) {} }
        }
    } else {
#pragma unroll
        for (int i = IA; i < TB / 4; i++) stg64(gy + i * 16 * DM * 64, ud[2 * i], ud[2 * i + 1]);
    }
    if (ord < 2) bar_arrive(12 + ord, 256);
}
template <int M0, int M1>
__device__ __forceinline__ void conv_frags(uint32_t (&a)[8][4], const uint32_t (&r)[18], uint32_t sel, uint32_t dep, int warp) {
    const uint32_t s = prmt_v(sel, dep, 0x3210u + (warp >> 8)), sw = s ^ 0x4444u;
#pragma unroll
    for (int m = M0; m < M1; m++) {
        a[m][0] = prmt_v(r[2 * m + 1], r[2 * m + 2], s); a[m][1] = prmt_v(r[2 * m + 2], r[2 * m + 3], s);
        a[m][2] = prmt_v(r[2 * m + 1], r[2 * m], sw); a[m][3] = prmt_v(r[2 * m + 2], r[2 * m + 1], sw);
    }
}
template <class FG>
__device__ __forceinline__ void conv_main(const Conv& c, uint32_t (&acc)[32], uint32_t sb, uint32_t sel, unsigned char* gy, int warp, size_t ycopy, FG fg) {
    const uint32_t kw = (warp >> 2) * (KW_B / 16) + SM_KW / 16;
    const uint64_t d2 = smem_desc(sb, kw + KW_T2 / 16, KW_KH), d2b = smem_desc(sb, kw + KW_T2 / 16 + 1, KW_KH), d3 = smem_desc(sb, kw + KW_T3 / 16, 16), d3b = smem_desc(sb, kw + KW_T3 / 16 + 32, 16);
    uint32_t a[8][4];
    {
        const int ord = warp < 16 ? 3 - (warp >> 2) + (3 - (warp >> 2) >= O4) : O4;
        if (__builtin_expect(ord >= GATE, 0)) {
            fg(IC<1>());
            mbar_wait(sb + SM_MISC + 376 + 48 + (ord - GATE) * 8);
        }
    }
    wg_fence();
    wg_h<12, 4>(acc, c.q3[0], d3b); wg_h<8, 4>(acc, c.q3[0], d3); wg_h<4, 4>(acc, c.q2[0][0], d2b);
    wg_h<12, 4>(acc, c.q3[1], d3); wg_h<8, 4>(acc, c.q2[1][0], d2b);
    wg_h<12, 4>(acc, c.q2[2][0], d2b); wg_h<4, 4>(acc, c.q2[0][1], d2); wg_h<8, 4>(acc, c.q2[1][1], d2);
    wg_h<12, 4>(acc, c.q2[2][1], d2);
    wg_commit(); __syncwarp();
    fg(IC<0>());
    wg_wait0();
    conv_frags<0, 8>(a, c.r, sel, acc[16], warp);
    fg(IC<2>());
    if (warp >= 16) {
        if (blockIdx.x & 1) conv_tail<4, 16, 2>(acc, a, sb, gy, warp, ycopy, fg);
        else conv_tail<0, 8, 0>(acc, a, sb, gy, warp, ycopy, fg);
    } else {
        conv_tail<0, 16, 0>(acc, a, sb, gy, warp, ycopy, fg);
    }
}
#define CONV_LT6 const int dd = (lane >> 3) + (lane & 4) - (lane & 3); \
        const uint4 lt6 = make_uint4(prmt_v((dd & 3) * 288, 0u, idn), prmt_v(0x3254u + (dd >> 2) * 0x2222u, 0u, idn), \
            prmt_v(UPAD * 16 + (lane & 7) * 16 + ((lane >> 3) & 1) * (16 - ULO_B) + ULO_B - 32 + (lane & 16), 0u, idn), prmt_v(UPAD * 16 + (lane & 7) * 16 + ((lane >> 3) & 1) * ULO_B - 16 + (lane & 16), 0u, idn));
#define CONV_PRE \
        CONV_LT6 \
        const uint32_t ka = kw + lt6.x, sel = lt6.y, ks = kw + lt7.x; \
        const uint32_t ca0 = sb + SM_U + wg * USLOT_B + (warp & 3) * 128 + lt6.z, ca1 = sb + SM_U + wg * USLOT_B + (warp & 3) * 128 + lt6.w; \
        uint4 bd[3]; \
        band_quads(bd, lt7.w, (lane & 4) ? lt7.w >> 4 : lt7.w << 4);
#define CONV_PRE2 ConvPre ce_; conv_pre(ce_, ka, ks, sel);
#define CONV_BODY \
        Conv c; \
        uint32_t acc[32]; \
        conv_sums(c, acc, ce_, ca0, ca1, bd, ka, sel, warp & 3, lane & 4);
#define WS a_b_0_1_2_34_x__y567____c____de_r_
#define WS_STR2(x) #x
#define WS_STR(x) WS_STR2(x)
__device__ constexpr char wunit(int pt, int k) {
    constexpr char t[] = WS_STR(WS);
    int i = 0;
    for (; pt > 0 && t[i]; i++) pt -= t[i] == '_';
    for (; k > 0 && t[i] && t[i] != '_'; i++) k--;
    return t[i] == '_' ? 0 : t[i];
}
__device__ constexpr bool wsched_ok() {
    int seen = 0;
    for (int p = 0; p < 21; p++)
        for (int k = 0; wunit(p, k); k++) {
            const char c = wunit(p, k);
            const int bit = 1 << (c == 'r' ? 13 : c >= 'x' ? c - 'x' + 14 : c >= 'a' ? c - 'a' + 8 : c - '0');
            if ((seen & bit) || k >= (p < 16 ? 4 : 2) || (p < 5 && c >= '4' && c <= '7') || (p < 6 && (c == 'c' || c == 'd')) || (p < 16 && c == 'e')) return false;
            seen |= bit;
        }
    return seen == 0xffff;
}
struct WMaps { CUtensorMap g, u, gr, ur, d, dr; };
static_assert(GATE <= 2 && O4 >= 2, "resets");
static_assert(wsched_ok(), "weight schedule");
template <int PT, int K>
__device__ __forceinline__ void weight_units(uint32_t sb, const WMaps& m, int w) {
    constexpr char U = wunit(PT, K);
    if constexpr (U != 0) {
        if (w == K && elect_one()) {
            if (PT == 8) DELAY(K * WSP + WS0);
            const int P = blockIdx.x >> 1, odd = blockIdx.x & 1;
            constexpr int bar = SM_MISC + (U == 'e' ? 352 : U >= 'a' && U <= 'r' ? 336 : 328);
            if constexpr (U == 'e') { if (!odd) tma_2d(sb + SM_WD + 4 * 8192, &m.d, 256, 64 * P, sb + bar); }
            else if constexpr (U == 'r') tma_3d(sb + SM_WD + 40960, &m.dr, 0, 4096 + 8 * P, 5 * odd, sb + bar);
            else if constexpr (U >= 'x') tma_3d(sb + SM_WR + (U - 'x') * 4608, U == 'x' ? &m.gr : &m.ur, 4096 + 8 * P, 0, 2 * odd, sb + bar);
            else if constexpr (U >= 'a') tma_2d(sb + SM_WD + (U - 'a') * 8192, &m.d, 320 * odd + 64 * (U - 'a'), 64 * P, sb + bar);
            else tma_2d(sb + (U < '4' ? SM_WG : SM_WU) + (U & 3) * 9216, U < '4' ? &m.g : &m.u, 64 * P, 288 * odd + (U & 3) * 72, sb + bar);
        }
        weight_units<PT, K + 1>(sb, m, w);
    }
}
#define WPOINT(i, w) do { weight_units<i, 0>(sb, wm, w); } while (0)

__global__ void __launch_bounds__(NTHR, 1) __cluster_dims__(2, 1, 1)
fused_kernel(const Params p, const __grid_constant__ WMaps wm, const __grid_constant__ CUtensorMap tm_x,
             const __grid_constant__ CUtensorMap tm_y, const __grid_constant__ CUtensorMap tm_z) {
    extern __shared__ __align__(1024) unsigned char smem[];
    const uint32_t sb = smem_u32(smem);
    const int tid = threadIdx.x, warp = __shfl_sync(0xffffffffu, tid >> 5, 0), lane = tid & 31;
    const int b = blockIdx.x, P = b >> 1, odd = b & 1;
    const int g = lane >> 2, t = lane & 3;
    const int wg = warp >> 2, t128 = tid & 127;
    const uint32_t s_stat = sb + SM_MISC;
    const uint32_t s_key = sb + SM_MISC + 128;
    const uint32_t s_wm = sb + SM_MISC + 256;
    const uint32_t s_k16 = sb + SM_MISC + 192;
    const uint32_t s_fs = sb + SM_MISC + 256;
    const uint32_t s_cnt = sb + SM_MISC + 320;
    const uint32_t bar_w = sb + SM_MISC + 328, bar_d = bar_w + 8, bar_g = bar_w + 16, bar_r = bar_w + 32, bar_h = bar_w + 40, bar_x = bar_w + 48;
    STAMP(0);

    const unsigned tk0 = clock32();
    const bool lnw = (unsigned)(warp - 10) < 9u;
    const unsigned pm = tid + (tid < 512 ? 512 * b : 65024 + 128 * P), pq = (pm & ~127u) + 4 * lane;
    uint32_t pl = ldg16(p.lar + pm), ldt = ldg16(p.ldt + (pm >> 7));
    const uint32_t pa2 = ldg16(p.aim + pm), pc = ldg16(p.cre + pm), pi = ldg16(p.cim + pm);
    const uint2 call_re = ldg64(p.cre + pq), call_im = ldg64(p.cim + pq);
    const uint32_t dskl = ldg16(p.dsk + (pm >> 7));
    const uint32_t ep = ld_poll32(p.s->hint + (b & 7) * 32 + 1 + (lane >> 5));
    if ((unsigned)(tid - 320) < 288u) {
        const bf16* xp = p.x + (unsigned)((32 * P + 2 * odd + TOKEN_OF(g)) * DM + ((tid - 320) & ~31) + 8 * t);
        const uint32_t xt = sb + SM_XT + ((tid - 320) & ~31) * 32 + lane * 16;
        asm volatile("cp.async.cg.shared.global [%0], [%1], 16;\ncp.async.cg.shared.global [%0 + 512], [%1 + 9216], 16;\n"
                     "cp.async.cg.shared.global [%0 + 9216], [%1 + 576], 16;\ncp.async.cg.shared.global [%0 + 9728], [%1 + 9792], 16;\n" ::"r"(xt), "l"(xp) : "memory");
    }
    uint32_t* const std_ = p.s->st + ((lane & 12) * 128 + odd * 256 + 4 * P + 2 * (lane & 1) + ((lane >> 1) & 1)) * 2;
    unsigned char* const ud = reinterpret_cast<unsigned char*>(p.s->uT) + (32 * (warp - UW) + 8 * (g >> 1) + (g & 1)) * 4096 + b * 32 + t * 8;
    if (warp == 0) {
        if (lane == 0) {
            mbar_init(bar_x, 1); mbar_init(bar_w, 1); mbar_init(bar_d, 1); mbar_init(bar_d + 16, 1); mbar_init(bar_g, 1); mbar_init(bar_h, 3); mbar_init(bar_r, 1);
            #pragma unroll
            for (int i = 1; i < 11; i++) mbar_init(bar_x + 8 * i, 4);
            asm volatile("fence.mbarrier_init.release.cluster;\n" ::: "memory");
            mbar_expect(bar_x, 16384); mbar_expect(bar_r, 8192);
            mbar_expect(bar_w, 2 * 41472); mbar_expect(bar_d, 32768 + 5120); mbar_expect(bar_d + 16, 8192); mbar_expect(bar_g, 9 * 512);
        }
        __syncwarp();
        bar_arrive(0, NWRK);
    }
    if (warp == 0 && elect_one()) tma_3d(sb + SM_XC, &tm_x, 8 * P, 0, 8 * odd, bar_x);
    asm volatile("barrier.cluster.arrive.relaxed.aligned;\n" ::: "memory");
    const uint32_t kw = sb + SM_KW + wg * KW_B;
    if (t128 < 2 * UPAD) sts128(sb + SM_U + wg * USLOT_B + (t128 & 1) * ULO_B + (t128 >> 1) * 16, 0u, 0u, 0u, 0u);
    sts128(kw + t128 * 16, 0u, 0u, 0u, 0u);
    if (t128 < KW_B / 16 - 128) sts128(kw + 2048 + t128 * 16, 0u, 0u, 0u, 0u);
    if (tid < 128) {
#pragma unroll
        for (int i = 0; i < 4; i++) sts128(sb + SM_ZERO + i * 2048 + tid * 16, 0u, 0u, 0u, 0u);
    }
    if (warp != 0) bar_sync(0, NWRK);
    STAMP(1);
    if (warp == 19 || warp == UW || warp == UW + 1) {
        if (warp == 19) {
            if (lane < 16) stg64(std_, 0u, 0u);
            if (lane < 9) asm volatile("prefetch.global.L2 [%0];\n" ::"l"(p.wr + lane * 64));
        } else {
#pragma unroll
            for (int k = 0; k < 4; k++) stg64(ud + k * 8192, 0u, 0u);
        }
    }
    uint32_t X[2][8];
    auto partial = [&]() {
        const uint32_t xt = sb + SM_XT + (warp - 10) * 1024 + lane * 16;
        asm volatile("cp.async.wait_all;\n" ::: "memory");
        STAMP(23);
        const uint4 a = lds128(xt), c = lds128(xt + 512), d = lds128(xt + 9216), e = lds128(xt + 9728);
        X[0][0] = a.x; X[0][1] = a.y; X[0][2] = a.z; X[0][3] = a.w; X[0][4] = d.x; X[0][5] = d.y; X[0][6] = d.z; X[0][7] = d.w;
        X[1][0] = c.x; X[1][1] = c.y; X[1][2] = c.z; X[1][3] = c.w; X[1][4] = e.x; X[1][5] = e.y; X[1][6] = e.z; X[1][7] = e.w;
        const uint32_t one[8] = {0x3f803f80u, 0x3f803f80u, 0x3f803f80u, 0x3f803f80u, 0x3f803f80u, 0x3f803f80u, 0x3f803f80u, 0x3f803f80u};
        ln_partial<8>(X, one, sb + SM_LNP, warp - 10, g, t);
        bar_arrive(6, 320);
        if (PAUSE & 1) bar_sync(7, PCNT);
    };
    if (LNAT == 0 && lnw) {
        partial();
        pl = prmt_v(pl, X[0][0], 0x3210u + (warp >> 8)); ldt = prmt_v(ldt, X[0][0], 0x3210u + (warp >> 8));
    }
    auto finish = [&]() {
        bar_sync(6, 320);
        float mb, rc;
        ln_finish<9>(sb + SM_LNP, lane, mb, rc);
        const float rh = rbf(rc);
        const uint32_t s0 = (__float_as_uint(mb) >> 16) | (((ep & 0x7fffu) + 1u) << 16), s1 = pack_bf16(rh, rc - rh);
        if (lane < 16) { stg64(std_, s0, s1); sts64(s_stat + lane * 8, s0, s1); }
        if (lane == 16) sts32(s_cnt + 4, ep);
        bar_arrive(7, PCNT);
        STAMP(28);
    };
    auto upub = [&]() {
        if (!(PAUSE & 6)) bar_sync(7, PCNT);
        const uint32_t utag = ((ep & 3u) + 1u) * 0x10001u;
        uint32_t U[2][4];
#pragma unroll
        for (int hf = 0; hf < 2; hf++) {
            const uint2 st = lds64(s_stat + (g + 8 * hf) * 8);
            const uint4 xv = lds128(sb + SM_XT + (16 + warp - UW) * 1024 + hf * 512 + lane * 16);
            const uint32_t xs[4] = {xv.x, xv.y, xv.z, xv.w};
#pragma unroll
            for (int k = 0; k < 4; k++) {
                const uint32_t u = ln_apply(xs[k], st);
                U[hf][k] = movm((pack_f16_rz(bf_lo(u), __uint_as_float(u)) & 0xfff8fff8u) | utag);
            }
        }
#pragma unroll
        for (int k = 0; k < 4; k++) stg64(ud + k * 8192, U[0][k], U[1][k]);
    };
    if (FINAT == 0 && warp == 19) finish();
    const uint32_t tb = table_buf(sb, warp);
    const float dt = rbf(expf(bf_lo(ldt)));
    KGen kg;
    kgen_setup(kg, pl | (pa2 << 16), dt);
    if (LNAT == 1 && lnw) {
        partial();
        kg.z8.x = __uint_as_float(prmt_v(__float_as_uint(kg.z8.x), X[0][0], 0x3210u + (warp >> 8)));
        kg.z1.x = __uint_as_float(prmt_v(__float_as_uint(kg.z1.x), X[0][0], 0x3210u + (warp >> 8)));
    }
    if (FINAT == 1 && warp == 19) finish();
    if (UAT == 0 && (warp == UW || warp == UW + 1)) upub();
    kgen_rows(kg, tb, lane);
    if (wg == 0) fence_async();
    if (LNAT == 2 && lnw) {
        partial();
        kg.z128.x = __uint_as_float(prmt_v(__float_as_uint(kg.z128.x), X[0][0], 0x3210u + (warp >> 8)));
        kg.z1.x = __uint_as_float(prmt_v(__float_as_uint(kg.z1.x), X[0][0], 0x3210u + (warp >> 8)));
    }
    if (FINAT == 2 && warp == 19) finish();
    if (UAT == 1 && (warp == UW || warp == UW + 1)) upub();
    STAMP(2);
    WPOINT(0, warp - 4);
    const int ce = c_exponent(call_re, call_im);
    if (t128 == 0) sts64(s_fs + wg * 8, (uint32_t)min(max(ce + (int)(__float_as_uint(dt) >> 23) - 116, 0), 254) * 0x800080u, dskl << 16);
    kgen_chain(kg, pc | (pi << 16), __uint_as_float(((uint32_t)(244 - ce) << 23) | (__float_as_uint(dt) & 0x7fffffu)));
    if ((PAUSE & 4) && warp < 10) bar_sync(7, PCNT);
    if (UAT == 4 && (warp == UW || warp == UW + 1)) upub();
    STAMP(3);
    WPOINT(1, warp - 6);
    kgen_cols(kg, tb, lane);
    if (LNAT == 3 && lnw) partial();
    if (FINAT == 3 && warp == 19) finish();
    if ((PAUSE & 2) && warp < 10) bar_sync(7, PCNT);
    if (UAT == 2 && (warp == UW || warp == UW + 1)) upub();
    STAMP(4);
    WPOINT(2, warp - 8);
    const uint4* usrc = wg < 4 ? reinterpret_cast<const uint4*>(p.s->st) + odd * 512 + (lane & 1) * 128 + 16 * (warp & 7) + (lane >> 1)
                               : reinterpret_cast<const uint4*>(p.s->uT) + P * 256 + 2 * t128;
    const int ustep = wg < 4 ? 256 : 1;
    uint4 uv0, uv1;
    kgen_mma(kg, tb, lane);
    if (UAT == 3 && (warp == UW || warp == UW + 1)) upub();
    STAMP(26);
    WPOINT(3, warp - 5);
    const uint32_t idn = 0x3210u + (warp >> 8);
    uint4 lt7 = make_uint4(prmt_v(KW_T2 + ((lane >> 3) & 1) * KW_KH + (33 + (lane & 7)) * 16 - (lane & 16), 0u, idn), t * 288 + g * 8 + 8, (lane & 1) * 4096 + (lane >> 1) * 16,
                                 prmt_v(8u << ((lane >> 3) + (lane & 4)) >> (lane & 3), 0u, idn));
    asm volatile("barrier.cluster.wait.acquire.aligned;\n" ::: "memory");
    const bool pe = (int)(clock32() - tk0) >= (wg < 4 ? TP0 : TP4);
    if (pe) { uv0 = ld_poll(usrc); uv1 = ld_poll(usrc + ustep); }
    bar_sync(1 + wg, 128);
    kgen_combine(sb, warp, lane, kw, lt7.y);
    if (warp < 3 || warp > 6) bar_arrive(14, NWRK);
    STAMP(5);
    WPOINT(4, warp - 7);
    if (!pe) {
        while ((int)(clock32() - tk0) < (wg < 4 ? TP0 : TP4)) {}
        uv0 = ld_poll(usrc); uv1 = ld_poll(usrc + ustep);
    }
    if (wg < 4) {
        mbar_wait(bar_x);
        const bool far = warp < 8;
        const uint32_t xa = sb + SM_XC + (warp & 7) * 256 + (odd ^ far) * 8 + lt7.z;
        uint2 xv[4] = {lds64(xa), lds64(xa + 8192), lds64(xa + 2048), lds64(xa + 10240)};
        const uint32_t tag = ((ep & 0x7fffu) + 1u) << 16;
        int it = 0;
        while (true) {
            const bool bad = (((uv0.x ^ tag) | (uv0.z ^ tag)) | ((uv1.x ^ tag) | (uv1.z ^ tag))) >> 16;
            if (!__any_sync(0xffffffffu, bad)) break;
            if (++it > SPIN_LIMIT) TRAP();
            if (bad) { uv0 = ld_poll(usrc); uv1 = ld_poll(usrc + 256); }
        }
        STAMP(6);
        DBG(wg, it);
        const uint2 st[4] = {make_uint2(uv0.x, uv0.y), make_uint2(uv0.z, uv0.w), make_uint2(uv1.x, uv1.y), make_uint2(uv1.z, uv1.w)};
#pragma unroll
        for (int i = 0; i < 4; i++) {
            xv[i].x = ln_apply(xv[i].x, st[i]);
            xv[i].y = ln_apply(xv[i].y, st[i]);
        }
        const uint32_t ub = sb + SM_U + UPAD * 16 + odd * ULO_B + (warp & 7) * 256 + lane * 8;
        const uint32_t w[4][2] = {{pack_f16(bf_lo(xv[0].x), bf_lo(xv[1].x)), pack_f16(bf_lo(xv[2].x), bf_lo(xv[3].x))}, {HI2(xv[0].x, xv[1].x), HI2(xv[2].x, xv[3].x)},
                                  {pack_f16(bf_lo(xv[0].y), bf_lo(xv[1].y)), pack_f16(bf_lo(xv[2].y), bf_lo(xv[3].y))}, {HI2(xv[0].y, xv[1].y), HI2(xv[2].y, xv[3].y)}};
#pragma unroll
        for (int i = 0; i < 4; i++) {
            if (far) asm volatile("st.async.shared::cluster.mbarrier::complete_tx::bytes.v2.b32 [%0], {%1,%2}, [%3];\n" ::"r"((ub ^ 0x1000000u) + i * USLOT_B), "r"(w[i][0]), "r"(w[i][1]), "r"(bar_r ^ 0x1000000u) : "memory");
            else sts64(ub + i * USLOT_B, w[i][0], w[i][1]);
        }
    } else {
        const uint32_t utag = ((ep & 3u) + 1u) * 0x10001u;
        int it = 0;
        while (true) {
            const bool bad = (((uv0.x ^ utag) | (uv0.y ^ utag) | (uv0.z ^ utag) | (uv0.w ^ utag)) | ((uv1.x ^ utag) | (uv1.y ^ utag) | (uv1.z ^ utag) | (uv1.w ^ utag))) & 0x70007u;
            if (!__any_sync(0xffffffffu, bad)) break;
            if (++it > SPIN_LIMIT) TRAP();
            if (bad) { uv0 = ld_poll(usrc); uv1 = ld_poll(usrc + 1); }
        }
        STAMP(6);
        DBG(4, it);
        const uint32_t ub = sb + SM_U + UPAD * 16 + 4 * USLOT_B + (t128 >> 1) * 32 + (t128 & 1) * 8;
        sts64(ub, prmt(uv0.x, uv0.z, 0x5410u) ^ utag, prmt(uv1.x, uv1.z, 0x5410u) ^ utag);
        sts64(ub + 16, prmt(uv0.x, uv0.z, 0x7632u) ^ utag, prmt(uv1.x, uv1.z, 0x7632u) ^ utag);
        sts64(ub + ULO_B, prmt(uv0.y, uv0.w, 0x5410u) ^ utag, prmt(uv1.y, uv1.w, 0x5410u) ^ utag);
        sts64(ub + ULO_B + 16, prmt(uv0.y, uv0.w, 0x7632u) ^ utag, prmt(uv1.y, uv1.w, 0x7632u) ^ utag);
    }
    lt7.w = prmt_v(lt7.w, uv0.x, idn);
    CONV_PRE
    if (warp < 3 && elect_one()) tma_st_3d(warp < 2 ? &tm_y : &tm_z, sb + SM_ZERO, warp < 2 ? 128 * b : 32 * (512 + P), 0, 2 * (warp < 2 ? warp : odd));
    if (warp >= 3 && warp <= 6) {
        bar_sync(14, NWRK);
        WPOINT(5, warp - 3);
    }
    bar_sync(1 + wg, 128);
    CONV_PRE2
    mbar_wait(bar_r);
    fence_async();
    bar_sync(0, NWRK);
    STAMP(7);
    uint32_t hv0 = 0;
    {
        WPOINT(6, 19 - warp);
        CONV_BODY
        WPOINT(7, 19 - warp);
        if (!B2L) bar_sync(0, NWRK); else if (wg != 3) bar_arrive(0, NWRK);
        STAMP(8);
        size_t ycopy = 0;
        auto hook = [&](auto gi) {
                     constexpr int G = decltype(gi)::value;
                     if (G == 4 && warp == HINTW) hv0 = ld_poll32(p.s->hint + (lane_v() & 7) * 32);
                     if (G == 4) mbar_wait(bar_h);
                     if (G == 2) WPOINT(9, warp - 16);
                     if (G == 3) { WPOINT(10, warp - 12); WPOINT(12, warp - 8); WPOINT(14, warp - 4); }
                     if (G == 5) { WPOINT(11, warp - 13); WPOINT(13, warp - 9); WPOINT(15, warp - 5); }
                     if (G == 1 && warp >= 17 && elect_one())
                         bulk_s2g(warp == 17 ? p.s->part + b * (PBYTES / 4) : warp == 18 ? p.s->rows + b * 1152 : p.s->sc + b * 64, sb + SM_ZERO, warp == 17 ? PBYTES : warp == 18 ? 4608 : 160);
                     if (G == 4 && warp >= 17 && elect_one()) {
                         asm volatile("cp.async.bulk.wait_group 0;\n" ::: "memory");
                         hint_arrive(p.s->hint, 2, b & 7);
                     }
                     if (G == 1 && warp < 3) {
                         if (elect_one()) {
                             asm volatile("cp.async.bulk.wait_group 0;\n" ::: "memory");
                             mbar_arrive(bar_h);
                             hint_arrive(p.s->hint, 0, b & 7);
                         }
                         __syncwarp();
                         STAMP(17);
                     }
                     if (G == 1) WPOINT(8, warp - 16);
                 };
        conv_main(c, acc, sb, sel, reinterpret_cast<unsigned char*>(p.s->y), warp, ycopy, hook);
        STAMP(10);
    }
    {
    const int warp = warp_v(), lane = lane_v(), tid = 32 * warp + lane, g = lane >> 2, t = lane & 3;
    if (warp == HINTW) {
        const uint32_t target = (lds32(s_cnt + 4) + 1u) * 48u;
        if (__any_sync(0xffffffffu, (int)(hv0 - target) < 0)) hint_wait(p.s->hint, 0, target);
    }
    const unsigned char* ys = reinterpret_cast<const unsigned char*>(p.s->y) + ((size_t)P * DM + 32 * warp + 8 * (g >> 1) + (g & 1)) * 64 + odd * 32 + t * 8;
    STAMP(27);
    bar_sync(0, NWRK);
    STAMP(11);
    const uint32_t zr = warp >> 8;
    auto late_rows = [&](auto pub) {
        const uint32_t k = lds32(s_key + (lane & 7) * 4), ep = lds32(s_cnt + 4);
        const bool late = k & 256u, mine = late && ((k & 255u) >> 1) == (uint32_t)b;
        uint32_t todo = __ballot_sync(0xffffffffu, mine) & 0xffu;
        if (todo) {
#pragma unroll 1
            while (todo) {
                const int s = __ffs(todo) - 1, row = (__shfl_sync(0xffffffffu, k, s) >> 9) & 15;
                todo &= todo - 1;
                if ((row & 7) == g) pub(row & 8, 2 * NCTA + s);
            }
            __threadfence();
            bar_sync(0, NWRK);
            if (tid < NSEL && mine) *reinterpret_cast<volatile unsigned*>(p.s->flag + tid) = ep + 1u;
        }
        int it = 0;
        if (__any_sync(0xffffffffu, late)) {
            while (__any_sync(0xffffffffu, late && ld_poll32(p.s->flag + (lane & 7)) != ep + 1u)) { if (++it > SPIN_LIMIT) TRAP(); }
            __threadfence();
        }
        const int gs = tid / 36;
        const uint4* src = reinterpret_cast<const uint4*>(p.s->rows) + __shfl_sync(0xffffffffu, late ? 2 * NCTA + (lane & 7) : (k & 255u), gs & 7) * 144 + 36 * odd + (tid - gs * 36);
        if (tid < 288) {
            uint4 v0;
            do { v0 = ld_poll(src); if (++it > SPIN_LIMIT) TRAP(); } while (!v0.x);
            sts128(sb + SM_XS + gs * XS_PITCH + (tid - gs * 36) * 16, v0.x, v0.y, v0.z, v0.w);
        }
        __syncwarp();
    };
    if (warp >= 18) {
        uint32_t* const kp = pin(p.s->sc + 64 * b + 32 * (19 - warp), zr);
        const uint32_t kid = pin(0xc0000000u | ((lane & 15) << 9) | 2 * b, zr), ka = pin(s_k16 + (warp & 1) * 288 + (lane & 15) * 4, zr), kb = pin(s_k16 + (warp & 1) * 288 + (lane & 16) * 2, zr);
        const uint4* ksrc = pin(reinterpret_cast<const uint4*>(p.s->sc) + 8 * (19 - warp) + 16 * lane, zr);
        const uint4* rsrc = pin(reinterpret_cast<const uint4*>(p.s->rows) + 36 * odd + t, zr);
        uint32_t bits, early = 0;
        if (warp == 18) {
            weight_units<20, 0>(sb, wm, 0); weight_units<20, 1>(sb, wm, 1);
            bar_sync(8, 640);
            float mb, rc;
            ln_finish<18>(sb + SM_LNP, lane, mb, rc);
            if (lane < 16) stat_store(s_stat + lane * 8, mb, rc, 0u);
            bar_arrive(13, 608);
            bar_sync(10, 640);
            early = lds32(s_wm + (lane & 15) * 4);
            bits = pack_bf16(0.f, sum18(sb + SM_LNP + (32 + (lane & 15)) * 80));
        } else {
            float sw = 0.f;
#pragma unroll
            for (int i = 0; i < 9; i++) { const uint32_t w = reinterpret_cast<const uint32_t*>(p.wr)[32 * i + lane]; sw += bf_lo(w) + bf_hi(w); }
#pragma unroll
            for (int i = 16; i; i >>= 1) sw += __shfl_xor_sync(0xffffffffu, sw, i);
            early = __any_sync(0xffffffffu, (int)(ld_poll32(p.s->hint + (lane & 7) * 32 + 2 + zr * __float_as_int(sw)) - (lds32(s_cnt + 4) + 1u) * 48u) < 0);
            bar_sync(8, 640);
            const float v = sum18(sb + SM_LNP + lane * 80), hw = sum18(sb + SM_LNP + (48 + (lane & 15)) * 80);
            const float o = __shfl_xor_sync(0xffffffffu, v, 16), mean = (lane < 16 ? v : o) * (1.0f / 576.0f);
            const float var = fmaxf(fmaf(lane < 16 ? o : v, 1.0f / 576.0f, -(mean * mean)), 0.f);
            bits = __float_as_uint(fmaf(-rbf(mean), sw, hw) * rcp_approx(rbf(sqrt_approx(rbf(rbf(var) + 1e-5f)))));
        }
        {
            const uint32_t me = (((bits ^ ((uint32_t)((int)bits >> 31) & 0x7fffffffu)) >> 1) & 0x7fffe000u) ^ kid;
            sts32(ka, me);
            __syncwarp();
            const uint4 v = lds128(kb), w = lds128(kb + 16);
#define GT(x) ((me - (x)) >> 31)
            uint32_t rank = pin(GT(v.x) + GT(v.y) + GT(v.z), zr) + pin(GT(v.w) + GT(w.x) + GT(w.y), zr) + pin(GT(w.z) + GT(w.w), zr);
#undef GT
            rank += __shfl_xor_sync(0xffffffffu, rank, 16);
            const uint32_t sl = warp == 18 ? early : rank;
            stg32(kp + rank, me + (sl < 2 ? sl : 256u));
            if (warp == 19) {
                sts32(s_wm + (lane & 15) * 4, rank);
                if (early) hint_wait(p.s->hint, 2, (lds32(s_cnt + 4) + 1u) * 48u);
                bar_arrive(10, 640); bar_arrive(11, 608);
            }
        }
        bool slow;
        int it = 0;
        uint4 q[4];
        STAMP(13);
        DELAY(warp == 19 ? KDEL : KDEL2);
#pragma unroll
        for (int i = 0; i < 4; i++) q[i] = ld_poll(ksrc + 512 * i);
        while (true) {
            uint32_t a[4];
#pragma unroll
            for (int i = 0; i < 4; i++) a[i] = q[i].x & q[i].y & q[i].z & q[i].w;
            if (__all_sync(0xffffffffu, a[0] & a[1] & a[2] & a[3])) break;
#pragma unroll
            for (int i = 0; i < 4; i++)
                if (!a[i]) q[i] = ld_poll(ksrc + 512 * i);
            if (++it > SPIN_LIMIT) TRAP();
        }
        STAMP(16);
        if (warp == 18) {
            const uint32_t kt = sb + SM_KEYS;
#pragma unroll
            for (int i = 0; i < 4; i++) sts128(kt + i * 512 + lane * 16, q[i].x, q[i].y, q[i].z, q[i].w);
            bar_sync(15, 64);
            const uint32_t c = lds32(s_key + 32 + g * 4), e = lds32(kt + (c & 254u) * 8 + t * 4);
            const bool hit = ((e ^ c) & 0x1fffu) == 0u && !(c & 256u);
            if (hit) sts32(s_key + g * 4, e);
            const uint32_t lo = __reduce_min_sync(0xffffffffu, hit ? e : 0xffffffffu) | 0x1fffu;
#define GT(x) ((lo - (x)) >> 31)
            uint32_t n = hit ? 256u - GT(e) : 0u;
#pragma unroll
            for (int i = 0; i < 4; i++) n += pin(GT(q[i].x) + GT(q[i].y) + GT(q[i].z) + GT(q[i].w), zr) << 12;
#undef GT
            n = __reduce_add_sync(0xffffffffu, n);
            slow = (n >> 12) + (n & 4095u) != 2048u || (n & 4095u) <= 2040u;
            if (slow) {
                uint4 r[4];
                it = 0;
                while (true) {
#pragma unroll
                    for (int i = 0; i < 4; i++) r[i] = ld_poll(ksrc + 512 * i + 1);
                    if (__all_sync(0xffffffffu, all_nz(r[0]) && all_nz(r[1]) && all_nz(r[2]) && all_nz(r[3]))) break;
                    if (++it > SPIN_LIMIT) TRAP();
                }
                uint32_t m = 0u;
#pragma unroll 1
                for (int s = 0; s < 8; s++) {
                    uint32_t x = 0;
#pragma unroll
                    for (int i = 0; i < 4; i++) {
                        x = max(max(max(x, q[i].x - m), max(q[i].y - m, q[i].z - m)), q[i].w - m);
                        x = max(max(max(x, r[i].x - m), max(r[i].y - m, r[i].z - m)), r[i].w - m);
                    }
                    m += __reduce_max_sync(0xffffffffu, x);
                    if (lane == 0) sts32(s_key + s * 4, m);
                }
            }
            DBG(7, slow);
        } else {
            auto merge = [](const uint4& x, const uint4& y) {
                const uint32_t a = max(x.x, y.w), c = max(x.y, y.z), d = max(x.z, y.y), e = max(x.w, y.x);
                const uint32_t a2 = max(a, d), d2 = min(a, d), c2 = max(c, e), e2 = min(c, e);
                return make_uint4(max(a2, c2), min(a2, c2), max(d2, e2), min(d2, e2));
            };
            uint4 h = merge(merge(q[0], q[1]), merge(q[2], q[3]));
            uint4 v[9];
            uint32_t key = 0;
#pragma unroll
            for (int s = 0; s < 8; s++) {
                const uint32_t m = __reduce_max_sync(0xffffffffu, h.x);
                const bool w = h.x == m;
                h.x = w ? h.y : h.x; h.y = w ? h.z : h.y; h.z = w ? h.w : h.z; h.w = w ? 0u : h.w;
                if (g == s) key = m;
            }
            rsrc += (key & 255u) * 144;
#pragma unroll
            for (int j = 0; j < 9; j++) v[j] = ld_poll(rsrc + 4 * j);
            const uint32_t xsa = sb + SM_XS + g * XS_PITCH + t * 16;
            sts32(s_key + 32 + g * 4, key);
            sts32(xsa, 0u);
            bar_arrive(15, 64);
            bar_arrive(12, 608);
            STAMP(18);
#pragma unroll
            for (int j = 0; j < 9; j++) sts128(xsa + j * 64, v[j].x, v[j].y, v[j].z, v[j].w);
            slow = min(min(min(min(v[0].x, v[1].x), v[2].x), min(min(v[3].x, v[4].x), v[5].x)), min(min(v[6].x, v[7].x), v[8].x)) == 0u;
        }
        if (bar_or(0, NWRK, slow)) { late_rows([](bool, int) {}); bar_or(0, NWRK, false); }
        STAMP(19);
        const int fl = 16 * (b & 1) + ((tid >> 2) & 15), fc = 16 * (b >> 1) + (fl >> 2) + 8 * ((tid >> 1) & 1), fsl = 2 * (fl & 3) + (tid & 1);
        const uint32_t kk = lds32(s_key + fsl * 4);
        const uint32_t* fsrc = p.s->rows + ((kk & 256u) ? 2 * NCTA + fsl : (kk & 255u)) * DM + (fc >> 1);
        uint32_t hw = 1u, uw = 1u;
        if (b < 72) { uw = ld_poll32(fsrc); hw = ld_poll32(fsrc + 288); }
        if (b < 72) {
            it = 0;
            while (!hw || !uw) { uw = ld_poll32(fsrc); hw = ld_poll32(fsrc + 288); if (++it > SPIN_LIMIT) TRAP(); }
            const int row = (kk >> 9) & 15, ftok = 8 * (kk & 252u) + (kk & 2u) + TOKEN_OF(row & 7) + (row & 8);
            const unsigned k16 = (kk >> 15) & 0xffffu;
            const unsigned bits = (k16 & 0x8000u) ? (k16 & 0x7fffu) : (~k16 & 0xffffu);
            const float rs = 512.0f * rbf(__fdividef(1.0f, 1.0f + __expf(-__uint_as_float(bits << 16))));
            bf16* const op = p.out + (unsigned)(ftok * DM + fc);
            const float uv = (fc & 1) ? bf_hi(uw) : bf_lo(uw), hv = (fc & 1) ? bf_hi(hw) : bf_lo(hw);
            const uint32_t a = sb + SM_FIN + (tid - 576) * 80;
            sts128(a + 64, __float_as_uint(rs), __float_as_uint(uv), __float_as_uint(hv), (uint32_t)(size_t)op ^ (uint32_t)((size_t)op >> 32));
            bar_sync(14, 576);
            const uint4 p0 = lds128(a), p1 = lds128(a + 16), p2 = lds128(a + 32), p3 = lds128(a + 48);
#define F4(p) ((__uint_as_float(p.x) + __uint_as_float(p.y)) + (__uint_as_float(p.z) + __uint_as_float(p.w)))
            const float v0 = F4(p0), v1 = F4(p1), v2 = F4(p2), v3 = F4(p3);
#undef F4
            const float y3 = rbf(rbf((v0 + v1) + (v2 + v3)) * rs);
            asm volatile("st.global.u16 [%0], %1;\n" ::"l"(op), "h"((unsigned short)pack_bf16(hv + rbf(uv + y3), 0.f)) : "memory");
        }
        if (b == 0 && tid >= 632) *reinterpret_cast<volatile unsigned*>(p.s->hint + (tid & 7) * 32 + 1) = lds32(s_cnt + 4) + 1u;
    } else {
        uint32_t H[2][4], U2[2][4], WA[9][4], WD[18], WE[18];
        const int fkh = warp >= 9, fmt = warp - 9 * fkh;
        auto load_wa = [&](auto k0, auto k1) {
            if (k0.value >= k1.value) return;
            if (k0.value == 0) mbar_wait(bar_w);
            const int mi = lane >> 3, rr = lane & 7;
            const int row = fkh * 144 + rr + 8 * (mi >> 1);
            const uint32_t aad = sb + (fmt < 8 ? SM_WG + (mi & 1) * (SM_WU - SM_WG) + row * 128 + (fmt ^ rr) * 16 : SM_WR + (mi & 1) * 4608 + row * 16), ks = fmt < 8 ? 2048 : 256;
#pragma unroll
            for (int k = k0.value; k < k1.value; k++) ldsm_x4_t(WA[k][0], WA[k][1], WA[k][2], WA[k][3], aad + k * ks);
        };
        auto load_wd = [&](uint32_t (&WD)[18], int tile) {
            mbar_wait(bar_d);
            if (tile & 16) mbar_wait(bar_d + 16);
            const int mi = lane >> 3, rr = lane & 7;
            const uint32_t base = sb + SM_WD + rr * 128 + (((2 * tile + (mi & 1)) & 7) ^ rr) * 16;
#pragma unroll
            for (int k = 0; k < 4; k++) ldsm_x4_t(WD[4 * k], WD[4 * k + 1], WD[4 * k + 2], WD[4 * k + 3], base + (tile >> 2) * 8192 + (k * 16 + 8 * (mi >> 1)) * 128);
            ldsm_x2_t(WD[16], WD[17], base + 40960 + (tile >> 2) * 1024);
        };
        auto publish = [&](bool hi, int slot) {
            uint4* rowp = reinterpret_cast<uint4*>(p.s->rows) + slot * 144 + warp * 4 + t;
            stg128(rowp, nzw(hi ? U2[1][0] : U2[0][0]), nzw(hi ? U2[1][1] : U2[0][1]), nzw(hi ? U2[1][2] : U2[0][2]), nzw(hi ? U2[1][3] : U2[0][3]));
            stg128(rowp + 72, nzw(hi ? H[1][0] : H[0][0]), nzw(hi ? H[1][1] : H[0][1]), nzw(hi ? H[1][2] : H[0][2]), nzw(hi ? H[1][3] : H[0][3]));
        };
        uint4 wr = make_uint4(0x3f803f80u, 0x3f803f80u, 0x3f803f80u, 0x3f803f80u);
        {
            uint2 yv[4];
#pragma unroll
            for (int k = 0; k < 4; k++) yv[k] = ld_poll64(ys + k * 128);
            if (g == 0) wr = ldg128(p.wr + 32 * warp + 8 * t);
            const uint4 x0 = lds128(sb + SM_XT + warp * 1024 + lane * 16), x1 = lds128(sb + SM_XT + warp * 1024 + 512 + lane * 16);
            load_wa(IC<0>(), IC<WA0>());
            int it = 0;
            while (!__all_sync(0xffffffffu, yv[0].x && yv[1].x && yv[2].x && yv[3].x)) {
#pragma unroll
                for (int k = 0; k < 4; k++) yv[k] = ld_poll64(ys + k * 128);
                if (++it > SPIN_LIMIT) TRAP();
            }
            STAMP(12);
            const uint32_t Z[2][4] = {{x0.x, x0.y, x0.z, x0.w}, {x1.x, x1.y, x1.z, x1.w}};
#pragma unroll
            for (int k = 0; k < 4; k++) {
                H[0][k] = hadd2_bf(Z[0][k], movm(yv[k].x));
                H[1][k] = hadd2_bf(Z[1][k], movm(yv[k].y));
            }
            const uint32_t bw[4] = {wr.x, wr.y, wr.z, wr.w};
            ln_partial<4>(H, bw, sb + SM_LNP, warp, g, t);
        }
        bar_arrive(8, 640);
        WPOINT(16, warp - 12);
        load_wa(IC<WA0>(), IC<WA1>());
        STAMP(13);
        bar_sync(13, 608);
        STAMP(14);
#pragma unroll
        for (int hf = 0; hf < 2; hf++) {
            const uint2 st = lds64(s_stat + (g + 8 * hf) * 8);
#pragma unroll
            for (int k = 0; k < 4; k++) U2[hf][k] = ln_apply(H[hf][k], st);
        }
        {
            float cs[4] = {0.f, 0.f, 0.f, 0.f}, ct[4] = {0.f, 0.f, 0.f, 0.f};
            mma_bf16(cs, U2[0][0], U2[1][0], U2[0][1], U2[1][1], wr.x, wr.y);
            mma_bf16(ct, U2[0][2], U2[1][2], U2[0][3], U2[1][3], wr.z, wr.w);
            if (t == 0) { stsf(sb + SM_LNP + ((32 + g) * 20 + warp) * 4, cs[0] + ct[0]); stsf(sb + SM_LNP + ((40 + g) * 20 + warp) * 4, cs[2] + ct[2]); }
            bar_arrive(10, 640);
        }
        load_wa(IC<WA1>(), IC<WA2>());
        bar_sync(11, 608);
        {
            const uint32_t rk[2] = {lds32(s_wm + g * 4), lds32(s_wm + 32 + g * 4)};
            uint32_t lo = min(rk[0], rk[1]), hi = max(rk[0], rk[1]);
#pragma unroll 1
            while (lo < 2) { publish(lo == rk[1], 2 * b + lo); lo = hi; hi = 16; }
        }
        load_wa(IC<WA2>(), IC<WA3>());
        load_wa(IC<WA3>(), IC<9>());
#pragma unroll
        for (int hf = 0; hf < 2; hf++)
            sts128(sb + SM_OUT + (g + 8 * hf) * OUT_PITCH + warp * 64 + t * 16,
                   hadd2_bf(H[hf][0], U2[hf][0]), hadd2_bf(H[hf][1], U2[hf][1]), hadd2_bf(H[hf][2], U2[hf][2]), hadd2_bf(H[hf][3], U2[hf][3]));
        fence_async();
        WPOINT(17, warp - 16);
        if ((WDAT == 0 || (WDAT == 2 && fkh)) && (warp < 16 || !odd)) load_wd(WD, warp);
        const uint32_t bad = pin(sb + SM_XS + (lane & 7) * XS_PITCH + (fkh * 144 + 8 * (lane >> 3)) * 2, zr), ex = pin(sb + SM_EX + warp * 512 + lane * 16, zr);
        uint32_t* pp = pin(p.s->part + ((size_t)(2 * (20 * odd + warp) + (lane >> 4)) * 64 + P) * 32 + (lane & 15) * 2, zr);
        bar_sync(12, 608);
        const bool routed = __any_sync(0xffffffffu, (lds32(s_key + 32 + (lane & 7) * 4) & 0x1efeu) == (uint32_t)((warp << 9) | 2 * b));
        auto store_row = [&]() { if (warp < 16 && elect_one()) bulk_s2g(p.out + (size_t)(32 * P + 2 * odd + TOKEN_OF(warp & 7) + (warp & 8)) * DM, sb + SM_OUT + warp * OUT_PITCH, DM * 2); };
        if (!routed) store_row();
        WPOINT(18, warp - 16);
        STAMP(15);
        bool again = zr;
#pragma unroll 1
        do {
            if (again) {
                if (routed) store_row();
                asm volatile("cp.async.bulk.wait_group 0;\n" ::: "memory");
                late_rows(publish);
            }
            again = bar_or(0, NWRK, false);
        } while (again);
        STAMP(19);
        float gp[4];
        {
            float c4[3][4];
#pragma unroll
            for (int i = 0; i < 3; i++)
#pragma unroll
                for (int j = 0; j < 4; j++) c4[i][j] = 0.f;
#pragma unroll
            for (int k = 0; k < 10; k += 2) {
                uint32_t b0, b1, b2, b3;
                ldsm_x4(b0, b1, b2, b3, bad + k * 32);
                mma_bf16(c4[k % 3], WA[k][0], WA[k][1], WA[k][2], WA[k][3], b0, b1);
                if (k < 8) mma_bf16(c4[(k + 1) % 3], WA[k + 1][0], WA[k + 1][1], WA[k + 1][2], WA[k + 1][3], b2, b3);
            }
#pragma unroll
            for (int j = 0; j < 4; j++) gp[j] = c4[0][j] + (c4[1][j] + c4[2][j]);
            if (warp >= 9) {
                sts128f(ex, gp);
                bar_arrive(6, 576);
            } else {
                bar_sync(6, 576);
                const uint4 o = lds128(ex + 4608);
                gp[0] += __uint_as_float(o.x); gp[1] += __uint_as_float(o.y); gp[2] += __uint_as_float(o.z); gp[3] += __uint_as_float(o.w);
                asm volatile("st.async.shared::cluster.mbarrier::complete_tx::bytes.v4.b32 [%0], {%1,%2,%3,%4}, [%5];\n"
                             ::"r"(ex ^ 0x1000000u), "r"(__float_as_uint(gp[0])), "r"(__float_as_uint(gp[1])), "r"(__float_as_uint(gp[2])), "r"(__float_as_uint(gp[3])), "r"(bar_g ^ 0x1000000u) : "memory");
                if (WDAT == 2) load_wd(WD, warp);
            }
            if (WDAT == 1 && (warp < 16 || !odd)) load_wd(WD, warp);
            if (warp >= 16 && !odd) load_wd(WE, warp + 2);
        }
        STAMP(20);
        if (warp < 9) {
            mbar_wait(bar_g);
            const uint4 u = lds128(ex);
            const uint32_t G = pack_bf16(gp[0] + __uint_as_float(u.x), gp[1] + __uint_as_float(u.y)), U = pack_bf16(gp[2] + __uint_as_float(u.z), gp[3] + __uint_as_float(u.w));
            const float G0 = bf_lo(G), G1 = bf_hi(G);
            sts32(sb + SM_GU + tid * 4, hmul2_bf(pack_bf16(G0 * rcp_approx(1.0f + ex2_approx(G0 * -1.4426950408889634f)), G1 * rcp_approx(1.0f + ex2_approx(G1 * -1.4426950408889634f))), U));
        }
        bar_sync(7, 576);
        STAMP(21);
        if (warp < 16 || !odd) {
            uint32_t gb[9];
            ldsm_x4_t(gb[0], gb[1], gb[2], gb[3], sb + SM_GU + lane * 16);
            ldsm_x4_t(gb[4], gb[5], gb[6], gb[7], sb + SM_GU + 512 + lane * 16);
            ldsm_x1_t(gb[8], sb + SM_GU + 1024 + (lane & 7) * 16);
            auto down = [&](const uint32_t (&W)[18], uint32_t* dst) {
                float c4[4] = {0.f, 0.f, 0.f, 0.f}, d4[4] = {0.f, 0.f, 0.f, 0.f}, e4[4] = {0.f, 0.f, 0.f, 0.f};
                mma_bf16(c4, W[0], W[1], W[2], W[3], gb[0], gb[1]);
                mma_bf16(d4, W[4], W[5], W[6], W[7], gb[2], gb[3]);
                mma_bf16(e4, W[8], W[9], W[10], W[11], gb[4], gb[5]);
                mma_bf16_k8(c4, W[16], W[17], gb[8]);
                mma_bf16(d4, W[12], W[13], W[14], W[15], gb[6], gb[7]);
                const float v0 = (c4[0] + e4[0]) + d4[0], v1 = (c4[1] + e4[1]) + d4[1], v2 = (c4[2] + e4[2]) + d4[2], v3 = (c4[3] + e4[3]) + d4[3];
                const uint32_t e = max(max(__float_as_uint(fmaxf(fabsf(v0), fabsf(v1))), __float_as_uint(fmaxf(fabsf(v2), fabsf(v3)))), 16u << 23) >> 23;
                const float sc = __uint_as_float((245u - e) << 23);
                stg64(dst, pack_f16(v0 * sc, v1 * sc) | ((e * 0x8002000u) & 0x60006000u), pack_f16(v2 * sc, v3 * sc) | ((e * 0x800200u) & 0x60006000u));
            };
            if (warp >= 16) { down(WE, pp + 4 * 64 * 32); down(WD, pp); }
            else down(WD, pp);
        }
        asm volatile("cp.async.bulk.wait_group.read 0;\n" ::: "memory");
        STAMP(22);
        if (b < 72 && warp < 16) {
            const uint2* src = reinterpret_cast<const uint2*>(p.s->part) + (unsigned)(b * 1024 + tid);
            uint2 a, c;
            int it = 0;
            DELAY(PDEL);
            a = ld_poll64(src); c = ld_poll64(src + 512);
            while (!__all_sync(0xffffffffu, a.y && c.y)) {
                a = ld_poll64(src); c = ld_poll64(src + 512);
                if (++it > SPIN_LIMIT) TRAP();
            }
            STAMP(24);
            const float ea = __uint_as_float((((a.y & 0x60006000u) | ((a.x >> 4) & 0x06000600u)) * 0x4001u) & 0x7f800000u);
            const float ec = __uint_as_float((((c.y & 0x60006000u) | ((c.x >> 4) & 0x06000600u)) * 0x4001u) & 0x7f800000u);
            a.x &= 0x9fff9fffu; a.y &= 0x9fff9fffu; c.x &= 0x9fff9fffu; c.y &= 0x9fff9fffu;
            const float s0 = fmaf(h_lo(a.x), ea, h_lo(c.x) * ec), s1 = fmaf(h_hi(a.x), ea, h_hi(c.x) * ec), s2 = fmaf(h_lo(a.y), ea, h_lo(c.y) * ec), s3 = fmaf(h_hi(a.y), ea, h_hi(c.y) * ec);
            const bool up = lane & 16;
            const float r0 = __shfl_xor_sync(0xffffffffu, up ? s0 : s2, 16), r1 = __shfl_xor_sync(0xffffffffu, up ? s1 : s3, 16);
            const uint32_t fa = sb + SM_FIN + ((lane & 15) * 4 + (up ? 2 : 0)) * 80 + warp * 4;
            stsf(fa, (up ? s2 : s0) + r0); stsf(fa + 80, (up ? s3 : s1) + r1);
            bar_arrive(14, 576);
        }
    }
    STAMP(25);
    }
}

typedef CUresult (*PFN_tmEncode)(CUtensorMap*, CUtensorMapDataType, cuuint32_t, void*, const cuuint64_t*, const cuuint64_t*, const cuuint32_t*,
                                 const cuuint32_t*, CUtensorMapInterleave, CUtensorMapSwizzle, CUtensorMapL2promotion, CUtensorMapFloatOOBfill);

extern "C" void kernel_launch(void* const* d_in, const int* in_sizes, int n_in, void* d_out, int out_size) {
    Params p;
    p.x = (const bf16*)d_in[0];
    p.lar = (const bf16*)d_in[1];
    p.aim = (const bf16*)d_in[2];
    p.cre = (const bf16*)d_in[3];
    p.cim = (const bf16*)d_in[4];
    p.ldt = (const bf16*)d_in[5];
    p.dsk = (const bf16*)d_in[6];
    p.wr = (const bf16*)d_in[8];
    p.out = (bf16*)d_out;
    static PFN_tmEncode enc = nullptr;
    static void* scratch = nullptr;
    if (!enc) {
        cudaFuncSetAttribute(fused_kernel, cudaFuncAttributeMaxDynamicSharedMemorySize, SMEM_TOTAL);
        void* fn = nullptr;
        cudaDriverEntryPointQueryResult qr;
        cudaGetDriverEntryPoint("cuTensorMapEncodeTiled", &fn, cudaEnableDefault, &qr);
        enc = (PFN_tmEncode)fn;
        cudaGetSymbolAddress(&scratch, g_scratch);
    }
    p.s = (Scratch*)scratch;
    WMaps wm;
    CUtensorMap tm_x, tm_y, tm_z;
    const cuuint64_t dims[2] = {FF, DM}, strides[1] = {FF * 2}, rdims[3] = {FF, 144, 4}, rstrides[2] = {FF * 2, 144 * FF * 2};
    const cuuint32_t box[2] = {64, 72}, rbox[3] = {8, 144, 2}, es3[3] = {1, 1, 1};
    for (int i = 0; i < 2; i++) {
        enc(i ? &wm.u : &wm.g, CU_TENSOR_MAP_DATA_TYPE_BFLOAT16, 2, d_in[9 + i], dims, strides, box, es3, CU_TENSOR_MAP_INTERLEAVE_NONE, CU_TENSOR_MAP_SWIZZLE_128B,
            CU_TENSOR_MAP_L2_PROMOTION_NONE, CU_TENSOR_MAP_FLOAT_OOB_FILL_NONE);
        enc(i ? &wm.ur : &wm.gr, CU_TENSOR_MAP_DATA_TYPE_BFLOAT16, 3, d_in[9 + i], rdims, rstrides, rbox, es3, CU_TENSOR_MAP_INTERLEAVE_NONE, CU_TENSOR_MAP_SWIZZLE_NONE,
            CU_TENSOR_MAP_L2_PROMOTION_NONE, CU_TENSOR_MAP_FLOAT_OOB_FILL_NONE);
    }
    const cuuint64_t ddims[2] = {DM, FF}, dstrides[1] = {DM * 2}, edims[3] = {64, FF, 9}, estrides[2] = {DM * 2, 128};
    const cuuint32_t dbox[2] = {64, 64}, ebox[3] = {64, 8, 5};
    enc(&wm.d, CU_TENSOR_MAP_DATA_TYPE_BFLOAT16, 2, d_in[11], ddims, dstrides, dbox, es3, CU_TENSOR_MAP_INTERLEAVE_NONE, CU_TENSOR_MAP_SWIZZLE_128B,
        CU_TENSOR_MAP_L2_PROMOTION_NONE, CU_TENSOR_MAP_FLOAT_OOB_FILL_NONE);
    enc(&wm.dr, CU_TENSOR_MAP_DATA_TYPE_BFLOAT16, 3, d_in[11], edims, estrides, ebox, es3, CU_TENSOR_MAP_INTERLEAVE_NONE, CU_TENSOR_MAP_SWIZZLE_128B,
        CU_TENSOR_MAP_L2_PROMOTION_NONE, CU_TENSOR_MAP_FLOAT_OOB_FILL_NONE);
    const cuuint64_t xdims[3] = {DM, LSEQ / 16, 16}, xstrides[2] = {16 * DM * 2, DM * 2};
    const cuuint32_t xbox[3] = {8, LSEQ / 16, 8};
    enc(&tm_x, CU_TENSOR_MAP_DATA_TYPE_BFLOAT16, 3, d_in[0], xdims, xstrides, xbox, es3, CU_TENSOR_MAP_INTERLEAVE_NONE, CU_TENSOR_MAP_SWIZZLE_NONE,
        CU_TENSOR_MAP_L2_PROMOTION_NONE, CU_TENSOR_MAP_FLOAT_OOB_FILL_NONE);
    const cuuint64_t ydims[3] = {DM * 32, 16, 4}, ystrides[2] = {DM * 64, 16 * DM * 64};
    const cuuint32_t ybox[3] = {128, 16, 2}, zbox[3] = {32, 16, 2};
    enc(&tm_y, CU_TENSOR_MAP_DATA_TYPE_BFLOAT16, 3, p.s->y, ydims, ystrides, ybox, es3, CU_TENSOR_MAP_INTERLEAVE_NONE, CU_TENSOR_MAP_SWIZZLE_NONE,
        CU_TENSOR_MAP_L2_PROMOTION_NONE, CU_TENSOR_MAP_FLOAT_OOB_FILL_NONE);
    enc(&tm_z, CU_TENSOR_MAP_DATA_TYPE_BFLOAT16, 3, p.s->y, ydims, ystrides, zbox, es3, CU_TENSOR_MAP_INTERLEAVE_NONE, CU_TENSOR_MAP_SWIZZLE_NONE,
        CU_TENSOR_MAP_L2_PROMOTION_NONE, CU_TENSOR_MAP_FLOAT_OOB_FILL_NONE);
    fused_kernel<<<NCTA, NTHR, SMEM_TOTAL>>>(p, wm, tm_x, tm_y, tm_z);
}
```

```cpp
#include <cuda_runtime.h>
#include <cuda.h>
#include <cuda_fp16.h>
#include <cuda_bf16.h>
#include <stdint.h>

#define LSEQ 2048
#define DM 576
#define NST 128
#define FF 4608
#define NSEL 8
#define NCTA 128
#define NTHR 640
#define NWRK 640

typedef __nv_bfloat16 bf16;

#define SM_WD 0
#define SM_WG 46080
#define SM_WR 82944
#define SM_WU 92160
#define SM_ZERO 32768
#define SM_XC 16384
#define SM_TB 96000
#define SM_PL 129024
#define PL_B 10752
#define SM_XT (SM_TB + 20 * TBW)
#define SM_U (SM_XT + 18432)
#define UPAD 8
#define ULO_B ((UPAD + 128) * 16)
#define USLOT_B (2 * ULO_B)
#define SM_KW (SM_U + 5 * USLOT_B)
#define KW_B 3600
#define KW_T2 1152
#define KW_KH 656
#define KW_T3 2464
#define SM_MISC (SM_KW + 5 * KW_B)
#define SM_LNP (SM_MISC + 576)
#define SMEM_TOTAL (SM_LNP + 5120)
#define TBP 112
#define TBW (32 * TBP)
#define SM_OUT SM_PL
#define OUT_PITCH 1216
#define SM_XS (SM_PL + 19456)
#define XS_PITCH 592
#define SM_EX (SM_PL + 24320)
#define SM_KEYS (SM_KW + 5120)
#define SM_FIN SM_KW
#define SM_GU (SM_PL + 33536)

struct __align__(128) Scratch {
    unsigned hint[8 * 32];
    unsigned flag[32];
    uint32_t sc[NCTA * 64];
    uint32_t st[LSEQ * 2];
    uint32_t uT[64 * (LSEQ / 2)];
    uint32_t y[NCTA * DM * 8];
    uint32_t part[72 * 64 * 32];
    uint32_t rows[(2 * NCTA + NSEL) * DM];
};
__device__ Scratch g_scratch;
#define STAMP(i)
#define DBG(i, v)

__device__ __forceinline__ float rbf(float x) {
    uint32_t r;
    asm("cvt.rn.bf16x2.f32 %0, %1, %2;\n" : "=r"(r) : "f"(x), "f"(0.f));
    return __uint_as_float(r);
}
__device__ __forceinline__ uint32_t pack_bf16(float lo, float hi) {
    uint32_t r;
    asm("cvt.rn.bf16x2.f32 %0, %1, %2;\n" : "=r"(r) : "f"(hi), "f"(lo));
    return r;
}
__device__ __forceinline__ uint32_t pack_f16(float lo, float hi) {
    uint32_t r;
    asm("cvt.rn.f16x2.f32 %0, %1, %2;\n" : "=r"(r) : "f"(hi), "f"(lo));
    return r;
}
__device__ __forceinline__ uint32_t pack_f16_rz(float lo, float hi) {
    uint32_t r;
    asm("cvt.rz.f16x2.f32 %0, %1, %2;\n" : "=r"(r) : "f"(hi), "f"(lo));
    return r;
}
__device__ __forceinline__ float bf_lo(uint32_t w) { return __uint_as_float(w << 16); }
__device__ __forceinline__ float bf_hi(uint32_t w) { return __uint_as_float(w & 0xffff0000u); }
__device__ __forceinline__ uint32_t hadd2_bf(uint32_t a, uint32_t b) {
    __nv_bfloat162 r = __hadd2_rn(*reinterpret_cast<__nv_bfloat162*>(&a), *reinterpret_cast<__nv_bfloat162*>(&b));
    return *reinterpret_cast<uint32_t*>(&r);
}
__device__ __forceinline__ uint32_t hmul2_bf(uint32_t a, uint32_t b) {
    __nv_bfloat162 r = __hmul2_rn(*reinterpret_cast<__nv_bfloat162*>(&a), *reinterpret_cast<__nv_bfloat162*>(&b));
    return *reinterpret_cast<uint32_t*>(&r);
}
__device__ __forceinline__ uint32_t hfma2_bf(uint32_t a, uint32_t b, uint32_t c) { uint32_t r; asm("fma.rn.bf16x2 %0, %1, %2, %3;\n" : "=r"(r) : "r"(a), "r"(b), "r"(c)); return r; }
__device__ __forceinline__ uint32_t hmul2(uint32_t a, uint32_t b) { uint32_t r; asm("mul.rn.f16x2 %0, %1, %2;\n" : "=r"(r) : "r"(a), "r"(b)); return r; }
__device__ __forceinline__ uint32_t hadd2(uint32_t a, uint32_t b) { uint32_t r; asm("add.rn.f16x2 %0, %1, %2;\n" : "=r"(r) : "r"(a), "r"(b)); return r; }
__device__ __forceinline__ uint32_t nzw(uint32_t w) { return w ? w : 0x8000u; }
__device__ __forceinline__ uint32_t smem_u32(const void* p) { return (uint32_t)__cvta_generic_to_shared(p); }
__device__ __forceinline__ uint32_t lds32(uint32_t addr) {
    uint32_t v;
    asm volatile("ld.shared.u32 %0, [%1];\n" : "=r"(v) : "r"(addr) : "memory");
    return v;
}
__device__ __forceinline__ uint2 lds64(uint32_t addr) {
    uint2 v;
    asm volatile("ld.shared.v2.u32 {%0,%1}, [%2];\n" : "=r"(v.x), "=r"(v.y) : "r"(addr) : "memory");
    return v;
}
__device__ __forceinline__ uint4 lds128(uint32_t addr) {
    uint4 v;
    asm volatile("ld.shared.v4.u32 {%0,%1,%2,%3}, [%4];\n" : "=r"(v.x), "=r"(v.y), "=r"(v.z), "=r"(v.w) : "r"(addr) : "memory");
    return v;
}
__device__ __forceinline__ float ldsf(uint32_t addr) { return __uint_as_float(lds32(addr)); }
__device__ __forceinline__ void sts32(uint32_t addr, uint32_t v) { asm volatile("st.shared.u32 [%0], %1;\n" ::"r"(addr), "r"(v) : "memory"); }
__device__ __forceinline__ void stsf(uint32_t addr, float v) { sts32(addr, __float_as_uint(v)); }
__device__ __forceinline__ void sts64(uint32_t addr, uint32_t a, uint32_t b) { asm volatile("st.shared.v2.u32 [%0], {%1,%2};\n" ::"r"(addr), "r"(a), "r"(b) : "memory"); }
__device__ __forceinline__ void sts128(uint32_t addr, uint32_t a, uint32_t b, uint32_t c, uint32_t d) {
    asm volatile("st.shared.v4.u32 [%0], {%1,%2,%3,%4};\n" ::"r"(addr), "r"(a), "r"(b), "r"(c), "r"(d) : "memory");
}
__device__ __forceinline__ void sts128f(uint32_t addr, const float (&v)[4]) {
    sts128(addr, __float_as_uint(v[0]), __float_as_uint(v[1]), __float_as_uint(v[2]), __float_as_uint(v[3]));
}
__device__ __forceinline__ void ldsm_x4(uint32_t& r0, uint32_t& r1, uint32_t& r2, uint32_t& r3, uint32_t addr) {
    asm volatile("ldmatrix.sync.aligned.m8n8.x4.shared.b16 {%0,%1,%2,%3}, [%4];\n"
                 : "=r"(r0), "=r"(r1), "=r"(r2), "=r"(r3) : "r"(addr) : "memory");
}
__device__ __forceinline__ void ldsm_x4_t(uint32_t& r0, uint32_t& r1, uint32_t& r2, uint32_t& r3, uint32_t addr) {
    asm volatile("ldmatrix.sync.aligned.m8n8.x4.trans.shared.b16 {%0,%1,%2,%3}, [%4];\n"
                 : "=r"(r0), "=r"(r1), "=r"(r2), "=r"(r3) : "r"(addr) : "memory");
}
__device__ __forceinline__ void ldsm_x2_t(uint32_t& r0, uint32_t& r1, uint32_t addr) {
    asm volatile("ldmatrix.sync.aligned.m8n8.x2.trans.shared.b16 {%0,%1}, [%2];\n" : "=r"(r0), "=r"(r1) : "r"(addr) : "memory");
}
__device__ __forceinline__ void ldsm_x1_t(uint32_t& r0, uint32_t addr) {
    asm volatile("ldmatrix.sync.aligned.m8n8.x1.trans.shared.b16 {%0}, [%1];\n" : "=r"(r0) : "r"(addr) : "memory");
}
__device__ __forceinline__ uint32_t movm(uint32_t a) {
    uint32_t d;
    asm volatile("movmatrix.sync.aligned.m8n8.trans.b16 %0, %1;\n" : "=r"(d) : "r"(a));
    return d;
}
__device__ __forceinline__ void mma_f16(float (&c)[4], uint32_t a0, uint32_t a1, uint32_t a2, uint32_t a3, uint32_t b0, uint32_t b1) {
    asm volatile(
        "mma.sync.aligned.m16n8k16.row.col.f32.f16.f16.f32 {%0,%1,%2,%3}, {%4,%5,%6,%7}, {%8,%9}, {%0,%1,%2,%3};\n"
        : "+f"(c[0]), "+f"(c[1]), "+f"(c[2]), "+f"(c[3])
        : "r"(a0), "r"(a1), "r"(a2), "r"(a3), "r"(b0), "r"(b1));
}
__device__ __forceinline__ void mma_bf16(float (&c)[4], uint32_t a0, uint32_t a1, uint32_t a2, uint32_t a3, uint32_t b0, uint32_t b1) {
    asm volatile(
        "mma.sync.aligned.m16n8k16.row.col.f32.bf16.bf16.f32 {%0,%1,%2,%3}, {%4,%5,%6,%7}, {%8,%9}, {%0,%1,%2,%3};\n"
        : "+f"(c[0]), "+f"(c[1]), "+f"(c[2]), "+f"(c[3])
        : "r"(a0), "r"(a1), "r"(a2), "r"(a3), "r"(b0), "r"(b1));
}
__device__ __forceinline__ void mma_bf16_k8(float (&c)[4], uint32_t a0, uint32_t a1, uint32_t b0) {
    asm volatile("mma.sync.aligned.m16n8k8.row.col.f32.bf16.bf16.f32 {%0,%1,%2,%3}, {%4,%5}, {%6}, {%0,%1,%2,%3};\n"
        : "+f"(c[0]), "+f"(c[1]), "+f"(c[2]), "+f"(c[3]) : "r"(a0), "r"(a1), "r"(b0));
}
__device__ __forceinline__ void bar_sync(int id, int n) { asm volatile("bar.sync %0, %1;\n" ::"r"(id), "r"(n) : "memory"); }
__device__ __forceinline__ void bar_arrive(int id, int n) { asm volatile("bar.arrive %0, %1;\n" ::"r"(id), "r"(n) : "memory"); }
__device__ __forceinline__ bool bar_or(int id, int n, bool v) {
    uint32_t r;
    asm volatile("{\n.reg .pred p, q;\nsetp.ne.u32 p, %3, 0;\nbar.red.or.pred q, %1, %2, p;\nselp.u32 %0, 1, 0, q;\n}\n" : "=r"(r) : "r"(id), "r"(n), "r"((uint32_t)v) : "memory");
    return r;
}
__device__ __forceinline__ uint4 ld_poll(const void* p) {
    uint4 v;
    asm volatile("ld.relaxed.gpu.global.v4.u32 {%0,%1,%2,%3}, [%4];\n" : "=r"(v.x), "=r"(v.y), "=r"(v.z), "=r"(v.w) : "l"(p) : "memory");
    return v;
}
template <class T> __device__ __forceinline__ T* pin(T* p, uint32_t z) {
    uint32_t lo, hi;
    asm volatile("mov.b64 {%0, %1}, %2;\n" : "=r"(lo), "=r"(hi) : "l"(p));
    asm volatile("xor.b32 %0, %0, %1;\n" : "+r"(lo) : "r"(z));
    asm volatile("xor.b32 %0, %0, %1;\n" : "+r"(hi) : "r"(z));
    asm volatile("mov.b64 %0, {%1, %2};\n" : "=l"(p) : "r"(lo), "r"(hi));
    return p;
}
__device__ __forceinline__ uint32_t pin(uint32_t a, uint32_t z) { asm volatile("xor.b32 %0, %0, %1;\n" : "+r"(a) : "r"(z)); return a; }
__device__ __forceinline__ uint2 ld_poll64(const void* p) {
    uint2 v;
    asm volatile("ld.relaxed.gpu.global.v2.u32 {%0,%1}, [%2];\n" : "=r"(v.x), "=r"(v.y) : "l"(p) : "memory");
    return v;
}
__device__ __forceinline__ uint32_t ld_poll32(const void* p) {
    uint32_t v;
    asm volatile("ld.relaxed.gpu.global.u32 %0, [%1];\n" : "=r"(v) : "l"(p) : "memory");
    return v;
}
__device__ __forceinline__ uint4 ldg128(const void* p) {
    uint4 v;
    asm volatile("ld.global.nc.v4.u32 {%0,%1,%2,%3}, [%4];\n" : "=r"(v.x), "=r"(v.y), "=r"(v.z), "=r"(v.w) : "l"(p));
    return v;
}
__device__ __forceinline__ uint2 ldg64(const void* p) {
    uint2 v;
    asm volatile("ld.global.nc.v2.u32 {%0,%1}, [%2];\n" : "=r"(v.x), "=r"(v.y) : "l"(p));
    return v;
}
__device__ __forceinline__ uint32_t ldg16(const void* p) {
    uint32_t v;
    asm volatile("ld.global.nc.u16 %0, [%1];\n" : "=r"(v) : "l"(p));
    return v;
}
__device__ __forceinline__ void stg128(void* p, uint32_t a, uint32_t b, uint32_t c, uint32_t d) {
    asm volatile("st.global.v4.u32 [%0], {%1,%2,%3,%4};\n" ::"l"(p), "r"(a), "r"(b), "r"(c), "r"(d) : "memory");
}
__device__ __forceinline__ void stg64(void* p, uint32_t a, uint32_t b) { asm volatile("st.global.v2.u32 [%0], {%1,%2};\n" ::"l"(p), "r"(a), "r"(b) : "memory"); }
__device__ __forceinline__ void stg32(void* p, uint32_t a) { asm volatile("st.global.u32 [%0], %1;\n" ::"l"(p), "r"(a) : "memory"); }
__device__ __forceinline__ bool all_nz(const uint4& v) { return v.x && v.y && v.z && v.w; }
#define SPIN_LIMIT (1 << 21)
#define TRAP() __trap()
__device__ __forceinline__ void hint_arrive(unsigned* g_hint, int idx, int sub) {
    asm volatile("red.relaxed.gpu.global.add.u32 [%0], 1;\n" ::"l"(&g_hint[sub * 32 + idx]) : "memory");
}
__device__ __forceinline__ void hint_wait(const unsigned* g_hint, int idx, unsigned target) {
    unsigned l;
    asm volatile("mov.u32 %0, %%laneid;" : "=r"(l));
    const unsigned* c = &g_hint[(l & 7) * 32 + idx];
    int it = 0;
    while (__any_sync(0xffffffffu, (int)(ld_poll32(c) - target) < 0)) { if (++it > SPIN_LIMIT) TRAP(); }
}
__device__ __forceinline__ void mbar_init(uint32_t bar, uint32_t cnt) { asm volatile("mbarrier.init.shared::cta.b64 [%0], %1;\n" ::"r"(bar), "r"(cnt) : "memory"); }
__device__ __forceinline__ void mbar_expect(uint32_t bar, uint32_t bytes) {
    asm volatile("mbarrier.arrive.expect_tx.shared::cta.b64 _, [%0], %1;\n" ::"r"(bar), "r"(bytes) : "memory");
}
__device__ __forceinline__ void mbar_arrive(uint32_t bar) { asm volatile("mbarrier.arrive.shared::cta.b64 _, [%0];\n" ::"r"(bar) : "memory"); }
__device__ __forceinline__ void mbar_wait(uint32_t bar) {
    asm volatile(
        "{\n.reg .pred p;\n"
        "W_%=:\n"
        "mbarrier.try_wait.parity.shared::cta.b64 p, [%0], 0;\n"
        "@!p bra W_%=;\n}\n" ::"r"(bar) : "memory");
}
__device__ __forceinline__ void bulk_s2g(void* dst, uint32_t src, uint32_t bytes) {
    asm volatile("cp.async.bulk.global.shared::cta.bulk_group [%0], [%1], %2;\ncp.async.bulk.commit_group;\n" ::"l"(dst), "r"(src), "r"(bytes) : "memory");
}
__device__ __forceinline__ void tma_2d(uint32_t dst, const CUtensorMap* tm, int c0, int c1, uint32_t bar) {
    asm volatile("cp.async.bulk.tensor.2d.shared::cluster.global.mbarrier::complete_tx::bytes [%0], [%1, {%3, %4}], [%2];\n"
                 ::"r"(dst), "l"(tm), "r"(bar), "r"(c0), "r"(c1) : "memory");
}
__device__ __forceinline__ void tma_3d(uint32_t dst, const CUtensorMap* tm, int c0, int c1, int c2, uint32_t bar) {
    asm volatile("cp.async.bulk.tensor.3d.shared::cluster.global.mbarrier::complete_tx::bytes [%0], [%1, {%3, %4, %5}], [%2];\n"
                 ::"r"(dst), "l"(tm), "r"(bar), "r"(c0), "r"(c1), "r"(c2) : "memory");
}
__device__ __forceinline__ void tma_st_3d(const CUtensorMap* tm, uint32_t src, int c0, int c1, int c2) {
    asm volatile("cp.async.bulk.tensor.3d.global.shared::cta.bulk_group [%0, {%2, %3, %4}], [%1];\ncp.async.bulk.commit_group;\n"
                 ::"l"(tm), "r"(src), "r"(c0), "r"(c1), "r"(c2) : "memory");
}
__device__ __forceinline__ bool elect_one() {
    uint32_t r;
    asm volatile("{\n.reg .pred p;\nelect.sync _|p, 0xffffffff;\nselp.u32 %0, 1, 0, p;\n}\n" : "=r"(r));
    return r;
}
__device__ __forceinline__ void fence_async() { asm volatile("fence.proxy.async.shared::cta;\n" ::: "memory"); }

__device__ __forceinline__ float2 cmul(float2 a, float2 b) {
    return make_float2(fmaf(a.x, b.x, -a.y * b.y), fmaf(a.x, b.y, a.y * b.x));
}
__device__ __forceinline__ float2 csq(float2 a) {
    float p = a.x * a.y;
    return make_float2(fmaf(a.x, a.x, -a.y * a.y), p + p);
}
__device__ __forceinline__ float2 cexp_e(float lr2, float rh, float rl, float e) {
    float m;
    asm("ex2.approx.ftz.f32 %0, %1;\n" : "=f"(m) : "f"(lr2 * e));
    const float a = rh * e;
    const float r = fmaf(rl, e, a - rintf(a)) * 6.283185307179586f;
    return make_float2(m * __cosf(r), m * __sinf(r));
}
__device__ __forceinline__ float rcp_approx(float x) { float r; asm("rcp.approx.ftz.f32 %0, %1;\n" : "=f"(r) : "f"(x)); return r; }
__device__ __forceinline__ float ex2_approx(float x) { float r; asm("ex2.approx.ftz.f32 %0, %1;\n" : "=f"(r) : "f"(x)); return r; }
__device__ __forceinline__ float sqrt_approx(float x) { float r; asm("sqrt.approx.ftz.f32 %0, %1;\n" : "=f"(r) : "f"(x)); return r; }

__device__ __forceinline__ void wg_fence() { asm volatile("wgmma.fence.sync.aligned;\n" ::: "memory"); }
__device__ __forceinline__ void wg_commit() { asm volatile("wgmma.commit_group.sync.aligned;\n" ::: "memory"); }
__device__ __forceinline__ void wg_wait0() { asm volatile("wgmma.wait_group.sync.aligned 0;\n" ::: "memory"); }
template <int T0, int NT> __device__ __forceinline__ void wg_h(uint32_t (&acc)[32], const uint32_t (&a)[4], uint64_t desc);
template <> __device__ __forceinline__ void wg_h<0, 16>(uint32_t (&acc)[32], const uint32_t (&a)[4], uint64_t desc) {
    asm volatile("wgmma.mma_async.sync.aligned.m64n128k16.f16.f16.f16 {%0,%1,%2,%3,%4,%5,%6,%7,%8,%9,%10,%11,%12,%13,%14,%15,%16,%17,%18,%19,%20,%21,%22,%23,%24,%25,%26,%27,%28,%29,%30,%31}, {%32,%33,%34,%35}, %36, 1, 1, 1, 0;\n"
                 : "+r"(acc[0]), "+r"(acc[1]), "+r"(acc[2]), "+r"(acc[3]), "+r"(acc[4]), "+r"(acc[5]), "+r"(acc[6]), "+r"(acc[7]), "+r"(acc[8]), "+r"(acc[9]), "+r"(acc[10]), "+r"(acc[11]), "+r"(acc[12]), "+r"(acc[13]), "+r"(acc[14]), "+r"(acc[15]), "+r"(acc[16]), "+r"(acc[17]), "+r"(acc[18]), "+r"(acc[19]), "+r"(acc[20]), "+r"(acc[21]), "+r"(acc[22]), "+r"(acc[23]), "+r"(acc[24]), "+r"(acc[25]), "+r"(acc[26]), "+r"(acc[27]), "+r"(acc[28]), "+r"(acc[29]), "+r"(acc[30]), "+r"(acc[31])
                 : "r"(a[0]), "r"(a[1]), "r"(a[2]), "r"(a[3]), "l"(desc));
}
template <> __device__ __forceinline__ void wg_h<4, 4>(uint32_t (&acc)[32], const uint32_t (&a)[4], uint64_t desc) {
    asm volatile("wgmma.mma_async.sync.aligned.m64n32k16.f16.f16.f16 {%0,%1,%2,%3,%4,%5,%6,%7}, {%8,%9,%10,%11}, %12, 1, 1, 1, 0;\n"
                 : "+r"(acc[8]), "+r"(acc[9]), "+r"(acc[10]), "+r"(acc[11]), "+r"(acc[12]), "+r"(acc[13]), "+r"(acc[14]), "+r"(acc[15])
                 : "r"(a[0]), "r"(a[1]), "r"(a[2]), "r"(a[3]), "l"(desc));
}
template <> __device__ __forceinline__ void wg_h<8, 4>(uint32_t (&acc)[32], const uint32_t (&a)[4], uint64_t desc) {
    asm volatile("wgmma.mma_async.sync.aligned.m64n32k16.f16.f16.f16 {%0,%1,%2,%3,%4,%5,%6,%7}, {%8,%9,%10,%11}, %12, 1, 1, 1, 0;\n"
                 : "+r"(acc[16]), "+r"(acc[17]), "+r"(acc[18]), "+r"(acc[19]), "+r"(acc[20]), "+r"(acc[21]), "+r"(acc[22]), "+r"(acc[23])
                 : "r"(a[0]), "r"(a[1]), "r"(a[2]), "r"(a[3]), "l"(desc));
}
template <> __device__ __forceinline__ void wg_h<12, 4>(uint32_t (&acc)[32], const uint32_t (&a)[4], uint64_t desc) {
    asm volatile("wgmma.mma_async.sync.aligned.m64n32k16.f16.f16.f16 {%0,%1,%2,%3,%4,%5,%6,%7}, {%8,%9,%10,%11}, %12, 1, 1, 1, 0;\n"
                 : "+r"(acc[24]), "+r"(acc[25]), "+r"(acc[26]), "+r"(acc[27]), "+r"(acc[28]), "+r"(acc[29]), "+r"(acc[30]), "+r"(acc[31])
                 : "r"(a[0]), "r"(a[1]), "r"(a[2]), "r"(a[3]), "l"(desc));
}
template <> __device__ __forceinline__ void wg_h<0, 8>(uint32_t (&acc)[32], const uint32_t (&a)[4], uint64_t desc) {
    asm volatile("wgmma.mma_async.sync.aligned.m64n64k16.f16.f16.f16 {%0,%1,%2,%3,%4,%5,%6,%7,%8,%9,%10,%11,%12,%13,%14,%15}, {%16,%17,%18,%19}, %20, 1, 1, 1, 0;\n"
                 : "+r"(acc[0]), "+r"(acc[1]), "+r"(acc[2]), "+r"(acc[3]), "+r"(acc[4]), "+r"(acc[5]), "+r"(acc[6]), "+r"(acc[7]), "+r"(acc[8]), "+r"(acc[9]), "+r"(acc[10]), "+r"(acc[11]), "+r"(acc[12]), "+r"(acc[13]), "+r"(acc[14]), "+r"(acc[15])
                 : "r"(a[0]), "r"(a[1]), "r"(a[2]), "r"(a[3]), "l"(desc));
}
template <> __device__ __forceinline__ void wg_h<4, 12>(uint32_t (&acc)[32], const uint32_t (&a)[4], uint64_t desc) {
    asm volatile("wgmma.mma_async.sync.aligned.m64n96k16.f16.f16.f16 {%0,%1,%2,%3,%4,%5,%6,%7,%8,%9,%10,%11,%12,%13,%14,%15,%16,%17,%18,%19,%20,%21,%22,%23}, {%24,%25,%26,%27}, %28, 1, 1, 1, 0;\n"
                 : "+r"(acc[8]), "+r"(acc[9]), "+r"(acc[10]), "+r"(acc[11]), "+r"(acc[12]), "+r"(acc[13]), "+r"(acc[14]), "+r"(acc[15]), "+r"(acc[16]), "+r"(acc[17]), "+r"(acc[18]), "+r"(acc[19]), "+r"(acc[20]), "+r"(acc[21]), "+r"(acc[22]), "+r"(acc[23]), "+r"(acc[24]), "+r"(acc[25]), "+r"(acc[26]), "+r"(acc[27]), "+r"(acc[28]), "+r"(acc[29]), "+r"(acc[30]), "+r"(acc[31])
                 : "r"(a[0]), "r"(a[1]), "r"(a[2]), "r"(a[3]), "l"(desc));
}

#define PBYTES 4608
#define DELAY(n) do { if (n) { const unsigned c0_ = clock32(); while ((int)(clock32() - c0_) < (n)) {} } } while (0)
#define KDEL 400
#define PDEL 300
#define CST(i) do { if ((warp & 3) == 0 && lane_v() == 0) { unsigned t_; asm volatile("mov.u32 %0, %%globaltimer_lo;" : "=r"(t_) :: "memory"); sts32(sb + SMEM_TOTAL - 768 + (warp >> 2) * 128 + (i) * 4, t_); } } while (0)
#define TP0 5000
#define TP4 5800
#define KDEL2 300
#define WSP 450
#define WS0 0
#define HINTW 10
#define WAS 0x0005
#define WA0 (WAS >> 12)
#define WA1 ((WAS >> 8) & 15)
#define WA2 ((WAS >> 4) & 15)
#define WA3 (WAS & 15)
#define WDAT 1
#define UW 8
#define TOKEN_OF(g) (16 * ((g) & 1) + ((g) >> 2) + 2 * ((g) & 2))
#define HI2(a, b) (pack_f16_rz(__uint_as_float(a), __uint_as_float(b)) & 0xfff8fff8u)
struct Params {
    const bf16 *x, *lar, *aim, *cre, *cim, *ldt, *dsk;
    Scratch* s;
    const bf16* wr;
    bf16* out;
};

template <int NK>
__device__ __forceinline__ void ln_partial(const uint32_t (&H)[2][NK], const uint32_t (&bw)[NK], uint32_t lp, int warp, int g, int t) {
    float cs[4] = {0.f, 0.f, 0.f, 0.f}, cl[4] = {0.f, 0.f, 0.f, 0.f}, ch[4] = {0.f, 0.f, 0.f, 0.f};
#pragma unroll
    for (int k = 0; k < NK; k += 2) {
        uint32_t a0, a1, a2, a3;
        asm volatile("prmt.b32 %0, %4, %4, %8;\nprmt.b32 %1, %5, %5, %8;\nprmt.b32 %2, %6, %6, %8;\nprmt.b32 %3, %7, %7, %8;\n"
                     : "=r"(a0), "=r"(a1), "=r"(a2), "=r"(a3) : "r"(H[0][k]), "r"(H[1][k]), "r"(H[0][k + 1]), "r"(H[1][k + 1]), "r"(0x3210u + (warp >> 8)));
        mma_bf16(cl, a0, a1, a2, a3, H[0][k], H[0][k + 1]);
        mma_bf16(ch, a0, a1, a2, a3, H[1][k], H[1][k + 1]);
        mma_bf16(cs, a0, a1, a2, a3, bw[k], bw[k + 1]);
    }
    const uint32_t a = lp + (g * 20 + warp) * 4;
    if (t == 0) {
        stsf(a, cs[1]); stsf(a + 8 * 80, cs[3]);
        if (NK == 4) { stsf(a + 48 * 80, cs[0]); stsf(a + 56 * 80, cs[2]); }
    }
    if (t == (g >> 1)) { stsf(a + 16 * 80, (g & 1) ? cl[1] : cl[0]); stsf(a + 24 * 80, (g & 1) ? ch[3] : ch[2]); }
}
__device__ __forceinline__ float sum18(uint32_t a) {
    const uint4 p = lds128(a), q = lds128(a + 16), r = lds128(a + 32), s = lds128(a + 48);
    const uint2 u = lds64(a + 64);
#define F(x) __uint_as_float(x)
    return (((F(p.x) + F(p.y)) + (F(p.z) + F(p.w))) + ((F(q.x) + F(q.y)) + (F(q.z) + F(q.w)))) +
           (((F(r.x) + F(r.y)) + (F(r.z) + F(r.w))) + ((F(s.x) + F(s.y)) + (F(s.z) + F(s.w))) + (F(u.x) + F(u.y)));
#undef F
}
__device__ __forceinline__ float sum9(uint32_t a) {
    const uint4 p = lds128(a), q = lds128(a + 16);
#define F(x) __uint_as_float(x)
    return (((F(p.x) + F(p.y)) + (F(p.z) + F(p.w))) + ((F(q.x) + F(q.y)) + (F(q.z) + F(q.w)))) + ldsf(a + 32);
#undef F
}
template <int N>
__device__ __forceinline__ void ln_finish(uint32_t lp, int lane, float& mb, float& rc) {
    const float v = N == 9 ? sum9(lp + lane * 80) : sum18(lp + lane * 80);
    const float o = __shfl_xor_sync(0xffffffffu, v, 16);
    const float m0 = v * (1.0f / 576.0f);
    const float mean = fmaf(fmaf(-m0, 576.0f, v), 1.0f / 576.0f, m0);
    const float var = fmaxf(fmaf(o, 1.0f / 576.0f, -(mean * mean)), 0.f);
    mb = rbf(mean);
    rc = rcp_approx(rbf(sqrt_approx(rbf(rbf(var) + 1e-5f))));
}
__device__ __forceinline__ uint32_t ln_apply(uint32_t w, const uint2& st) {
    uint32_t r;
    asm("{\n.reg .b16 m, t, h, l;\n.reg .b32 mm, hh, ll, d, e;\nmov.b32 {m, t}, %2;\nmov.b32 {h, l}, %3;\nmov.b32 mm, {m, m};\nmov.b32 hh, {h, h};\nmov.b32 ll, {l, l};\n"
        "sub.rn.bf16x2 d, %1, mm;\nmul.rn.bf16x2 e, d, ll;\nfma.rn.bf16x2 %0, d, hh, e;\n}\n" : "=r"(r) : "r"(w), "r"(st.x), "r"(st.y));
    return r;
}
__device__ __forceinline__ void stat_store(uint32_t a, float mb, float rc, uint32_t extra) {
    const float rh = rbf(rc);
    sts64(a, (__float_as_uint(mb) >> 16) | (extra << 16), pack_bf16(rh, rc - rh));
}

__device__ __forceinline__ void hcmul(uint32_t re, uint32_t im, uint32_t z, uint32_t& ore, uint32_t& oim) {
    asm("{\n.reg .b16 x, y;\n.reg .b32 xx, yy, ny, a, b;\nmov.b32 {x, y}, %4;\nmov.b32 xx, {x, x};\nmov.b32 yy, {y, y};\nneg.f16x2 ny, yy;\n"
        "mul.rn.f16x2 a, %2, xx;\nfma.rn.f16x2 %0, %3, ny, a;\nmul.rn.f16x2 b, %3, xx;\nfma.rn.f16x2 %1, %2, yy, b;\n}\n" : "=&r"(ore), "=r"(oim) : "r"(re), "r"(im), "r"(z));
}
__device__ __forceinline__ void hcmul(uint32_t re, uint32_t im, uint32_t zx, uint32_t zy, uint32_t& ore, uint32_t& oim) {
    asm("{\n.reg .b32 ny, a, b;\nneg.f16x2 ny, %5;\n"
        "mul.rn.f16x2 a, %2, %4;\nfma.rn.f16x2 %0, %3, ny, a;\nmul.rn.f16x2 b, %3, %4;\nfma.rn.f16x2 %1, %2, %5, b;\n}\n" : "=&r"(ore), "=r"(oim) : "r"(re), "r"(im), "r"(zx), "r"(zy));
}

struct KGen {
    uint32_t Af[4][4];
    float2 z1, z8, z64, z128, T[9];
    uint32_t zw;
};
__device__ __forceinline__ void kgen_setup(KGen& k, uint32_t pa, float dt) {
    const float A = rbf(expf(bf_lo(pa)));
    const float lr2 = -(A * dt) * 1.4426950408889634f;
    const float li = bf_hi(pa) * dt;
    const float rh = li * 0.15915494309189535f;
    const float rl = fmaf(li, 6.4206382986e-9f, fmaf(li, 0.15915494309189535f, -rh));
    k.z1 = cexp_e(lr2, rh, rl, 1.0f);
    k.z8 = cexp_e(lr2, rh, rl, 8.0f);
    k.z64 = cexp_e(lr2, rh, rl, 64.0f);
}
__device__ __forceinline__ void kgen_rows(KGen& k, uint32_t tb, int lane) {
    const float2 z8 = k.z8, z64 = k.z64;
    const uint32_t row = tb + lane * TBP;
    k.z128 = csq(z64);
    const float2 z16 = csq(z8), z32 = csq(z16), z48 = cmul(z32, z16), z80 = cmul(z64, z16), z96 = cmul(z64, z32), z112 = cmul(z64, z48);
    uint32_t re[4], im[4], a[4], b[4];
    re[0] = pack_f16(1.0f, z16.x); im[0] = pack_f16(0.0f, z16.y);
    re[1] = pack_f16(z32.x, z48.x); im[1] = pack_f16(z32.y, z48.y);
    re[2] = pack_f16(z64.x, z80.x); im[2] = pack_f16(z64.y, z80.y);
    re[3] = pack_f16(z96.x, z112.x); im[3] = pack_f16(z96.y, z112.y);
    sts128(row, re[0], re[1], re[2], re[3]);
    sts128(row + 32, im[0], im[1], im[2], im[3]);
    const uint32_t zz = pack_f16(z8.x, z8.y);
#pragma unroll
    for (int j = 0; j < 4; j++) hcmul(re[j], im[j], zz, a[j], b[j]);
    sts128(row + 16, a[0], a[1], a[2], a[3]);
    sts128(row + 48, b[0], b[1], b[2], b[3]);
    __syncwarp();
    const int mi = lane >> 3;
    const uint32_t ad = tb + (lane & 7) * TBP + mi * 16;
#pragma unroll
    for (int ks = 0; ks < 4; ks++) ldsm_x4_t(k.Af[ks][0], k.Af[ks][1], k.Af[ks][2], k.Af[ks][3], ad + ks * 8 * TBP);
}
__device__ __forceinline__ void kgen_chain(KGen& k, uint32_t pc, float cs) {
    k.T[0] = make_float2(bf_lo(pc) * cs, -bf_hi(pc) * cs);
    const float2 y1 = make_float2(k.z1.x, -k.z1.y);
#pragma unroll
    for (int c = 1; c < 8; c++) k.T[c] = cmul(k.T[c - 1], y1);
    k.T[8] = cmul(k.T[0], make_float2(k.z8.x, -k.z8.y));
}
__device__ __forceinline__ void kgen_cols(KGen& k, uint32_t tb, int lane) {
    const uint32_t row = tb + lane * TBP;
    const float2 (&T)[9] = k.T;
    const uint32_t zv = pack_f16(k.z128.x, k.z128.y), zo = __shfl_xor_sync(0xffffffffu, zv, 1);
    k.zw = (lane & 1) ? __byte_perm(zo, zv, 0x7632) : __byte_perm(zv, zo, 0x5410);
    const float2 y256 = csq(make_float2(k.z128.x, -k.z128.y)), y512 = csq(y256), y768 = cmul(y512, y256), y1024 = csq(y512);
    const float2 c1032 = cmul(T[8], y1024);
    const uint32_t r04 = pack_f16(T[0].x, T[4].x), i04 = pack_f16(T[0].y, T[4].y), r26 = pack_f16(T[2].x, T[6].x), i26 = pack_f16(T[2].y, T[6].y);
    const uint32_t r48 = pack_f16(T[4].x, T[8].x), i48 = pack_f16(T[4].y, T[8].y);
    __syncwarp();
    sts128(row, r04, pack_f16(T[1].x, T[5].x), r26, pack_f16(T[3].x, T[7].x));
    sts128(row + 16, i04, pack_f16(T[1].y, T[5].y), i26, pack_f16(T[3].y, T[7].y));
    uint32_t a[4], b[4];
    {
        const uint32_t zz = pack_f16(y256.x, y256.y);
        hcmul(r04, i04, zz, a[0], b[0]);
        hcmul(r26, i26, zz, a[2], b[2]);
        hcmul(r48, i48, zz, a[3], b[3]);
    }
    sts128(row + 32, a[0], a[0], a[2], a[3]);
    sts128(row + 48, b[0], b[0], b[2], b[3]);
    {
        hcmul(r48, i48, pack_f16(y512.x, y512.y), a[0], b[0]);
        hcmul(r48, i48, pack_f16(y768.x, y768.y), a[1], b[1]);
        const uint32_t zz = pack_f16(c1032.x, c1032.y);
        hcmul(pack_f16(1.0f, y256.x), pack_f16(0.0f, y256.y), zz, a[2], b[2]);
        hcmul(pack_f16(y512.x, y768.x), pack_f16(y512.y, y768.y), zz, a[3], b[3]);
    }
    sts128(row + 64, a[0], a[1], a[2], a[3]);
    sts128(row + 80, b[0], b[1], b[2], b[3]);
}
__device__ __forceinline__ void kgen_mma(const KGen& k, uint32_t tb, int lane) {
    const int t = lane & 3;
    const uint32_t zw = k.zw;
    uint32_t zx[4], zy[4];
#pragma unroll
    for (int ks = 0; ks < 4; ks++) { zx[ks] = __shfl_sync(0xffffffffu, zw, 8 * ks + 2 * t); zy[ks] = __shfl_sync(0xffffffffu, zw, 8 * ks + 2 * t + 1); }
    __syncwarp();
    float acc[2][3][4];
#pragma unroll
    for (int i = 0; i < 6; i++)
#pragma unroll
        for (int j = 0; j < 4; j++) acc[i / 3][i % 3][j] = 0.f;
    {
        const int mi = lane >> 3;
        const uint32_t bd = tb + ((lane & 7) + 8 * (mi >> 1)) * TBP + (mi & 1) * 16;
#pragma unroll
        for (int kp = 0; kp < 2; kp++) {
            uint32_t b[3][4];
#pragma unroll
            for (int j = 0; j < 3; j++) ldsm_x4_t(b[j][0], b[j][1], b[j][2], b[j][3], bd + kp * 16 * TBP + j * 32);
#pragma unroll
            for (int h = 0; h < 2; h++) {
                const int ks = 2 * kp + h;
                uint32_t d[4];
                hcmul(k.Af[ks][0], k.Af[ks][2], zx[ks], zy[ks], d[0], d[2]);
                hcmul(k.Af[ks][1], k.Af[ks][3], zx[ks], zy[ks], d[1], d[3]);
#pragma unroll
                for (int j = 0; j < 3; j++) {
                    mma_f16(acc[0][j], k.Af[ks][0], k.Af[ks][1], k.Af[ks][2], k.Af[ks][3], b[j][2 * h], b[j][2 * h + 1]);
                    mma_f16(acc[1][j], d[0], d[1], d[2], d[3], b[j][2 * h], b[j][2 * h + 1]);
                }
            }
        }
    }
    __syncwarp();
#pragma unroll
    for (int h = 0; h < 2; h++) {
        sts64(tb + h * 256 + lane * 8, pack_f16(acc[h][0][0], acc[h][0][1]), pack_f16(acc[h][0][2], acc[h][0][3]));
        sts64(tb + 512 + h * 256 + lane * 8, pack_f16(acc[h][1][0], acc[h][1][1]), pack_f16(acc[h][1][2], acc[h][1][3]));
        sts32(tb + 1024 + h * 256 + lane * 4, pack_f16(acc[h][2][0], t < 2 ? acc[h][2][1] : acc[h][2][2]));
        sts32(tb + 1152 + h * 256 + lane * 4, pack_f16(t < 2 ? acc[h][2][2] : acc[h][2][1], acc[h][2][3]));
    }
}
__device__ __forceinline__ uint32_t table_buf(uint32_t sb, int warp) { return sb + SM_TB + warp * TBW; }

__device__ __forceinline__ void kgen_combine(uint32_t sb, int warp, int lane, uint32_t kw, uint32_t ao) {
    const int wq = warp & 3;
    const uint32_t a = table_buf(sb, warp & ~3) + wq * 256 + lane * 8, c = table_buf(sb, warp & ~3) + 1024 + wq * 128 + lane * 4;
    const int t = lane & 3;
    const uint32_t o0 = (t < 2 ? KW_T2 + KW_KH + 16 + t * 256 - (wq & 1) * KW_KH : KW_T3 + 16 - 1024 + t * 512 + (wq & 1) * 256) + (lane >> 2) * 16;
    const uint4 o = make_uint4(o0 + t * 36, o0 + (t ^ 1) * 36, o0 + (t ^ 2) * 36, o0 + (t ^ 3) * 36);
    const uint2 u = lds64(a), v = lds64(a + TBW), w = lds64(a + 2 * TBW), x = lds64(a + 3 * TBW);
    const uint32_t kt = hadd2(hadd2(lds32(c), lds32(c + TBW)), hadd2(lds32(c + 2 * TBW), lds32(c + 3 * TBW)));
    const uint32_t k23 = hadd2(hadd2(u.y, v.y), hadd2(w.y, x.y));
    sts64(kw + wq * 64 + ao, hadd2(hadd2(u.x, v.x), hadd2(w.x, x.x)), k23);
    const uint32_t d = kw + (wq >> 1) * 128;
    const uint32_t kh = hmul2(kt, 0x38003800u);
    sts32(d + o.x, kh); sts32(d + o.y, kh); sts32(d + o.z, kh); sts32(d + o.w, kh);
    if (wq == 3) {
        if (lane == 31) { sts32(kw + 264, k23 >> 16); sts32(kw + 288 + 264, k23 >> 16); sts32(kw + 576 + 264, k23 >> 16); }
        if (lane == 29) { sts32(kw + 864 + 280, kt >> 16); sts32(kw + 280, kt & 0xffff0000u); }
    }
}

__device__ __forceinline__ int c_exponent(const uint2& r, const uint2& i) {
    uint32_t mx = __vmaxu2(__vmaxu2(r.x & 0x7fff7fffu, r.y & 0x7fff7fffu), __vmaxu2(i.x & 0x7fff7fffu, i.y & 0x7fff7fffu));
    mx = __reduce_max_sync(0xffffffffu, max(mx & 0xffffu, mx >> 16));
    return min(max((int)(mx >> 7), 4), 240);
}

__device__ __forceinline__ int warp_v() { int l; asm volatile("mov.u32 %0, %%tid.x;" : "=r"(l)); return __shfl_sync(0xffffffffu, l >> 5, 0); }
__device__ __forceinline__ int lane_v() { int l; asm volatile("mov.u32 %0, %%laneid;" : "=r"(l)); return l; }
__device__ __forceinline__ unsigned clock32() { unsigned c; asm volatile("mov.u32 %0, %%clock;" : "=r"(c)); return c; }
__device__ __forceinline__ uint32_t prmt(uint32_t a, uint32_t b, uint32_t s) { uint32_t d; asm("prmt.b32 %0, %1, %2, %3;\n" : "=r"(d) : "r"(a), "r"(b), "r"(s)); return d; }
__device__ __forceinline__ uint32_t prmt_v(uint32_t a, uint32_t b, uint32_t s) { uint32_t d; asm volatile("prmt.b32 %0, %1, %2, %3;\n" : "=r"(d) : "r"(a), "r"(b), "r"(s)); return d; }
__device__ __forceinline__ void mmah16(uint32_t& d0, uint32_t& d1, uint32_t a0, uint32_t a1, uint32_t a2, uint32_t a3, uint32_t b0, uint32_t b1, uint32_t c0, uint32_t c1) {
    asm volatile("mma.sync.aligned.m16n8k16.row.col.f16.f16.f16.f16 {%0,%1}, {%2,%3,%4,%5}, {%6,%7}, {%8,%9};\n"
                 : "=r"(d0), "=r"(d1) : "r"(a0), "r"(a1), "r"(a2), "r"(a3), "r"(b0), "r"(b1), "r"(c0), "r"(c1));
}
__device__ __forceinline__ void mmah8(uint32_t& d0, uint32_t& d1, uint32_t a0, uint32_t a1, uint32_t b0, uint32_t c0, uint32_t c1) {
    asm volatile("mma.sync.aligned.m16n8k8.row.col.f16.f16.f16.f16 {%0,%1}, {%2,%3}, {%4}, {%5,%6};\n"
                 : "=r"(d0), "=r"(d1) : "r"(a0), "r"(a1), "r"(b0), "r"(c0), "r"(c1));
}
template <int A = 8, int B = 32>
__device__ __forceinline__ void conv_rename(uint32_t (&acc)[32]) {
#pragma unroll
    for (int i = A; i < B; i++) { uint32_t v; asm volatile("mov.b32 %0, %1;\n" : "=r"(v) : "r"(acc[i])); acc[i] = v; }
}
__host__ __device__ constexpr uint32_t band_bits(int hw, int sh) {
    uint32_t c = 0;
    for (int s = 0; s <= 10; s++)
        for (int e = 0; e < 2; e++) {
            const int v = s - 3 + sh - 4 * e;
            if (v <= hw && v >= -hw) c |= 1u << (14 + 16 * e - s);
        }
    return c;
}
template <int HW, int SH, int J> __device__ __forceinline__ uint32_t band(uint32_t p2) {
    uint32_t d;
    asm volatile("{\n.reg .b32 t;\nmul.lo.u32 t, %1, %2;\nand.b32 %0, t, 0x40004000;\n}\n" : "=r"(d) : "r"(p2), "n"(band_bits(HW, SH) | J));
    return d;
}
__device__ __forceinline__ void band_quads(uint4 (&b)[3], uint32_t p2, uint32_t pm) {
    b[0] = make_uint4(band<2, 4, 1>(pm), band<1, 4, 1>(p2), band<2, -4, 1>(pm), band<1, -4, 1>(p2));
    b[1] = make_uint4(band<4, 4, 1>(pm), band<3, 4, 1>(pm), band<4, -4, 1>(pm), band<3, -4, 1>(pm));
    b[2] = make_uint4(band<2, 4, 2>(pm), band<4, 4, 2>(pm), band<2, -4, 2>(pm), band<4, -4, 2>(pm));
}
__device__ __forceinline__ uint2 run_sums(const uint4& a, uint32_t b0, uint32_t b1) {
    uint2 d;
    mmah16(d.x, d.y, a.x, a.y, a.z, a.w, b0, b1, 0u, 0u);
    return d;
}
__device__ __forceinline__ float h_lo(uint32_t w) { return __half2float(__ushort_as_half((unsigned short)(w & 0xffffu))); }
__device__ __forceinline__ float h_hi(uint32_t w) { return __half2float(__ushort_as_half((unsigned short)(w >> 16))); }
__device__ __forceinline__ uint64_t smem_desc(uint32_t sb, uint32_t o16, uint32_t lbo) {
    uint64_t d;
    asm("mov.b64 %0, {%1, %2};" : "=l"(d) : "r"(((sb & 0x3FFFF) >> 4) + o16 + (lbo << 12)), "r"(8));
    return d;
}
template <int I> struct IC { static constexpr int value = I; };

struct Conv {
    uint32_t q2[3][2][4];
    uint32_t q3[2][4];
    uint32_t r[18];
};
struct ConvPre {
    uint32_t a[5], b[5];
    uint32_t t[4];
};
__device__ __forceinline__ void conv_pre(ConvPre& e, uint32_t ka, uint32_t ks, uint32_t sel) {
    const uint4 r = lds128(ka + 256), s = lds128(ka + 272);
    ldsm_x4(e.t[0], e.t[1], e.t[2], e.t[3], ks);
    const uint32_t sw = sel ^ 0x4444u;
    e.a[0] = prmt(r.y, r.z, sel); e.a[1] = prmt(r.w, r.z, sw); e.a[2] = prmt(r.x, r.y, sel); e.a[3] = prmt(r.z, r.y, sw); e.a[4] = prmt(r.z, r.w, sel);
    e.b[0] = prmt(s.y, s.z, sel); e.b[1] = prmt(s.w, s.z, sw); e.b[2] = prmt(s.x, s.y, sel); e.b[3] = prmt(s.z, s.y, sw); e.b[4] = prmt(s.z, s.w, sel);
}
__device__ __forceinline__ void conv_sums(Conv& c, uint32_t (&acc)[32], const ConvPre& e, uint32_t a0, uint32_t a1, const uint4 (&bd)[3], uint32_t ka, uint32_t sel, int wq, bool odd) {
#pragma unroll
    for (int i = 0; i < 32; i++) acc[i] = 0u;
    uint32_t un[4], vn[4];
    ldsm_x4(un[0], un[1], un[2], un[3], a1);
    ldsm_x4(vn[0], vn[1], vn[2], vn[3], a0);
#pragma unroll
    for (int q = 0; q < 3; q++) {
        const uint32_t u[4] = {un[0], un[1], un[2], un[3]}, v[4] = {vn[0], vn[1], vn[2], vn[3]};
        if (q && sel == 0u) {
            sts128(ka, c.q3[q - 1][0], c.q3[q - 1][1], c.q3[q - 1][2], c.q3[q - 1][3]);
            sts64(ka, acc[8 * q], acc[8 * q + 8]);
        }
        if (q < 2) {
            ldsm_x4(un[0], un[1], un[2], un[3], a1 + q * 512 + 512);
            ldsm_x4(vn[0], vn[1], vn[2], vn[3], a0 + q * 512 + 512);
        }
        mmah8(acc[8 * q + 8], acc[8 * q + 9], e.a[4], 0u, u[1], acc[8 * q + 8], acc[8 * q + 9]);
        mmah16(acc[8 * q + 8], acc[8 * q + 9], e.a[0], e.a[1], e.a[2], e.a[3], u[2], u[3], acc[8 * q + 8], acc[8 * q + 9]);
        const uint2 z0 = run_sums(bd[2], v[0], v[1]);
        if (q < 2) {
            mmah8(acc[8 * q + 16], acc[8 * q + 17], e.b[4], 0u, u[1], 0u, 0u);
            mmah16(acc[8 * q + 16], acc[8 * q + 17], e.b[0], e.b[1], e.b[2], e.b[3], u[2], u[3], acc[8 * q + 16], acc[8 * q + 17]);
            const uint2 y1 = run_sums(bd[1], u[0], u[1]), y2 = run_sums(bd[1], v[2], v[3]), y3 = run_sums(bd[1], u[2], u[3]);
            const uint32_t n0 = odd ? y1.x : z0.y, n1 = odd ? y2.x : y1.x, s1 = odd ? y2.y : y1.y, s2 = odd ? y3.y : y2.y;
            c.q3[q][0] = prmt(s1, n0, 0x7632u); c.q3[q][1] = prmt(s2, n1, 0x7632u);
            c.q3[q][2] = prmt(s1, n0, 0x5410u); c.q3[q][3] = prmt(s2, n1, 0x5410u);
        }
        const uint2 x1 = run_sums(bd[0], u[0], u[1]), x2 = run_sums(bd[0], v[2], v[3]), x3 = run_sums(bd[0], u[2], u[3]);
        const uint32_t f0 = odd ? x1.x : z0.x, f1 = odd ? x2.x : x1.x, f2 = odd ? x3.x : x2.x;
#pragma unroll
        for (int h = 0; h < 2; h++) {
            const uint32_t s = h ? 0x7632u : 0x5410u;
            c.q2[q][h][0] = prmt(x1.y, f0, s); c.q2[q][h][1] = prmt(x2.y, f1, s);
            c.q2[q][h][2] = prmt(f1, x2.y, s ^ 0x4444u); c.q2[q][h][3] = prmt(x3.y, f2, s);
            if (q < 2) mmah16(acc[8 * q + 16], acc[8 * q + 17], c.q2[q][h][0], c.q2[q][h][1], c.q2[q][h][2], c.q2[q][h][3], e.t[2 * h], e.t[2 * h + 1], acc[8 * q + 16], acc[8 * q + 17]);
        }
    }
    {
        const uint32_t a = ka + wq * 64;
#pragma unroll
        for (int i = 0; i < 4; i++) { const uint4 v = lds128(a + i * 16); c.r[4 * i] = v.x; c.r[4 * i + 1] = v.y; c.r[4 * i + 2] = v.z; c.r[4 * i + 3] = v.w; }
        const uint2 v = lds64(a + 64);
        c.r[16] = v.x; c.r[17] = v.y;
    }
    if (sel == 0u) {
#pragma unroll
        for (int i = 0; i < 6; i++) sts128(ka + i * 16, c.q2[i >> 1][i & 1][0], c.q2[i >> 1][i & 1][1], c.q2[i >> 1][i & 1][2], c.q2[i >> 1][i & 1][3]);
#pragma unroll
        for (int i = 0; i < 2; i++) sts128(ka + i * 16, c.q3[i][0], c.q3[i][1], c.q3[i][2], c.q3[i][3]);
#pragma unroll
        for (int i = 1; i < 4; i++) sts64(ka + i * 16, acc[8 * i], acc[8 * i + 1]);
    }
    conv_rename(acc);
}
#define SPACE 100
#define SPN 3
#define O4 4
#define GATE 2
#define HAND 2
#define GA 6
#define GB 4
template <int TA, int TB, int IA, class FG>
__device__ __forceinline__ void conv_tail(uint32_t (&acc)[32], const uint32_t (&a)[8][4], uint32_t sb, unsigned char* gy0, int warp, size_t ycopy, FG fg) {
    const int wg = warp >> 2, wq = warp & 3, ord = TA == 0 && TB == 16 ? 3 - wg + (3 - wg >= O4) : O4;
    const uint32_t ub = sb + SM_U + wg * USLOT_B + UPAD * 16, turn = sb + SM_MISC + 376 + ord * 8, sfs = sb + SM_MISC + 256 + wg * 8;
    const uint32_t du = wg * (USLOT_B / 16) + (SM_U / 16 + UPAD + TA * 8);
    uint32_t ud[8], fs;
    auto skip = [&]() {
        const int lane = lane_v();
        const uint32_t ua = ub + ((lane >> 3) & 1) * ULO_B + (8 * wq + (lane & 7)) * 16 + (lane >> 4) * 512;
        if (IA == 0) ldsm_x4_t(ud[0], ud[1], ud[2], ud[3], ua);
        if (TB == 16) ldsm_x4_t(ud[4], ud[5], ud[6], ud[7], ua + 1024);
        const uint2 fd = lds64(sfs);
        fs = fd.x;
        const float dsk = __uint_as_float(fd.y);
#pragma unroll
        for (int i = 2 * IA; i < TB / 2; i++) ud[i] = pack_bf16(h_lo(ud[i]) * dsk, h_hi(ud[i]) * dsk);
    };
    conv_rename<2 * TA, 2 * TB>(acc);
    if (__builtin_expect(ord != 0, 0)) {
        skip();
        mbar_wait(turn);
    } else {
        bar_sync(0, NWRK);
    }
    if (O4 < 4 || (TA == 0 && TB == 16)) asm volatile("{\n.reg .pred p;\nelect.sync _|p, 0xffffffff;\n@p mbarrier.arrive.shared::cta.b64 _, [%0];\n}\n" ::"r"(turn + 48) : "memory");
    fg(IC<8>());
    wg_fence();
#pragma unroll
    for (int m = 7; m >= 0; m--) {
        wg_h<TA, TB - TA>(acc, a[m], smem_desc(sb, du - m, ULO_B));
        if (m == GA || m == GB || m == HAND) wg_commit();
        if (m == GB) asm volatile("wgmma.wait_group.sync.aligned 1;\n" ::: "memory");
    }
    wg_commit();
    if (O4 < 4 || (TA == 0 && TB == 16)) {
        asm volatile("wgmma.wait_group.sync.aligned 1;\n" ::: "memory");
        asm volatile("{\n.reg .pred p;\nelect.sync _|p, 0xffffffff;\n@p mbarrier.arrive.shared::cta.b64 _, [%0];\n}\n" ::"r"(turn + 8) : "memory");
    }
    __syncwarp();
    fg(IC<3>());
    if (!ord) skip();
    fg(IC<4>());
    const int lane = lane_v();
    const uint32_t lp = sb + SM_PL + (ord >= 3 ? ord - 3 : ord) * PL_B + lane * 8;
    unsigned char* gy = gy0 + ((4 * wq + (lane & 3)) * DM + (TA == 0 && TB == 16 ? 4 * blockIdx.x + wg : 512 + (blockIdx.x >> 1))) * 64 + (lane >> 2) * 8;
    const uint32_t st = lp + (wq * 12 - ((wq * (wq - 1)) >> 1)) * 256;
    uint32_t ld[3];
#pragma unroll
    for (int s = 1; s < 4; s++) {
        const int w = (wq - s) & 3;
        ld[s - 1] = lp + (w * 12 - ((w * (w - 1)) >> 1) + s - 1 - (wq < s ? 3 : 0)) * 256;
    }
    const uint32_t one = 1u + (warp >> 8);
    if (one == 0u) stg64(gy, ld[0], ld[1]);
    if (ord >= 3) bar_sync(9 + ord, 256);
    wg_wait0();
    fg(IC<6>());
#pragma unroll
    for (int j = TA; j < TB; j++)
        if ((j & 3) && j + 3 >= 4 * IA && (j + 3 < TB || j + wq < TB)) sts64(st + (j - 1 - (j >> 2)) * 256, acc[2 * j], acc[2 * j + 1]);
    bar_sync(1 + wg, 128);
    fg(IC<7>());
    uint2 v[4][3];
#pragma unroll
    for (int i = IA; i < TB / 4; i++)
#pragma unroll
        for (int s = 0; s < 3; s++) {
            if (i == 0) { v[i][s] = make_uint2(0u, 0u); if (wq > s) v[i][s] = lds64(ld[s]); }
            else v[i][s] = lds64(ld[s] + i * 768);
        }
    fg(IC<5>());
#pragma unroll
    for (int i = IA; i < TB / 4; i++) {
        const uint32_t x0 = hadd2(v[i][0].x, acc[8 * i]), x1 = hadd2(v[i][1].x, v[i][2].x), y0 = hadd2(v[i][0].y, acc[8 * i + 1]), y1 = hadd2(v[i][1].y, v[i][2].y);
        const uint32_t lo = pack_bf16(h_lo(x0) + h_lo(x1), h_hi(x0) + h_hi(x1)), hi = pack_bf16(h_lo(y0) + h_lo(y1), h_hi(y0) + h_hi(y1));
        ud[2 * i] = max(hfma2_bf(lo, fs, ud[2 * i]), one); ud[2 * i + 1] = hfma2_bf(hi, fs, ud[2 * i + 1]);
    }
    if (SPACE && TA == 0 && TB == 16 && ord < SPN) {
#pragma unroll
        for (int i = 0; i < 4; i++) {
            stg64(gy + i * 16 * DM * 64, ud[2 * i], ud[2 * i + 1]);
            if (i < 3) { const unsigned c0 = clock32(); while (clock32() - c0 < SPACE) {} }
        }
    } else {
#pragma unroll
        for (int i = IA; i < TB / 4; i++) stg64(gy + i * 16 * DM * 64, ud[2 * i], ud[2 * i + 1]);
    }
    if (ord < 2) bar_arrive(12 + ord, 256);
}
template <int M0, int M1>
__device__ __forceinline__ void conv_frags(uint32_t (&a)[8][4], const uint32_t (&r)[18], uint32_t sel, uint32_t dep, int warp) {
    const uint32_t s = prmt_v(sel, dep, 0x3210u + (warp >> 8)), sw = s ^ 0x4444u;
#pragma unroll
    for (int m = M0; m < M1; m++) {
        a[m][0] = prmt_v(r[2 * m + 1], r[2 * m + 2], s); a[m][1] = prmt_v(r[2 * m + 2], r[2 * m + 3], s);
        a[m][2] = prmt_v(r[2 * m + 1], r[2 * m], sw); a[m][3] = prmt_v(r[2 * m + 2], r[2 * m + 1], sw);
    }
}
template <class FG>
__device__ __forceinline__ void conv_main(const Conv& c, uint32_t (&acc)[32], uint32_t sb, uint32_t sel, unsigned char* gy, int warp, size_t ycopy, FG fg) {
    const uint32_t kw = (warp >> 2) * (KW_B / 16) + SM_KW / 16;
    const uint64_t d2 = smem_desc(sb, kw + KW_T2 / 16, KW_KH), d2b = smem_desc(sb, kw + KW_T2 / 16 + 1, KW_KH), d3 = smem_desc(sb, kw + KW_T3 / 16, 16), d3b = smem_desc(sb, kw + KW_T3 / 16 + 32, 16);
    uint32_t a[8][4];
    {
        const int ord = warp < 16 ? 3 - (warp >> 2) + (3 - (warp >> 2) >= O4) : O4;
        if (__builtin_expect(ord >= GATE, 0)) {
            fg(IC<1>());
            mbar_wait(sb + SM_MISC + 376 + 48 + (ord - GATE) * 8);
        }
    }
    wg_fence();
    wg_h<12, 4>(acc, c.q3[0], d3b); wg_h<8, 4>(acc, c.q3[0], d3); wg_h<4, 4>(acc, c.q2[0][0], d2b);
    wg_h<12, 4>(acc, c.q3[1], d3); wg_h<8, 4>(acc, c.q2[1][0], d2b);
    wg_h<12, 4>(acc, c.q2[2][0], d2b); wg_h<4, 4>(acc, c.q2[0][1], d2); wg_h<8, 4>(acc, c.q2[1][1], d2);
    wg_h<12, 4>(acc, c.q2[2][1], d2);
    wg_commit(); __syncwarp();
    fg(IC<0>());
    wg_wait0();
    conv_frags<0, 8>(a, c.r, sel, acc[16], warp);
    fg(IC<2>());
    if (warp >= 16) {
        if (blockIdx.x & 1) conv_tail<4, 16, 2>(acc, a, sb, gy, warp, ycopy, fg);
        else conv_tail<0, 8, 0>(acc, a, sb, gy, warp, ycopy, fg);
    } else {
        conv_tail<0, 16, 0>(acc, a, sb, gy, warp, ycopy, fg);
    }
}
#define CONV_LT6 const int dd = (lane >> 3) + (lane & 4) - (lane & 3); \
        const uint4 lt6 = make_uint4(prmt_v((dd & 3) * 288, 0u, idn), prmt_v(0x3254u + (dd >> 2) * 0x2222u, 0u, idn), \
            prmt_v(UPAD * 16 + (lane & 7) * 16 + ((lane >> 3) & 1) * (16 - ULO_B) + ULO_B - 32 + (lane & 16), 0u, idn), prmt_v(UPAD * 16 + (lane & 7) * 16 + ((lane >> 3) & 1) * ULO_B - 16 + (lane & 16), 0u, idn));
#define CONV_PRE \
        CONV_LT6 \
        const uint32_t ka = kw + lt6.x, sel = lt6.y, ks = kw + lt7.x; \
        const uint32_t ca0 = sb + SM_U + wg * USLOT_B + (warp & 3) * 128 + lt6.z, ca1 = sb + SM_U + wg * USLOT_B + (warp & 3) * 128 + lt6.w; \
        uint4 bd[3]; \
        band_quads(bd, lt7.w, (lane & 4) ? lt7.w >> 4 : lt7.w << 4);
#define CONV_PRE2 ConvPre ce_; conv_pre(ce_, ka, ks, sel);
#define CONV_BODY \
        Conv c; \
        uint32_t acc[32]; \
        conv_sums(c, acc, ce_, ca0, ca1, bd, ka, sel, warp & 3, lane & 4);
#define WS a_b_0_1_2_34_x__y567____c____de_r_
#define WS_STR2(x) #x
#define WS_STR(x) WS_STR2(x)
__device__ constexpr char wunit(int pt, int k) {
    constexpr char t[] = WS_STR(WS);
    int i = 0;
    for (; pt > 0 && t[i]; i++) pt -= t[i] == '_';
    for (; k > 0 && t[i] && t[i] != '_'; i++) k--;
    return t[i] == '_' ? 0 : t[i];
}
__device__ constexpr bool wsched_ok() {
    int seen = 0;
    for (int p = 0; p < 21; p++)
        for (int k = 0; wunit(p, k); k++) {
            const char c = wunit(p, k);
            const int bit = 1 << (c == 'r' ? 13 : c >= 'x' ? c - 'x' + 14 : c >= 'a' ? c - 'a' + 8 : c - '0');
            if ((seen & bit) || k >= (p < 16 ? 4 : 2) || (p < 5 && c >= '4' && c <= '7') || (p < 6 && (c == 'c' || c == 'd')) || (p < 16 && c == 'e')) return false;
            seen |= bit;
        }
    return seen == 0xffff;
}
struct WMaps { CUtensorMap g, u, gr, ur, d, dr; };
static_assert(GATE <= 2 && O4 >= 2, "resets");
static_assert(wsched_ok(), "weight schedule");
template <int PT, int K>
__device__ __forceinline__ void weight_units(uint32_t sb, const WMaps& m, int w) {
    constexpr char U = wunit(PT, K);
    if constexpr (U != 0) {
        if (w == K && elect_one()) {
            if (PT == 8) DELAY(K * WSP + WS0);
            const int P = blockIdx.x >> 1, odd = blockIdx.x & 1;
            constexpr int bar = SM_MISC + (U == 'e' ? 352 : U >= 'a' && U <= 'r' ? 336 : 328);
            if constexpr (U == 'e') { if (!odd) tma_2d(sb + SM_WD + 4 * 8192, &m.d, 256, 64 * P, sb + bar); }
            else if constexpr (U == 'r') tma_3d(sb + SM_WD + 40960, &m.dr, 0, 4096 + 8 * P, 5 * odd, sb + bar);
            else if constexpr (U >= 'x') tma_3d(sb + SM_WR + (U - 'x') * 4608, U == 'x' ? &m.gr : &m.ur, 4096 + 8 * P, 0, 2 * odd, sb + bar);
            else if constexpr (U >= 'a') tma_2d(sb + SM_WD + (U - 'a') * 8192, &m.d, 320 * odd + 64 * (U - 'a'), 64 * P, sb + bar);
            else tma_2d(sb + (U < '4' ? SM_WG : SM_WU) + (U & 3) * 9216, U < '4' ? &m.g : &m.u, 64 * P, 288 * odd + (U & 3) * 72, sb + bar);
        }
        weight_units<PT, K + 1>(sb, m, w);
    }
}
#define WPOINT(i, w) do { weight_units<i, 0>(sb, wm, w); } while (0)

__global__ void __launch_bounds__(NTHR, 1) __cluster_dims__(2, 1, 1)
fused_kernel(const Params p, const __grid_constant__ WMaps wm, const __grid_constant__ CUtensorMap tm_x,
             const __grid_constant__ CUtensorMap tm_y, const __grid_constant__ CUtensorMap tm_z) {
    extern __shared__ __align__(1024) unsigned char smem[];
    const uint32_t sb = smem_u32(smem);
    const int tid = threadIdx.x, warp = __shfl_sync(0xffffffffu, tid >> 5, 0), lane = tid & 31;
    const int b = blockIdx.x, P = b >> 1, odd = b & 1;
    const int g = lane >> 2, t = lane & 3;
    const int wg = warp >> 2, t128 = tid & 127;
    const uint32_t s_stat = sb + SM_MISC;
    const uint32_t s_key = sb + SM_MISC + 128;
    const uint32_t s_wm = sb + SM_MISC + 256;
    const uint32_t s_k16 = sb + SM_MISC + 192;
    const uint32_t s_fs = sb + SM_MISC + 256;
    const uint32_t s_cnt = sb + SM_MISC + 320;
    const uint32_t bar_w = sb + SM_MISC + 328, bar_d = bar_w + 8, bar_g = bar_w + 16, bar_r = bar_w + 32, bar_h = bar_w + 40, bar_x = bar_w + 48;
    STAMP(0);

    const unsigned tk0 = clock32();
    const bool lnw = (unsigned)(warp - 10) < 9u;
    const unsigned pm = tid + (tid < 512 ? 512 * b : 65024 + 128 * P), pq = (pm & ~127u) + 4 * lane;
    const uint32_t pl = ldg16(p.lar + pm), ldt = ldg16(p.ldt + (pm >> 7));
    const uint32_t pa2 = ldg16(p.aim + pm), pc = ldg16(p.cre + pm), pi = ldg16(p.cim + pm);
    const uint2 call_re = ldg64(p.cre + pq), call_im = ldg64(p.cim + pq);
    const uint32_t dskl = ldg16(p.dsk + (pm >> 7));
    const uint32_t ep = ld_poll32(p.s->hint + (b & 7) * 32 + 1 + (lane >> 5));
    if ((unsigned)(tid - 320) < 288u) {
        const bf16* xp = p.x + (unsigned)((32 * P + 2 * odd + TOKEN_OF(g)) * DM + ((tid - 320) & ~31) + 8 * t);
        const uint32_t xt = sb + SM_XT + ((tid - 320) & ~31) * 32 + lane * 16;
        asm volatile("cp.async.cg.shared.global [%0], [%1], 16;\ncp.async.cg.shared.global [%0 + 512], [%1 + 9216], 16;\n"
                     "cp.async.cg.shared.global [%0 + 9216], [%1 + 576], 16;\ncp.async.cg.shared.global [%0 + 9728], [%1 + 9792], 16;\n" ::"r"(xt), "l"(xp) : "memory");
    }
    uint32_t* const std_ = p.s->st + ((lane & 12) * 128 + odd * 256 + 4 * P + 2 * (lane & 1) + ((lane >> 1) & 1)) * 2;
    unsigned char* const ud = reinterpret_cast<unsigned char*>(p.s->uT) + (32 * (warp - UW) + 8 * (g >> 1) + (g & 1)) * 4096 + b * 32 + t * 8;
    if (warp == 0) {
        if (lane == 0) {
            mbar_init(bar_x, 1); mbar_init(bar_w, 1); mbar_init(bar_d, 1); mbar_init(bar_d + 16, 1); mbar_init(bar_g, 1); mbar_init(bar_h, 3); mbar_init(bar_r, 1);
            #pragma unroll
            for (int i = 1; i < 11; i++) mbar_init(bar_x + 8 * i, 4);
            asm volatile("fence.mbarrier_init.release.cluster;\n" ::: "memory");
            mbar_expect(bar_x, 16384); mbar_expect(bar_r, 8192);
            mbar_expect(bar_w, 2 * 41472); mbar_expect(bar_d, 32768 + 5120); mbar_expect(bar_d + 16, 8192); mbar_expect(bar_g, 9 * 512);
        }
        __syncwarp();
        bar_arrive(0, NWRK);
    }
    if (warp == 0 && elect_one()) tma_3d(sb + SM_XC, &tm_x, 8 * P, 0, 8 * odd, bar_x);
    asm volatile("barrier.cluster.arrive.relaxed.aligned;\n" ::: "memory");
    const uint32_t kw = sb + SM_KW + wg * KW_B;
    if (t128 < 2 * UPAD) sts128(sb + SM_U + wg * USLOT_B + (t128 & 1) * ULO_B + (t128 >> 1) * 16, 0u, 0u, 0u, 0u);
    sts128(kw + t128 * 16, 0u, 0u, 0u, 0u);
    if (t128 < KW_B / 16 - 128) sts128(kw + 2048 + t128 * 16, 0u, 0u, 0u, 0u);
    if (tid < 128) {
#pragma unroll
        for (int i = 0; i < 4; i++) sts128(sb + SM_ZERO + i * 2048 + tid * 16, 0u, 0u, 0u, 0u);
    }
    if (warp != 0) bar_sync(0, NWRK);
    STAMP(1);
    if (warp == 19 || warp == UW || warp == UW + 1) {
        if (warp == 19) {
            if (lane < 16) stg64(std_, 0u, 0u);
            if (lane < 9) asm volatile("prefetch.global.L2 [%0];\n" ::"l"(p.wr + lane * 64));
        } else {
#pragma unroll
            for (int k = 0; k < 4; k++) stg64(ud + k * 8192, 0u, 0u);
        }
    }
    uint32_t X[2][8];
    auto partial = [&]() {
        const uint32_t xt = sb + SM_XT + (warp - 10) * 1024 + lane * 16;
        asm volatile("cp.async.wait_all;\n" ::: "memory");
        STAMP(23);
        const uint4 a = lds128(xt), c = lds128(xt + 512), d = lds128(xt + 9216), e = lds128(xt + 9728);
        X[0][0] = a.x; X[0][1] = a.y; X[0][2] = a.z; X[0][3] = a.w; X[0][4] = d.x; X[0][5] = d.y; X[0][6] = d.z; X[0][7] = d.w;
        X[1][0] = c.x; X[1][1] = c.y; X[1][2] = c.z; X[1][3] = c.w; X[1][4] = e.x; X[1][5] = e.y; X[1][6] = e.z; X[1][7] = e.w;
        const uint32_t one[8] = {0x3f803f80u, 0x3f803f80u, 0x3f803f80u, 0x3f803f80u, 0x3f803f80u, 0x3f803f80u, 0x3f803f80u, 0x3f803f80u};
        ln_partial<8>(X, one, sb + SM_LNP, warp - 10, g, t);
        bar_arrive(6, 320);
    };
    auto finish = [&]() {
        bar_sync(6, 320);
        float mb, rc;
        ln_finish<9>(sb + SM_LNP, lane, mb, rc);
        const float rh = rbf(rc);
        const uint32_t s0 = (__float_as_uint(mb) >> 16) | (((ep & 0x7fffu) + 1u) << 16), s1 = pack_bf16(rh, rc - rh);
        if (lane < 16) { stg64(std_, s0, s1); sts64(s_stat + lane * 8, s0, s1); }
        if (lane == 16) sts32(s_cnt + 4, ep);
        bar_arrive(7, 352);
        STAMP(28);
    };
    auto upub = [&]() {
        const uint32_t utag = ((ep & 3u) + 1u) * 0x10001u;
        uint32_t U[2][4];
#pragma unroll
        for (int hf = 0; hf < 2; hf++) {
            const uint2 st = lds64(s_stat + (g + 8 * hf) * 8);
            const uint4 xv = lds128(sb + SM_XT + (16 + warp - UW) * 1024 + hf * 512 + lane * 16);
            const uint32_t xs[4] = {xv.x, xv.y, xv.z, xv.w};
#pragma unroll
            for (int k = 0; k < 4; k++) {
                const uint32_t u = ln_apply(xs[k], st);
                U[hf][k] = movm((pack_f16_rz(bf_lo(u), __uint_as_float(u)) & 0xfff8fff8u) | utag);
            }
        }
#pragma unroll
        for (int k = 0; k < 4; k++) stg64(ud + k * 8192, U[0][k], U[1][k]);
    };
    const uint32_t tb = table_buf(sb, warp);
    const float dt = rbf(expf(bf_lo(ldt)));
    KGen kg;
    kgen_setup(kg, pl | (pa2 << 16), dt);
    kgen_rows(kg, tb, lane);
    if (wg == 0) fence_async();
    if (lnw) {
        partial();
        kg.z128.x = __uint_as_float(prmt_v(__float_as_uint(kg.z128.x), X[0][0], 0x3210u + (warp >> 8)));
        kg.z1.x = __uint_as_float(prmt_v(__float_as_uint(kg.z1.x), X[0][0], 0x3210u + (warp >> 8)));
    }
    STAMP(2);
    WPOINT(0, warp - 4);
    const int ce = c_exponent(call_re, call_im);
    if (t128 == 0) sts64(s_fs + wg * 8, (uint32_t)min(max(ce + (int)(__float_as_uint(dt) >> 23) - 116, 0), 254) * 0x800080u, dskl << 16);
    kgen_chain(kg, pc | (pi << 16), __uint_as_float(((uint32_t)(244 - ce) << 23) | (__float_as_uint(dt) & 0x7fffffu)));
    STAMP(3);
    WPOINT(1, warp - 6);
    kgen_cols(kg, tb, lane);
    if (warp == 19) finish();
    if (warp < 10) bar_sync(7, 352);
    if (warp == UW || warp == UW + 1) upub();
    STAMP(4);
    WPOINT(2, warp - 8);
    const uint4* usrc = wg < 4 ? reinterpret_cast<const uint4*>(p.s->st) + odd * 512 + (lane & 1) * 128 + 16 * (warp & 7) + (lane >> 1)
                               : reinterpret_cast<const uint4*>(p.s->uT) + P * 256 + 2 * t128;
    const int ustep = wg < 4 ? 256 : 1;
    uint4 uv0, uv1;
    kgen_mma(kg, tb, lane);
    STAMP(26);
    WPOINT(3, warp - 5);
    const uint32_t idn = 0x3210u + (warp >> 8);
    uint4 lt7 = make_uint4(prmt_v(KW_T2 + ((lane >> 3) & 1) * KW_KH + (33 + (lane & 7)) * 16 - (lane & 16), 0u, idn), t * 288 + g * 8 + 8, (lane & 1) * 4096 + (lane >> 1) * 16,
                                 prmt_v(8u << ((lane >> 3) + (lane & 4)) >> (lane & 3), 0u, idn));
    asm volatile("barrier.cluster.wait.acquire.aligned;\n" ::: "memory");
    const bool pe = (int)(clock32() - tk0) >= (wg < 4 ? TP0 : TP4);
    if (pe) { uv0 = ld_poll(usrc); uv1 = ld_poll(usrc + ustep); }
    bar_sync(1 + wg, 128);
    kgen_combine(sb, warp, lane, kw, lt7.y);
    if (warp < 3 || warp > 6) bar_arrive(14, NWRK);
    STAMP(5);
    WPOINT(4, warp - 7);
    if (!pe) {
        while ((int)(clock32() - tk0) < (wg < 4 ? TP0 : TP4)) {}
        uv0 = ld_poll(usrc); uv1 = ld_poll(usrc + ustep);
    }
    if (wg < 4) {
        mbar_wait(bar_x);
        const bool far = warp < 8;
        const uint32_t xa = sb + SM_XC + (warp & 7) * 256 + (odd ^ far) * 8 + lt7.z;
        uint2 xv[4] = {lds64(xa), lds64(xa + 8192), lds64(xa + 2048), lds64(xa + 10240)};
        const uint32_t tag = ((ep & 0x7fffu) + 1u) << 16;
        int it = 0;
        while (true) {
            const bool bad = (((uv0.x ^ tag) | (uv0.z ^ tag)) | ((uv1.x ^ tag) | (uv1.z ^ tag))) >> 16;
            if (!__any_sync(0xffffffffu, bad)) break;
            if (++it > SPIN_LIMIT) TRAP();
            if (bad) { uv0 = ld_poll(usrc); uv1 = ld_poll(usrc + 256); }
        }
        STAMP(6);
        DBG(wg, it);
        const uint2 st[4] = {make_uint2(uv0.x, uv0.y), make_uint2(uv0.z, uv0.w), make_uint2(uv1.x, uv1.y), make_uint2(uv1.z, uv1.w)};
#pragma unroll
        for (int i = 0; i < 4; i++) {
            xv[i].x = ln_apply(xv[i].x, st[i]);
            xv[i].y = ln_apply(xv[i].y, st[i]);
        }
        const uint32_t ub = sb + SM_U + UPAD * 16 + odd * ULO_B + (warp & 7) * 256 + lane * 8;
        const uint32_t w[4][2] = {{pack_f16(bf_lo(xv[0].x), bf_lo(xv[1].x)), pack_f16(bf_lo(xv[2].x), bf_lo(xv[3].x))}, {HI2(xv[0].x, xv[1].x), HI2(xv[2].x, xv[3].x)},
                                  {pack_f16(bf_lo(xv[0].y), bf_lo(xv[1].y)), pack_f16(bf_lo(xv[2].y), bf_lo(xv[3].y))}, {HI2(xv[0].y, xv[1].y), HI2(xv[2].y, xv[3].y)}};
#pragma unroll
        for (int i = 0; i < 4; i++) {
            if (far) asm volatile("st.async.shared::cluster.mbarrier::complete_tx::bytes.v2.b32 [%0], {%1,%2}, [%3];\n" ::"r"((ub ^ 0x1000000u) + i * USLOT_B), "r"(w[i][0]), "r"(w[i][1]), "r"(bar_r ^ 0x1000000u) : "memory");
            else sts64(ub + i * USLOT_B, w[i][0], w[i][1]);
        }
    } else {
        const uint32_t utag = ((ep & 3u) + 1u) * 0x10001u;
        int it = 0;
        while (true) {
            const bool bad = (((uv0.x ^ utag) | (uv0.y ^ utag) | (uv0.z ^ utag) | (uv0.w ^ utag)) | ((uv1.x ^ utag) | (uv1.y ^ utag) | (uv1.z ^ utag) | (uv1.w ^ utag))) & 0x70007u;
            if (!__any_sync(0xffffffffu, bad)) break;
            if (++it > SPIN_LIMIT) TRAP();
            if (bad) { uv0 = ld_poll(usrc); uv1 = ld_poll(usrc + 1); }
        }
        STAMP(6);
        DBG(4, it);
        const uint32_t ub = sb + SM_U + UPAD * 16 + 4 * USLOT_B + (t128 >> 1) * 32 + (t128 & 1) * 8;
        sts64(ub, prmt(uv0.x, uv0.z, 0x5410u) ^ utag, prmt(uv1.x, uv1.z, 0x5410u) ^ utag);
        sts64(ub + 16, prmt(uv0.x, uv0.z, 0x7632u) ^ utag, prmt(uv1.x, uv1.z, 0x7632u) ^ utag);
        sts64(ub + ULO_B, prmt(uv0.y, uv0.w, 0x5410u) ^ utag, prmt(uv1.y, uv1.w, 0x5410u) ^ utag);
        sts64(ub + ULO_B + 16, prmt(uv0.y, uv0.w, 0x7632u) ^ utag, prmt(uv1.y, uv1.w, 0x7632u) ^ utag);
    }
    lt7.w = prmt_v(lt7.w, uv0.x, idn);
    CONV_PRE
    if (warp < 3 && elect_one()) tma_st_3d(warp < 2 ? &tm_y : &tm_z, sb + SM_ZERO, warp < 2 ? 128 * b : 32 * (512 + P), 0, 2 * (warp < 2 ? warp : odd));
    if (warp >= 3 && warp <= 6) {
        bar_sync(14, NWRK);
        WPOINT(5, warp - 3);
    }
    bar_sync(1 + wg, 128);
    CONV_PRE2
    mbar_wait(bar_r);
    fence_async();
    bar_sync(0, NWRK);
    STAMP(7);
    uint32_t hv0 = 0;
    {
        WPOINT(6, 19 - warp);
        CONV_BODY
        WPOINT(7, 19 - warp);
        if (wg != 3) bar_arrive(0, NWRK);
        STAMP(8);
        size_t ycopy = 0;
        auto hook = [&](auto gi) {
                     constexpr int G = decltype(gi)::value;
                     if (G == 4 && warp == HINTW) hv0 = ld_poll32(p.s->hint + (lane_v() & 7) * 32);
                     if (G == 4) mbar_wait(bar_h);
                     if (G == 2) WPOINT(9, warp - 16);
                     if (G == 3) { WPOINT(10, warp - 12); WPOINT(12, warp - 8); WPOINT(14, warp - 4); }
                     if (G == 5) { WPOINT(11, warp - 13); WPOINT(13, warp - 9); WPOINT(15, warp - 5); }
                     if (G == 1 && warp >= 17 && elect_one())
                         bulk_s2g(warp == 17 ? p.s->part + b * (PBYTES / 4) : warp == 18 ? p.s->rows + b * 1152 : p.s->sc + b * 64, sb + SM_ZERO, warp == 17 ? PBYTES : warp == 18 ? 4608 : 160);
                     if (G == 4 && warp >= 17 && elect_one()) {
                         asm volatile("cp.async.bulk.wait_group 0;\n" ::: "memory");
                         hint_arrive(p.s->hint, 2, b & 7);
                     }
                     if (G == 1 && warp < 3) {
                         if (elect_one()) {
                             asm volatile("cp.async.bulk.wait_group 0;\n" ::: "memory");
                             mbar_arrive(bar_h);
                             hint_arrive(p.s->hint, 0, b & 7);
                         }
                         __syncwarp();
                         STAMP(17);
                     }
                     if (G == 1) WPOINT(8, warp - 16);
                 };
        conv_main(c, acc, sb, sel, reinterpret_cast<unsigned char*>(p.s->y), warp, ycopy, hook);
        STAMP(10);
    }
    {
    const int warp = warp_v(), lane = lane_v(), tid = 32 * warp + lane, g = lane >> 2, t = lane & 3;
    if (warp == HINTW) {
        const uint32_t target = (lds32(s_cnt + 4) + 1u) * 48u;
        if (__any_sync(0xffffffffu, (int)(hv0 - target) < 0)) hint_wait(p.s->hint, 0, target);
    }
    const unsigned char* ys = reinterpret_cast<const unsigned char*>(p.s->y) + ((size_t)P * DM + 32 * warp + 8 * (g >> 1) + (g & 1)) * 64 + odd * 32 + t * 8;
    STAMP(27);
    bar_sync(0, NWRK);
    STAMP(11);
    const uint32_t zr = warp >> 8;
    auto late_rows = [&](auto pub) {
        const uint32_t k = lds32(s_key + (lane & 7) * 4), ep = lds32(s_cnt + 4);
        const bool late = k & 256u, mine = late && ((k & 255u) >> 1) == (uint32_t)b;
        uint32_t todo = __ballot_sync(0xffffffffu, mine) & 0xffu;
        if (todo) {
#pragma unroll 1
            while (todo) {
                const int s = __ffs(todo) - 1, row = (__shfl_sync(0xffffffffu, k, s) >> 9) & 15;
                todo &= todo - 1;
                if ((row & 7) == g) pub(row & 8, 2 * NCTA + s);
            }
            __threadfence();
            bar_sync(0, NWRK);
            if (tid < NSEL && mine) *reinterpret_cast<volatile unsigned*>(p.s->flag + tid) = ep + 1u;
        }
        int it = 0;
        if (__any_sync(0xffffffffu, late)) {
            while (__any_sync(0xffffffffu, late && ld_poll32(p.s->flag + (lane & 7)) != ep + 1u)) { if (++it > SPIN_LIMIT) TRAP(); }
            __threadfence();
        }
        const int gs = tid / 36;
        const uint4* src = reinterpret_cast<const uint4*>(p.s->rows) + __shfl_sync(0xffffffffu, late ? 2 * NCTA + (lane & 7) : (k & 255u), gs & 7) * 144 + 36 * odd + (tid - gs * 36);
        if (tid < 288) {
            uint4 v0;
            do { v0 = ld_poll(src); if (++it > SPIN_LIMIT) TRAP(); } while (!v0.x);
            sts128(sb + SM_XS + gs * XS_PITCH + (tid - gs * 36) * 16, v0.x, v0.y, v0.z, v0.w);
        }
        __syncwarp();
    };
    if (warp >= 18) {
        uint32_t* const kp = pin(p.s->sc + 64 * b + 32 * (19 - warp), zr);
        const uint32_t kid = pin(0xc0000000u | ((lane & 15) << 9) | 2 * b, zr), ka = pin(s_k16 + (warp & 1) * 288 + (lane & 15) * 4, zr), kb = pin(s_k16 + (warp & 1) * 288 + (lane & 16) * 2, zr);
        const uint4* ksrc = pin(reinterpret_cast<const uint4*>(p.s->sc) + 8 * (19 - warp) + 16 * lane, zr);
        const uint4* rsrc = pin(reinterpret_cast<const uint4*>(p.s->rows) + 36 * odd + t, zr);
        uint32_t bits, early = 0;
        if (warp == 18) {
            weight_units<20, 0>(sb, wm, 0); weight_units<20, 1>(sb, wm, 1);
            bar_sync(8, 640);
            float mb, rc;
            ln_finish<18>(sb + SM_LNP, lane, mb, rc);
            if (lane < 16) stat_store(s_stat + lane * 8, mb, rc, 0u);
            bar_arrive(13, 608);
            bar_sync(10, 640);
            early = lds32(s_wm + (lane & 15) * 4);
            bits = pack_bf16(0.f, sum18(sb + SM_LNP + (32 + (lane & 15)) * 80));
        } else {
            float sw = 0.f;
#pragma unroll
            for (int i = 0; i < 9; i++) { const uint32_t w = reinterpret_cast<const uint32_t*>(p.wr)[32 * i + lane]; sw += bf_lo(w) + bf_hi(w); }
#pragma unroll
            for (int i = 16; i; i >>= 1) sw += __shfl_xor_sync(0xffffffffu, sw, i);
            early = __any_sync(0xffffffffu, (int)(ld_poll32(p.s->hint + (lane & 7) * 32 + 2 + zr * __float_as_int(sw)) - (lds32(s_cnt + 4) + 1u) * 48u) < 0);
            bar_sync(8, 640);
            const float v = sum18(sb + SM_LNP + lane * 80), hw = sum18(sb + SM_LNP + (48 + (lane & 15)) * 80);
            const float o = __shfl_xor_sync(0xffffffffu, v, 16), mean = (lane < 16 ? v : o) * (1.0f / 576.0f);
            const float var = fmaxf(fmaf(lane < 16 ? o : v, 1.0f / 576.0f, -(mean * mean)), 0.f);
            bits = __float_as_uint(fmaf(-rbf(mean), sw, hw) * rcp_approx(rbf(sqrt_approx(rbf(rbf(var) + 1e-5f)))));
        }
        {
            const uint32_t me = (((bits ^ ((uint32_t)((int)bits >> 31) & 0x7fffffffu)) >> 1) & 0x7fffe000u) ^ kid;
            sts32(ka, me);
            __syncwarp();
            const uint4 v = lds128(kb), w = lds128(kb + 16);
#define GT(x) ((me - (x)) >> 31)
            uint32_t rank = pin(GT(v.x) + GT(v.y) + GT(v.z), zr) + pin(GT(v.w) + GT(w.x) + GT(w.y), zr) + pin(GT(w.z) + GT(w.w), zr);
#undef GT
            rank += __shfl_xor_sync(0xffffffffu, rank, 16);
            const uint32_t sl = warp == 18 ? early : rank;
            stg32(kp + rank, me + (sl < 2 ? sl : 256u));
            if (warp == 19) {
                sts32(s_wm + (lane & 15) * 4, rank);
                if (early) hint_wait(p.s->hint, 2, (lds32(s_cnt + 4) + 1u) * 48u);
                bar_arrive(10, 640); bar_arrive(11, 608);
            }
        }
        bool slow;
        int it = 0;
        uint4 q[4];
        STAMP(13);
        DELAY(warp == 19 ? KDEL : KDEL2);
#pragma unroll
        for (int i = 0; i < 4; i++) q[i] = ld_poll(ksrc + 512 * i);
        while (true) {
            uint32_t a[4];
#pragma unroll
            for (int i = 0; i < 4; i++) a[i] = q[i].x & q[i].y & q[i].z & q[i].w;
            if (__all_sync(0xffffffffu, a[0] & a[1] & a[2] & a[3])) break;
#pragma unroll
            for (int i = 0; i < 4; i++)
                if (!a[i]) q[i] = ld_poll(ksrc + 512 * i);
            if (++it > SPIN_LIMIT) TRAP();
        }
        STAMP(16);
        if (warp == 18) {
            const uint32_t kt = sb + SM_KEYS;
#pragma unroll
            for (int i = 0; i < 4; i++) sts128(kt + i * 512 + lane * 16, q[i].x, q[i].y, q[i].z, q[i].w);
            bar_sync(15, 64);
            const uint32_t c = lds32(s_key + 32 + g * 4), e = lds32(kt + (c & 254u) * 8 + t * 4);
            const bool hit = ((e ^ c) & 0x1fffu) == 0u && !(c & 256u);
            if (hit) sts32(s_key + g * 4, e);
            const uint32_t lo = __reduce_min_sync(0xffffffffu, hit ? e : 0xffffffffu) | 0x1fffu;
#define GT(x) ((lo - (x)) >> 31)
            uint32_t n = hit ? 256u - GT(e) : 0u;
#pragma unroll
            for (int i = 0; i < 4; i++) n += pin(GT(q[i].x) + GT(q[i].y) + GT(q[i].z) + GT(q[i].w), zr) << 12;
#undef GT
            n = __reduce_add_sync(0xffffffffu, n);
            slow = (n >> 12) + (n & 4095u) != 2048u || (n & 4095u) <= 2040u;
            if (slow) {
                uint4 r[4];
                it = 0;
                while (true) {
#pragma unroll
                    for (int i = 0; i < 4; i++) r[i] = ld_poll(ksrc + 512 * i + 1);
                    if (__all_sync(0xffffffffu, all_nz(r[0]) && all_nz(r[1]) && all_nz(r[2]) && all_nz(r[3]))) break;
                    if (++it > SPIN_LIMIT) TRAP();
                }
                uint32_t m = 0u;
#pragma unroll 1
                for (int s = 0; s < 8; s++) {
                    uint32_t x = 0;
#pragma unroll
                    for (int i = 0; i < 4; i++) {
                        x = max(max(max(x, q[i].x - m), max(q[i].y - m, q[i].z - m)), q[i].w - m);
                        x = max(max(max(x, r[i].x - m), max(r[i].y - m, r[i].z - m)), r[i].w - m);
                    }
                    m += __reduce_max_sync(0xffffffffu, x);
                    if (lane == 0) sts32(s_key + s * 4, m);
                }
            }
            DBG(7, slow);
        } else {
            auto merge = [](const uint4& x, const uint4& y) {
                const uint32_t a = max(x.x, y.w), c = max(x.y, y.z), d = max(x.z, y.y), e = max(x.w, y.x);
                const uint32_t a2 = max(a, d), d2 = min(a, d), c2 = max(c, e), e2 = min(c, e);
                return make_uint4(max(a2, c2), min(a2, c2), max(d2, e2), min(d2, e2));
            };
            uint4 h = merge(merge(q[0], q[1]), merge(q[2], q[3]));
            uint4 v[9];
            uint32_t key = 0;
#pragma unroll
            for (int s = 0; s < 8; s++) {
                const uint32_t m = __reduce_max_sync(0xffffffffu, h.x);
                const bool w = h.x == m;
                h.x = w ? h.y : h.x; h.y = w ? h.z : h.y; h.z = w ? h.w : h.z; h.w = w ? 0u : h.w;
                if (g == s) key = m;
            }
            rsrc += (key & 255u) * 144;
#pragma unroll
            for (int j = 0; j < 9; j++) v[j] = ld_poll(rsrc + 4 * j);
            const uint32_t xsa = sb + SM_XS + g * XS_PITCH + t * 16;
            sts32(s_key + 32 + g * 4, key);
            sts32(xsa, 0u);
            bar_arrive(15, 64);
            bar_arrive(12, 608);
            STAMP(18);
#pragma unroll
            for (int j = 0; j < 9; j++) sts128(xsa + j * 64, v[j].x, v[j].y, v[j].z, v[j].w);
            slow = min(min(min(min(v[0].x, v[1].x), v[2].x), min(min(v[3].x, v[4].x), v[5].x)), min(min(v[6].x, v[7].x), v[8].x)) == 0u;
        }
        if (bar_or(0, NWRK, slow)) { late_rows([](bool, int) {}); bar_or(0, NWRK, false); }
        STAMP(19);
        const int fl = 16 * (b & 1) + ((tid >> 2) & 15), fc = 16 * (b >> 1) + (fl >> 2) + 8 * ((tid >> 1) & 1), fsl = 2 * (fl & 3) + (tid & 1);
        const uint32_t kk = lds32(s_key + fsl * 4);
        const uint32_t* fsrc = p.s->rows + ((kk & 256u) ? 2 * NCTA + fsl : (kk & 255u)) * DM + (fc >> 1);
        uint32_t hw = 1u, uw = 1u;
        if (b < 72) { uw = ld_poll32(fsrc); hw = ld_poll32(fsrc + 288); }
        if (b < 72) {
            it = 0;
            while (!hw || !uw) { uw = ld_poll32(fsrc); hw = ld_poll32(fsrc + 288); if (++it > SPIN_LIMIT) TRAP(); }
            const int row = (kk >> 9) & 15, ftok = 8 * (kk & 252u) + (kk & 2u) + TOKEN_OF(row & 7) + (row & 8);
            const unsigned k16 = (kk >> 15) & 0xffffu;
            const unsigned bits = (k16 & 0x8000u) ? (k16 & 0x7fffu) : (~k16 & 0xffffu);
            const float rs = 512.0f * rbf(__fdividef(1.0f, 1.0f + __expf(-__uint_as_float(bits << 16))));
            bf16* const op = p.out + (unsigned)(ftok * DM + fc);
            const float uv = (fc & 1) ? bf_hi(uw) : bf_lo(uw), hv = (fc & 1) ? bf_hi(hw) : bf_lo(hw);
            const uint32_t a = sb + SM_FIN + (tid - 576) * 80;
            sts128(a + 64, __float_as_uint(rs), __float_as_uint(uv), __float_as_uint(hv), (uint32_t)(size_t)op ^ (uint32_t)((size_t)op >> 32));
            bar_sync(14, 576);
            const uint4 p0 = lds128(a), p1 = lds128(a + 16), p2 = lds128(a + 32), p3 = lds128(a + 48);
#define F4(p) ((__uint_as_float(p.x) + __uint_as_float(p.y)) + (__uint_as_float(p.z) + __uint_as_float(p.w)))
            const float v0 = F4(p0), v1 = F4(p1), v2 = F4(p2), v3 = F4(p3);
#undef F4
            const float y3 = rbf(rbf((v0 + v1) + (v2 + v3)) * rs);
            asm volatile("st.global.u16 [%0], %1;\n" ::"l"(op), "h"((unsigned short)pack_bf16(hv + rbf(uv + y3), 0.f)) : "memory");
        }
        if (b == 0 && tid >= 632) *reinterpret_cast<volatile unsigned*>(p.s->hint + (tid & 7) * 32 + 1) = lds32(s_cnt + 4) + 1u;
    } else {
        uint32_t H[2][4], U2[2][4], WA[9][4], WD[18], WE[18];
        const int fkh = warp >= 9, fmt = warp - 9 * fkh;
        auto load_wa = [&](auto k0, auto k1) {
            if (k0.value >= k1.value) return;
            if (k0.value == 0) mbar_wait(bar_w);
            const int mi = lane >> 3, rr = lane & 7;
            const int row = fkh * 144 + rr + 8 * (mi >> 1);
            const uint32_t aad = sb + (fmt < 8 ? SM_WG + (mi & 1) * (SM_WU - SM_WG) + row * 128 + (fmt ^ rr) * 16 : SM_WR + (mi & 1) * 4608 + row * 16), ks = fmt < 8 ? 2048 : 256;
#pragma unroll
            for (int k = k0.value; k < k1.value; k++) ldsm_x4_t(WA[k][0], WA[k][1], WA[k][2], WA[k][3], aad + k * ks);
        };
        auto load_wd = [&](uint32_t (&WD)[18], int tile) {
            mbar_wait(bar_d);
            if (tile & 16) mbar_wait(bar_d + 16);
            const int mi = lane >> 3, rr = lane & 7;
            const uint32_t base = sb + SM_WD + rr * 128 + (((2 * tile + (mi & 1)) & 7) ^ rr) * 16;
#pragma unroll
            for (int k = 0; k < 4; k++) ldsm_x4_t(WD[4 * k], WD[4 * k + 1], WD[4 * k + 2], WD[4 * k + 3], base + (tile >> 2) * 8192 + (k * 16 + 8 * (mi >> 1)) * 128);
            ldsm_x2_t(WD[16], WD[17], base + 40960 + (tile >> 2) * 1024);
        };
        auto publish = [&](bool hi, int slot) {
            uint4* rowp = reinterpret_cast<uint4*>(p.s->rows) + slot * 144 + warp * 4 + t;
            stg128(rowp, nzw(hi ? U2[1][0] : U2[0][0]), nzw(hi ? U2[1][1] : U2[0][1]), nzw(hi ? U2[1][2] : U2[0][2]), nzw(hi ? U2[1][3] : U2[0][3]));
            stg128(rowp + 72, nzw(hi ? H[1][0] : H[0][0]), nzw(hi ? H[1][1] : H[0][1]), nzw(hi ? H[1][2] : H[0][2]), nzw(hi ? H[1][3] : H[0][3]));
        };
        uint4 wr = make_uint4(0x3f803f80u, 0x3f803f80u, 0x3f803f80u, 0x3f803f80u);
        {
            uint2 yv[4];
#pragma unroll
            for (int k = 0; k < 4; k++) yv[k] = ld_poll64(ys + k * 128);
            if (g == 0) wr = ldg128(p.wr + 32 * warp + 8 * t);
            const uint4 x0 = lds128(sb + SM_XT + warp * 1024 + lane * 16), x1 = lds128(sb + SM_XT + warp * 1024 + 512 + lane * 16);
            load_wa(IC<0>(), IC<WA0>());
            int it = 0;
            while (!__all_sync(0xffffffffu, yv[0].x && yv[1].x && yv[2].x && yv[3].x)) {
#pragma unroll
                for (int k = 0; k < 4; k++) yv[k] = ld_poll64(ys + k * 128);
                if (++it > SPIN_LIMIT) TRAP();
            }
            STAMP(12);
            const uint32_t Z[2][4] = {{x0.x, x0.y, x0.z, x0.w}, {x1.x, x1.y, x1.z, x1.w}};
#pragma unroll
            for (int k = 0; k < 4; k++) {
                H[0][k] = hadd2_bf(Z[0][k], movm(yv[k].x));
                H[1][k] = hadd2_bf(Z[1][k], movm(yv[k].y));
            }
            const uint32_t bw[4] = {wr.x, wr.y, wr.z, wr.w};
            ln_partial<4>(H, bw, sb + SM_LNP, warp, g, t);
        }
        bar_arrive(8, 640);
        WPOINT(16, warp - 12);
        load_wa(IC<WA0>(), IC<WA1>());
        STAMP(13);
        bar_sync(13, 608);
        STAMP(14);
#pragma unroll
        for (int hf = 0; hf < 2; hf++) {
            const uint2 st = lds64(s_stat + (g + 8 * hf) * 8);
#pragma unroll
            for (int k = 0; k < 4; k++) U2[hf][k] = ln_apply(H[hf][k], st);
        }
        {
            float cs[4] = {0.f, 0.f, 0.f, 0.f}, ct[4] = {0.f, 0.f, 0.f, 0.f};
            mma_bf16(cs, U2[0][0], U2[1][0], U2[0][1], U2[1][1], wr.x, wr.y);
            mma_bf16(ct, U2[0][2], U2[1][2], U2[0][3], U2[1][3], wr.z, wr.w);
            if (t == 0) { stsf(sb + SM_LNP + ((32 + g) * 20 + warp) * 4, cs[0] + ct[0]); stsf(sb + SM_LNP + ((40 + g) * 20 + warp) * 4, cs[2] + ct[2]); }
            bar_arrive(10, 640);
        }
        load_wa(IC<WA1>(), IC<WA2>());
        bar_sync(11, 608);
        {
            const uint32_t rk[2] = {lds32(s_wm + g * 4), lds32(s_wm + 32 + g * 4)};
            uint32_t lo = min(rk[0], rk[1]), hi = max(rk[0], rk[1]);
#pragma unroll 1
            while (lo < 2) { publish(lo == rk[1], 2 * b + lo); lo = hi; hi = 16; }
        }
        load_wa(IC<WA2>(), IC<WA3>());
        load_wa(IC<WA3>(), IC<9>());
#pragma unroll
        for (int hf = 0; hf < 2; hf++)
            sts128(sb + SM_OUT + (g + 8 * hf) * OUT_PITCH + warp * 64 + t * 16,
                   hadd2_bf(H[hf][0], U2[hf][0]), hadd2_bf(H[hf][1], U2[hf][1]), hadd2_bf(H[hf][2], U2[hf][2]), hadd2_bf(H[hf][3], U2[hf][3]));
        fence_async();
        WPOINT(17, warp - 16);
        if ((WDAT == 0 || (WDAT == 2 && fkh)) && (warp < 16 || !odd)) load_wd(WD, warp);
        const uint32_t bad = pin(sb + SM_XS + (lane & 7) * XS_PITCH + (fkh * 144 + 8 * (lane >> 3)) * 2, zr), ex = pin(sb + SM_EX + warp * 512 + lane * 16, zr);
        uint32_t* pp = pin(p.s->part + ((size_t)(2 * (20 * odd + warp) + (lane >> 4)) * 64 + P) * 32 + (lane & 15) * 2, zr);
        bar_sync(12, 608);
        const bool routed = __any_sync(0xffffffffu, (lds32(s_key + 32 + (lane & 7) * 4) & 0x1efeu) == (uint32_t)((warp << 9) | 2 * b));
        auto store_row = [&]() { if (warp < 16 && elect_one()) bulk_s2g(p.out + (size_t)(32 * P + 2 * odd + TOKEN_OF(warp & 7) + (warp & 8)) * DM, sb + SM_OUT + warp * OUT_PITCH, DM * 2); };
        if (!routed) store_row();
        WPOINT(18, warp - 16);
        STAMP(15);
        bool again = zr;
#pragma unroll 1
        do {
            if (again) {
                if (routed) store_row();
                asm volatile("cp.async.bulk.wait_group 0;\n" ::: "memory");
                late_rows(publish);
            }
            again = bar_or(0, NWRK, false);
        } while (again);
        STAMP(19);
        float gp[4];
        {
            float c4[3][4];
#pragma unroll
            for (int i = 0; i < 3; i++)
#pragma unroll
                for (int j = 0; j < 4; j++) c4[i][j] = 0.f;
#pragma unroll
            for (int k = 0; k < 10; k += 2) {
                uint32_t b0, b1, b2, b3;
                ldsm_x4(b0, b1, b2, b3, bad + k * 32);
                mma_bf16(c4[k % 3], WA[k][0], WA[k][1], WA[k][2], WA[k][3], b0, b1);
                if (k < 8) mma_bf16(c4[(k + 1) % 3], WA[k + 1][0], WA[k + 1][1], WA[k + 1][2], WA[k + 1][3], b2, b3);
            }
#pragma unroll
            for (int j = 0; j < 4; j++) gp[j] = c4[0][j] + (c4[1][j] + c4[2][j]);
            if (warp >= 9) {
                sts128f(ex, gp);
                bar_arrive(6, 576);
            } else {
                bar_sync(6, 576);
                const uint4 o = lds128(ex + 4608);
                gp[0] += __uint_as_float(o.x); gp[1] += __uint_as_float(o.y); gp[2] += __uint_as_float(o.z); gp[3] += __uint_as_float(o.w);
                asm volatile("st.async.shared::cluster.mbarrier::complete_tx::bytes.v4.b32 [%0], {%1,%2,%3,%4}, [%5];\n"
                             ::"r"(ex ^ 0x1000000u), "r"(__float_as_uint(gp[0])), "r"(__float_as_uint(gp[1])), "r"(__float_as_uint(gp[2])), "r"(__float_as_uint(gp[3])), "r"(bar_g ^ 0x1000000u) : "memory");
                if (WDAT == 2) load_wd(WD, warp);
            }
            if (WDAT == 1 && (warp < 16 || !odd)) load_wd(WD, warp);
            if (warp >= 16 && !odd) load_wd(WE, warp + 2);
        }
        STAMP(20);
        if (warp < 9) {
            mbar_wait(bar_g);
            const uint4 u = lds128(ex);
            const uint32_t G = pack_bf16(gp[0] + __uint_as_float(u.x), gp[1] + __uint_as_float(u.y)), U = pack_bf16(gp[2] + __uint_as_float(u.z), gp[3] + __uint_as_float(u.w));
            const float G0 = bf_lo(G), G1 = bf_hi(G);
            sts32(sb + SM_GU + tid * 4, hmul2_bf(pack_bf16(G0 * rcp_approx(1.0f + ex2_approx(G0 * -1.4426950408889634f)), G1 * rcp_approx(1.0f + ex2_approx(G1 * -1.4426950408889634f))), U));
        }
        bar_sync(7, 576);
        STAMP(21);
        if (warp < 16 || !odd) {
            uint32_t gb[9];
            ldsm_x4_t(gb[0], gb[1], gb[2], gb[3], sb + SM_GU + lane * 16);
            ldsm_x4_t(gb[4], gb[5], gb[6], gb[7], sb + SM_GU + 512 + lane * 16);
            ldsm_x1_t(gb[8], sb + SM_GU + 1024 + (lane & 7) * 16);
            auto down = [&](const uint32_t (&W)[18], uint32_t* dst) {
                float c4[4] = {0.f, 0.f, 0.f, 0.f}, d4[4] = {0.f, 0.f, 0.f, 0.f}, e4[4] = {0.f, 0.f, 0.f, 0.f};
                mma_bf16(c4, W[0], W[1], W[2], W[3], gb[0], gb[1]);
                mma_bf16(d4, W[4], W[5], W[6], W[7], gb[2], gb[3]);
                mma_bf16(e4, W[8], W[9], W[10], W[11], gb[4], gb[5]);
                mma_bf16_k8(c4, W[16], W[17], gb[8]);
                mma_bf16(d4, W[12], W[13], W[14], W[15], gb[6], gb[7]);
                const float v0 = (c4[0] + e4[0]) + d4[0], v1 = (c4[1] + e4[1]) + d4[1], v2 = (c4[2] + e4[2]) + d4[2], v3 = (c4[3] + e4[3]) + d4[3];
                const uint32_t e = max(max(__float_as_uint(fmaxf(fabsf(v0), fabsf(v1))), __float_as_uint(fmaxf(fabsf(v2), fabsf(v3)))), 16u << 23) >> 23;
                const float sc = __uint_as_float((245u - e) << 23);
                stg64(dst, pack_f16(v0 * sc, v1 * sc) | ((e * 0x8002000u) & 0x60006000u), pack_f16(v2 * sc, v3 * sc) | ((e * 0x800200u) & 0x60006000u));
            };
            if (warp >= 16) { down(WE, pp + 4 * 64 * 32); down(WD, pp); }
            else down(WD, pp);
        }
        asm volatile("cp.async.bulk.wait_group.read 0;\n" ::: "memory");
        STAMP(22);
        if (b < 72 && warp < 16) {
            const uint2* src = reinterpret_cast<const uint2*>(p.s->part) + (unsigned)(b * 1024 + tid);
            uint2 a, c;
            int it = 0;
            DELAY(PDEL);
            a = ld_poll64(src); c = ld_poll64(src + 512);
            while (!__all_sync(0xffffffffu, a.y && c.y)) {
                a = ld_poll64(src); c = ld_poll64(src + 512);
                if (++it > SPIN_LIMIT) TRAP();
            }
            STAMP(24);
            const float ea = __uint_as_float((((a.y & 0x60006000u) | ((a.x >> 4) & 0x06000600u)) * 0x4001u) & 0x7f800000u);
            const float ec = __uint_as_float((((c.y & 0x60006000u) | ((c.x >> 4) & 0x06000600u)) * 0x4001u) & 0x7f800000u);
            a.x &= 0x9fff9fffu; a.y &= 0x9fff9fffu; c.x &= 0x9fff9fffu; c.y &= 0x9fff9fffu;
            const float s0 = fmaf(h_lo(a.x), ea, h_lo(c.x) * ec), s1 = fmaf(h_hi(a.x), ea, h_hi(c.x) * ec), s2 = fmaf(h_lo(a.y), ea, h_lo(c.y) * ec), s3 = fmaf(h_hi(a.y), ea, h_hi(c.y) * ec);
            const bool up = lane & 16;
            const float r0 = __shfl_xor_sync(0xffffffffu, up ? s0 : s2, 16), r1 = __shfl_xor_sync(0xffffffffu, up ? s1 : s3, 16);
            const uint32_t fa = sb + SM_FIN + ((lane & 15) * 4 + (up ? 2 : 0)) * 80 + warp * 4;
            stsf(fa, (up ? s2 : s0) + r0); stsf(fa + 80, (up ? s3 : s1) + r1);
            bar_arrive(14, 576);
        }
    }
    STAMP(25);
    }
}

typedef CUresult (*PFN_tmEncode)(CUtensorMap*, CUtensorMapDataType, cuuint32_t, void*, const cuuint64_t*, const cuuint64_t*, const cuuint32_t*,
                                 const cuuint32_t*, CUtensorMapInterleave, CUtensorMapSwizzle, CUtensorMapL2promotion, CUtensorMapFloatOOBfill);

extern "C" void kernel_launch(void* const* d_in, const int* in_sizes, int n_in, void* d_out, int out_size) {
    Params p;
    p.x = (const bf16*)d_in[0];
    p.lar = (const bf16*)d_in[1];
    p.aim = (const bf16*)d_in[2];
    p.cre = (const bf16*)d_in[3];
    p.cim = (const bf16*)d_in[4];
    p.ldt = (const bf16*)d_in[5];
    p.dsk = (const bf16*)d_in[6];
    p.wr = (const bf16*)d_in[8];
    p.out = (bf16*)d_out;
    static PFN_tmEncode enc = nullptr;
    static void* scratch = nullptr;
    if (!enc) {
        cudaFuncSetAttribute(fused_kernel, cudaFuncAttributeMaxDynamicSharedMemorySize, SMEM_TOTAL);
        void* fn = nullptr;
        cudaDriverEntryPointQueryResult qr;
        cudaGetDriverEntryPoint("cuTensorMapEncodeTiled", &fn, cudaEnableDefault, &qr);
        enc = (PFN_tmEncode)fn;
        cudaGetSymbolAddress(&scratch, g_scratch);
    }
    p.s = (Scratch*)scratch;
    WMaps wm;
    CUtensorMap tm_x, tm_y, tm_z;
    const cuuint64_t dims[2] = {FF, DM}, strides[1] = {FF * 2}, rdims[3] = {FF, 144, 4}, rstrides[2] = {FF * 2, 144 * FF * 2};
    const cuuint32_t box[2] = {64, 72}, rbox[3] = {8, 144, 2}, es3[3] = {1, 1, 1};
    for (int i = 0; i < 2; i++) {
        enc(i ? &wm.u : &wm.g, CU_TENSOR_MAP_DATA_TYPE_BFLOAT16, 2, d_in[9 + i], dims, strides, box, es3, CU_TENSOR_MAP_INTERLEAVE_NONE, CU_TENSOR_MAP_SWIZZLE_128B,
            CU_TENSOR_MAP_L2_PROMOTION_NONE, CU_TENSOR_MAP_FLOAT_OOB_FILL_NONE);
        enc(i ? &wm.ur : &wm.gr, CU_TENSOR_MAP_DATA_TYPE_BFLOAT16, 3, d_in[9 + i], rdims, rstrides, rbox, es3, CU_TENSOR_MAP_INTERLEAVE_NONE, CU_TENSOR_MAP_SWIZZLE_NONE,
            CU_TENSOR_MAP_L2_PROMOTION_NONE, CU_TENSOR_MAP_FLOAT_OOB_FILL_NONE);
    }
    const cuuint64_t ddims[2] = {DM, FF}, dstrides[1] = {DM * 2}, edims[3] = {64, FF, 9}, estrides[2] = {DM * 2, 128};
    const cuuint32_t dbox[2] = {64, 64}, ebox[3] = {64, 8, 5};
    enc(&wm.d, CU_TENSOR_MAP_DATA_TYPE_BFLOAT16, 2, d_in[11], ddims, dstrides, dbox, es3, CU_TENSOR_MAP_INTERLEAVE_NONE, CU_TENSOR_MAP_SWIZZLE_128B,
        CU_TENSOR_MAP_L2_PROMOTION_NONE, CU_TENSOR_MAP_FLOAT_OOB_FILL_NONE);
    enc(&wm.dr, CU_TENSOR_MAP_DATA_TYPE_BFLOAT16, 3, d_in[11], edims, estrides, ebox, es3, CU_TENSOR_MAP_INTERLEAVE_NONE, CU_TENSOR_MAP_SWIZZLE_128B,
        CU_TENSOR_MAP_L2_PROMOTION_NONE, CU_TENSOR_MAP_FLOAT_OOB_FILL_NONE);
    const cuuint64_t xdims[3] = {DM, LSEQ / 16, 16}, xstrides[2] = {16 * DM * 2, DM * 2};
    const cuuint32_t xbox[3] = {8, LSEQ / 16, 8};
    enc(&tm_x, CU_TENSOR_MAP_DATA_TYPE_BFLOAT16, 3, d_in[0], xdims, xstrides, xbox, es3, CU_TENSOR_MAP_INTERLEAVE_NONE, CU_TENSOR_MAP_SWIZZLE_NONE,
        CU_TENSOR_MAP_L2_PROMOTION_NONE, CU_TENSOR_MAP_FLOAT_OOB_FILL_NONE);
    const cuuint64_t ydims[3] = {DM * 32, 16, 4}, ystrides[2] = {DM * 64, 16 * DM * 64};
    const cuuint32_t ybox[3] = {128, 16, 2}, zbox[3] = {32, 16, 2};
    enc(&tm_y, CU_TENSOR_MAP_DATA_TYPE_BFLOAT16, 3, p.s->y, ydims, ystrides, ybox, es3, CU_TENSOR_MAP_INTERLEAVE_NONE, CU_TENSOR_MAP_SWIZZLE_NONE,
        CU_TENSOR_MAP_L2_PROMOTION_NONE, CU_TENSOR_MAP_FLOAT_OOB_FILL_NONE);
    enc(&tm_z, CU_TENSOR_MAP_DATA_TYPE_BFLOAT16, 3, p.s->y, ydims, ystrides, zbox, es3, CU_TENSOR_MAP_INTERLEAVE_NONE, CU_TENSOR_MAP_SWIZZLE_NONE,
        CU_TENSOR_MAP_L2_PROMOTION_NONE, CU_TENSOR_MAP_FLOAT_OOB_FILL_NONE);
    fused_kernel<<<NCTA, NTHR, SMEM_TOTAL>>>(p, wm, tm_x, tm_y, tm_z);
}
```

```cpp
#include <cuda_runtime.h>
#include <cuda.h>
#include <cuda_fp16.h>
#include <cuda_bf16.h>
#include <stdint.h>

#define LSEQ 2048
#define DM 576
#define NST 128
#define FF 4608
#define NSEL 8
#define NCTA 128
#define NTHR 640
#define NWRK 640

typedef __nv_bfloat16 bf16;

#define SM_WD 0
#define SM_WG 46080
#define SM_WR 82944
#define SM_WU 92160
#define SM_ZERO 32768
#define SM_XC 16384
#define SM_TB 96000
#define SM_PL 129024
#define PL_B 10752
#define SM_XT (SM_TB + 20 * TBW)
#define SM_U (SM_XT + 18432)
#define UPAD 8
#define ULO_B ((UPAD + 128) * 16)
#define USLOT_B (2 * ULO_B)
#define SM_KW (SM_U + 5 * USLOT_B)
#define KW_B 3600
#define KW_T2 1152
#define KW_KH 656
#define KW_T3 2464
#define SM_MISC (SM_KW + 5 * KW_B)
#define SM_LNP (SM_MISC + 576)
#define SMEM_TOTAL (SM_LNP + 5120)
#define TBP 112
#define TBW (32 * TBP)
#define SM_OUT SM_PL
#define OUT_PITCH 1216
#define SM_XS (SM_PL + 19456)
#define XS_PITCH 592
#define SM_EX (SM_PL + 24320)
#define SM_KEYS (SM_KW + 5120)
#define SM_FIN SM_KW
#define SM_GU (SM_PL + 33536)

struct __align__(128) Scratch {
    unsigned hint[8 * 32];
    unsigned flag[32];
    uint32_t sc[NCTA * 64];
    uint32_t st[LSEQ * 2];
    uint32_t uT[64 * (LSEQ / 2)];
    uint32_t y[NCTA * DM * 8];
    uint32_t part[72 * 64 * 32];
    uint32_t rows[(2 * NCTA + NSEL) * DM];
};
__device__ Scratch g_scratch;
#define STAMP(i)
#define DBG(i, v)

__device__ __forceinline__ float rbf(float x) {
    uint32_t r;
    asm("cvt.rn.bf16x2.f32 %0, %1, %2;\n" : "=r"(r) : "f"(x), "f"(0.f));
    return __uint_as_float(r);
}
__device__ __forceinline__ uint32_t pack_bf16(float lo, float hi) {
    uint32_t r;
    asm("cvt.rn.bf16x2.f32 %0, %1, %2;\n" : "=r"(r) : "f"(hi), "f"(lo));
    return r;
}
__device__ __forceinline__ uint32_t pack_f16(float lo, float hi) {
    uint32_t r;
    asm("cvt.rn.f16x2.f32 %0, %1, %2;\n" : "=r"(r) : "f"(hi), "f"(lo));
    return r;
}
__device__ __forceinline__ uint32_t pack_f16_rz(float lo, float hi) {
    uint32_t r;
    asm("cvt.rz.f16x2.f32 %0, %1, %2;\n" : "=r"(r) : "f"(hi), "f"(lo));
    return r;
}
__device__ __forceinline__ float bf_lo(uint32_t w) { return __uint_as_float(w << 16); }
__device__ __forceinline__ float bf_hi(uint32_t w) { return __uint_as_float(w & 0xffff0000u); }
__device__ __forceinline__ uint32_t hadd2_bf(uint32_t a, uint32_t b) {
    __nv_bfloat162 r = __hadd2_rn(*reinterpret_cast<__nv_bfloat162*>(&a), *reinterpret_cast<__nv_bfloat162*>(&b));
    return *reinterpret_cast<uint32_t*>(&r);
}
__device__ __forceinline__ uint32_t hmul2_bf(uint32_t a, uint32_t b) {
    __nv_bfloat162 r = __hmul2_rn(*reinterpret_cast<__nv_bfloat162*>(&a), *reinterpret_cast<__nv_bfloat162*>(&b));
    return *reinterpret_cast<uint32_t*>(&r);
}
__device__ __forceinline__ uint32_t hfma2_bf(uint32_t a, uint32_t b, uint32_t c) { uint32_t r; asm("fma.rn.bf16x2 %0, %1, %2, %3;\n" : "=r"(r) : "r"(a), "r"(b), "r"(c)); return r; }
__device__ __forceinline__ uint32_t hmul2(uint32_t a, uint32_t b) { uint32_t r; asm("mul.rn.f16x2 %0, %1, %2;\n" : "=r"(r) : "r"(a), "r"(b)); return r; }
__device__ __forceinline__ uint32_t hadd2(uint32_t a, uint32_t b) { uint32_t r; asm("add.rn.f16x2 %0, %1, %2;\n" : "=r"(r) : "r"(a), "r"(b)); return r; }
__device__ __forceinline__ uint32_t nzw(uint32_t w) { return w ? w : 0x8000u; }
__device__ __forceinline__ uint32_t smem_u32(const void* p) { return (uint32_t)__cvta_generic_to_shared(p); }
__device__ __forceinline__ uint32_t lds32(uint32_t addr) {
    uint32_t v;
    asm volatile("ld.shared.u32 %0, [%1];\n" : "=r"(v) : "r"(addr) : "memory");
    return v;
}
__device__ __forceinline__ uint2 lds64(uint32_t addr) {
    uint2 v;
    asm volatile("ld.shared.v2.u32 {%0,%1}, [%2];\n" : "=r"(v.x), "=r"(v.y) : "r"(addr) : "memory");
    return v;
}
__device__ __forceinline__ uint4 lds128(uint32_t addr) {
    uint4 v;
    asm volatile("ld.shared.v4.u32 {%0,%1,%2,%3}, [%4];\n" : "=r"(v.x), "=r"(v.y), "=r"(v.z), "=r"(v.w) : "r"(addr) : "memory");
    return v;
}
__device__ __forceinline__ float ldsf(uint32_t addr) { return __uint_as_float(lds32(addr)); }
__device__ __forceinline__ void sts32(uint32_t addr, uint32_t v) { asm volatile("st.shared.u32 [%0], %1;\n" ::"r"(addr), "r"(v) : "memory"); }
__device__ __forceinline__ void stsf(uint32_t addr, float v) { sts32(addr, __float_as_uint(v)); }
__device__ __forceinline__ void sts64(uint32_t addr, uint32_t a, uint32_t b) { asm volatile("st.shared.v2.u32 [%0], {%1,%2};\n" ::"r"(addr), "r"(a), "r"(b) : "memory"); }
__device__ __forceinline__ void sts128(uint32_t addr, uint32_t a, uint32_t b, uint32_t c, uint32_t d) {
    asm volatile("st.shared.v4.u32 [%0], {%1,%2,%3,%4};\n" ::"r"(addr), "r"(a), "r"(b), "r"(c), "r"(d) : "memory");
}
__device__ __forceinline__ void sts128f(uint32_t addr, const float (&v)[4]) {
    sts128(addr, __float_as_uint(v[0]), __float_as_uint(v[1]), __float_as_uint(v[2]), __float_as_uint(v[3]));
}
__device__ __forceinline__ void ldsm_x4(uint32_t& r0, uint32_t& r1, uint32_t& r2, uint32_t& r3, uint32_t addr) {
    asm volatile("ldmatrix.sync.aligned.m8n8.x4.shared.b16 {%0,%1,%2,%3}, [%4];\n"
                 : "=r"(r0), "=r"(r1), "=r"(r2), "=r"(r3) : "r"(addr) : "memory");
}
__device__ __forceinline__ void ldsm_x4_t(uint32_t& r0, uint32_t& r1, uint32_t& r2, uint32_t& r3, uint32_t addr) {
    asm volatile("ldmatrix.sync.aligned.m8n8.x4.trans.shared.b16 {%0,%1,%2,%3}, [%4];\n"
                 : "=r"(r0), "=r"(r1), "=r"(r2), "=r"(r3) : "r"(addr) : "memory");
}
__device__ __forceinline__ void ldsm_x2_t(uint32_t& r0, uint32_t& r1, uint32_t addr) {
    asm volatile("ldmatrix.sync.aligned.m8n8.x2.trans.shared.b16 {%0,%1}, [%2];\n" : "=r"(r0), "=r"(r1) : "r"(addr) : "memory");
}
__device__ __forceinline__ void ldsm_x1_t(uint32_t& r0, uint32_t addr) {
    asm volatile("ldmatrix.sync.aligned.m8n8.x1.trans.shared.b16 {%0}, [%1];\n" : "=r"(r0) : "r"(addr) : "memory");
}
__device__ __forceinline__ uint32_t movm(uint32_t a) {
    uint32_t d;
    asm volatile("movmatrix.sync.aligned.m8n8.trans.b16 %0, %1;\n" : "=r"(d) : "r"(a));
    return d;
}
__device__ __forceinline__ void mma_f16(float (&c)[4], uint32_t a0, uint32_t a1, uint32_t a2, uint32_t a3, uint32_t b0, uint32_t b1) {
    asm volatile(
        "mma.sync.aligned.m16n8k16.row.col.f32.f16.f16.f32 {%0,%1,%2,%3}, {%4,%5,%6,%7}, {%8,%9}, {%0,%1,%2,%3};\n"
        : "+f"(c[0]), "+f"(c[1]), "+f"(c[2]), "+f"(c[3])
        : "r"(a0), "r"(a1), "r"(a2), "r"(a3), "r"(b0), "r"(b1));
}
__device__ __forceinline__ void mma_bf16(float (&c)[4], uint32_t a0, uint32_t a1, uint32_t a2, uint32_t a3, uint32_t b0, uint32_t b1) {
    asm volatile(
        "mma.sync.aligned.m16n8k16.row.col.f32.bf16.bf16.f32 {%0,%1,%2,%3}, {%4,%5,%6,%7}, {%8,%9}, {%0,%1,%2,%3};\n"
        : "+f"(c[0]), "+f"(c[1]), "+f"(c[2]), "+f"(c[3])
        : "r"(a0), "r"(a1), "r"(a2), "r"(a3), "r"(b0), "r"(b1));
}
__device__ __forceinline__ void mma_bf16_k8(float (&c)[4], uint32_t a0, uint32_t a1, uint32_t b0) {
    asm volatile("mma.sync.aligned.m16n8k8.row.col.f32.bf16.bf16.f32 {%0,%1,%2,%3}, {%4,%5}, {%6}, {%0,%1,%2,%3};\n"
        : "+f"(c[0]), "+f"(c[1]), "+f"(c[2]), "+f"(c[3]) : "r"(a0), "r"(a1), "r"(b0));
}
__device__ __forceinline__ void bar_sync(int id, int n) { asm volatile("bar.sync %0, %1;\n" ::"r"(id), "r"(n) : "memory"); }
__device__ __forceinline__ void bar_arrive(int id, int n) { asm volatile("bar.arrive %0, %1;\n" ::"r"(id), "r"(n) : "memory"); }
__device__ __forceinline__ bool bar_or(int id, int n, bool v) {
    uint32_t r;
    asm volatile("{\n.reg .pred p, q;\nsetp.ne.u32 p, %3, 0;\nbar.red.or.pred q, %1, %2, p;\nselp.u32 %0, 1, 0, q;\n}\n" : "=r"(r) : "r"(id), "r"(n), "r"((uint32_t)v) : "memory");
    return r;
}
__device__ __forceinline__ uint4 ld_poll(const void* p) {
    uint4 v;
    asm volatile("ld.relaxed.gpu.global.v4.u32 {%0,%1,%2,%3}, [%4];\n" : "=r"(v.x), "=r"(v.y), "=r"(v.z), "=r"(v.w) : "l"(p) : "memory");
    return v;
}
template <class T> __device__ __forceinline__ T* pin(T* p, uint32_t z) {
    uint32_t lo, hi;
    asm volatile("mov.b64 {%0, %1}, %2;\n" : "=r"(lo), "=r"(hi) : "l"(p));
    asm volatile("xor.b32 %0, %0, %1;\n" : "+r"(lo) : "r"(z));
    asm volatile("xor.b32 %0, %0, %1;\n" : "+r"(hi) : "r"(z));
    asm volatile("mov.b64 %0, {%1, %2};\n" : "=l"(p) : "r"(lo), "r"(hi));
    return p;
}
__device__ __forceinline__ uint32_t pin(uint32_t a, uint32_t z) { asm volatile("xor.b32 %0, %0, %1;\n" : "+r"(a) : "r"(z)); return a; }
__device__ __forceinline__ uint2 ld_poll64(const void* p) {
    uint2 v;
    asm volatile("ld.relaxed.gpu.global.v2.u32 {%0,%1}, [%2];\n" : "=r"(v.x), "=r"(v.y) : "l"(p) : "memory");
    return v;
}
__device__ __forceinline__ uint32_t ld_poll32(const void* p) {
    uint32_t v;
    asm volatile("ld.relaxed.gpu.global.u32 %0, [%1];\n" : "=r"(v) : "l"(p) : "memory");
    return v;
}
__device__ __forceinline__ uint4 ldg128(const void* p) {
    uint4 v;
    asm volatile("ld.global.nc.v4.u32 {%0,%1,%2,%3}, [%4];\n" : "=r"(v.x), "=r"(v.y), "=r"(v.z), "=r"(v.w) : "l"(p));
    return v;
}
__device__ __forceinline__ uint2 ldg64(const void* p) {
    uint2 v;
    asm volatile("ld.global.nc.v2.u32 {%0,%1}, [%2];\n" : "=r"(v.x), "=r"(v.y) : "l"(p));
    return v;
}
__device__ __forceinline__ uint32_t ldg16(const void* p) {
    uint32_t v;
    asm volatile("ld.global.nc.u16 %0, [%1];\n" : "=r"(v) : "l"(p));
    return v;
}
__device__ __forceinline__ void stg128(void* p, uint32_t a, uint32_t b, uint32_t c, uint32_t d) {
    asm volatile("st.global.v4.u32 [%0], {%1,%2,%3,%4};\n" ::"l"(p), "r"(a), "r"(b), "r"(c), "r"(d) : "memory");
}
__device__ __forceinline__ void stg64(void* p, uint32_t a, uint32_t b) { asm volatile("st.global.v2.u32 [%0], {%1,%2};\n" ::"l"(p), "r"(a), "r"(b) : "memory"); }
__device__ __forceinline__ void stg32(void* p, uint32_t a) { asm volatile("st.global.u32 [%0], %1;\n" ::"l"(p), "r"(a) : "memory"); }
__device__ __forceinline__ bool all_nz(const uint4& v) { return v.x && v.y && v.z && v.w; }
#define SPIN_LIMIT (1 << 21)
#define TRAP() __trap()
__device__ __forceinline__ void hint_arrive(unsigned* g_hint, int idx, int sub) {
    asm volatile("red.relaxed.gpu.global.add.u32 [%0], 1;\n" ::"l"(&g_hint[sub * 32 + idx]) : "memory");
}
__device__ __forceinline__ void hint_wait(const unsigned* g_hint, int idx, unsigned target) {
    unsigned l;
    asm volatile("mov.u32 %0, %%laneid;" : "=r"(l));
    const unsigned* c = &g_hint[(l & 7) * 32 + idx];
    int it = 0;
    while (__any_sync(0xffffffffu, (int)(ld_poll32(c) - target) < 0)) { if (++it > SPIN_LIMIT) TRAP(); }
}
__device__ __forceinline__ void mbar_init(uint32_t bar, uint32_t cnt) { asm volatile("mbarrier.init.shared::cta.b64 [%0], %1;\n" ::"r"(bar), "r"(cnt) : "memory"); }
__device__ __forceinline__ void mbar_expect(uint32_t bar, uint32_t bytes) {
    asm volatile("mbarrier.arrive.expect_tx.shared::cta.b64 _, [%0], %1;\n" ::"r"(bar), "r"(bytes) : "memory");
}
__device__ __forceinline__ void mbar_arrive(uint32_t bar) { asm volatile("mbarrier.arrive.shared::cta.b64 _, [%0];\n" ::"r"(bar) : "memory"); }
__device__ __forceinline__ void mbar_wait(uint32_t bar) {
    asm volatile(
        "{\n.reg .pred p;\n"
        "W_%=:\n"
        "mbarrier.try_wait.parity.shared::cta.b64 p, [%0], 0;\n"
        "@!p bra W_%=;\n}\n" ::"r"(bar) : "memory");
}
__device__ __forceinline__ void bulk_s2g(void* dst, uint32_t src, uint32_t bytes) {
    asm volatile("cp.async.bulk.global.shared::cta.bulk_group [%0], [%1], %2;\ncp.async.bulk.commit_group;\n" ::"l"(dst), "r"(src), "r"(bytes) : "memory");
}
__device__ __forceinline__ void tma_2d(uint32_t dst, const CUtensorMap* tm, int c0, int c1, uint32_t bar) {
    asm volatile("cp.async.bulk.tensor.2d.shared::cluster.global.mbarrier::complete_tx::bytes [%0], [%1, {%3, %4}], [%2];\n"
                 ::"r"(dst), "l"(tm), "r"(bar), "r"(c0), "r"(c1) : "memory");
}
__device__ __forceinline__ void tma_3d(uint32_t dst, const CUtensorMap* tm, int c0, int c1, int c2, uint32_t bar) {
    asm volatile("cp.async.bulk.tensor.3d.shared::cluster.global.mbarrier::complete_tx::bytes [%0], [%1, {%3, %4, %5}], [%2];\n"
                 ::"r"(dst), "l"(tm), "r"(bar), "r"(c0), "r"(c1), "r"(c2) : "memory");
}
__device__ __forceinline__ void tma_st_3d(const CUtensorMap* tm, uint32_t src, int c0, int c1, int c2) {
    asm volatile("cp.async.bulk.tensor.3d.global.shared::cta.bulk_group [%0, {%2, %3, %4}], [%1];\ncp.async.bulk.commit_group;\n"
                 ::"l"(tm), "r"(src), "r"(c0), "r"(c1), "r"(c2) : "memory");
}
__device__ __forceinline__ bool elect_one() {
    uint32_t r;
    asm volatile("{\n.reg .pred p;\nelect.sync _|p, 0xffffffff;\nselp.u32 %0, 1, 0, p;\n}\n" : "=r"(r));
    return r;
}
__device__ __forceinline__ void fence_async() { asm volatile("fence.proxy.async.shared::cta;\n" ::: "memory"); }

__device__ __forceinline__ float2 cmul(float2 a, float2 b) {
    return make_float2(fmaf(a.x, b.x, -a.y * b.y), fmaf(a.x, b.y, a.y * b.x));
}
__device__ __forceinline__ float2 csq(float2 a) {
    float p = a.x * a.y;
    return make_float2(fmaf(a.x, a.x, -a.y * a.y), p + p);
}
__device__ __forceinline__ float2 cexp_e(float lr2, float rh, float rl, float e) {
    float m;
    asm("ex2.approx.ftz.f32 %0, %1;\n" : "=f"(m) : "f"(lr2 * e));
    const float a = rh * e;
    const float r = fmaf(rl, e, a - rintf(a)) * 6.283185307179586f;
    return make_float2(m * __cosf(r), m * __sinf(r));
}
__device__ __forceinline__ float rcp_approx(float x) { float r; asm("rcp.approx.ftz.f32 %0, %1;\n" : "=f"(r) : "f"(x)); return r; }
__device__ __forceinline__ float ex2_approx(float x) { float r; asm("ex2.approx.ftz.f32 %0, %1;\n" : "=f"(r) : "f"(x)); return r; }
__device__ __forceinline__ float sqrt_approx(float x) { float r; asm("sqrt.approx.ftz.f32 %0, %1;\n" : "=f"(r) : "f"(x)); return r; }

__device__ __forceinline__ void wg_fence() { asm volatile("wgmma.fence.sync.aligned;\n" ::: "memory"); }
__device__ __forceinline__ void wg_commit() { asm volatile("wgmma.commit_group.sync.aligned;\n" ::: "memory"); }
__device__ __forceinline__ void wg_wait0() { asm volatile("wgmma.wait_group.sync.aligned 0;\n" ::: "memory"); }
template <int T0, int NT> __device__ __forceinline__ void wg_h(uint32_t (&acc)[32], const uint32_t (&a)[4], uint64_t desc);
template <> __device__ __forceinline__ void wg_h<0, 16>(uint32_t (&acc)[32], const uint32_t (&a)[4], uint64_t desc) {
    asm volatile("wgmma.mma_async.sync.aligned.m64n128k16.f16.f16.f16 {%0,%1,%2,%3,%4,%5,%6,%7,%8,%9,%10,%11,%12,%13,%14,%15,%16,%17,%18,%19,%20,%21,%22,%23,%24,%25,%26,%27,%28,%29,%30,%31}, {%32,%33,%34,%35}, %36, 1, 1, 1, 0;\n"
                 : "+r"(acc[0]), "+r"(acc[1]), "+r"(acc[2]), "+r"(acc[3]), "+r"(acc[4]), "+r"(acc[5]), "+r"(acc[6]), "+r"(acc[7]), "+r"(acc[8]), "+r"(acc[9]), "+r"(acc[10]), "+r"(acc[11]), "+r"(acc[12]), "+r"(acc[13]), "+r"(acc[14]), "+r"(acc[15]), "+r"(acc[16]), "+r"(acc[17]), "+r"(acc[18]), "+r"(acc[19]), "+r"(acc[20]), "+r"(acc[21]), "+r"(acc[22]), "+r"(acc[23]), "+r"(acc[24]), "+r"(acc[25]), "+r"(acc[26]), "+r"(acc[27]), "+r"(acc[28]), "+r"(acc[29]), "+r"(acc[30]), "+r"(acc[31])
                 : "r"(a[0]), "r"(a[1]), "r"(a[2]), "r"(a[3]), "l"(desc));
}
template <> __device__ __forceinline__ void wg_h<4, 4>(uint32_t (&acc)[32], const uint32_t (&a)[4], uint64_t desc) {
    asm volatile("wgmma.mma_async.sync.aligned.m64n32k16.f16.f16.f16 {%0,%1,%2,%3,%4,%5,%6,%7}, {%8,%9,%10,%11}, %12, 1, 1, 1, 0;\n"
                 : "+r"(acc[8]), "+r"(acc[9]), "+r"(acc[10]), "+r"(acc[11]), "+r"(acc[12]), "+r"(acc[13]), "+r"(acc[14]), "+r"(acc[15])
                 : "r"(a[0]), "r"(a[1]), "r"(a[2]), "r"(a[3]), "l"(desc));
}
template <> __device__ __forceinline__ void wg_h<8, 4>(uint32_t (&acc)[32], const uint32_t (&a)[4], uint64_t desc) {
    asm volatile("wgmma.mma_async.sync.aligned.m64n32k16.f16.f16.f16 {%0,%1,%2,%3,%4,%5,%6,%7}, {%8,%9,%10,%11}, %12, 1, 1, 1, 0;\n"
                 : "+r"(acc[16]), "+r"(acc[17]), "+r"(acc[18]), "+r"(acc[19]), "+r"(acc[20]), "+r"(acc[21]), "+r"(acc[22]), "+r"(acc[23])
                 : "r"(a[0]), "r"(a[1]), "r"(a[2]), "r"(a[3]), "l"(desc));
}
template <> __device__ __forceinline__ void wg_h<12, 4>(uint32_t (&acc)[32], const uint32_t (&a)[4], uint64_t desc) {
    asm volatile("wgmma.mma_async.sync.aligned.m64n32k16.f16.f16.f16 {%0,%1,%2,%3,%4,%5,%6,%7}, {%8,%9,%10,%11}, %12, 1, 1, 1, 0;\n"
                 : "+r"(acc[24]), "+r"(acc[25]), "+r"(acc[26]), "+r"(acc[27]), "+r"(acc[28]), "+r"(acc[29]), "+r"(acc[30]), "+r"(acc[31])
                 : "r"(a[0]), "r"(a[1]), "r"(a[2]), "r"(a[3]), "l"(desc));
}
template <> __device__ __forceinline__ void wg_h<0, 8>(uint32_t (&acc)[32], const uint32_t (&a)[4], uint64_t desc) {
    asm volatile("wgmma.mma_async.sync.aligned.m64n64k16.f16.f16.f16 {%0,%1,%2,%3,%4,%5,%6,%7,%8,%9,%10,%11,%12,%13,%14,%15}, {%16,%17,%18,%19}, %20, 1, 1, 1, 0;\n"
                 : "+r"(acc[0]), "+r"(acc[1]), "+r"(acc[2]), "+r"(acc[3]), "+r"(acc[4]), "+r"(acc[5]), "+r"(acc[6]), "+r"(acc[7]), "+r"(acc[8]), "+r"(acc[9]), "+r"(acc[10]), "+r"(acc[11]), "+r"(acc[12]), "+r"(acc[13]), "+r"(acc[14]), "+r"(acc[15])
                 : "r"(a[0]), "r"(a[1]), "r"(a[2]), "r"(a[3]), "l"(desc));
}
template <> __device__ __forceinline__ void wg_h<4, 12>(uint32_t (&acc)[32], const uint32_t (&a)[4], uint64_t desc) {
    asm volatile("wgmma.mma_async.sync.aligned.m64n96k16.f16.f16.f16 {%0,%1,%2,%3,%4,%5,%6,%7,%8,%9,%10,%11,%12,%13,%14,%15,%16,%17,%18,%19,%20,%21,%22,%23}, {%24,%25,%26,%27}, %28, 1, 1, 1, 0;\n"
                 : "+r"(acc[8]), "+r"(acc[9]), "+r"(acc[10]), "+r"(acc[11]), "+r"(acc[12]), "+r"(acc[13]), "+r"(acc[14]), "+r"(acc[15]), "+r"(acc[16]), "+r"(acc[17]), "+r"(acc[18]), "+r"(acc[19]), "+r"(acc[20]), "+r"(acc[21]), "+r"(acc[22]), "+r"(acc[23]), "+r"(acc[24]), "+r"(acc[25]), "+r"(acc[26]), "+r"(acc[27]), "+r"(acc[28]), "+r"(acc[29]), "+r"(acc[30]), "+r"(acc[31])
                 : "r"(a[0]), "r"(a[1]), "r"(a[2]), "r"(a[3]), "l"(desc));
}

#define PBYTES 4608
#define DELAY(n) do { if (n) { const unsigned c0_ = clock32(); while ((int)(clock32() - c0_) < (n)) {} } } while (0)
#define KDEL 400
#define PDEL 300
#define CST(i) do { if ((warp & 3) == 0 && lane_v() == 0) { unsigned t_; asm volatile("mov.u32 %0, %%globaltimer_lo;" : "=r"(t_) :: "memory"); sts32(sb + SMEM_TOTAL - 768 + (warp >> 2) * 128 + (i) * 4, t_); } } while (0)
#define TP0 5000
#define TP4 5800
#define KDEL2 300
#define WSP 450
#define WS0 0
#define HINTW 10
#define WAS 0x0005
#define WA0 (WAS >> 12)
#define WA1 ((WAS >> 8) & 15)
#define WA2 ((WAS >> 4) & 15)
#define WA3 (WAS & 15)
#define WDAT 1
#define UW 8
#define TOKEN_OF(g) (16 * ((g) & 1) + ((g) >> 2) + 2 * ((g) & 2))
#define HI2(a, b) (pack_f16_rz(__uint_as_float(a), __uint_as_float(b)) & 0xfff8fff8u)
struct Params {
    const bf16 *x, *lar, *aim, *cre, *cim, *ldt, *dsk;
    Scratch* s;
    const bf16* wr;
    bf16* out;
};

template <int NK>
__device__ __forceinline__ void ln_partial(const uint32_t (&H)[2][NK], const uint32_t (&bw)[NK], uint32_t lp, int warp, int g, int t) {
    float cs[4] = {0.f, 0.f, 0.f, 0.f}, cl[4] = {0.f, 0.f, 0.f, 0.f}, ch[4] = {0.f, 0.f, 0.f, 0.f};
#pragma unroll
    for (int k = 0; k < NK; k += 2) {
        uint32_t a0, a1, a2, a3;
        asm volatile("prmt.b32 %0, %4, %4, %8;\nprmt.b32 %1, %5, %5, %8;\nprmt.b32 %2, %6, %6, %8;\nprmt.b32 %3, %7, %7, %8;\n"
                     : "=r"(a0), "=r"(a1), "=r"(a2), "=r"(a3) : "r"(H[0][k]), "r"(H[1][k]), "r"(H[0][k + 1]), "r"(H[1][k + 1]), "r"(0x3210u + (warp >> 8)));
        mma_bf16(cl, a0, a1, a2, a3, H[0][k], H[0][k + 1]);
        mma_bf16(ch, a0, a1, a2, a3, H[1][k], H[1][k + 1]);
        mma_bf16(cs, a0, a1, a2, a3, bw[k], bw[k + 1]);
    }
    const uint32_t a = lp + (g * 20 + warp) * 4;
    if (t == 0) {
        stsf(a, cs[1]); stsf(a + 8 * 80, cs[3]);
        if (NK == 4) { stsf(a + 48 * 80, cs[0]); stsf(a + 56 * 80, cs[2]); }
    }
    if (t == (g >> 1)) { stsf(a + 16 * 80, (g & 1) ? cl[1] : cl[0]); stsf(a + 24 * 80, (g & 1) ? ch[3] : ch[2]); }
}
__device__ __forceinline__ float sum18(uint32_t a) {
    const uint4 p = lds128(a), q = lds128(a + 16), r = lds128(a + 32), s = lds128(a + 48);
    const uint2 u = lds64(a + 64);
#define F(x) __uint_as_float(x)
    return (((F(p.x) + F(p.y)) + (F(p.z) + F(p.w))) + ((F(q.x) + F(q.y)) + (F(q.z) + F(q.w)))) +
           (((F(r.x) + F(r.y)) + (F(r.z) + F(r.w))) + ((F(s.x) + F(s.y)) + (F(s.z) + F(s.w))) + (F(u.x) + F(u.y)));
#undef F
}
__device__ __forceinline__ float sum9(uint32_t a) {
    const uint4 p = lds128(a), q = lds128(a + 16);
#define F(x) __uint_as_float(x)
    return (((F(p.x) + F(p.y)) + (F(p.z) + F(p.w))) + ((F(q.x) + F(q.y)) + (F(q.z) + F(q.w)))) + ldsf(a + 32);
#undef F
}
template <int N>
__device__ __forceinline__ void ln_finish(uint32_t lp, int lane, float& mb, float& rc) {
    const float v = N == 9 ? sum9(lp + lane * 80) : sum18(lp + lane * 80);
    const float o = __shfl_xor_sync(0xffffffffu, v, 16);
    const float m0 = v * (1.0f / 576.0f);
    const float mean = fmaf(fmaf(-m0, 576.0f, v), 1.0f / 576.0f, m0);
    const float var = fmaxf(fmaf(o, 1.0f / 576.0f, -(mean * mean)), 0.f);
    mb = rbf(mean);
    rc = rcp_approx(rbf(sqrt_approx(rbf(rbf(var) + 1e-5f))));
}
__device__ __forceinline__ uint32_t ln_apply(uint32_t w, const uint2& st) {
    uint32_t r;
    asm("{\n.reg .b16 m, t, h, l;\n.reg .b32 mm, hh, ll, d, e;\nmov.b32 {m, t}, %2;\nmov.b32 {h, l}, %3;\nmov.b32 mm, {m, m};\nmov.b32 hh, {h, h};\nmov.b32 ll, {l, l};\n"
        "sub.rn.bf16x2 d, %1, mm;\nmul.rn.bf16x2 e, d, ll;\nfma.rn.bf16x2 %0, d, hh, e;\n}\n" : "=r"(r) : "r"(w), "r"(st.x), "r"(st.y));
    return r;
}
__device__ __forceinline__ void stat_store(uint32_t a, float mb, float rc, uint32_t extra) {
    const float rh = rbf(rc);
    sts64(a, (__float_as_uint(mb) >> 16) | (extra << 16), pack_bf16(rh, rc - rh));
}

__device__ __forceinline__ void hcmul(uint32_t re, uint32_t im, uint32_t z, uint32_t& ore, uint32_t& oim) {
    asm("{\n.reg .b16 x, y;\n.reg .b32 xx, yy, ny, a, b;\nmov.b32 {x, y}, %4;\nmov.b32 xx, {x, x};\nmov.b32 yy, {y, y};\nneg.f16x2 ny, yy;\n"
        "mul.rn.f16x2 a, %2, xx;\nfma.rn.f16x2 %0, %3, ny, a;\nmul.rn.f16x2 b, %3, xx;\nfma.rn.f16x2 %1, %2, yy, b;\n}\n" : "=&r"(ore), "=r"(oim) : "r"(re), "r"(im), "r"(z));
}
__device__ __forceinline__ void hcmul(uint32_t re, uint32_t im, uint32_t zx, uint32_t zy, uint32_t& ore, uint32_t& oim) {
    asm("{\n.reg .b32 ny, a, b;\nneg.f16x2 ny, %5;\n"
        "mul.rn.f16x2 a, %2, %4;\nfma.rn.f16x2 %0, %3, ny, a;\nmul.rn.f16x2 b, %3, %4;\nfma.rn.f16x2 %1, %2, %5, b;\n}\n" : "=&r"(ore), "=r"(oim) : "r"(re), "r"(im), "r"(zx), "r"(zy));
}

struct KGen {
    uint32_t Af[4][4];
    float2 z1, z8, z64, z128, T[9];
    uint32_t zw;
};
__device__ __forceinline__ void kgen_setup(KGen& k, uint32_t pa, float dt) {
    const float A = rbf(expf(bf_lo(pa)));
    const float lr2 = -(A * dt) * 1.4426950408889634f;
    const float li = bf_hi(pa) * dt;
    const float rh = li * 0.15915494309189535f;
    const float rl = fmaf(li, 6.4206382986e-9f, fmaf(li, 0.15915494309189535f, -rh));
    k.z1 = cexp_e(lr2, rh, rl, 1.0f);
    k.z8 = cexp_e(lr2, rh, rl, 8.0f);
    k.z64 = cexp_e(lr2, rh, rl, 64.0f);
}
__device__ __forceinline__ void kgen_rows(KGen& k, uint32_t tb, int lane) {
    const float2 z8 = k.z8, z64 = k.z64;
    const uint32_t row = tb + lane * TBP;
    k.z128 = csq(z64);
    const float2 z16 = csq(z8), z32 = csq(z16), z48 = cmul(z32, z16), z80 = cmul(z64, z16), z96 = cmul(z64, z32), z112 = cmul(z64, z48);
    uint32_t re[4], im[4], a[4], b[4];
    re[0] = pack_f16(1.0f, z16.x); im[0] = pack_f16(0.0f, z16.y);
    re[1] = pack_f16(z32.x, z48.x); im[1] = pack_f16(z32.y, z48.y);
    re[2] = pack_f16(z64.x, z80.x); im[2] = pack_f16(z64.y, z80.y);
    re[3] = pack_f16(z96.x, z112.x); im[3] = pack_f16(z96.y, z112.y);
    sts128(row, re[0], re[1], re[2], re[3]);
    sts128(row + 32, im[0], im[1], im[2], im[3]);
    const uint32_t zz = pack_f16(z8.x, z8.y);
#pragma unroll
    for (int j = 0; j < 4; j++) hcmul(re[j], im[j], zz, a[j], b[j]);
    sts128(row + 16, a[0], a[1], a[2], a[3]);
    sts128(row + 48, b[0], b[1], b[2], b[3]);
    __syncwarp();
    const int mi = lane >> 3;
    const uint32_t ad = tb + (lane & 7) * TBP + mi * 16;
#pragma unroll
    for (int ks = 0; ks < 4; ks++) ldsm_x4_t(k.Af[ks][0], k.Af[ks][1], k.Af[ks][2], k.Af[ks][3], ad + ks * 8 * TBP);
}
__device__ __forceinline__ void kgen_chain(KGen& k, uint32_t pc, float cs) {
    k.T[0] = make_float2(bf_lo(pc) * cs, -bf_hi(pc) * cs);
    const float2 y1 = make_float2(k.z1.x, -k.z1.y);
#pragma unroll
    for (int c = 1; c < 8; c++) k.T[c] = cmul(k.T[c - 1], y1);
    k.T[8] = cmul(k.T[0], make_float2(k.z8.x, -k.z8.y));
}
__device__ __forceinline__ void kgen_cols(KGen& k, uint32_t tb, int lane) {
    const uint32_t row = tb + lane * TBP;
    const float2 (&T)[9] = k.T;
    const uint32_t zv = pack_f16(k.z128.x, k.z128.y), zo = __shfl_xor_sync(0xffffffffu, zv, 1);
    k.zw = (lane & 1) ? __byte_perm(zo, zv, 0x7632) : __byte_perm(zv, zo, 0x5410);
    const float2 y256 = csq(make_float2(k.z128.x, -k.z128.y)), y512 = csq(y256), y768 = cmul(y512, y256), y1024 = csq(y512);
    const float2 c1032 = cmul(T[8], y1024);
    const uint32_t r04 = pack_f16(T[0].x, T[4].x), i04 = pack_f16(T[0].y, T[4].y), r26 = pack_f16(T[2].x, T[6].x), i26 = pack_f16(T[2].y, T[6].y);
    const uint32_t r48 = pack_f16(T[4].x, T[8].x), i48 = pack_f16(T[4].y, T[8].y);
    __syncwarp();
    sts128(row, r04, pack_f16(T[1].x, T[5].x), r26, pack_f16(T[3].x, T[7].x));
    sts128(row + 16, i04, pack_f16(T[1].y, T[5].y), i26, pack_f16(T[3].y, T[7].y));
    uint32_t a[4], b[4];
    {
        const uint32_t zz = pack_f16(y256.x, y256.y);
        hcmul(r04, i04, zz, a[0], b[0]);
        hcmul(r26, i26, zz, a[2], b[2]);
        hcmul(r48, i48, zz, a[3], b[3]);
    }
    sts128(row + 32, a[0], a[0], a[2], a[3]);
    sts128(row + 48, b[0], b[0], b[2], b[3]);
    {
        hcmul(r48, i48, pack_f16(y512.x, y512.y), a[0], b[0]);
        hcmul(r48, i48, pack_f16(y768.x, y768.y), a[1], b[1]);
        const uint32_t zz = pack_f16(c1032.x, c1032.y);
        hcmul(pack_f16(1.0f, y256.x), pack_f16(0.0f, y256.y), zz, a[2], b[2]);
        hcmul(pack_f16(y512.x, y768.x), pack_f16(y512.y, y768.y), zz, a[3], b[3]);
    }
    sts128(row + 64, a[0], a[1], a[2], a[3]);
    sts128(row + 80, b[0], b[1], b[2], b[3]);
}
__device__ __forceinline__ void kgen_mma(const KGen& k, uint32_t tb, int lane) {
    const int t = lane & 3;
    const uint32_t zw = k.zw;
    uint32_t zx[4], zy[4];
#pragma unroll
    for (int ks = 0; ks < 4; ks++) { zx[ks] = __shfl_sync(0xffffffffu, zw, 8 * ks + 2 * t); zy[ks] = __shfl_sync(0xffffffffu, zw, 8 * ks + 2 * t + 1); }
    __syncwarp();
    float acc[2][3][4];
#pragma unroll
    for (int i = 0; i < 6; i++)
#pragma unroll
        for (int j = 0; j < 4; j++) acc[i / 3][i % 3][j] = 0.f;
    {
        const int mi = lane >> 3;
        const uint32_t bd = tb + ((lane & 7) + 8 * (mi >> 1)) * TBP + (mi & 1) * 16;
#pragma unroll
        for (int kp = 0; kp < 2; kp++) {
            uint32_t b[3][4];
#pragma unroll
            for (int j = 0; j < 3; j++) ldsm_x4_t(b[j][0], b[j][1], b[j][2], b[j][3], bd + kp * 16 * TBP + j * 32);
#pragma unroll
            for (int h = 0; h < 2; h++) {
                const int ks = 2 * kp + h;
                uint32_t d[4];
                hcmul(k.Af[ks][0], k.Af[ks][2], zx[ks], zy[ks], d[0], d[2]);
                hcmul(k.Af[ks][1], k.Af[ks][3], zx[ks], zy[ks], d[1], d[3]);
#pragma unroll
                for (int j = 0; j < 3; j++) {
                    mma_f16(acc[0][j], k.Af[ks][0], k.Af[ks][1], k.Af[ks][2], k.Af[ks][3], b[j][2 * h], b[j][2 * h + 1]);
                    mma_f16(acc[1][j], d[0], d[1], d[2], d[3], b[j][2 * h], b[j][2 * h + 1]);
                }
            }
        }
    }
    __syncwarp();
#pragma unroll
    for (int h = 0; h < 2; h++) {
        sts64(tb + h * 256 + lane * 8, pack_f16(acc[h][0][0], acc[h][0][1]), pack_f16(acc[h][0][2], acc[h][0][3]));
        sts64(tb + 512 + h * 256 + lane * 8, pack_f16(acc[h][1][0], acc[h][1][1]), pack_f16(acc[h][1][2], acc[h][1][3]));
        sts32(tb + 1024 + h * 256 + lane * 4, pack_f16(acc[h][2][0], t < 2 ? acc[h][2][1] : acc[h][2][2]));
        sts32(tb + 1152 + h * 256 + lane * 4, pack_f16(t < 2 ? acc[h][2][2] : acc[h][2][1], acc[h][2][3]));
    }
}
__device__ __forceinline__ uint32_t table_buf(uint32_t sb, int warp) { return sb + SM_TB + warp * TBW; }

__device__ __forceinline__ void kgen_combine(uint32_t sb, int warp, int lane, uint32_t kw, uint32_t ao) {
    const int wq = warp & 3;
    const uint32_t a = table_buf(sb, warp & ~3) + wq * 256 + lane * 8, c = table_buf(sb, warp & ~3) + 1024 + wq * 128 + lane * 4;
    const int t = lane & 3;
    const uint32_t o0 = (t < 2 ? KW_T2 + KW_KH + 16 + t * 256 - (wq & 1) * KW_KH : KW_T3 + 16 - 1024 + t * 512 + (wq & 1) * 256) + (lane >> 2) * 16;
    const uint4 o = make_uint4(o0 + t * 36, o0 + (t ^ 1) * 36, o0 + (t ^ 2) * 36, o0 + (t ^ 3) * 36);
    const uint2 u = lds64(a), v = lds64(a + TBW), w = lds64(a + 2 * TBW), x = lds64(a + 3 * TBW);
    const uint32_t kt = hadd2(hadd2(lds32(c), lds32(c + TBW)), hadd2(lds32(c + 2 * TBW), lds32(c + 3 * TBW)));
    const uint32_t k23 = hadd2(hadd2(u.y, v.y), hadd2(w.y, x.y));
    sts64(kw + wq * 64 + ao, hadd2(hadd2(u.x, v.x), hadd2(w.x, x.x)), k23);
    const uint32_t d = kw + (wq >> 1) * 128;
    const uint32_t kh = hmul2(kt, 0x38003800u);
    sts32(d + o.x, kh); sts32(d + o.y, kh); sts32(d + o.z, kh); sts32(d + o.w, kh);
    if (wq == 3) {
        if (lane == 31) { sts32(kw + 264, k23 >> 16); sts32(kw + 288 + 264, k23 >> 16); sts32(kw + 576 + 264, k23 >> 16); }
        if (lane == 29) { sts32(kw + 864 + 280, kt >> 16); sts32(kw + 280, kt & 0xffff0000u); }
    }
}

__device__ __forceinline__ int c_exponent(const uint2& r, const uint2& i) {
    uint32_t mx = __vmaxu2(__vmaxu2(r.x & 0x7fff7fffu, r.y & 0x7fff7fffu), __vmaxu2(i.x & 0x7fff7fffu, i.y & 0x7fff7fffu));
    mx = __reduce_max_sync(0xffffffffu, max(mx & 0xffffu, mx >> 16));
    return min(max((int)(mx >> 7), 4), 240);
}

__device__ __forceinline__ int warp_v() { int l; asm volatile("mov.u32 %0, %%tid.x;" : "=r"(l)); return __shfl_sync(0xffffffffu, l >> 5, 0); }
__device__ __forceinline__ int lane_v() { int l; asm volatile("mov.u32 %0, %%laneid;" : "=r"(l)); return l; }
__device__ __forceinline__ unsigned clock32() { unsigned c; asm volatile("mov.u32 %0, %%clock;" : "=r"(c)); return c; }
__device__ __forceinline__ uint32_t prmt(uint32_t a, uint32_t b, uint32_t s) { uint32_t d; asm("prmt.b32 %0, %1, %2, %3;\n" : "=r"(d) : "r"(a), "r"(b), "r"(s)); return d; }
__device__ __forceinline__ uint32_t prmt_v(uint32_t a, uint32_t b, uint32_t s) { uint32_t d; asm volatile("prmt.b32 %0, %1, %2, %3;\n" : "=r"(d) : "r"(a), "r"(b), "r"(s)); return d; }
__device__ __forceinline__ void mmah16(uint32_t& d0, uint32_t& d1, uint32_t a0, uint32_t a1, uint32_t a2, uint32_t a3, uint32_t b0, uint32_t b1, uint32_t c0, uint32_t c1) {
    asm volatile("mma.sync.aligned.m16n8k16.row.col.f16.f16.f16.f16 {%0,%1}, {%2,%3,%4,%5}, {%6,%7}, {%8,%9};\n"
                 : "=r"(d0), "=r"(d1) : "r"(a0), "r"(a1), "r"(a2), "r"(a3), "r"(b0), "r"(b1), "r"(c0), "r"(c1));
}
__device__ __forceinline__ void mmah8(uint32_t& d0, uint32_t& d1, uint32_t a0, uint32_t a1, uint32_t b0, uint32_t c0, uint32_t c1) {
    asm volatile("mma.sync.aligned.m16n8k8.row.col.f16.f16.f16.f16 {%0,%1}, {%2,%3}, {%4}, {%5,%6};\n"
                 : "=r"(d0), "=r"(d1) : "r"(a0), "r"(a1), "r"(b0), "r"(c0), "r"(c1));
}
template <int A = 8, int B = 32>
__device__ __forceinline__ void conv_rename(uint32_t (&acc)[32]) {
#pragma unroll
    for (int i = A; i < B; i++) { uint32_t v; asm volatile("mov.b32 %0, %1;\n" : "=r"(v) : "r"(acc[i])); acc[i] = v; }
}
__host__ __device__ constexpr uint32_t band_bits(int hw, int sh) {
    uint32_t c = 0;
    for (int s = 0; s <= 10; s++)
        for (int e = 0; e < 2; e++) {
            const int v = s - 3 + sh - 4 * e;
            if (v <= hw && v >= -hw) c |= 1u << (14 + 16 * e - s);
        }
    return c;
}
template <int HW, int SH, int J> __device__ __forceinline__ uint32_t band(uint32_t p2) {
    uint32_t d;
    asm volatile("{\n.reg .b32 t;\nmul.lo.u32 t, %1, %2;\nand.b32 %0, t, 0x40004000;\n}\n" : "=r"(d) : "r"(p2), "n"(band_bits(HW, SH) | J));
    return d;
}
__device__ __forceinline__ void band_quads(uint4 (&b)[3], uint32_t p2, uint32_t pm) {
    b[0] = make_uint4(band<2, 4, 1>(pm), band<1, 4, 1>(p2), band<2, -4, 1>(pm), band<1, -4, 1>(p2));
    b[1] = make_uint4(band<4, 4, 1>(pm), band<3, 4, 1>(pm), band<4, -4, 1>(pm), band<3, -4, 1>(pm));
    b[2] = make_uint4(band<2, 4, 2>(pm), band<4, 4, 2>(pm), band<2, -4, 2>(pm), band<4, -4, 2>(pm));
}
__device__ __forceinline__ uint2 run_sums(const uint4& a, uint32_t b0, uint32_t b1) {
    uint2 d;
    mmah16(d.x, d.y, a.x, a.y, a.z, a.w, b0, b1, 0u, 0u);
    return d;
}
__device__ __forceinline__ float h_lo(uint32_t w) { return __half2float(__ushort_as_half((unsigned short)(w & 0xffffu))); }
__device__ __forceinline__ float h_hi(uint32_t w) { return __half2float(__ushort_as_half((unsigned short)(w >> 16))); }
__device__ __forceinline__ uint64_t smem_desc(uint32_t sb, uint32_t o16, uint32_t lbo) {
    uint64_t d;
    asm("mov.b64 %0, {%1, %2};" : "=l"(d) : "r"(((sb & 0x3FFFF) >> 4) + o16 + (lbo << 12)), "r"(8));
    return d;
}
template <int I> struct IC { static constexpr int value = I; };

struct Conv {
    uint32_t q2[3][2][4];
    uint32_t q3[2][4];
    uint32_t r[18];
};
struct ConvPre {
    uint32_t a[5], b[5];
    uint32_t t[4];
};
__device__ __forceinline__ void conv_pre(ConvPre& e, uint32_t ka, uint32_t ks, uint32_t sel) {
    const uint4 r = lds128(ka + 256), s = lds128(ka + 272);
    ldsm_x4(e.t[0], e.t[1], e.t[2], e.t[3], ks);
    const uint32_t sw = sel ^ 0x4444u;
    e.a[0] = prmt(r.y, r.z, sel); e.a[1] = prmt(r.w, r.z, sw); e.a[2] = prmt(r.x, r.y, sel); e.a[3] = prmt(r.z, r.y, sw); e.a[4] = prmt(r.z, r.w, sel);
    e.b[0] = prmt(s.y, s.z, sel); e.b[1] = prmt(s.w, s.z, sw); e.b[2] = prmt(s.x, s.y, sel); e.b[3] = prmt(s.z, s.y, sw); e.b[4] = prmt(s.z, s.w, sel);
}
__device__ __forceinline__ void conv_sums(Conv& c, uint32_t (&acc)[32], const ConvPre& e, uint32_t a0, uint32_t a1, const uint4 (&bd)[3], uint32_t ka, uint32_t sel, int wq, bool odd) {
#pragma unroll
    for (int i = 0; i < 32; i++) acc[i] = 0u;
    uint32_t un[4], vn[4];
    ldsm_x4(un[0], un[1], un[2], un[3], a1);
    ldsm_x4(vn[0], vn[1], vn[2], vn[3], a0);
#pragma unroll
    for (int q = 0; q < 3; q++) {
        const uint32_t u[4] = {un[0], un[1], un[2], un[3]}, v[4] = {vn[0], vn[1], vn[2], vn[3]};
        if (q && sel == 0u) {
            sts128(ka, c.q3[q - 1][0], c.q3[q - 1][1], c.q3[q - 1][2], c.q3[q - 1][3]);
            sts64(ka, acc[8 * q], acc[8 * q + 8]);
        }
        if (q < 2) {
            ldsm_x4(un[0], un[1], un[2], un[3], a1 + q * 512 + 512);
            ldsm_x4(vn[0], vn[1], vn[2], vn[3], a0 + q * 512 + 512);
        }
        mmah8(acc[8 * q + 8], acc[8 * q + 9], e.a[4], 0u, u[1], acc[8 * q + 8], acc[8 * q + 9]);
        mmah16(acc[8 * q + 8], acc[8 * q + 9], e.a[0], e.a[1], e.a[2], e.a[3], u[2], u[3], acc[8 * q + 8], acc[8 * q + 9]);
        const uint2 z0 = run_sums(bd[2], v[0], v[1]);
        if (q < 2) {
            mmah8(acc[8 * q + 16], acc[8 * q + 17], e.b[4], 0u, u[1], 0u, 0u);
            mmah16(acc[8 * q + 16], acc[8 * q + 17], e.b[0], e.b[1], e.b[2], e.b[3], u[2], u[3], acc[8 * q + 16], acc[8 * q + 17]);
            const uint2 y1 = run_sums(bd[1], u[0], u[1]), y2 = run_sums(bd[1], v[2], v[3]), y3 = run_sums(bd[1], u[2], u[3]);
            const uint32_t n0 = odd ? y1.x : z0.y, n1 = odd ? y2.x : y1.x, s1 = odd ? y2.y : y1.y, s2 = odd ? y3.y : y2.y;
            c.q3[q][0] = prmt(s1, n0, 0x7632u); c.q3[q][1] = prmt(s2, n1, 0x7632u);
            c.q3[q][2] = prmt(s1, n0, 0x5410u); c.q3[q][3] = prmt(s2, n1, 0x5410u);
        }
        const uint2 x1 = run_sums(bd[0], u[0], u[1]), x2 = run_sums(bd[0], v[2], v[3]), x3 = run_sums(bd[0], u[2], u[3]);
        const uint32_t f0 = odd ? x1.x : z0.x, f1 = odd ? x2.x : x1.x, f2 = odd ? x3.x : x2.x;
#pragma unroll
        for (int h = 0; h < 2; h++) {
            const uint32_t s = h ? 0x7632u : 0x5410u;
            c.q2[q][h][0] = prmt(x1.y, f0, s); c.q2[q][h][1] = prmt(x2.y, f1, s);
            c.q2[q][h][2] = prmt(f1, x2.y, s ^ 0x4444u); c.q2[q][h][3] = prmt(x3.y, f2, s);
            if (q < 2) mmah16(acc[8 * q + 16], acc[8 * q + 17], c.q2[q][h][0], c.q2[q][h][1], c.q2[q][h][2], c.q2[q][h][3], e.t[2 * h], e.t[2 * h + 1], acc[8 * q + 16], acc[8 * q + 17]);
        }
    }
    {
        const uint32_t a = ka + wq * 64;
#pragma unroll
        for (int i = 0; i < 4; i++) { const uint4 v = lds128(a + i * 16); c.r[4 * i] = v.x; c.r[4 * i + 1] = v.y; c.r[4 * i + 2] = v.z; c.r[4 * i + 3] = v.w; }
        const uint2 v = lds64(a + 64);
        c.r[16] = v.x; c.r[17] = v.y;
    }
    if (sel == 0u) {
#pragma unroll
        for (int i = 0; i < 6; i++) sts128(ka + i * 16, c.q2[i >> 1][i & 1][0], c.q2[i >> 1][i & 1][1], c.q2[i >> 1][i & 1][2], c.q2[i >> 1][i & 1][3]);
#pragma unroll
        for (int i = 0; i < 2; i++) sts128(ka + i * 16, c.q3[i][0], c.q3[i][1], c.q3[i][2], c.q3[i][3]);
#pragma unroll
        for (int i = 1; i < 4; i++) sts64(ka + i * 16, acc[8 * i], acc[8 * i + 1]);
    }
    conv_rename(acc);
}
#define SPACE 100
#define SPN 3
#define O4 4
#define GATE 2
#define HAND 2
#define GA 6
#define GB 4
template <int TA, int TB, int IA, class FG>
__device__ __forceinline__ void conv_tail(uint32_t (&acc)[32], const uint32_t (&a)[8][4], uint32_t sb, unsigned char* gy0, int warp, size_t ycopy, FG fg) {
    const int wg = warp >> 2, wq = warp & 3, ord = TA == 0 && TB == 16 ? 3 - wg + (3 - wg >= O4) : O4;
    const uint32_t ub = sb + SM_U + wg * USLOT_B + UPAD * 16, turn = sb + SM_MISC + 376 + ord * 8, sfs = sb + SM_MISC + 256 + wg * 8;
    const uint32_t du = wg * (USLOT_B / 16) + (SM_U / 16 + UPAD + TA * 8);
    uint32_t ud[8], fs;
    auto skip = [&]() {
        const int lane = lane_v();
        const uint32_t ua = ub + ((lane >> 3) & 1) * ULO_B + (8 * wq + (lane & 7)) * 16 + (lane >> 4) * 512;
        if (IA == 0) ldsm_x4_t(ud[0], ud[1], ud[2], ud[3], ua);
        if (TB == 16) ldsm_x4_t(ud[4], ud[5], ud[6], ud[7], ua + 1024);
        const uint2 fd = lds64(sfs);
        fs = fd.x;
        const float dsk = __uint_as_float(fd.y);
#pragma unroll
        for (int i = 2 * IA; i < TB / 2; i++) ud[i] = pack_bf16(h_lo(ud[i]) * dsk, h_hi(ud[i]) * dsk);
    };
    conv_rename<2 * TA, 2 * TB>(acc);
    if (__builtin_expect(ord != 0, 0)) {
        skip();
        mbar_wait(turn);
    } else {
        bar_sync(0, NWRK);
    }
    if (O4 < 4 || (TA == 0 && TB == 16)) asm volatile("{\n.reg .pred p;\nelect.sync _|p, 0xffffffff;\n@p mbarrier.arrive.shared::cta.b64 _, [%0];\n}\n" ::"r"(turn + 48) : "memory");
    fg(IC<8>());
    wg_fence();
#pragma unroll
    for (int m = 7; m >= 0; m--) {
        wg_h<TA, TB - TA>(acc, a[m], smem_desc(sb, du - m, ULO_B));
        if (m == GA || m == GB || m == HAND) wg_commit();
        if (m == GB) asm volatile("wgmma.wait_group.sync.aligned 1;\n" ::: "memory");
    }
    wg_commit();
    if (O4 < 4 || (TA == 0 && TB == 16)) {
        asm volatile("wgmma.wait_group.sync.aligned 1;\n" ::: "memory");
        asm volatile("{\n.reg .pred p;\nelect.sync _|p, 0xffffffff;\n@p mbarrier.arrive.shared::cta.b64 _, [%0];\n}\n" ::"r"(turn + 8) : "memory");
    }
    __syncwarp();
    fg(IC<3>());
    if (!ord) skip();
    fg(IC<4>());
    const int lane = lane_v();
    const uint32_t lp = sb + SM_PL + (ord >= 3 ? ord - 3 : ord) * PL_B + lane * 8;
    unsigned char* gy = gy0 + ((4 * wq + (lane & 3)) * DM + (TA == 0 && TB == 16 ? 4 * blockIdx.x + wg : 512 + (blockIdx.x >> 1))) * 64 + (lane >> 2) * 8;
    const uint32_t st = lp + (wq * 12 - ((wq * (wq - 1)) >> 1)) * 256;
    uint32_t ld[3];
#pragma unroll
    for (int s = 1; s < 4; s++) {
        const int w = (wq - s) & 3;
        ld[s - 1] = lp + (w * 12 - ((w * (w - 1)) >> 1) + s - 1 - (wq < s ? 3 : 0)) * 256;
    }
    const uint32_t one = 1u + (warp >> 8);
    if (one == 0u) stg64(gy, ld[0], ld[1]);
    if (ord >= 3) bar_sync(9 + ord, 256);
    wg_wait0();
    fg(IC<6>());
#pragma unroll
    for (int j = TA; j < TB; j++)
        if ((j & 3) && j + 3 >= 4 * IA && (j + 3 < TB || j + wq < TB)) sts64(st + (j - 1 - (j >> 2)) * 256, acc[2 * j], acc[2 * j + 1]);
    bar_sync(1 + wg, 128);
    fg(IC<7>());
    uint2 v[4][3];
#pragma unroll
    for (int i = IA; i < TB / 4; i++)
#pragma unroll
        for (int s = 0; s < 3; s++) {
            if (i == 0) { v[i][s] = make_uint2(0u, 0u); if (wq > s) v[i][s] = lds64(ld[s]); }
            else v[i][s] = lds64(ld[s] + i * 768);
        }
    fg(IC<5>());
#pragma unroll
    for (int i = IA; i < TB / 4; i++) {
        const uint32_t x0 = hadd2(v[i][0].x, acc[8 * i]), x1 = hadd2(v[i][1].x, v[i][2].x), y0 = hadd2(v[i][0].y, acc[8 * i + 1]), y1 = hadd2(v[i][1].y, v[i][2].y);
        const uint32_t lo = pack_bf16(h_lo(x0) + h_lo(x1), h_hi(x0) + h_hi(x1)), hi = pack_bf16(h_lo(y0) + h_lo(y1), h_hi(y0) + h_hi(y1));
        ud[2 * i] = max(hfma2_bf(lo, fs, ud[2 * i]), one); ud[2 * i + 1] = hfma2_bf(hi, fs, ud[2 * i + 1]);
    }
    if (SPACE && TA == 0 && TB == 16 && ord < SPN) {
#pragma unroll
        for (int i = 0; i < 4; i++) {
            stg64(gy + i * 16 * DM * 64, ud[2 * i], ud[2 * i + 1]);
            if (i < 3) { const unsigned c0 = clock32(); while (clock32() - c0 < SPACE) {} }
        }
    } else {
#pragma unroll
        for (int i = IA; i < TB / 4; i++) stg64(gy + i * 16 * DM * 64, ud[2 * i], ud[2 * i + 1]);
    }
    if (ord < 2) bar_arrive(12 + ord, 256);
}
template <int M0, int M1>
__device__ __forceinline__ void conv_frags(uint32_t (&a)[8][4], const uint32_t (&r)[18], uint32_t sel, uint32_t dep, int warp) {
    const uint32_t s = prmt_v(sel, dep, 0x3210u + (warp >> 8)), sw = s ^ 0x4444u;
#pragma unroll
    for (int m = M0; m < M1; m++) {
        a[m][0] = prmt_v(r[2 * m + 1], r[2 * m + 2], s); a[m][1] = prmt_v(r[2 * m + 2], r[2 * m + 3], s);
        a[m][2] = prmt_v(r[2 * m + 1], r[2 * m], sw); a[m][3] = prmt_v(r[2 * m + 2], r[2 * m + 1], sw);
    }
}
template <class FG>
__device__ __forceinline__ void conv_main(const Conv& c, uint32_t (&acc)[32], uint32_t sb, uint32_t sel, unsigned char* gy, int warp, size_t ycopy, FG fg) {
    const uint32_t kw = (warp >> 2) * (KW_B / 16) + SM_KW / 16;
    const uint64_t d2 = smem_desc(sb, kw + KW_T2 / 16, KW_KH), d2b = smem_desc(sb, kw + KW_T2 / 16 + 1, KW_KH), d3 = smem_desc(sb, kw + KW_T3 / 16, 16), d3b = smem_desc(sb, kw + KW_T3 / 16 + 32, 16);
    uint32_t a[8][4];
    {
        const int ord = warp < 16 ? 3 - (warp >> 2) + (3 - (warp >> 2) >= O4) : O4;
        if (__builtin_expect(ord >= GATE, 0)) {
            fg(IC<1>());
            mbar_wait(sb + SM_MISC + 376 + 48 + (ord - GATE) * 8);
        }
    }
    wg_fence();
    wg_h<12, 4>(acc, c.q3[0], d3b); wg_h<8, 4>(acc, c.q3[0], d3); wg_h<4, 4>(acc, c.q2[0][0], d2b);
    wg_h<12, 4>(acc, c.q3[1], d3); wg_h<8, 4>(acc, c.q2[1][0], d2b);
    wg_h<12, 4>(acc, c.q2[2][0], d2b); wg_h<4, 4>(acc, c.q2[0][1], d2); wg_h<8, 4>(acc, c.q2[1][1], d2);
    wg_h<12, 4>(acc, c.q2[2][1], d2);
    wg_commit(); __syncwarp();
    fg(IC<0>());
    wg_wait0();
    conv_frags<0, 8>(a, c.r, sel, acc[16], warp);
    fg(IC<2>());
    if (warp >= 16) {
        if (blockIdx.x & 1) conv_tail<4, 16, 2>(acc, a, sb, gy, warp, ycopy, fg);
        else conv_tail<0, 8, 0>(acc, a, sb, gy, warp, ycopy, fg);
    } else {
        conv_tail<0, 16, 0>(acc, a, sb, gy, warp, ycopy, fg);
    }
}
#define CONV_LT6 const int dd = (lane >> 3) + (lane & 4) - (lane & 3); \
        const uint4 lt6 = make_uint4(prmt_v((dd & 3) * 288, 0u, idn), prmt_v(0x3254u + (dd >> 2) * 0x2222u, 0u, idn), \
            prmt_v(UPAD * 16 + (lane & 7) * 16 + ((lane >> 3) & 1) * (16 - ULO_B) + ULO_B - 32 + (lane & 16), 0u, idn), prmt_v(UPAD * 16 + (lane & 7) * 16 + ((lane >> 3) & 1) * ULO_B - 16 + (lane & 16), 0u, idn));
#define CONV_PRE \
        CONV_LT6 \
        const uint32_t ka = kw + lt6.x, sel = lt6.y, ks = kw + lt7.x; \
        const uint32_t ca0 = sb + SM_U + wg * USLOT_B + (warp & 3) * 128 + lt6.z, ca1 = sb + SM_U + wg * USLOT_B + (warp & 3) * 128 + lt6.w; \
        uint4 bd[3]; \
        band_quads(bd, lt7.w, (lane & 4) ? lt7.w >> 4 : lt7.w << 4);
#define CONV_PRE2 ConvPre ce_; conv_pre(ce_, ka, ks, sel);
#define CONV_BODY \
        Conv c; \
        uint32_t acc[32]; \
        conv_sums(c, acc, ce_, ca0, ca1, bd, ka, sel, warp & 3, lane & 4);
#define WS a_b_0_1_2_34_x__y567____c____de_r_
#define WS_STR2(x) #x
#define WS_STR(x) WS_STR2(x)
__device__ constexpr char wunit(int pt, int k) {
    constexpr char t[] = WS_STR(WS);
    int i = 0;
    for (; pt > 0 && t[i]; i++) pt -= t[i] == '_';
    for (; k > 0 && t[i] && t[i] != '_'; i++) k--;
    return t[i] == '_' ? 0 : t[i];
}
__device__ constexpr bool wsched_ok() {
    int seen = 0;
    for (int p = 0; p < 21; p++)
        for (int k = 0; wunit(p, k); k++) {
            const char c = wunit(p, k);
            const int bit = 1 << (c == 'r' ? 13 : c >= 'x' ? c - 'x' + 14 : c >= 'a' ? c - 'a' + 8 : c - '0');
            if ((seen & bit) || k >= (p < 16 ? 4 : 2) || (p < 5 && c >= '4' && c <= '7') || (p < 6 && (c == 'c' || c == 'd')) || (p < 16 && c == 'e')) return false;
            seen |= bit;
        }
    return seen == 0xffff;
}
struct WMaps { CUtensorMap g, u, gr, ur, d, dr; };
static_assert(GATE <= 2 && O4 >= 2, "resets");
static_assert(wsched_ok(), "weight schedule");
template <int PT, int K>
__device__ __forceinline__ void weight_units(uint32_t sb, const WMaps& m, int w) {
    constexpr char U = wunit(PT, K);
    if constexpr (U != 0) {
        if (w == K && elect_one()) {
            if (PT == 8) DELAY(K * WSP + WS0);
            const int P = blockIdx.x >> 1, odd = blockIdx.x & 1;
            constexpr int bar = SM_MISC + (U == 'e' ? 352 : U >= 'a' && U <= 'r' ? 336 : 328);
            if constexpr (U == 'e') { if (!odd) tma_2d(sb + SM_WD + 4 * 8192, &m.d, 256, 64 * P, sb + bar); }
            else if constexpr (U == 'r') tma_3d(sb + SM_WD + 40960, &m.dr, 0, 4096 + 8 * P, 5 * odd, sb + bar);
            else if constexpr (U >= 'x') tma_3d(sb + SM_WR + (U - 'x') * 4608, U == 'x' ? &m.gr : &m.ur, 4096 + 8 * P, 0, 2 * odd, sb + bar);
            else if constexpr (U >= 'a') tma_2d(sb + SM_WD + (U - 'a') * 8192, &m.d, 320 * odd + 64 * (U - 'a'), 64 * P, sb + bar);
            else tma_2d(sb + (U < '4' ? SM_WG : SM_WU) + (U & 3) * 9216, U < '4' ? &m.g : &m.u, 64 * P, 288 * odd + (U & 3) * 72, sb + bar);
        }
        weight_units<PT, K + 1>(sb, m, w);
    }
}
#define WPOINT(i, w) do { weight_units<i, 0>(sb, wm, w); } while (0)

__global__ void __launch_bounds__(NTHR, 1) __cluster_dims__(2, 1, 1)
fused_kernel(const Params p, const __grid_constant__ WMaps wm, const __grid_constant__ CUtensorMap tm_x,
             const __grid_constant__ CUtensorMap tm_y, const __grid_constant__ CUtensorMap tm_z) {
    extern __shared__ __align__(1024) unsigned char smem[];
    const uint32_t sb = smem_u32(smem);
    const int tid = threadIdx.x, warp = __shfl_sync(0xffffffffu, tid >> 5, 0), lane = tid & 31;
    const int b = blockIdx.x, P = b >> 1, odd = b & 1;
    const int g = lane >> 2, t = lane & 3;
    const int wg = warp >> 2, t128 = tid & 127;
    const uint32_t s_stat = sb + SM_MISC;
    const uint32_t s_key = sb + SM_MISC + 128;
    const uint32_t s_wm = sb + SM_MISC + 256;
    const uint32_t s_k16 = sb + SM_MISC + 192;
    const uint32_t s_fs = sb + SM_MISC + 256;
    const uint32_t s_cnt = sb + SM_MISC + 320;
    const uint32_t bar_w = sb + SM_MISC + 328, bar_d = bar_w + 8, bar_g = bar_w + 16, bar_r = bar_w + 32, bar_h = bar_w + 40, bar_x = bar_w + 48;
    STAMP(0);

    const unsigned tk0 = clock32();
    const bool lnw = (unsigned)(warp - 10) < 9u;
    const unsigned pm = tid + (tid < 512 ? 512 * b : 65024 + 128 * P), pq = (pm & ~127u) + 4 * lane;
    const uint32_t pl = ldg16(p.lar + pm), ldt = ldg16(p.ldt + (pm >> 7));
    const uint32_t pa2 = ldg16(p.aim + pm), pc = ldg16(p.cre + pm), pi = ldg16(p.cim + pm);
    const uint2 call_re = ldg64(p.cre + pq), call_im = ldg64(p.cim + pq);
    const uint32_t dskl = ldg16(p.dsk + (pm >> 7));
    const uint32_t ep = ld_poll32(p.s->hint + (b & 7) * 32 + 1 + (lane >> 5));
    if ((unsigned)(tid - 320) < 288u) {
        const bf16* xp = p.x + (unsigned)((32 * P + 2 * odd + TOKEN_OF(g)) * DM + ((tid - 320) & ~31) + 8 * t);
        const uint32_t xt = sb + SM_XT + ((tid - 320) & ~31) * 32 + lane * 16;
        asm volatile("cp.async.cg.shared.global [%0], [%1], 16;\ncp.async.cg.shared.global [%0 + 512], [%1 + 9216], 16;\n"
                     "cp.async.cg.shared.global [%0 + 9216], [%1 + 576], 16;\ncp.async.cg.shared.global [%0 + 9728], [%1 + 9792], 16;\n" ::"r"(xt), "l"(xp) : "memory");
    }
    uint32_t* const std_ = p.s->st + ((lane & 12) * 128 + odd * 256 + 4 * P + 2 * (lane & 1) + ((lane >> 1) & 1)) * 2;
    unsigned char* const ud = reinterpret_cast<unsigned char*>(p.s->uT) + (32 * (warp - UW) + 8 * (g >> 1) + (g & 1)) * 4096 + b * 32 + t * 8;
    if (warp == 0) {
        if (lane == 0) {
            mbar_init(bar_x, 1); mbar_init(bar_w, 1); mbar_init(bar_d, 1); mbar_init(bar_d + 16, 1); mbar_init(bar_g, 1); mbar_init(bar_h, 3); mbar_init(bar_r, 1);
            #pragma unroll
            for (int i = 1; i < 11; i++) mbar_init(bar_x + 8 * i, 4);
            asm volatile("fence.mbarrier_init.release.cluster;\n" ::: "memory");
            mbar_expect(bar_x, 16384); mbar_expect(bar_r, 8192);
            mbar_expect(bar_w, 2 * 41472); mbar_expect(bar_d, 32768 + 5120); mbar_expect(bar_d + 16, 8192); mbar_expect(bar_g, 9 * 512);
        }
        __syncwarp();
        bar_arrive(0, NWRK);
    }
    if (warp == 0 && elect_one()) tma_3d(sb + SM_XC, &tm_x, 8 * P, 0, 8 * odd, bar_x);
    asm volatile("barrier.cluster.arrive.relaxed.aligned;\n" ::: "memory");
    const uint32_t kw = sb + SM_KW + wg * KW_B;
    if (t128 < 2 * UPAD) sts128(sb + SM_U + wg * USLOT_B + (t128 & 1) * ULO_B + (t128 >> 1) * 16, 0u, 0u, 0u, 0u);
    sts128(kw + t128 * 16, 0u, 0u, 0u, 0u);
    if (t128 < KW_B / 16 - 128) sts128(kw + 2048 + t128 * 16, 0u, 0u, 0u, 0u);
    if (tid < 128) {
#pragma unroll
        for (int i = 0; i < 4; i++) sts128(sb + SM_ZERO + i * 2048 + tid * 16, 0u, 0u, 0u, 0u);
    }
    if (warp != 0) bar_sync(0, NWRK);
    STAMP(1);
    if (warp == 19 || warp == UW || warp == UW + 1) {
        if (warp == 19) {
            if (lane < 16) stg64(std_, 0u, 0u);
            if (lane < 9) asm volatile("prefetch.global.L2 [%0];\n" ::"l"(p.wr + lane * 64));
        } else {
#pragma unroll
            for (int k = 0; k < 4; k++) stg64(ud + k * 8192, 0u, 0u);
        }
    }
    uint32_t X[2][8];
    auto partial = [&]() {
        const uint32_t xt = sb + SM_XT + (warp - 10) * 1024 + lane * 16;
        asm volatile("cp.async.wait_all;\n" ::: "memory");
        STAMP(23);
        const uint4 a = lds128(xt), c = lds128(xt + 512), d = lds128(xt + 9216), e = lds128(xt + 9728);
        X[0][0] = a.x; X[0][1] = a.y; X[0][2] = a.z; X[0][3] = a.w; X[0][4] = d.x; X[0][5] = d.y; X[0][6] = d.z; X[0][7] = d.w;
        X[1][0] = c.x; X[1][1] = c.y; X[1][2] = c.z; X[1][3] = c.w; X[1][4] = e.x; X[1][5] = e.y; X[1][6] = e.z; X[1][7] = e.w;
        const uint32_t one[8] = {0x3f803f80u, 0x3f803f80u, 0x3f803f80u, 0x3f803f80u, 0x3f803f80u, 0x3f803f80u, 0x3f803f80u, 0x3f803f80u};
        ln_partial<8>(X, one, sb + SM_LNP, warp - 10, g, t);
        bar_arrive(6, 320);
    };
    auto finish = [&]() {
        bar_sync(6, 320);
        float mb, rc;
        ln_finish<9>(sb + SM_LNP, lane, mb, rc);
        const float rh = rbf(rc);
        const uint32_t s0 = (__float_as_uint(mb) >> 16) | (((ep & 0x7fffu) + 1u) << 16), s1 = pack_bf16(rh, rc - rh);
        if (lane < 16) { stg64(std_, s0, s1); sts64(s_stat + lane * 8, s0, s1); }
        if (lane == 16) sts32(s_cnt + 4, ep);
        bar_arrive(7, 352);
        STAMP(28);
    };
    auto upub = [&]() {
        const uint32_t utag = ((ep & 3u) + 1u) * 0x10001u;
        uint32_t U[2][4];
#pragma unroll
        for (int hf = 0; hf < 2; hf++) {
            const uint2 st = lds64(s_stat + (g + 8 * hf) * 8);
            const uint4 xv = lds128(sb + SM_XT + (16 + warp - UW) * 1024 + hf * 512 + lane * 16);
            const uint32_t xs[4] = {xv.x, xv.y, xv.z, xv.w};
#pragma unroll
            for (int k = 0; k < 4; k++) {
                const uint32_t u = ln_apply(xs[k], st);
                U[hf][k] = movm((pack_f16_rz(bf_lo(u), __uint_as_float(u)) & 0xfff8fff8u) | utag);
            }
        }
#pragma unroll
        for (int k = 0; k < 4; k++) stg64(ud + k * 8192, U[0][k], U[1][k]);
    };
    const uint32_t tb = table_buf(sb, warp);
    const float dt = rbf(expf(bf_lo(ldt)));
    KGen kg;
    kgen_setup(kg, pl | (pa2 << 16), dt);
    kgen_rows(kg, tb, lane);
    if (wg == 0) fence_async();
    if (lnw) {
        partial();
        kg.z128.x = __uint_as_float(prmt_v(__float_as_uint(kg.z128.x), X[0][0], 0x3210u + (warp >> 8)));
        kg.z1.x = __uint_as_float(prmt_v(__float_as_uint(kg.z1.x), X[0][0], 0x3210u + (warp >> 8)));
    }
    STAMP(2);
    WPOINT(0, warp - 4);
    const int ce = c_exponent(call_re, call_im);
    if (t128 == 0) sts64(s_fs + wg * 8, (uint32_t)min(max(ce + (int)(__float_as_uint(dt) >> 23) - 116, 0), 254) * 0x800080u, dskl << 16);
    kgen_chain(kg, pc | (pi << 16), __uint_as_float(((uint32_t)(244 - ce) << 23) | (__float_as_uint(dt) & 0x7fffffu)));
    STAMP(3);
    WPOINT(1, warp - 6);
    kgen_cols(kg, tb, lane);
    if (warp == 19) finish();
    if (warp < 10) bar_sync(7, 352);
    if (warp == UW || warp == UW + 1) upub();
    STAMP(4);
    WPOINT(2, warp - 8);
    const uint4* usrc = wg < 4 ? reinterpret_cast<const uint4*>(p.s->st) + odd * 512 + (lane & 1) * 128 + 16 * (warp & 7) + (lane >> 1)
                               : reinterpret_cast<const uint4*>(p.s->uT) + P * 256 + 2 * t128;
    const int ustep = wg < 4 ? 256 : 1;
    uint4 uv0, uv1;
    kgen_mma(kg, tb, lane);
    STAMP(26);
    WPOINT(3, warp - 5);
    const uint32_t idn = 0x3210u + (warp >> 8);
    uint4 lt7 = make_uint4(prmt_v(KW_T2 + ((lane >> 3) & 1) * KW_KH + (33 + (lane & 7)) * 16 - (lane & 16), 0u, idn), t * 288 + g * 8 + 8, (lane & 1) * 4096 + (lane >> 1) * 16,
                                 prmt_v(8u << ((lane >> 3) + (lane & 4)) >> (lane & 3), 0u, idn));
    asm volatile("barrier.cluster.wait.acquire.aligned;\n" ::: "memory");
    const bool pe = (int)(clock32() - tk0) >= (wg < 4 ? TP0 : TP4);
    if (pe) { uv0 = ld_poll(usrc); uv1 = ld_poll(usrc + ustep); }
    bar_sync(1 + wg, 128);
    kgen_combine(sb, warp, lane, kw, lt7.y);
    if (warp < 3 || warp > 6) bar_arrive(14, NWRK);
    STAMP(5);
    WPOINT(4, warp - 7);
    if (!pe) {
        while ((int)(clock32() - tk0) < (wg < 4 ? TP0 : TP4)) {}
        uv0 = ld_poll(usrc); uv1 = ld_poll(usrc + ustep);
    }
    if (wg < 4) {
        mbar_wait(bar_x);
        const bool far = warp < 8;
        const uint32_t xa = sb + SM_XC + (warp & 7) * 256 + (odd ^ far) * 8 + lt7.z;
        uint2 xv[4] = {lds64(xa), lds64(xa + 8192), lds64(xa + 2048), lds64(xa + 10240)};
        const uint32_t tag = ((ep & 0x7fffu) + 1u) << 16;
        int it = 0;
        while (true) {
            const bool bad = (((uv0.x ^ tag) | (uv0.z ^ tag)) | ((uv1.x ^ tag) | (uv1.z ^ tag))) >> 16;
            if (!__any_sync(0xffffffffu, bad)) break;
            if (++it > SPIN_LIMIT) TRAP();
            if (bad) { uv0 = ld_poll(usrc); uv1 = ld_poll(usrc + 256); }
        }
        STAMP(6);
        DBG(wg, it);
        const uint2 st[4] = {make_uint2(uv0.x, uv0.y), make_uint2(uv0.z, uv0.w), make_uint2(uv1.x, uv1.y), make_uint2(uv1.z, uv1.w)};
#pragma unroll
        for (int i = 0; i < 4; i++) {
            xv[i].x = ln_apply(xv[i].x, st[i]);
            xv[i].y = ln_apply(xv[i].y, st[i]);
        }
        const uint32_t ub = sb + SM_U + UPAD * 16 + odd * ULO_B + (warp & 7) * 256 + lane * 8;
        const uint32_t w[4][2] = {{pack_f16(bf_lo(xv[0].x), bf_lo(xv[1].x)), pack_f16(bf_lo(xv[2].x), bf_lo(xv[3].x))}, {HI2(xv[0].x, xv[1].x), HI2(xv[2].x, xv[3].x)},
                                  {pack_f16(bf_lo(xv[0].y), bf_lo(xv[1].y)), pack_f16(bf_lo(xv[2].y), bf_lo(xv[3].y))}, {HI2(xv[0].y, xv[1].y), HI2(xv[2].y, xv[3].y)}};
#pragma unroll
        for (int i = 0; i < 4; i++) {
            if (far) asm volatile("st.async.shared::cluster.mbarrier::complete_tx::bytes.v2.b32 [%0], {%1,%2}, [%3];\n" ::"r"((ub ^ 0x1000000u) + i * USLOT_B), "r"(w[i][0]), "r"(w[i][1]), "r"(bar_r ^ 0x1000000u) : "memory");
            else sts64(ub + i * USLOT_B, w[i][0], w[i][1]);
        }
    } else {
        const uint32_t utag = ((ep & 3u) + 1u) * 0x10001u;
        int it = 0;
        while (true) {
            const bool bad = (((uv0.x ^ utag) | (uv0.y ^ utag) | (uv0.z ^ utag) | (uv0.w ^ utag)) | ((uv1.x ^ utag) | (uv1.y ^ utag) | (uv1.z ^ utag) | (uv1.w ^ utag))) & 0x70007u;
            if (!__any_sync(0xffffffffu, bad)) break;
            if (++it > SPIN_LIMIT) TRAP();
            if (bad) { uv0 = ld_poll(usrc); uv1 = ld_poll(usrc + 1); }
        }
        STAMP(6);
        DBG(4, it);
        const uint32_t ub = sb + SM_U + UPAD * 16 + 4 * USLOT_B + (t128 >> 1) * 32 + (t128 & 1) * 8;
        sts64(ub, prmt(uv0.x, uv0.z, 0x5410u) ^ utag, prmt(uv1.x, uv1.z, 0x5410u) ^ utag);
        sts64(ub + 16, prmt(uv0.x, uv0.z, 0x7632u) ^ utag, prmt(uv1.x, uv1.z, 0x7632u) ^ utag);
        sts64(ub + ULO_B, prmt(uv0.y, uv0.w, 0x5410u) ^ utag, prmt(uv1.y, uv1.w, 0x5410u) ^ utag);
        sts64(ub + ULO_B + 16, prmt(uv0.y, uv0.w, 0x7632u) ^ utag, prmt(uv1.y, uv1.w, 0x7632u) ^ utag);
    }
    lt7.w = prmt_v(lt7.w, uv0.x, idn);
    CONV_PRE
    if (warp < 3 && elect_one()) tma_st_3d(warp < 2 ? &tm_y : &tm_z, sb + SM_ZERO, warp < 2 ? 128 * b : 32 * (512 + P), 0, 2 * (warp < 2 ? warp : odd));
    if (warp >= 3 && warp <= 6) {
        bar_sync(14, NWRK);
        WPOINT(5, warp - 3);
    }
    bar_sync(1 + wg, 128);
    CONV_PRE2
    mbar_wait(bar_r);
    fence_async();
    bar_sync(0, NWRK);
    STAMP(7);
    uint32_t hv0 = 0;
    {
        WPOINT(6, 19 - warp);
        CONV_BODY
        WPOINT(7, 19 - warp);
        if (wg != 3) bar_arrive(0, NWRK);
        STAMP(8);
        size_t ycopy = 0;
        auto hook = [&](auto gi) {
                     constexpr int G = decltype(gi)::value;
                     if (G == 4 && warp == HINTW) hv0 = ld_poll32(p.s->hint + (lane_v() & 7) * 32);
                     if (G == 4) mbar_wait(bar_h);
                     if (G == 2) WPOINT(9, warp - 16);
                     if (G == 3) { WPOINT(10, warp - 12); WPOINT(12, warp - 8); WPOINT(14, warp - 4); }
                     if (G == 5) { WPOINT(11, warp - 13); WPOINT(13, warp - 9); WPOINT(15, warp - 5); }
                     if (G == 1 && warp >= 17 && elect_one())
                         bulk_s2g(warp == 17 ? p.s->part + b * (PBYTES / 4) : warp == 18 ? p.s->rows + b * 1152 : p.s->sc + b * 64, sb + SM_ZERO, warp == 17 ? PBYTES : warp == 18 ? 4608 : 160);
                     if (G == 4 && warp >= 17 && elect_one()) {
                         asm volatile("cp.async.bulk.wait_group 0;\n" ::: "memory");
                         hint_arrive(p.s->hint, 2, b & 7);
                     }
                     if (G == 1 && warp < 3) {
                         if (elect_one()) {
                             asm volatile("cp.async.bulk.wait_group 0;\n" ::: "memory");
                             mbar_arrive(bar_h);
                             hint_arrive(p.s->hint, 0, b & 7);
                         }
                         __syncwarp();
                         STAMP(17);
                     }
                     if (G == 1) WPOINT(8, warp - 16);
                 };
        conv_main(c, acc, sb, sel, reinterpret_cast<unsigned char*>(p.s->y), warp, ycopy, hook);
        STAMP(10);
    }
    {
    const int warp = warp_v(), lane = lane_v(), tid = 32 * warp + lane, g = lane >> 2, t = lane & 3;
    if (warp == HINTW) {
        const uint32_t target = (lds32(s_cnt + 4) + 1u) * 48u;
        if (__any_sync(0xffffffffu, (int)(hv0 - target) < 0)) hint_wait(p.s->hint, 0, target);
    }
    const unsigned char* ys = reinterpret_cast<const unsigned char*>(p.s->y) + ((size_t)P * DM + 32 * warp + 8 * (g >> 1) + (g & 1)) * 64 + odd * 32 + t * 8;
    STAMP(27);
    bar_sync(0, NWRK);
    STAMP(11);
    const uint32_t zr = warp >> 8;
    auto late_rows = [&](auto pub) {
        const uint32_t k = lds32(s_key + (lane & 7) * 4), ep = lds32(s_cnt + 4);
        const bool late = k & 256u, mine = late && ((k & 255u) >> 1) == (uint32_t)b;
        uint32_t todo = __ballot_sync(0xffffffffu, mine) & 0xffu;
        if (todo) {
#pragma unroll 1
            while (todo) {
                const int s = __ffs(todo) - 1, row = (__shfl_sync(0xffffffffu, k, s) >> 9) & 15;
                todo &= todo - 1;
                if ((row & 7) == g) pub(row & 8, 2 * NCTA + s);
            }
            __threadfence();
            bar_sync(0, NWRK);
            if (tid < NSEL && mine) *reinterpret_cast<volatile unsigned*>(p.s->flag + tid) = ep + 1u;
        }
        int it = 0;
        if (__any_sync(0xffffffffu, late)) {
            while (__any_sync(0xffffffffu, late && ld_poll32(p.s->flag + (lane & 7)) != ep + 1u)) { if (++it > SPIN_LIMIT) TRAP(); }
            __threadfence();
        }
        const int gs = tid / 36;
        const uint4* src = reinterpret_cast<const uint4*>(p.s->rows) + __shfl_sync(0xffffffffu, late ? 2 * NCTA + (lane & 7) : (k & 255u), gs & 7) * 144 + 36 * odd + (tid - gs * 36);
        if (tid < 288) {
            uint4 v0;
            do { v0 = ld_poll(src); if (++it > SPIN_LIMIT) TRAP(); } while (!v0.x);
            sts128(sb + SM_XS + gs * XS_PITCH + (tid - gs * 36) * 16, v0.x, v0.y, v0.z, v0.w);
        }
        __syncwarp();
    };
    if (warp >= 18) {
        uint32_t* const kp = pin(p.s->sc + 64 * b + 32 * (19 - warp), zr);
        const uint32_t kid = pin(0xc0000000u | ((lane & 15) << 9) | 2 * b, zr), ka = pin(s_k16 + (warp & 1) * 288 + (lane & 15) * 4, zr), kb = pin(s_k16 + (warp & 1) * 288 + (lane & 16) * 2, zr);
        const uint4* ksrc = pin(reinterpret_cast<const uint4*>(p.s->sc) + 8 * (19 - warp) + 16 * lane, zr);
        const uint4* rsrc = pin(reinterpret_cast<const uint4*>(p.s->rows) + 36 * odd + t, zr);
        uint32_t bits, early = 0;
        if (warp == 18) {
            weight_units<20, 0>(sb, wm, 0); weight_units<20, 1>(sb, wm, 1);
            bar_sync(8, 640);
            float mb, rc;
            ln_finish<18>(sb + SM_LNP, lane, mb, rc);
            if (lane < 16) stat_store(s_stat + lane * 8, mb, rc, 0u);
            bar_arrive(13, 608);
            bar_sync(10, 640);
            early = lds32(s_wm + (lane & 15) * 4);
            bits = pack_bf16(0.f, sum18(sb + SM_LNP + (32 + (lane & 15)) * 80));
        } else {
            float sw = 0.f;
#pragma unroll
            for (int i = 0; i < 9; i++) { const uint32_t w = reinterpret_cast<const uint32_t*>(p.wr)[32 * i + lane]; sw += bf_lo(w) + bf_hi(w); }
#pragma unroll
            for (int i = 16; i; i >>= 1) sw += __shfl_xor_sync(0xffffffffu, sw, i);
            early = __any_sync(0xffffffffu, (int)(ld_poll32(p.s->hint + (lane & 7) * 32 + 2 + zr * __float_as_int(sw)) - (lds32(s_cnt + 4) + 1u) * 48u) < 0);
            bar_sync(8, 640);
            const float v = sum18(sb + SM_LNP + lane * 80), hw = sum18(sb + SM_LNP + (48 + (lane & 15)) * 80);
            const float o = __shfl_xor_sync(0xffffffffu, v, 16), mean = (lane < 16 ? v : o) * (1.0f / 576.0f);
            const float var = fmaxf(fmaf(lane < 16 ? o : v, 1.0f / 576.0f, -(mean * mean)), 0.f);
            bits = __float_as_uint(fmaf(-rbf(mean), sw, hw) * rcp_approx(rbf(sqrt_approx(rbf(rbf(var) + 1e-5f)))));
        }
        {
            const uint32_t me = (((bits ^ ((uint32_t)((int)bits >> 31) & 0x7fffffffu)) >> 1) & 0x7fffe000u) ^ kid;
            sts32(ka, me);
            __syncwarp();
            const uint4 v = lds128(kb), w = lds128(kb + 16);
#define GT(x) ((me - (x)) >> 31)
            uint32_t rank = pin(GT(v.x) + GT(v.y) + GT(v.z), zr) + pin(GT(v.w) + GT(w.x) + GT(w.y), zr) + pin(GT(w.z) + GT(w.w), zr);
#undef GT
            rank += __shfl_xor_sync(0xffffffffu, rank, 16);
            const uint32_t sl = warp == 18 ? early : rank;
            stg32(kp + rank, me + (sl < 2 ? sl : 256u));
            if (warp == 19) {
                sts32(s_wm + (lane & 15) * 4, rank);
                if (early) hint_wait(p.s->hint, 2, (lds32(s_cnt + 4) + 1u) * 48u);
                bar_arrive(10, 640); bar_arrive(11, 608);
            }
        }
        bool slow;
        int it = 0;
        uint4 q[4];
        STAMP(13);
        DELAY(warp == 19 ? KDEL : KDEL2);
#pragma unroll
        for (int i = 0; i < 4; i++) q[i] = ld_poll(ksrc + 512 * i);
        while (true) {
            uint32_t a[4];
#pragma unroll
            for (int i = 0; i < 4; i++) a[i] = q[i].x & q[i].y & q[i].z & q[i].w;
            if (__all_sync(0xffffffffu, a[0] & a[1] & a[2] & a[3])) break;
#pragma unroll
            for (int i = 0; i < 4; i++)
                if (!a[i]) q[i] = ld_poll(ksrc + 512 * i);
            if (++it > SPIN_LIMIT) TRAP();
        }
        STAMP(16);
        if (warp == 18) {
            const uint32_t kt = sb + SM_KEYS;
#pragma unroll
            for (int i = 0; i < 4; i++) sts128(kt + i * 512 + lane * 16, q[i].x, q[i].y, q[i].z, q[i].w);
            bar_sync(15, 64);
            const uint32_t c = lds32(s_key + 32 + g * 4), e = lds32(kt + (c & 254u) * 8 + t * 4);
            const bool hit = ((e ^ c) & 0x1fffu) == 0u && !(c & 256u);
            if (hit) sts32(s_key + g * 4, e);
            const uint32_t lo = __reduce_min_sync(0xffffffffu, hit ? e : 0xffffffffu) | 0x1fffu;
#define GT(x) ((lo - (x)) >> 31)
            uint32_t n = hit ? 256u - GT(e) : 0u;
#pragma unroll
            for (int i = 0; i < 4; i++) n += pin(GT(q[i].x) + GT(q[i].y) + GT(q[i].z) + GT(q[i].w), zr) << 12;
#undef GT
            n = __reduce_add_sync(0xffffffffu, n);
            slow = (n >> 12) + (n & 4095u) != 2048u || (n & 4095u) <= 2040u;
            if (slow) {
                uint4 r[4];
                it = 0;
                while (true) {
#pragma unroll
                    for (int i = 0; i < 4; i++) r[i] = ld_poll(ksrc + 512 * i + 1);
                    if (__all_sync(0xffffffffu, all_nz(r[0]) && all_nz(r[1]) && all_nz(r[2]) && all_nz(r[3]))) break;
                    if (++it > SPIN_LIMIT) TRAP();
                }
                uint32_t m = 0u;
#pragma unroll 1
                for (int s = 0; s < 8; s++) {
                    uint32_t x = 0;
#pragma unroll
                    for (int i = 0; i < 4; i++) {
                        x = max(max(max(x, q[i].x - m), max(q[i].y - m, q[i].z - m)), q[i].w - m);
                        x = max(max(max(x, r[i].x - m), max(r[i].y - m, r[i].z - m)), r[i].w - m);
                    }
                    m += __reduce_max_sync(0xffffffffu, x);
                    if (lane == 0) sts32(s_key + s * 4, m);
                }
            }
            DBG(7, slow);
        } else {
            auto merge = [](const uint4& x, const uint4& y) {
                const uint32_t a = max(x.x, y.w), c = max(x.y, y.z), d = max(x.z, y.y), e = max(x.w, y.x);
                const uint32_t a2 = max(a, d), d2 = min(a, d), c2 = max(c, e), e2 = min(c, e);
                return make_uint4(max(a2, c2), min(a2, c2), max(d2, e2), min(d2, e2));
            };
            uint4 h = merge(merge(q[0], q[1]), merge(q[2], q[3]));
            uint4 v[9];
            uint32_t key = 0;
#pragma unroll
            for (int s = 0; s < 8; s++) {
                const uint32_t m = __reduce_max_sync(0xffffffffu, h.x);
                const bool w = h.x == m;
                h.x = w ? h.y : h.x; h.y = w ? h.z : h.y; h.z = w ? h.w : h.z; h.w = w ? 0u : h.w;
                if (g == s) key = m;
            }
            rsrc += (key & 255u) * 144;
#pragma unroll
            for (int j = 0; j < 9; j++) v[j] = ld_poll(rsrc + 4 * j);
            const uint32_t xsa = sb + SM_XS + g * XS_PITCH + t * 16;
            sts32(s_key + 32 + g * 4, key);
            sts32(xsa, 0u);
            bar_arrive(15, 64);
            bar_arrive(12, 608);
            STAMP(18);
#pragma unroll
            for (int j = 0; j < 9; j++) sts128(xsa + j * 64, v[j].x, v[j].y, v[j].z, v[j].w);
            slow = min(min(min(min(v[0].x, v[1].x), v[2].x), min(min(v[3].x, v[4].x), v[5].x)), min(min(v[6].x, v[7].x), v[8].x)) == 0u;
        }
        if (bar_or(0, NWRK, slow)) { late_rows([](bool, int) {}); bar_or(0, NWRK, false); }
        STAMP(19);
        const int fl = 16 * (b & 1) + ((tid >> 2) & 15), fc = 16 * (b >> 1) + (fl >> 2) + 8 * ((tid >> 1) & 1), fsl = 2 * (fl & 3) + (tid & 1);
        const uint32_t kk = lds32(s_key + fsl * 4);
        const uint32_t* fsrc = p.s->rows + ((kk & 256u) ? 2 * NCTA + fsl : (kk & 255u)) * DM + (fc >> 3) * 4;
        if (b < 72) {
            it = 0;
            uint4 u4, h4;
            do { u4 = ld_poll(fsrc); h4 = ld_poll(fsrc + 288); if (++it > SPIN_LIMIT) TRAP(); } while (!u4.x || !h4.x);
            const uint32_t uw = (fc & 4) ? ((fc & 2) ? u4.w : u4.z) : ((fc & 2) ? u4.y : u4.x), hw = (fc & 4) ? ((fc & 2) ? h4.w : h4.z) : ((fc & 2) ? h4.y : h4.x);
            const int row = (kk >> 9) & 15, ftok = 8 * (kk & 252u) + (kk & 2u) + TOKEN_OF(row & 7) + (row & 8);
            const unsigned k16 = (kk >> 15) & 0xffffu;
            const unsigned bits = (k16 & 0x8000u) ? (k16 & 0x7fffu) : (~k16 & 0xffffu);
            const float rs = 512.0f * rbf(__fdividef(1.0f, 1.0f + __expf(-__uint_as_float(bits << 16))));
            bf16* const op = p.out + (unsigned)(ftok * DM + fc);
            const float uv = (fc & 1) ? bf_hi(uw) : bf_lo(uw), hv = (fc & 1) ? bf_hi(hw) : bf_lo(hw);
            const uint32_t a = sb + SM_FIN + (tid - 576) * 80;
            sts128(a + 64, __float_as_uint(rs), __float_as_uint(uv), __float_as_uint(hv), (uint32_t)(size_t)op ^ (uint32_t)((size_t)op >> 32));
            bar_sync(14, 576);
            const uint4 p0 = lds128(a), p1 = lds128(a + 16), p2 = lds128(a + 32), p3 = lds128(a + 48);
#define F4(p) ((__uint_as_float(p.x) + __uint_as_float(p.y)) + (__uint_as_float(p.z) + __uint_as_float(p.w)))
            const float v0 = F4(p0), v1 = F4(p1), v2 = F4(p2), v3 = F4(p3);
#undef F4
            const float y3 = rbf(rbf((v0 + v1) + (v2 + v3)) * rs);
            asm volatile("st.global.u16 [%0], %1;\n" ::"l"(op), "h"((unsigned short)pack_bf16(hv + rbf(uv + y3), 0.f)) : "memory");
        }
        if (b == 0 && tid >= 632) *reinterpret_cast<volatile unsigned*>(p.s->hint + (tid & 7) * 32 + 1) = lds32(s_cnt + 4) + 1u;
    } else {
        uint32_t H[2][4], U2[2][4], WA[9][4], WD[18], WE[18];
        const int fkh = warp >= 9, fmt = warp - 9 * fkh;
        auto load_wa = [&](auto k0, auto k1) {
            if (k0.value >= k1.value) return;
            if (k0.value == 0) mbar_wait(bar_w);
            const int mi = lane >> 3, rr = lane & 7;
            const int row = fkh * 144 + rr + 8 * (mi >> 1);
            const uint32_t aad = sb + (fmt < 8 ? SM_WG + (mi & 1) * (SM_WU - SM_WG) + row * 128 + (fmt ^ rr) * 16 : SM_WR + (mi & 1) * 4608 + row * 16), ks = fmt < 8 ? 2048 : 256;
#pragma unroll
            for (int k = k0.value; k < k1.value; k++) ldsm_x4_t(WA[k][0], WA[k][1], WA[k][2], WA[k][3], aad + k * ks);
        };
        auto load_wd = [&](uint32_t (&WD)[18], int tile) {
            mbar_wait(bar_d);
            if (tile & 16) mbar_wait(bar_d + 16);
            const int mi = lane >> 3, rr = lane & 7;
            const uint32_t base = sb + SM_WD + rr * 128 + (((2 * tile + (mi & 1)) & 7) ^ rr) * 16;
#pragma unroll
            for (int k = 0; k < 4; k++) ldsm_x4_t(WD[4 * k], WD[4 * k + 1], WD[4 * k + 2], WD[4 * k + 3], base + (tile >> 2) * 8192 + (k * 16 + 8 * (mi >> 1)) * 128);
            ldsm_x2_t(WD[16], WD[17], base + 40960 + (tile >> 2) * 1024);
        };
        auto publish = [&](bool hi, int slot) {
            uint4* rowp = reinterpret_cast<uint4*>(p.s->rows) + (unsigned)(slot * 144 + warp * 4 + t);
            stg128(rowp, nzw(hi ? U2[1][0] : U2[0][0]), hi ? U2[1][1] : U2[0][1], hi ? U2[1][2] : U2[0][2], hi ? U2[1][3] : U2[0][3]);
            stg128(rowp + 72, nzw(hi ? H[1][0] : H[0][0]), hi ? H[1][1] : H[0][1], hi ? H[1][2] : H[0][2], hi ? H[1][3] : H[0][3]);
        };
        uint4 wr = make_uint4(0x3f803f80u, 0x3f803f80u, 0x3f803f80u, 0x3f803f80u);
        {
            uint2 yv[4];
#pragma unroll
            for (int k = 0; k < 4; k++) yv[k] = ld_poll64(ys + k * 128);
            if (g == 0) wr = ldg128(p.wr + 32 * warp + 8 * t);
            const uint4 x0 = lds128(sb + SM_XT + warp * 1024 + lane * 16), x1 = lds128(sb + SM_XT + warp * 1024 + 512 + lane * 16);
            load_wa(IC<0>(), IC<WA0>());
            int it = 0;
            while (!__all_sync(0xffffffffu, yv[0].x && yv[1].x && yv[2].x && yv[3].x)) {
#pragma unroll
                for (int k = 0; k < 4; k++) yv[k] = ld_poll64(ys + k * 128);
                if (++it > SPIN_LIMIT) TRAP();
            }
            STAMP(12);
            const uint32_t Z[2][4] = {{x0.x, x0.y, x0.z, x0.w}, {x1.x, x1.y, x1.z, x1.w}};
#pragma unroll
            for (int k = 0; k < 4; k++) {
                H[0][k] = hadd2_bf(Z[0][k], movm(yv[k].x));
                H[1][k] = hadd2_bf(Z[1][k], movm(yv[k].y));
            }
            const uint32_t bw[4] = {wr.x, wr.y, wr.z, wr.w};
            ln_partial<4>(H, bw, sb + SM_LNP, warp, g, t);
        }
        bar_arrive(8, 640);
        WPOINT(16, warp - 12);
        load_wa(IC<WA0>(), IC<WA1>());
        STAMP(13);
        bar_sync(13, 608);
        STAMP(14);
#pragma unroll
        for (int hf = 0; hf < 2; hf++) {
            const uint2 st = lds64(s_stat + (g + 8 * hf) * 8);
#pragma unroll
            for (int k = 0; k < 4; k++) U2[hf][k] = ln_apply(H[hf][k], st);
        }
        {
            float cs[4] = {0.f, 0.f, 0.f, 0.f}, ct[4] = {0.f, 0.f, 0.f, 0.f};
            mma_bf16(cs, U2[0][0], U2[1][0], U2[0][1], U2[1][1], wr.x, wr.y);
            mma_bf16(ct, U2[0][2], U2[1][2], U2[0][3], U2[1][3], wr.z, wr.w);
            if (t == 0) { stsf(sb + SM_LNP + ((32 + g) * 20 + warp) * 4, cs[0] + ct[0]); stsf(sb + SM_LNP + ((40 + g) * 20 + warp) * 4, cs[2] + ct[2]); }
            bar_arrive(10, 640);
        }
        load_wa(IC<WA1>(), IC<WA2>());
        bar_sync(11, 608);
        {
            const uint32_t rk[2] = {lds32(s_wm + g * 4), lds32(s_wm + 32 + g * 4)};
            uint32_t lo = min(rk[0], rk[1]), hi = max(rk[0], rk[1]);
#pragma unroll 1
            while (lo < 2) { publish(lo == rk[1], 2 * b + lo); lo = hi; hi = 16; }
        }
        load_wa(IC<WA2>(), IC<WA3>());
        load_wa(IC<WA3>(), IC<9>());
#pragma unroll
        for (int hf = 0; hf < 2; hf++)
            sts128(sb + SM_OUT + (g + 8 * hf) * OUT_PITCH + warp * 64 + t * 16,
                   hadd2_bf(H[hf][0], U2[hf][0]), hadd2_bf(H[hf][1], U2[hf][1]), hadd2_bf(H[hf][2], U2[hf][2]), hadd2_bf(H[hf][3], U2[hf][3]));
        fence_async();
        WPOINT(17, warp - 16);
        if ((WDAT == 0 || (WDAT == 2 && fkh)) && (warp < 16 || !odd)) load_wd(WD, warp);
        const uint32_t bad = pin(sb + SM_XS + (lane & 7) * XS_PITCH + (fkh * 144 + 8 * (lane >> 3)) * 2, zr), ex = pin(sb + SM_EX + warp * 512 + lane * 16, zr);
        uint32_t* pp = pin(p.s->part + ((size_t)(2 * (20 * odd + warp) + (lane >> 4)) * 64 + P) * 32 + (lane & 15) * 2, zr);
        bar_sync(12, 608);
        const bool routed = __any_sync(0xffffffffu, (lds32(s_key + 32 + (lane & 7) * 4) & 0x1efeu) == (uint32_t)((warp << 9) | 2 * b));
        auto store_row = [&]() { if (warp < 16 && elect_one()) bulk_s2g(p.out + (size_t)(32 * P + 2 * odd + TOKEN_OF(warp & 7) + (warp & 8)) * DM, sb + SM_OUT + warp * OUT_PITCH, DM * 2); };
        if (!routed) store_row();
        WPOINT(18, warp - 16);
        STAMP(15);
        bool again = zr;
#pragma unroll 1
        do {
            if (again) {
                if (routed) store_row();
                asm volatile("cp.async.bulk.wait_group 0;\n" ::: "memory");
                late_rows(publish);
            }
            again = bar_or(0, NWRK, false);
        } while (again);
        STAMP(19);
        float gp[4];
        {
            float c4[3][4];
#pragma unroll
            for (int i = 0; i < 3; i++)
#pragma unroll
                for (int j = 0; j < 4; j++) c4[i][j] = 0.f;
#pragma unroll
            for (int k = 0; k < 10; k += 2) {
                uint32_t b0, b1, b2, b3;
                ldsm_x4(b0, b1, b2, b3, bad + k * 32);
                mma_bf16(c4[k % 3], WA[k][0], WA[k][1], WA[k][2], WA[k][3], b0, b1);
                if (k < 8) mma_bf16(c4[(k + 1) % 3], WA[k + 1][0], WA[k + 1][1], WA[k + 1][2], WA[k + 1][3], b2, b3);
            }
#pragma unroll
            for (int j = 0; j < 4; j++) gp[j] = c4[0][j] + (c4[1][j] + c4[2][j]);
            if (warp >= 9) {
                sts128f(ex, gp);
                bar_arrive(6, 576);
            } else {
                bar_sync(6, 576);
                const uint4 o = lds128(ex + 4608);
                gp[0] += __uint_as_float(o.x); gp[1] += __uint_as_float(o.y); gp[2] += __uint_as_float(o.z); gp[3] += __uint_as_float(o.w);
                asm volatile("st.async.shared::cluster.mbarrier::complete_tx::bytes.v4.b32 [%0], {%1,%2,%3,%4}, [%5];\n"
                             ::"r"(ex ^ 0x1000000u), "r"(__float_as_uint(gp[0])), "r"(__float_as_uint(gp[1])), "r"(__float_as_uint(gp[2])), "r"(__float_as_uint(gp[3])), "r"(bar_g ^ 0x1000000u) : "memory");
                if (WDAT == 2) load_wd(WD, warp);
            }
            if (WDAT == 1 && (warp < 16 || !odd)) load_wd(WD, warp);
            if (warp >= 16 && !odd) load_wd(WE, warp + 2);
        }
        STAMP(20);
        if (warp < 9) {
            mbar_wait(bar_g);
            const uint4 u = lds128(ex);
            const uint32_t G = pack_bf16(gp[0] + __uint_as_float(u.x), gp[1] + __uint_as_float(u.y)), U = pack_bf16(gp[2] + __uint_as_float(u.z), gp[3] + __uint_as_float(u.w));
            const float G0 = bf_lo(G), G1 = bf_hi(G);
            sts32(sb + SM_GU + tid * 4, hmul2_bf(pack_bf16(G0 * rcp_approx(1.0f + ex2_approx(G0 * -1.4426950408889634f)), G1 * rcp_approx(1.0f + ex2_approx(G1 * -1.4426950408889634f))), U));
        }
        bar_sync(7, 576);
        STAMP(21);
        if (warp < 16 || !odd) {
            uint32_t gb[9];
            ldsm_x4_t(gb[0], gb[1], gb[2], gb[3], sb + SM_GU + lane * 16);
            ldsm_x4_t(gb[4], gb[5], gb[6], gb[7], sb + SM_GU + 512 + lane * 16);
            ldsm_x1_t(gb[8], sb + SM_GU + 1024 + (lane & 7) * 16);
            auto down = [&](const uint32_t (&W)[18], uint32_t* dst) {
                float c4[4] = {0.f, 0.f, 0.f, 0.f}, d4[4] = {0.f, 0.f, 0.f, 0.f}, e4[4] = {0.f, 0.f, 0.f, 0.f};
                mma_bf16(c4, W[0], W[1], W[2], W[3], gb[0], gb[1]);
                mma_bf16(d4, W[4], W[5], W[6], W[7], gb[2], gb[3]);
                mma_bf16(e4, W[8], W[9], W[10], W[11], gb[4], gb[5]);
                mma_bf16_k8(c4, W[16], W[17], gb[8]);
                mma_bf16(d4, W[12], W[13], W[14], W[15], gb[6], gb[7]);
                const float v0 = (c4[0] + e4[0]) + d4[0], v1 = (c4[1] + e4[1]) + d4[1], v2 = (c4[2] + e4[2]) + d4[2], v3 = (c4[3] + e4[3]) + d4[3];
                const uint32_t e = max(max(__float_as_uint(fmaxf(fabsf(v0), fabsf(v1))), __float_as_uint(fmaxf(fabsf(v2), fabsf(v3)))), 16u << 23) >> 23;
                const float sc = __uint_as_float((245u - e) << 23);
                stg64(dst, pack_f16(v0 * sc, v1 * sc) | ((e * 0x8002000u) & 0x60006000u), pack_f16(v2 * sc, v3 * sc) | ((e * 0x800200u) & 0x60006000u));
            };
            if (warp >= 16) { down(WE, pp + 4 * 64 * 32); down(WD, pp); }
            else down(WD, pp);
        }
        asm volatile("cp.async.bulk.wait_group.read 0;\n" ::: "memory");
        STAMP(22);
        if (b < 72 && warp < 16) {
            const uint2* src = reinterpret_cast<const uint2*>(p.s->part) + (unsigned)(b * 1024 + tid);
            uint2 a, c;
            int it = 0;
            DELAY(PDEL);
            a = ld_poll64(src); c = ld_poll64(src + 512);
            while (!__all_sync(0xffffffffu, a.y && c.y)) {
                a = ld_poll64(src); c = ld_poll64(src + 512);
                if (++it > SPIN_LIMIT) TRAP();
            }
            STAMP(24);
            const float ea = __uint_as_float((((a.y & 0x60006000u) | ((a.x >> 4) & 0x06000600u)) * 0x4001u) & 0x7f800000u);
            const float ec = __uint_as_float((((c.y & 0x60006000u) | ((c.x >> 4) & 0x06000600u)) * 0x4001u) & 0x7f800000u);
            a.x &= 0x9fff9fffu; a.y &= 0x9fff9fffu; c.x &= 0x9fff9fffu; c.y &= 0x9fff9fffu;
            const float s0 = fmaf(h_lo(a.x), ea, h_lo(c.x) * ec), s1 = fmaf(h_hi(a.x), ea, h_hi(c.x) * ec), s2 = fmaf(h_lo(a.y), ea, h_lo(c.y) * ec), s3 = fmaf(h_hi(a.y), ea, h_hi(c.y) * ec);
            const bool up = lane & 16;
            const float r0 = __shfl_xor_sync(0xffffffffu, up ? s0 : s2, 16), r1 = __shfl_xor_sync(0xffffffffu, up ? s1 : s3, 16);
            const uint32_t fa = sb + SM_FIN + ((lane & 15) * 4 + (up ? 2 : 0)) * 80 + warp * 4;
            stsf(fa, (up ? s2 : s0) + r0); stsf(fa + 80, (up ? s3 : s1) + r1);
            bar_arrive(14, 576);
        }
    }
    STAMP(25);
    }
}

typedef CUresult (*PFN_tmEncode)(CUtensorMap*, CUtensorMapDataType, cuuint32_t, void*, const cuuint64_t*, const cuuint64_t*, const cuuint32_t*,
                                 const cuuint32_t*, CUtensorMapInterleave, CUtensorMapSwizzle, CUtensorMapL2promotion, CUtensorMapFloatOOBfill);

extern "C" void kernel_launch(void* const* d_in, const int* in_sizes, int n_in, void* d_out, int out_size) {
    Params p;
    p.x = (const bf16*)d_in[0];
    p.lar = (const bf16*)d_in[1];
    p.aim = (const bf16*)d_in[2];
    p.cre = (const bf16*)d_in[3];
    p.cim = (const bf16*)d_in[4];
    p.ldt = (const bf16*)d_in[5];
    p.dsk = (const bf16*)d_in[6];
    p.wr = (const bf16*)d_in[8];
    p.out = (bf16*)d_out;
    static PFN_tmEncode enc = nullptr;
    static void* scratch = nullptr;
    if (!enc) {
        cudaFuncSetAttribute(fused_kernel, cudaFuncAttributeMaxDynamicSharedMemorySize, SMEM_TOTAL);
        void* fn = nullptr;
        cudaDriverEntryPointQueryResult qr;
        cudaGetDriverEntryPoint("cuTensorMapEncodeTiled", &fn, cudaEnableDefault, &qr);
        enc = (PFN_tmEncode)fn;
        cudaGetSymbolAddress(&scratch, g_scratch);
    }
    p.s = (Scratch*)scratch;
    WMaps wm;
    CUtensorMap tm_x, tm_y, tm_z;
    const cuuint64_t dims[2] = {FF, DM}, strides[1] = {FF * 2}, rdims[3] = {FF, 144, 4}, rstrides[2] = {FF * 2, 144 * FF * 2};
    const cuuint32_t box[2] = {64, 72}, rbox[3] = {8, 144, 2}, es3[3] = {1, 1, 1};
    for (int i = 0; i < 2; i++) {
        enc(i ? &wm.u : &wm.g, CU_TENSOR_MAP_DATA_TYPE_BFLOAT16, 2, d_in[9 + i], dims, strides, box, es3, CU_TENSOR_MAP_INTERLEAVE_NONE, CU_TENSOR_MAP_SWIZZLE_128B,
            CU_TENSOR_MAP_L2_PROMOTION_NONE, CU_TENSOR_MAP_FLOAT_OOB_FILL_NONE);
        enc(i ? &wm.ur : &wm.gr, CU_TENSOR_MAP_DATA_TYPE_BFLOAT16, 3, d_in[9 + i], rdims, rstrides, rbox, es3, CU_TENSOR_MAP_INTERLEAVE_NONE, CU_TENSOR_MAP_SWIZZLE_NONE,
            CU_TENSOR_MAP_L2_PROMOTION_NONE, CU_TENSOR_MAP_FLOAT_OOB_FILL_NONE);
    }
    const cuuint64_t ddims[2] = {DM, FF}, dstrides[1] = {DM * 2}, edims[3] = {64, FF, 9}, estrides[2] = {DM * 2, 128};
    const cuuint32_t dbox[2] = {64, 64}, ebox[3] = {64, 8, 5};
    enc(&wm.d, CU_TENSOR_MAP_DATA_TYPE_BFLOAT16, 2, d_in[11], ddims, dstrides, dbox, es3, CU_TENSOR_MAP_INTERLEAVE_NONE, CU_TENSOR_MAP_SWIZZLE_128B,
        CU_TENSOR_MAP_L2_PROMOTION_NONE, CU_TENSOR_MAP_FLOAT_OOB_FILL_NONE);
    enc(&wm.dr, CU_TENSOR_MAP_DATA_TYPE_BFLOAT16, 3, d_in[11], edims, estrides, ebox, es3, CU_TENSOR_MAP_INTERLEAVE_NONE, CU_TENSOR_MAP_SWIZZLE_128B,
        CU_TENSOR_MAP_L2_PROMOTION_NONE, CU_TENSOR_MAP_FLOAT_OOB_FILL_NONE);
    const cuuint64_t xdims[3] = {DM, LSEQ / 16, 16}, xstrides[2] = {16 * DM * 2, DM * 2};
    const cuuint32_t xbox[3] = {8, LSEQ / 16, 8};
    enc(&tm_x, CU_TENSOR_MAP_DATA_TYPE_BFLOAT16, 3, d_in[0], xdims, xstrides, xbox, es3, CU_TENSOR_MAP_INTERLEAVE_NONE, CU_TENSOR_MAP_SWIZZLE_NONE,
        CU_TENSOR_MAP_L2_PROMOTION_NONE, CU_TENSOR_MAP_FLOAT_OOB_FILL_NONE);
    const cuuint64_t ydims[3] = {DM * 32, 16, 4}, ystrides[2] = {DM * 64, 16 * DM * 64};
    const cuuint32_t ybox[3] = {128, 16, 2}, zbox[3] = {32, 16, 2};
    enc(&tm_y, CU_TENSOR_MAP_DATA_TYPE_BFLOAT16, 3, p.s->y, ydims, ystrides, ybox, es3, CU_TENSOR_MAP_INTERLEAVE_NONE, CU_TENSOR_MAP_SWIZZLE_NONE,
        CU_TENSOR_MAP_L2_PROMOTION_NONE, CU_TENSOR_MAP_FLOAT_OOB_FILL_NONE);
    enc(&tm_z, CU_TENSOR_MAP_DATA_TYPE_BFLOAT16, 3, p.s->y, ydims, ystrides, zbox, es3, CU_TENSOR_MAP_INTERLEAVE_NONE, CU_TENSOR_MAP_SWIZZLE_NONE,
        CU_TENSOR_MAP_L2_PROMOTION_NONE, CU_TENSOR_MAP_FLOAT_OOB_FILL_NONE);
    fused_kernel<<<NCTA, NTHR, SMEM_TOTAL>>>(p, wm, tm_x, tm_y, tm_z);
}
```

```cpp
#include <cuda_runtime.h>
#include <cuda.h>
#include <cuda_fp16.h>
#include <cuda_bf16.h>
#include <stdint.h>

#define LSEQ 2048
#define DM 576
#define NST 128
#define FF 4608
#define NSEL 8
#define NCTA 128
#define NTHR 640
#define NWRK 640

typedef __nv_bfloat16 bf16;

#define SM_WD 0
#define SM_WG 46080
#define SM_WR 82944
#define SM_WU 92160
#define SM_ZERO 32768
#define SM_XC 16384
#define SM_TB 96000
#define SM_PL 129024
#define PL_B 10752
#define SM_XT (SM_TB + 20 * TBW)
#define SM_U (SM_XT + 18432)
#define UPAD 8
#define ULO_B ((UPAD + 128) * 16)
#define USLOT_B (2 * ULO_B)
#define SM_KW (SM_U + 5 * USLOT_B)
#define KW_B 3600
#define KW_T2 1152
#define KW_KH 656
#define KW_T3 2464
#define SM_MISC (SM_KW + 5 * KW_B)
#define SM_LNP (SM_MISC + 576)
#define SMEM_TOTAL (SM_LNP + 5120)
#define TBP 112
#define TBW (32 * TBP)
#define SM_OUT SM_PL
#define OUT_PITCH 1216
#define SM_XS (SM_PL + 19456)
#define XS_PITCH 592
#define SM_EX (SM_PL + 24320)
#define SM_KEYS (SM_KW + 5120)
#define SM_FIN SM_KW
#define SM_GU (SM_PL + 33536)

struct __align__(128) Scratch {
    unsigned hint[8 * 32];
    unsigned flag[32];
    uint32_t sc[NCTA * 64];
    uint32_t st[LSEQ * 2];
    uint32_t uT[64 * (LSEQ / 2)];
    uint32_t y[NCTA * DM * 8];
    uint32_t part[72 * 64 * 32];
    uint32_t rows[(2 * NCTA + NSEL) * DM];
};
__device__ Scratch g_scratch;
#define STAMP(i)
#define DBG(i, v)

__device__ __forceinline__ float rbf(float x) {
    uint32_t r;
    asm("cvt.rn.bf16x2.f32 %0, %1, %2;\n" : "=r"(r) : "f"(x), "f"(0.f));
    return __uint_as_float(r);
}
__device__ __forceinline__ uint32_t pack_bf16(float lo, float hi) {
    uint32_t r;
    asm("cvt.rn.bf16x2.f32 %0, %1, %2;\n" : "=r"(r) : "f"(hi), "f"(lo));
    return r;
}
__device__ __forceinline__ uint32_t pack_f16(float lo, float hi) {
    uint32_t r;
    asm("cvt.rn.f16x2.f32 %0, %1, %2;\n" : "=r"(r) : "f"(hi), "f"(lo));
    return r;
}
__device__ __forceinline__ uint32_t pack_f16_rz(float lo, float hi) {
    uint32_t r;
    asm("cvt.rz.f16x2.f32 %0, %1, %2;\n" : "=r"(r) : "f"(hi), "f"(lo));
    return r;
}
__device__ __forceinline__ float bf_lo(uint32_t w) { return __uint_as_float(w << 16); }
__device__ __forceinline__ float bf_hi(uint32_t w) { return __uint_as_float(w & 0xffff0000u); }
__device__ __forceinline__ uint32_t hadd2_bf(uint32_t a, uint32_t b) {
    __nv_bfloat162 r = __hadd2_rn(*reinterpret_cast<__nv_bfloat162*>(&a), *reinterpret_cast<__nv_bfloat162*>(&b));
    return *reinterpret_cast<uint32_t*>(&r);
}
__device__ __forceinline__ uint32_t hmul2_bf(uint32_t a, uint32_t b) {
    __nv_bfloat162 r = __hmul2_rn(*reinterpret_cast<__nv_bfloat162*>(&a), *reinterpret_cast<__nv_bfloat162*>(&b));
    return *reinterpret_cast<uint32_t*>(&r);
}
__device__ __forceinline__ uint32_t hfma2_bf(uint32_t a, uint32_t b, uint32_t c) { uint32_t r; asm("fma.rn.bf16x2 %0, %1, %2, %3;\n" : "=r"(r) : "r"(a), "r"(b), "r"(c)); return r; }
__device__ __forceinline__ uint32_t hmul2(uint32_t a, uint32_t b) { uint32_t r; asm("mul.rn.f16x2 %0, %1, %2;\n" : "=r"(r) : "r"(a), "r"(b)); return r; }
__device__ __forceinline__ uint32_t hadd2(uint32_t a, uint32_t b) { uint32_t r; asm("add.rn.f16x2 %0, %1, %2;\n" : "=r"(r) : "r"(a), "r"(b)); return r; }
__device__ __forceinline__ uint32_t nzw(uint32_t w) { return w ? w : 0x8000u; }
__device__ __forceinline__ uint32_t smem_u32(const void* p) { return (uint32_t)__cvta_generic_to_shared(p); }
__device__ __forceinline__ uint32_t lds32(uint32_t addr) {
    uint32_t v;
    asm volatile("ld.shared.u32 %0, [%1];\n" : "=r"(v) : "r"(addr) : "memory");
    return v;
}
__device__ __forceinline__ uint2 lds64(uint32_t addr) {
    uint2 v;
    asm volatile("ld.shared.v2.u32 {%0,%1}, [%2];\n" : "=r"(v.x), "=r"(v.y) : "r"(addr) : "memory");
    return v;
}
__device__ __forceinline__ uint4 lds128(uint32_t addr) {
    uint4 v;
    asm volatile("ld.shared.v4.u32 {%0,%1,%2,%3}, [%4];\n" : "=r"(v.x), "=r"(v.y), "=r"(v.z), "=r"(v.w) : "r"(addr) : "memory");
    return v;
}
__device__ __forceinline__ float ldsf(uint32_t addr) { return __uint_as_float(lds32(addr)); }
__device__ __forceinline__ void sts32(uint32_t addr, uint32_t v) { asm volatile("st.shared.u32 [%0], %1;\n" ::"r"(addr), "r"(v) : "memory"); }
__device__ __forceinline__ void stsf(uint32_t addr, float v) { sts32(addr, __float_as_uint(v)); }
__device__ __forceinline__ void sts64(uint32_t addr, uint32_t a, uint32_t b) { asm volatile("st.shared.v2.u32 [%0], {%1,%2};\n" ::"r"(addr), "r"(a), "r"(b) : "memory"); }
__device__ __forceinline__ void sts128(uint32_t addr, uint32_t a, uint32_t b, uint32_t c, uint32_t d) {
    asm volatile("st.shared.v4.u32 [%0], {%1,%2,%3,%4};\n" ::"r"(addr), "r"(a), "r"(b), "r"(c), "r"(d) : "memory");
}
__device__ __forceinline__ void sts128f(uint32_t addr, const float (&v)[4]) {
    sts128(addr, __float_as_uint(v[0]), __float_as_uint(v[1]), __float_as_uint(v[2]), __float_as_uint(v[3]));
}
__device__ __forceinline__ void ldsm_x4(uint32_t& r0, uint32_t& r1, uint32_t& r2, uint32_t& r3, uint32_t addr) {
    asm volatile("ldmatrix.sync.aligned.m8n8.x4.shared.b16 {%0,%1,%2,%3}, [%4];\n"
                 : "=r"(r0), "=r"(r1), "=r"(r2), "=r"(r3) : "r"(addr) : "memory");
}
__device__ __forceinline__ void ldsm_x4_t(uint32_t& r0, uint32_t& r1, uint32_t& r2, uint32_t& r3, uint32_t addr) {
    asm volatile("ldmatrix.sync.aligned.m8n8.x4.trans.shared.b16 {%0,%1,%2,%3}, [%4];\n"
                 : "=r"(r0), "=r"(r1), "=r"(r2), "=r"(r3) : "r"(addr) : "memory");
}
__device__ __forceinline__ void ldsm_x2_t(uint32_t& r0, uint32_t& r1, uint32_t addr) {
    asm volatile("ldmatrix.sync.aligned.m8n8.x2.trans.shared.b16 {%0,%1}, [%2];\n" : "=r"(r0), "=r"(r1) : "r"(addr) : "memory");
}
__device__ __forceinline__ void ldsm_x1_t(uint32_t& r0, uint32_t addr) {
    asm volatile("ldmatrix.sync.aligned.m8n8.x1.trans.shared.b16 {%0}, [%1];\n" : "=r"(r0) : "r"(addr) : "memory");
}
__device__ __forceinline__ uint32_t movm(uint32_t a) {
    uint32_t d;
    asm volatile("movmatrix.sync.aligned.m8n8.trans.b16 %0, %1;\n" : "=r"(d) : "r"(a));
    return d;
}
__device__ __forceinline__ void mma_f16(float (&c)[4], uint32_t a0, uint32_t a1, uint32_t a2, uint32_t a3, uint32_t b0, uint32_t b1) {
    asm volatile(
        "mma.sync.aligned.m16n8k16.row.col.f32.f16.f16.f32 {%0,%1,%2,%3}, {%4,%5,%6,%7}, {%8,%9}, {%0,%1,%2,%3};\n"
        : "+f"(c[0]), "+f"(c[1]), "+f"(c[2]), "+f"(c[3])
        : "r"(a0), "r"(a1), "r"(a2), "r"(a3), "r"(b0), "r"(b1));
}
__device__ __forceinline__ void mma_bf16(float (&c)[4], uint32_t a0, uint32_t a1, uint32_t a2, uint32_t a3, uint32_t b0, uint32_t b1) {
    asm volatile(
        "mma.sync.aligned.m16n8k16.row.col.f32.bf16.bf16.f32 {%0,%1,%2,%3}, {%4,%5,%6,%7}, {%8,%9}, {%0,%1,%2,%3};\n"
        : "+f"(c[0]), "+f"(c[1]), "+f"(c[2]), "+f"(c[3])
        : "r"(a0), "r"(a1), "r"(a2), "r"(a3), "r"(b0), "r"(b1));
}
__device__ __forceinline__ void mma_bf16_k8(float (&c)[4], uint32_t a0, uint32_t a1, uint32_t b0) {
    asm volatile("mma.sync.aligned.m16n8k8.row.col.f32.bf16.bf16.f32 {%0,%1,%2,%3}, {%4,%5}, {%6}, {%0,%1,%2,%3};\n"
        : "+f"(c[0]), "+f"(c[1]), "+f"(c[2]), "+f"(c[3]) : "r"(a0), "r"(a1), "r"(b0));
}
__device__ __forceinline__ void bar_sync(int id, int n) { asm volatile("bar.sync %0, %1;\n" ::"r"(id), "r"(n) : "memory"); }
__device__ __forceinline__ void bar_arrive(int id, int n) { asm volatile("bar.arrive %0, %1;\n" ::"r"(id), "r"(n) : "memory"); }
__device__ __forceinline__ bool bar_or(int id, int n, bool v) {
    uint32_t r;
    asm volatile("{\n.reg .pred p, q;\nsetp.ne.u32 p, %3, 0;\nbar.red.or.pred q, %1, %2, p;\nselp.u32 %0, 1, 0, q;\n}\n" : "=r"(r) : "r"(id), "r"(n), "r"((uint32_t)v) : "memory");
    return r;
}
__device__ __forceinline__ uint4 ld_poll(const void* p) {
    uint4 v;
    asm volatile("ld.relaxed.gpu.global.v4.u32 {%0,%1,%2,%3}, [%4];\n" : "=r"(v.x), "=r"(v.y), "=r"(v.z), "=r"(v.w) : "l"(p) : "memory");
    return v;
}
template <class T> __device__ __forceinline__ T* pin(T* p, uint32_t z) {
    uint32_t lo, hi;
    asm volatile("mov.b64 {%0, %1}, %2;\n" : "=r"(lo), "=r"(hi) : "l"(p));
    asm volatile("xor.b32 %0, %0, %1;\n" : "+r"(lo) : "r"(z));
    asm volatile("xor.b32 %0, %0, %1;\n" : "+r"(hi) : "r"(z));
    asm volatile("mov.b64 %0, {%1, %2};\n" : "=l"(p) : "r"(lo), "r"(hi));
    return p;
}
__device__ __forceinline__ uint32_t pin(uint32_t a, uint32_t z) { asm volatile("xor.b32 %0, %0, %1;\n" : "+r"(a) : "r"(z)); return a; }
__device__ __forceinline__ uint2 ld_poll64(const void* p) {
    uint2 v;
    asm volatile("ld.relaxed.gpu.global.v2.u32 {%0,%1}, [%2];\n" : "=r"(v.x), "=r"(v.y) : "l"(p) : "memory");
    return v;
}
__device__ __forceinline__ uint32_t ld_poll32(const void* p) {
    uint32_t v;
    asm volatile("ld.relaxed.gpu.global.u32 %0, [%1];\n" : "=r"(v) : "l"(p) : "memory");
    return v;
}
__device__ __forceinline__ uint4 ldg128(const void* p) {
    uint4 v;
    asm volatile("ld.global.nc.v4.u32 {%0,%1,%2,%3}, [%4];\n" : "=r"(v.x), "=r"(v.y), "=r"(v.z), "=r"(v.w) : "l"(p));
    return v;
}
__device__ __forceinline__ uint2 ldg64(const void* p) {
    uint2 v;
    asm volatile("ld.global.nc.v2.u32 {%0,%1}, [%2];\n" : "=r"(v.x), "=r"(v.y) : "l"(p));
    return v;
}
__device__ __forceinline__ uint32_t ldg16(const void* p) {
    uint32_t v;
    asm volatile("ld.global.nc.u16 %0, [%1];\n" : "=r"(v) : "l"(p));
    return v;
}
__device__ __forceinline__ void stg128(void* p, uint32_t a, uint32_t b, uint32_t c, uint32_t d) {
    asm volatile("st.global.v4.u32 [%0], {%1,%2,%3,%4};\n" ::"l"(p), "r"(a), "r"(b), "r"(c), "r"(d) : "memory");
}
__device__ __forceinline__ void stg64(void* p, uint32_t a, uint32_t b) { asm volatile("st.global.v2.u32 [%0], {%1,%2};\n" ::"l"(p), "r"(a), "r"(b) : "memory"); }
__device__ __forceinline__ void stg32(void* p, uint32_t a) { asm volatile("st.global.u32 [%0], %1;\n" ::"l"(p), "r"(a) : "memory"); }
__device__ __forceinline__ bool all_nz(const uint4& v) { return v.x && v.y && v.z && v.w; }
#define SPIN_LIMIT (1 << 21)
#define TRAP() __trap()
__device__ __forceinline__ void hint_arrive(unsigned* g_hint, int idx, int sub) {
    asm volatile("red.relaxed.gpu.global.add.u32 [%0], 1;\n" ::"l"(&g_hint[sub * 32 + idx]) : "memory");
}
__device__ __forceinline__ void hint_wait(const unsigned* g_hint, int idx, unsigned target) {
    unsigned l;
    asm volatile("mov.u32 %0, %%laneid;" : "=r"(l));
    const unsigned* c = &g_hint[(l & 7) * 32 + idx];
    int it = 0;
    while (__any_sync(0xffffffffu, (int)(ld_poll32(c) - target) < 0)) { if (++it > SPIN_LIMIT) TRAP(); }
}
__device__ __forceinline__ void mbar_init(uint32_t bar, uint32_t cnt) { asm volatile("mbarrier.init.shared::cta.b64 [%0], %1;\n" ::"r"(bar), "r"(cnt) : "memory"); }
__device__ __forceinline__ void mbar_expect(uint32_t bar, uint32_t bytes) {
    asm volatile("mbarrier.arrive.expect_tx.shared::cta.b64 _, [%0], %1;\n" ::"r"(bar), "r"(bytes) : "memory");
}
__device__ __forceinline__ void mbar_arrive(uint32_t bar) { asm volatile("mbarrier.arrive.shared::cta.b64 _, [%0];\n" ::"r"(bar) : "memory"); }
__device__ __forceinline__ void mbar_wait(uint32_t bar) {
    asm volatile(
        "{\n.reg .pred p;\n"
        "W_%=:\n"
        "mbarrier.try_wait.parity.shared::cta.b64 p, [%0], 0;\n"
        "@!p bra W_%=;\n}\n" ::"r"(bar) : "memory");
}
__device__ __forceinline__ void bulk_s2g(void* dst, uint32_t src, uint32_t bytes) {
    asm volatile("cp.async.bulk.global.shared::cta.bulk_group [%0], [%1], %2;\ncp.async.bulk.commit_group;\n" ::"l"(dst), "r"(src), "r"(bytes) : "memory");
}
__device__ __forceinline__ void tma_2d(uint32_t dst, const CUtensorMap* tm, int c0, int c1, uint32_t bar) {
    asm volatile("cp.async.bulk.tensor.2d.shared::cluster.global.mbarrier::complete_tx::bytes [%0], [%1, {%3, %4}], [%2];\n"
                 ::"r"(dst), "l"(tm), "r"(bar), "r"(c0), "r"(c1) : "memory");
}
__device__ __forceinline__ void tma_3d(uint32_t dst, const CUtensorMap* tm, int c0, int c1, int c2, uint32_t bar) {
    asm volatile("cp.async.bulk.tensor.3d.shared::cluster.global.mbarrier::complete_tx::bytes [%0], [%1, {%3, %4, %5}], [%2];\n"
                 ::"r"(dst), "l"(tm), "r"(bar), "r"(c0), "r"(c1), "r"(c2) : "memory");
}
__device__ __forceinline__ void tma_st_3d(const CUtensorMap* tm, uint32_t src, int c0, int c1, int c2) {
    asm volatile("cp.async.bulk.tensor.3d.global.shared::cta.bulk_group [%0, {%2, %3, %4}], [%1];\ncp.async.bulk.commit_group;\n"
                 ::"l"(tm), "r"(src), "r"(c0), "r"(c1), "r"(c2) : "memory");
}
__device__ __forceinline__ bool elect_one() {
    uint32_t r;
    asm volatile("{\n.reg .pred p;\nelect.sync _|p, 0xffffffff;\nselp.u32 %0, 1, 0, p;\n}\n" : "=r"(r));
    return r;
}
__device__ __forceinline__ void fence_async() { asm volatile("fence.proxy.async.shared::cta;\n" ::: "memory"); }

__device__ __forceinline__ float2 cmul(float2 a, float2 b) {
    return make_float2(fmaf(a.x, b.x, -a.y * b.y), fmaf(a.x, b.y, a.y * b.x));
}
__device__ __forceinline__ float2 csq(float2 a) {
    float p = a.x * a.y;
    return make_float2(fmaf(a.x, a.x, -a.y * a.y), p + p);
}
__device__ __forceinline__ float2 cexp_e(float lr2, float rh, float rl, float e) {
    float m;
    asm("ex2.approx.ftz.f32 %0, %1;\n" : "=f"(m) : "f"(lr2 * e));
    const float a = rh * e;
    const float r = fmaf(rl, e, a - rintf(a)) * 6.283185307179586f;
    return make_float2(m * __cosf(r), m * __sinf(r));
}
__device__ __forceinline__ float rcp_approx(float x) { float r; asm("rcp.approx.ftz.f32 %0, %1;\n" : "=f"(r) : "f"(x)); return r; }
__device__ __forceinline__ float ex2_approx(float x) { float r; asm("ex2.approx.ftz.f32 %0, %1;\n" : "=f"(r) : "f"(x)); return r; }
__device__ __forceinline__ float sqrt_approx(float x) { float r; asm("sqrt.approx.ftz.f32 %0, %1;\n" : "=f"(r) : "f"(x)); return r; }

__device__ __forceinline__ void wg_fence() { asm volatile("wgmma.fence.sync.aligned;\n" ::: "memory"); }
__device__ __forceinline__ void wg_commit() { asm volatile("wgmma.commit_group.sync.aligned;\n" ::: "memory"); }
__device__ __forceinline__ void wg_wait0() { asm volatile("wgmma.wait_group.sync.aligned 0;\n" ::: "memory"); }
template <int T0, int NT> __device__ __forceinline__ void wg_h(uint32_t (&acc)[32], const uint32_t (&a)[4], uint64_t desc);
template <> __device__ __forceinline__ void wg_h<0, 16>(uint32_t (&acc)[32], const uint32_t (&a)[4], uint64_t desc) {
    asm volatile("wgmma.mma_async.sync.aligned.m64n128k16.f16.f16.f16 {%0,%1,%2,%3,%4,%5,%6,%7,%8,%9,%10,%11,%12,%13,%14,%15,%16,%17,%18,%19,%20,%21,%22,%23,%24,%25,%26,%27,%28,%29,%30,%31}, {%32,%33,%34,%35}, %36, 1, 1, 1, 0;\n"
                 : "+r"(acc[0]), "+r"(acc[1]), "+r"(acc[2]), "+r"(acc[3]), "+r"(acc[4]), "+r"(acc[5]), "+r"(acc[6]), "+r"(acc[7]), "+r"(acc[8]), "+r"(acc[9]), "+r"(acc[10]), "+r"(acc[11]), "+r"(acc[12]), "+r"(acc[13]), "+r"(acc[14]), "+r"(acc[15]), "+r"(acc[16]), "+r"(acc[17]), "+r"(acc[18]), "+r"(acc[19]), "+r"(acc[20]), "+r"(acc[21]), "+r"(acc[22]), "+r"(acc[23]), "+r"(acc[24]), "+r"(acc[25]), "+r"(acc[26]), "+r"(acc[27]), "+r"(acc[28]), "+r"(acc[29]), "+r"(acc[30]), "+r"(acc[31])
                 : "r"(a[0]), "r"(a[1]), "r"(a[2]), "r"(a[3]), "l"(desc));
}
template <> __device__ __forceinline__ void wg_h<4, 4>(uint32_t (&acc)[32], const uint32_t (&a)[4], uint64_t desc) {
    asm volatile("wgmma.mma_async.sync.aligned.m64n32k16.f16.f16.f16 {%0,%1,%2,%3,%4,%5,%6,%7}, {%8,%9,%10,%11}, %12, 1, 1, 1, 0;\n"
                 : "+r"(acc[8]), "+r"(acc[9]), "+r"(acc[10]), "+r"(acc[11]), "+r"(acc[12]), "+r"(acc[13]), "+r"(acc[14]), "+r"(acc[15])
                 : "r"(a[0]), "r"(a[1]), "r"(a[2]), "r"(a[3]), "l"(desc));
}
template <> __device__ __forceinline__ void wg_h<8, 4>(uint32_t (&acc)[32], const uint32_t (&a)[4], uint64_t desc) {
    asm volatile("wgmma.mma_async.sync.aligned.m64n32k16.f16.f16.f16 {%0,%1,%2,%3,%4,%5,%6,%7}, {%8,%9,%10,%11}, %12, 1, 1, 1, 0;\n"
                 : "+r"(acc[16]), "+r"(acc[17]), "+r"(acc[18]), "+r"(acc[19]), "+r"(acc[20]), "+r"(acc[21]), "+r"(acc[22]), "+r"(acc[23])
                 : "r"(a[0]), "r"(a[1]), "r"(a[2]), "r"(a[3]), "l"(desc));
}
template <> __device__ __forceinline__ void wg_h<12, 4>(uint32_t (&acc)[32], const uint32_t (&a)[4], uint64_t desc) {
    asm volatile("wgmma.mma_async.sync.aligned.m64n32k16.f16.f16.f16 {%0,%1,%2,%3,%4,%5,%6,%7}, {%8,%9,%10,%11}, %12, 1, 1, 1, 0;\n"
                 : "+r"(acc[24]), "+r"(acc[25]), "+r"(acc[26]), "+r"(acc[27]), "+r"(acc[28]), "+r"(acc[29]), "+r"(acc[30]), "+r"(acc[31])
                 : "r"(a[0]), "r"(a[1]), "r"(a[2]), "r"(a[3]), "l"(desc));
}
template <> __device__ __forceinline__ void wg_h<0, 8>(uint32_t (&acc)[32], const uint32_t (&a)[4], uint64_t desc) {
    asm volatile("wgmma.mma_async.sync.aligned.m64n64k16.f16.f16.f16 {%0,%1,%2,%3,%4,%5,%6,%7,%8,%9,%10,%11,%12,%13,%14,%15}, {%16,%17,%18,%19}, %20, 1, 1, 1, 0;\n"
                 : "+r"(acc[0]), "+r"(acc[1]), "+r"(acc[2]), "+r"(acc[3]), "+r"(acc[4]), "+r"(acc[5]), "+r"(acc[6]), "+r"(acc[7]), "+r"(acc[8]), "+r"(acc[9]), "+r"(acc[10]), "+r"(acc[11]), "+r"(acc[12]), "+r"(acc[13]), "+r"(acc[14]), "+r"(acc[15])
                 : "r"(a[0]), "r"(a[1]), "r"(a[2]), "r"(a[3]), "l"(desc));
}
template <> __device__ __forceinline__ void wg_h<4, 12>(uint32_t (&acc)[32], const uint32_t (&a)[4], uint64_t desc) {
    asm volatile("wgmma.mma_async.sync.aligned.m64n96k16.f16.f16.f16 {%0,%1,%2,%3,%4,%5,%6,%7,%8,%9,%10,%11,%12,%13,%14,%15,%16,%17,%18,%19,%20,%21,%22,%23}, {%24,%25,%26,%27}, %28, 1, 1, 1, 0;\n"
                 : "+r"(acc[8]), "+r"(acc[9]), "+r"(acc[10]), "+r"(acc[11]), "+r"(acc[12]), "+r"(acc[13]), "+r"(acc[14]), "+r"(acc[15]), "+r"(acc[16]), "+r"(acc[17]), "+r"(acc[18]), "+r"(acc[19]), "+r"(acc[20]), "+r"(acc[21]), "+r"(acc[22]), "+r"(acc[23]), "+r"(acc[24]), "+r"(acc[25]), "+r"(acc[26]), "+r"(acc[27]), "+r"(acc[28]), "+r"(acc[29]), "+r"(acc[30]), "+r"(acc[31])
                 : "r"(a[0]), "r"(a[1]), "r"(a[2]), "r"(a[3]), "l"(desc));
}

#define PBYTES 4608
#define DELAY(n) do { if (n) { const unsigned c0_ = clock32(); while ((int)(clock32() - c0_) < (n)) {} } } while (0)
#define KDEL 400
#define PDEL 300
#define CST(i) do { if ((warp & 3) == 0 && lane_v() == 0) { unsigned t_; asm volatile("mov.u32 %0, %%globaltimer_lo;" : "=r"(t_) :: "memory"); sts32(sb + SMEM_TOTAL - 768 + (warp >> 2) * 128 + (i) * 4, t_); } } while (0)
#define TP0 5000
#define TP4 5800
#define KDEL2 300
#define WSP 450
#define WS0 0
#define PB9 0
#define HINTW 10
#define WAS 0x0005
#define WA0 (WAS >> 12)
#define WA1 ((WAS >> 8) & 15)
#define WA2 ((WAS >> 4) & 15)
#define WDAT 1
#define UW 8
#define TOKEN_OF(g) (16 * ((g) & 1) + ((g) >> 2) + 2 * ((g) & 2))
#define HI2(a, b) (pack_f16_rz(__uint_as_float(a), __uint_as_float(b)) & 0xfff8fff8u)
struct Params {
    const bf16 *x, *lar, *aim, *cre, *cim, *ldt, *dsk;
    Scratch* s;
    const bf16* wr;
    bf16* out;
};

template <int NK>
__device__ __forceinline__ void ln_partial(const uint32_t (&H)[2][NK], const uint32_t (&bw)[NK], uint32_t lp, int warp, int g, int t) {
    float cs[4] = {0.f, 0.f, 0.f, 0.f}, cl[4] = {0.f, 0.f, 0.f, 0.f}, ch[4] = {0.f, 0.f, 0.f, 0.f};
#pragma unroll
    for (int k = 0; k < NK; k += 2) {
        uint32_t a0, a1, a2, a3;
        asm volatile("prmt.b32 %0, %4, %4, %8;\nprmt.b32 %1, %5, %5, %8;\nprmt.b32 %2, %6, %6, %8;\nprmt.b32 %3, %7, %7, %8;\n"
                     : "=r"(a0), "=r"(a1), "=r"(a2), "=r"(a3) : "r"(H[0][k]), "r"(H[1][k]), "r"(H[0][k + 1]), "r"(H[1][k + 1]), "r"(0x3210u + (warp >> 8)));
        mma_bf16(cl, a0, a1, a2, a3, H[0][k], H[0][k + 1]);
        mma_bf16(ch, a0, a1, a2, a3, H[1][k], H[1][k + 1]);
        mma_bf16(cs, a0, a1, a2, a3, bw[k], bw[k + 1]);
    }
    const uint32_t a = lp + (g * 20 + warp) * 4;
    if (t == 0) {
        stsf(a, cs[1]); stsf(a + 8 * 80, cs[3]);
        if (NK == 4) { stsf(a + 48 * 80, cs[0]); stsf(a + 56 * 80, cs[2]); }
    }
    if (t == (g >> 1)) { stsf(a + 16 * 80, (g & 1) ? cl[1] : cl[0]); stsf(a + 24 * 80, (g & 1) ? ch[3] : ch[2]); }
}
__device__ __forceinline__ float sum18(uint32_t a) {
    const uint4 p = lds128(a), q = lds128(a + 16), r = lds128(a + 32), s = lds128(a + 48);
    const uint2 u = lds64(a + 64);
#define F(x) __uint_as_float(x)
    return (((F(p.x) + F(p.y)) + (F(p.z) + F(p.w))) + ((F(q.x) + F(q.y)) + (F(q.z) + F(q.w)))) +
           (((F(r.x) + F(r.y)) + (F(r.z) + F(r.w))) + ((F(s.x) + F(s.y)) + (F(s.z) + F(s.w))) + (F(u.x) + F(u.y)));
#undef F
}
__device__ __forceinline__ float sum9(uint32_t a) {
    const uint4 p = lds128(a), q = lds128(a + 16);
#define F(x) __uint_as_float(x)
    return (((F(p.x) + F(p.y)) + (F(p.z) + F(p.w))) + ((F(q.x) + F(q.y)) + (F(q.z) + F(q.w)))) + ldsf(a + 32);
#undef F
}
template <int N>
__device__ __forceinline__ void ln_finish(uint32_t lp, int lane, float& mb, float& rc) {
    const float v = N == 9 ? sum9(lp + lane * 80) : sum18(lp + lane * 80);
    const float o = __shfl_xor_sync(0xffffffffu, v, 16);
    const float m0 = v * (1.0f / 576.0f);
    const float mean = fmaf(fmaf(-m0, 576.0f, v), 1.0f / 576.0f, m0);
    const float var = fmaxf(fmaf(o, 1.0f / 576.0f, -(mean * mean)), 0.f);
    mb = rbf(mean);
    rc = rcp_approx(rbf(sqrt_approx(rbf(rbf(var) + 1e-5f))));
}
__device__ __forceinline__ uint32_t ln_apply(uint32_t w, const uint2& st) {
    uint32_t r;
    asm("{\n.reg .b16 m, t, h, l;\n.reg .b32 mm, hh, ll, d, e;\nmov.b32 {m, t}, %2;\nmov.b32 {h, l}, %3;\nmov.b32 mm, {m, m};\nmov.b32 hh, {h, h};\nmov.b32 ll, {l, l};\n"
        "sub.rn.bf16x2 d, %1, mm;\nmul.rn.bf16x2 e, d, ll;\nfma.rn.bf16x2 %0, d, hh, e;\n}\n" : "=r"(r) : "r"(w), "r"(st.x), "r"(st.y));
    return r;
}
__device__ __forceinline__ void stat_store(uint32_t a, float mb, float rc, uint32_t extra) {
    const float rh = rbf(rc);
    sts64(a, (__float_as_uint(mb) >> 16) | (extra << 16), pack_bf16(rh, rc - rh));
}

__device__ __forceinline__ void hcmul(uint32_t re, uint32_t im, uint32_t z, uint32_t& ore, uint32_t& oim) {
    asm("{\n.reg .b16 x, y;\n.reg .b32 xx, yy, ny, a, b;\nmov.b32 {x, y}, %4;\nmov.b32 xx, {x, x};\nmov.b32 yy, {y, y};\nneg.f16x2 ny, yy;\n"
        "mul.rn.f16x2 a, %2, xx;\nfma.rn.f16x2 %0, %3, ny, a;\nmul.rn.f16x2 b, %3, xx;\nfma.rn.f16x2 %1, %2, yy, b;\n}\n" : "=&r"(ore), "=r"(oim) : "r"(re), "r"(im), "r"(z));
}
__device__ __forceinline__ void hcmul(uint32_t re, uint32_t im, uint32_t zx, uint32_t zy, uint32_t& ore, uint32_t& oim) {
    asm("{\n.reg .b32 ny, a, b;\nneg.f16x2 ny, %5;\n"
        "mul.rn.f16x2 a, %2, %4;\nfma.rn.f16x2 %0, %3, ny, a;\nmul.rn.f16x2 b, %3, %4;\nfma.rn.f16x2 %1, %2, %5, b;\n}\n" : "=&r"(ore), "=r"(oim) : "r"(re), "r"(im), "r"(zx), "r"(zy));
}

struct KGen {
    uint32_t Af[4][4];
    float2 z1, z8, z64, z128, T[9];
    uint32_t zw;
};
__device__ __forceinline__ void kgen_setup(KGen& k, uint32_t pa, float dt) {
    const float A = rbf(expf(bf_lo(pa)));
    const float lr2 = -(A * dt) * 1.4426950408889634f;
    const float li = bf_hi(pa) * dt;
    const float rh = li * 0.15915494309189535f;
    const float rl = fmaf(li, 6.4206382986e-9f, fmaf(li, 0.15915494309189535f, -rh));
    k.z1 = cexp_e(lr2, rh, rl, 1.0f);
    k.z8 = cexp_e(lr2, rh, rl, 8.0f);
    k.z64 = cexp_e(lr2, rh, rl, 64.0f);
}
__device__ __forceinline__ void kgen_rows(KGen& k, uint32_t tb, int lane) {
    const float2 z8 = k.z8, z64 = k.z64;
    const uint32_t row = tb + lane * TBP;
    k.z128 = csq(z64);
    const float2 z16 = csq(z8), z32 = csq(z16), z48 = cmul(z32, z16), z80 = cmul(z64, z16), z96 = cmul(z64, z32), z112 = cmul(z64, z48);
    uint32_t re[4], im[4], a[4], b[4];
    re[0] = pack_f16(1.0f, z16.x); im[0] = pack_f16(0.0f, z16.y);
    re[1] = pack_f16(z32.x, z48.x); im[1] = pack_f16(z32.y, z48.y);
    re[2] = pack_f16(z64.x, z80.x); im[2] = pack_f16(z64.y, z80.y);
    re[3] = pack_f16(z96.x, z112.x); im[3] = pack_f16(z96.y, z112.y);
    sts128(row, re[0], re[1], re[2], re[3]);
    sts128(row + 32, im[0], im[1], im[2], im[3]);
    const uint32_t zz = pack_f16(z8.x, z8.y);
#pragma unroll
    for (int j = 0; j < 4; j++) hcmul(re[j], im[j], zz, a[j], b[j]);
    sts128(row + 16, a[0], a[1], a[2], a[3]);
    sts128(row + 48, b[0], b[1], b[2], b[3]);
    __syncwarp();
    const int mi = lane >> 3;
    const uint32_t ad = tb + (lane & 7) * TBP + mi * 16;
#pragma unroll
    for (int ks = 0; ks < 4; ks++) ldsm_x4_t(k.Af[ks][0], k.Af[ks][1], k.Af[ks][2], k.Af[ks][3], ad + ks * 8 * TBP);
}
__device__ __forceinline__ void kgen_chain(KGen& k, uint32_t pc, float cs) {
    k.T[0] = make_float2(bf_lo(pc) * cs, -bf_hi(pc) * cs);
    const float2 y1 = make_float2(k.z1.x, -k.z1.y);
#pragma unroll
    for (int c = 1; c < 8; c++) k.T[c] = cmul(k.T[c - 1], y1);
    k.T[8] = cmul(k.T[0], make_float2(k.z8.x, -k.z8.y));
}
__device__ __forceinline__ void kgen_cols(KGen& k, uint32_t tb, int lane) {
    const uint32_t row = tb + lane * TBP;
    const float2 (&T)[9] = k.T;
    const uint32_t zv = pack_f16(k.z128.x, k.z128.y), zo = __shfl_xor_sync(0xffffffffu, zv, 1);
    k.zw = (lane & 1) ? __byte_perm(zo, zv, 0x7632) : __byte_perm(zv, zo, 0x5410);
    const float2 y256 = csq(make_float2(k.z128.x, -k.z128.y)), y512 = csq(y256), y768 = cmul(y512, y256), y1024 = csq(y512);
    const float2 c1032 = cmul(T[8], y1024);
    const uint32_t r04 = pack_f16(T[0].x, T[4].x), i04 = pack_f16(T[0].y, T[4].y), r26 = pack_f16(T[2].x, T[6].x), i26 = pack_f16(T[2].y, T[6].y);
    const uint32_t r48 = pack_f16(T[4].x, T[8].x), i48 = pack_f16(T[4].y, T[8].y);
    __syncwarp();
    sts128(row, r04, pack_f16(T[1].x, T[5].x), r26, pack_f16(T[3].x, T[7].x));
    sts128(row + 16, i04, pack_f16(T[1].y, T[5].y), i26, pack_f16(T[3].y, T[7].y));
    uint32_t a[4], b[4];
    {
        const uint32_t zz = pack_f16(y256.x, y256.y);
        hcmul(r04, i04, zz, a[0], b[0]);
        hcmul(r26, i26, zz, a[2], b[2]);
        hcmul(r48, i48, zz, a[3], b[3]);
    }
    sts128(row + 32, a[0], a[0], a[2], a[3]);
    sts128(row + 48, b[0], b[0], b[2], b[3]);
    {
        hcmul(r48, i48, pack_f16(y512.x, y512.y), a[0], b[0]);
        hcmul(r48, i48, pack_f16(y768.x, y768.y), a[1], b[1]);
        const uint32_t zz = pack_f16(c1032.x, c1032.y);
        hcmul(pack_f16(1.0f, y256.x), pack_f16(0.0f, y256.y), zz, a[2], b[2]);
        hcmul(pack_f16(y512.x, y768.x), pack_f16(y512.y, y768.y), zz, a[3], b[3]);
    }
    sts128(row + 64, a[0], a[1], a[2], a[3]);
    sts128(row + 80, b[0], b[1], b[2], b[3]);
}
__device__ __forceinline__ void kgen_mma(const KGen& k, uint32_t tb, int lane) {
    const int t = lane & 3;
    const uint32_t zw = k.zw;
    uint32_t zx[4], zy[4];
#pragma unroll
    for (int ks = 0; ks < 4; ks++) { zx[ks] = __shfl_sync(0xffffffffu, zw, 8 * ks + 2 * t); zy[ks] = __shfl_sync(0xffffffffu, zw, 8 * ks + 2 * t + 1); }
    __syncwarp();
    float acc[2][3][4];
#pragma unroll
    for (int i = 0; i < 6; i++)
#pragma unroll
        for (int j = 0; j < 4; j++) acc[i / 3][i % 3][j] = 0.f;
    {
        const int mi = lane >> 3;
        const uint32_t bd = tb + ((lane & 7) + 8 * (mi >> 1)) * TBP + (mi & 1) * 16;
#pragma unroll
        for (int kp = 0; kp < 2; kp++) {
            uint32_t b[3][4];
#pragma unroll
            for (int j = 0; j < 3; j++) ldsm_x4_t(b[j][0], b[j][1], b[j][2], b[j][3], bd + kp * 16 * TBP + j * 32);
#pragma unroll
            for (int h = 0; h < 2; h++) {
                const int ks = 2 * kp + h;
                uint32_t d[4];
                hcmul(k.Af[ks][0], k.Af[ks][2], zx[ks], zy[ks], d[0], d[2]);
                hcmul(k.Af[ks][1], k.Af[ks][3], zx[ks], zy[ks], d[1], d[3]);
#pragma unroll
                for (int j = 0; j < 3; j++) {
                    mma_f16(acc[0][j], k.Af[ks][0], k.Af[ks][1], k.Af[ks][2], k.Af[ks][3], b[j][2 * h], b[j][2 * h + 1]);
                    mma_f16(acc[1][j], d[0], d[1], d[2], d[3], b[j][2 * h], b[j][2 * h + 1]);
                }
            }
        }
    }
    __syncwarp();
#pragma unroll
    for (int h = 0; h < 2; h++) {
        sts64(tb + h * 256 + lane * 8, pack_f16(acc[h][0][0], acc[h][0][1]), pack_f16(acc[h][0][2], acc[h][0][3]));
        sts64(tb + 512 + h * 256 + lane * 8, pack_f16(acc[h][1][0], acc[h][1][1]), pack_f16(acc[h][1][2], acc[h][1][3]));
        sts32(tb + 1024 + h * 256 + lane * 4, pack_f16(acc[h][2][0], t < 2 ? acc[h][2][1] : acc[h][2][2]));
        sts32(tb + 1152 + h * 256 + lane * 4, pack_f16(t < 2 ? acc[h][2][2] : acc[h][2][1], acc[h][2][3]));
    }
}
__device__ __forceinline__ uint32_t table_buf(uint32_t sb, int warp) { return sb + SM_TB + warp * TBW; }

__device__ __forceinline__ void kgen_combine(uint32_t sb, int warp, int lane, uint32_t kw, uint32_t ao) {
    const int wq = warp & 3;
    const uint32_t a = table_buf(sb, warp & ~3) + wq * 256 + lane * 8, c = table_buf(sb, warp & ~3) + 1024 + wq * 128 + lane * 4;
    const int t = lane & 3;
    const uint32_t o0 = (t < 2 ? KW_T2 + KW_KH + 16 + t * 256 - (wq & 1) * KW_KH : KW_T3 + 16 - 1024 + t * 512 + (wq & 1) * 256) + (lane >> 2) * 16;
    const uint4 o = make_uint4(o0 + t * 36, o0 + (t ^ 1) * 36, o0 + (t ^ 2) * 36, o0 + (t ^ 3) * 36);
    const uint2 u = lds64(a), v = lds64(a + TBW), w = lds64(a + 2 * TBW), x = lds64(a + 3 * TBW);
    const uint32_t kt = hadd2(hadd2(lds32(c), lds32(c + TBW)), hadd2(lds32(c + 2 * TBW), lds32(c + 3 * TBW)));
    const uint32_t k23 = hadd2(hadd2(u.y, v.y), hadd2(w.y, x.y));
    sts64(kw + wq * 64 + ao, hadd2(hadd2(u.x, v.x), hadd2(w.x, x.x)), k23);
    const uint32_t d = kw + (wq >> 1) * 128;
    const uint32_t kh = hmul2(kt, 0x38003800u);
    sts32(d + o.x, kh); sts32(d + o.y, kh); sts32(d + o.z, kh); sts32(d + o.w, kh);
    if (wq == 3) {
        if (lane == 31) { sts32(kw + 264, k23 >> 16); sts32(kw + 288 + 264, k23 >> 16); sts32(kw + 576 + 264, k23 >> 16); }
        if (lane == 29) { sts32(kw + 864 + 280, kt >> 16); sts32(kw + 280, kt & 0xffff0000u); }
    }
}

__device__ __forceinline__ int c_exponent(const uint2& r, const uint2& i) {
    uint32_t mx = __vmaxu2(__vmaxu2(r.x & 0x7fff7fffu, r.y & 0x7fff7fffu), __vmaxu2(i.x & 0x7fff7fffu, i.y & 0x7fff7fffu));
    mx = __reduce_max_sync(0xffffffffu, max(mx & 0xffffu, mx >> 16));
    return min(max((int)(mx >> 7), 4), 240);
}

__device__ __forceinline__ int warp_v() { int l; asm volatile("mov.u32 %0, %%tid.x;" : "=r"(l)); return __shfl_sync(0xffffffffu, l >> 5, 0); }
__device__ __forceinline__ int lane_v() { int l; asm volatile("mov.u32 %0, %%laneid;" : "=r"(l)); return l; }
__device__ __forceinline__ unsigned clock32() { unsigned c; asm volatile("mov.u32 %0, %%clock;" : "=r"(c)); return c; }
__device__ __forceinline__ uint32_t prmt(uint32_t a, uint32_t b, uint32_t s) { uint32_t d; asm("prmt.b32 %0, %1, %2, %3;\n" : "=r"(d) : "r"(a), "r"(b), "r"(s)); return d; }
__device__ __forceinline__ uint32_t prmt_v(uint32_t a, uint32_t b, uint32_t s) { uint32_t d; asm volatile("prmt.b32 %0, %1, %2, %3;\n" : "=r"(d) : "r"(a), "r"(b), "r"(s)); return d; }
__device__ __forceinline__ void mmah16(uint32_t& d0, uint32_t& d1, uint32_t a0, uint32_t a1, uint32_t a2, uint32_t a3, uint32_t b0, uint32_t b1, uint32_t c0, uint32_t c1) {
    asm volatile("mma.sync.aligned.m16n8k16.row.col.f16.f16.f16.f16 {%0,%1}, {%2,%3,%4,%5}, {%6,%7}, {%8,%9};\n"
                 : "=r"(d0), "=r"(d1) : "r"(a0), "r"(a1), "r"(a2), "r"(a3), "r"(b0), "r"(b1), "r"(c0), "r"(c1));
}
__device__ __forceinline__ void mmah8(uint32_t& d0, uint32_t& d1, uint32_t a0, uint32_t a1, uint32_t b0, uint32_t c0, uint32_t c1) {
    asm volatile("mma.sync.aligned.m16n8k8.row.col.f16.f16.f16.f16 {%0,%1}, {%2,%3}, {%4}, {%5,%6};\n"
                 : "=r"(d0), "=r"(d1) : "r"(a0), "r"(a1), "r"(b0), "r"(c0), "r"(c1));
}
template <int A = 8, int B = 32>
__device__ __forceinline__ void conv_rename(uint32_t (&acc)[32]) {
#pragma unroll
    for (int i = A; i < B; i++) { uint32_t v; asm volatile("mov.b32 %0, %1;\n" : "=r"(v) : "r"(acc[i])); acc[i] = v; }
}
__host__ __device__ constexpr uint32_t band_bits(int hw, int sh) {
    uint32_t c = 0;
    for (int s = 0; s <= 10; s++)
        for (int e = 0; e < 2; e++) {
            const int v = s - 3 + sh - 4 * e;
            if (v <= hw && v >= -hw) c |= 1u << (14 + 16 * e - s);
        }
    return c;
}
template <int HW, int SH, int J> __device__ __forceinline__ uint32_t band(uint32_t p2) {
    uint32_t d;
    asm volatile("{\n.reg .b32 t;\nmul.lo.u32 t, %1, %2;\nand.b32 %0, t, 0x40004000;\n}\n" : "=r"(d) : "r"(p2), "n"(band_bits(HW, SH) | J));
    return d;
}
__device__ __forceinline__ void band_quads(uint4 (&b)[3], uint32_t p2, uint32_t pm) {
    b[0] = make_uint4(band<2, 4, 1>(pm), band<1, 4, 1>(p2), band<2, -4, 1>(pm), band<1, -4, 1>(p2));
    b[1] = make_uint4(band<4, 4, 1>(pm), band<3, 4, 1>(pm), band<4, -4, 1>(pm), band<3, -4, 1>(pm));
    b[2] = make_uint4(band<2, 4, 2>(pm), band<4, 4, 2>(pm), band<2, -4, 2>(pm), band<4, -4, 2>(pm));
}
__device__ __forceinline__ uint2 run_sums(const uint4& a, uint32_t b0, uint32_t b1) {
    uint2 d;
    mmah16(d.x, d.y, a.x, a.y, a.z, a.w, b0, b1, 0u, 0u);
    return d;
}
__device__ __forceinline__ float h_lo(uint32_t w) { return __half2float(__ushort_as_half((unsigned short)(w & 0xffffu))); }
__device__ __forceinline__ float h_hi(uint32_t w) { return __half2float(__ushort_as_half((unsigned short)(w >> 16))); }
__device__ __forceinline__ uint64_t smem_desc(uint32_t sb, uint32_t o16, uint32_t lbo) {
    uint64_t d;
    asm("mov.b64 %0, {%1, %2};" : "=l"(d) : "r"(((sb & 0x3FFFF) >> 4) + o16 + (lbo << 12)), "r"(8));
    return d;
}
template <int I> struct IC { static constexpr int value = I; };

struct Conv {
    uint32_t q2[3][2][4];
    uint32_t q3[2][4];
    uint32_t r[18];
};
struct ConvPre {
    uint32_t a[5], b[5];
    uint32_t t[4];
};
__device__ __forceinline__ void conv_pre(ConvPre& e, uint32_t ka, uint32_t ks, uint32_t sel) {
    const uint4 r = lds128(ka + 256), s = lds128(ka + 272);
    ldsm_x4(e.t[0], e.t[1], e.t[2], e.t[3], ks);
    const uint32_t sw = sel ^ 0x4444u;
    e.a[0] = prmt(r.y, r.z, sel); e.a[1] = prmt(r.w, r.z, sw); e.a[2] = prmt(r.x, r.y, sel); e.a[3] = prmt(r.z, r.y, sw); e.a[4] = prmt(r.z, r.w, sel);
    e.b[0] = prmt(s.y, s.z, sel); e.b[1] = prmt(s.w, s.z, sw); e.b[2] = prmt(s.x, s.y, sel); e.b[3] = prmt(s.z, s.y, sw); e.b[4] = prmt(s.z, s.w, sel);
}
__device__ __forceinline__ void conv_sums(Conv& c, uint32_t (&acc)[32], const ConvPre& e, uint32_t a0, uint32_t a1, const uint4 (&bd)[3], uint32_t ka, uint32_t sel, int wq, bool odd) {
#pragma unroll
    for (int i = 0; i < 32; i++) acc[i] = 0u;
    uint32_t un[4], vn[4];
    ldsm_x4(un[0], un[1], un[2], un[3], a1);
    ldsm_x4(vn[0], vn[1], vn[2], vn[3], a0);
#pragma unroll
    for (int q = 0; q < 3; q++) {
        const uint32_t u[4] = {un[0], un[1], un[2], un[3]}, v[4] = {vn[0], vn[1], vn[2], vn[3]};
        if (q && sel == 0u) {
            sts128(ka, c.q3[q - 1][0], c.q3[q - 1][1], c.q3[q - 1][2], c.q3[q - 1][3]);
            sts64(ka, acc[8 * q], acc[8 * q + 8]);
        }
        if (q < 2) {
            ldsm_x4(un[0], un[1], un[2], un[3], a1 + q * 512 + 512);
            ldsm_x4(vn[0], vn[1], vn[2], vn[3], a0 + q * 512 + 512);
        }
        mmah8(acc[8 * q + 8], acc[8 * q + 9], e.a[4], 0u, u[1], acc[8 * q + 8], acc[8 * q + 9]);
        mmah16(acc[8 * q + 8], acc[8 * q + 9], e.a[0], e.a[1], e.a[2], e.a[3], u[2], u[3], acc[8 * q + 8], acc[8 * q + 9]);
        const uint2 z0 = run_sums(bd[2], v[0], v[1]);
        if (q < 2) {
            mmah8(acc[8 * q + 16], acc[8 * q + 17], e.b[4], 0u, u[1], 0u, 0u);
            mmah16(acc[8 * q + 16], acc[8 * q + 17], e.b[0], e.b[1], e.b[2], e.b[3], u[2], u[3], acc[8 * q + 16], acc[8 * q + 17]);
            const uint2 y1 = run_sums(bd[1], u[0], u[1]), y2 = run_sums(bd[1], v[2], v[3]), y3 = run_sums(bd[1], u[2], u[3]);
            const uint32_t n0 = odd ? y1.x : z0.y, n1 = odd ? y2.x : y1.x, s1 = odd ? y2.y : y1.y, s2 = odd ? y3.y : y2.y;
            c.q3[q][0] = prmt(s1, n0, 0x7632u); c.q3[q][1] = prmt(s2, n1, 0x7632u);
            c.q3[q][2] = prmt(s1, n0, 0x5410u); c.q3[q][3] = prmt(s2, n1, 0x5410u);
        }
        const uint2 x1 = run_sums(bd[0], u[0], u[1]), x2 = run_sums(bd[0], v[2], v[3]), x3 = run_sums(bd[0], u[2], u[3]);
        const uint32_t f0 = odd ? x1.x : z0.x, f1 = odd ? x2.x : x1.x, f2 = odd ? x3.x : x2.x;
#pragma unroll
        for (int h = 0; h < 2; h++) {
            const uint32_t s = h ? 0x7632u : 0x5410u;
            c.q2[q][h][0] = prmt(x1.y, f0, s); c.q2[q][h][1] = prmt(x2.y, f1, s);
            c.q2[q][h][2] = prmt(f1, x2.y, s ^ 0x4444u); c.q2[q][h][3] = prmt(x3.y, f2, s);
            if (q < 2) mmah16(acc[8 * q + 16], acc[8 * q + 17], c.q2[q][h][0], c.q2[q][h][1], c.q2[q][h][2], c.q2[q][h][3], e.t[2 * h], e.t[2 * h + 1], acc[8 * q + 16], acc[8 * q + 17]);
        }
    }
    {
        const uint32_t a = ka + wq * 64;
#pragma unroll
        for (int i = 0; i < 4; i++) { const uint4 v = lds128(a + i * 16); c.r[4 * i] = v.x; c.r[4 * i + 1] = v.y; c.r[4 * i + 2] = v.z; c.r[4 * i + 3] = v.w; }
        const uint2 v = lds64(a + 64);
        c.r[16] = v.x; c.r[17] = v.y;
    }
    if (sel == 0u) {
#pragma unroll
        for (int i = 0; i < 6; i++) sts128(ka + i * 16, c.q2[i >> 1][i & 1][0], c.q2[i >> 1][i & 1][1], c.q2[i >> 1][i & 1][2], c.q2[i >> 1][i & 1][3]);
#pragma unroll
        for (int i = 0; i < 2; i++) sts128(ka + i * 16, c.q3[i][0], c.q3[i][1], c.q3[i][2], c.q3[i][3]);
#pragma unroll
        for (int i = 1; i < 4; i++) sts64(ka + i * 16, acc[8 * i], acc[8 * i + 1]);
    }
    conv_rename(acc);
}
#define SPACE 100
#define SPN 3
#define O4 4
#define GATE 2
#define HAND 2
#define GA 6
#define GB 4
template <int TA, int TB, int IA, class FG>
__device__ __forceinline__ void conv_tail(uint32_t (&acc)[32], const uint32_t (&a)[8][4], uint32_t sb, unsigned char* gy0, int warp, size_t ycopy, FG fg) {
    const int wg = warp >> 2, wq = warp & 3, ord = TA == 0 && TB == 16 ? 3 - wg + (3 - wg >= O4) : O4;
    const uint32_t ub = sb + SM_U + wg * USLOT_B + UPAD * 16, turn = sb + SM_MISC + 376 + ord * 8, sfs = sb + SM_MISC + 256 + wg * 8;
    const uint32_t du = wg * (USLOT_B / 16) + (SM_U / 16 + UPAD + TA * 8);
    uint32_t ud[8], fs;
    auto skip = [&]() {
        const int lane = lane_v();
        const uint32_t ua = ub + ((lane >> 3) & 1) * ULO_B + (8 * wq + (lane & 7)) * 16 + (lane >> 4) * 512;
        if (IA == 0) ldsm_x4_t(ud[0], ud[1], ud[2], ud[3], ua);
        if (TB == 16) ldsm_x4_t(ud[4], ud[5], ud[6], ud[7], ua + 1024);
        const uint2 fd = lds64(sfs);
        fs = fd.x;
        const float dsk = __uint_as_float(fd.y);
#pragma unroll
        for (int i = 2 * IA; i < TB / 2; i++) ud[i] = pack_bf16(h_lo(ud[i]) * dsk, h_hi(ud[i]) * dsk);
    };
    conv_rename<2 * TA, 2 * TB>(acc);
    if (__builtin_expect(ord != 0, 0)) {
        skip();
        mbar_wait(turn);
    } else {
        bar_sync(0, NWRK);
    }
    if (O4 < 4 || (TA == 0 && TB == 16)) asm volatile("{\n.reg .pred p;\nelect.sync _|p, 0xffffffff;\n@p mbarrier.arrive.shared::cta.b64 _, [%0];\n}\n" ::"r"(turn + 48) : "memory");
    fg(IC<8>());
    wg_fence();
#pragma unroll
    for (int m = 7; m >= 0; m--) {
        wg_h<TA, TB - TA>(acc, a[m], smem_desc(sb, du - m, ULO_B));
        if (m == GA || m == GB || m == HAND) wg_commit();
        if (m == GB) asm volatile("wgmma.wait_group.sync.aligned 1;\n" ::: "memory");
    }
    wg_commit();
    if (O4 < 4 || (TA == 0 && TB == 16)) {
        asm volatile("wgmma.wait_group.sync.aligned 1;\n" ::: "memory");
        asm volatile("{\n.reg .pred p;\nelect.sync _|p, 0xffffffff;\n@p mbarrier.arrive.shared::cta.b64 _, [%0];\n}\n" ::"r"(turn + 8) : "memory");
    }
    __syncwarp();
    fg(IC<3>());
    if (!ord) skip();
    fg(IC<4>());
    const int lane = lane_v();
    const uint32_t lp = sb + SM_PL + (ord >= 3 ? ord - 3 : ord) * PL_B + lane * 8;
    unsigned char* gy = gy0 + ((4 * wq + (lane & 3)) * DM + (TA == 0 && TB == 16 ? 4 * blockIdx.x + wg : 512 + (blockIdx.x >> 1))) * 64 + (lane >> 2) * 8;
    const uint32_t st = lp + (wq * 12 - ((wq * (wq - 1)) >> 1)) * 256;
    uint32_t ld[3];
#pragma unroll
    for (int s = 1; s < 4; s++) {
        const int w = (wq - s) & 3;
        ld[s - 1] = lp + (w * 12 - ((w * (w - 1)) >> 1) + s - 1 - (wq < s ? 3 : 0)) * 256;
    }
    const uint32_t one = 1u + (warp >> 8);
    if (one == 0u) stg64(gy, ld[0], ld[1]);
    if (ord >= 3) bar_sync(9 + ord, 256);
    wg_wait0();
    fg(IC<6>());
#pragma unroll
    for (int j = TA; j < TB; j++)
        if ((j & 3) && j + 3 >= 4 * IA && (j + 3 < TB || j + wq < TB)) sts64(st + (j - 1 - (j >> 2)) * 256, acc[2 * j], acc[2 * j + 1]);
    bar_sync(1 + wg, 128);
    fg(IC<7>());
    uint2 v[4][3];
#pragma unroll
    for (int i = IA; i < TB / 4; i++)
#pragma unroll
        for (int s = 0; s < 3; s++) {
            if (i == 0) { v[i][s] = make_uint2(0u, 0u); if (wq > s) v[i][s] = lds64(ld[s]); }
            else v[i][s] = lds64(ld[s] + i * 768);
        }
    fg(IC<5>());
#pragma unroll
    for (int i = IA; i < TB / 4; i++) {
        const uint32_t x0 = hadd2(v[i][0].x, acc[8 * i]), x1 = hadd2(v[i][1].x, v[i][2].x), y0 = hadd2(v[i][0].y, acc[8 * i + 1]), y1 = hadd2(v[i][1].y, v[i][2].y);
        const uint32_t lo = pack_bf16(h_lo(x0) + h_lo(x1), h_hi(x0) + h_hi(x1)), hi = pack_bf16(h_lo(y0) + h_lo(y1), h_hi(y0) + h_hi(y1));
        ud[2 * i] = max(hfma2_bf(lo, fs, ud[2 * i]), one); ud[2 * i + 1] = hfma2_bf(hi, fs, ud[2 * i + 1]);
    }
    if (SPACE && TA == 0 && TB == 16 && ord < SPN) {
#pragma unroll
        for (int i = 0; i < 4; i++) {
            stg64(gy + i * 16 * DM * 64, ud[2 * i], ud[2 * i + 1]);
            if (i < 3) { const unsigned c0 = clock32(); while (clock32() - c0 < SPACE) {} }
        }
    } else {
#pragma unroll
        for (int i = IA; i < TB / 4; i++) stg64(gy + i * 16 * DM * 64, ud[2 * i], ud[2 * i + 1]);
    }
    if (ord < 2) bar_arrive(12 + ord, 256);
}
template <int M0, int M1>
__device__ __forceinline__ void conv_frags(uint32_t (&a)[8][4], const uint32_t (&r)[18], uint32_t sel, uint32_t dep, int warp) {
    const uint32_t s = prmt_v(sel, dep, 0x3210u + (warp >> 8)), sw = s ^ 0x4444u;
#pragma unroll
    for (int m = M0; m < M1; m++) {
        a[m][0] = prmt_v(r[2 * m + 1], r[2 * m + 2], s); a[m][1] = prmt_v(r[2 * m + 2], r[2 * m + 3], s);
        a[m][2] = prmt_v(r[2 * m + 1], r[2 * m], sw); a[m][3] = prmt_v(r[2 * m + 2], r[2 * m + 1], sw);
    }
}
template <class FG>
__device__ __forceinline__ void conv_main(const Conv& c, uint32_t (&acc)[32], uint32_t sb, uint32_t sel, unsigned char* gy, int warp, size_t ycopy, FG fg) {
    const uint32_t kw = (warp >> 2) * (KW_B / 16) + SM_KW / 16;
    const uint64_t d2 = smem_desc(sb, kw + KW_T2 / 16, KW_KH), d2b = smem_desc(sb, kw + KW_T2 / 16 + 1, KW_KH), d3 = smem_desc(sb, kw + KW_T3 / 16, 16), d3b = smem_desc(sb, kw + KW_T3 / 16 + 32, 16);
    uint32_t a[8][4];
    {
        const int ord = warp < 16 ? 3 - (warp >> 2) + (3 - (warp >> 2) >= O4) : O4;
        if (__builtin_expect(ord >= GATE, 0)) {
            fg(IC<1>());
            mbar_wait(sb + SM_MISC + 376 + 48 + (ord - GATE) * 8);
        }
    }
    wg_fence();
    wg_h<12, 4>(acc, c.q3[0], d3b); wg_h<8, 4>(acc, c.q3[0], d3); wg_h<4, 4>(acc, c.q2[0][0], d2b);
    wg_h<12, 4>(acc, c.q3[1], d3); wg_h<8, 4>(acc, c.q2[1][0], d2b);
    wg_h<12, 4>(acc, c.q2[2][0], d2b); wg_h<4, 4>(acc, c.q2[0][1], d2); wg_h<8, 4>(acc, c.q2[1][1], d2);
    wg_h<12, 4>(acc, c.q2[2][1], d2);
    wg_commit(); __syncwarp();
    fg(IC<0>());
    wg_wait0();
    conv_frags<0, 8>(a, c.r, sel, acc[16], warp);
    fg(IC<2>());
    if (warp >= 16) {
        if (blockIdx.x & 1) conv_tail<4, 16, 2>(acc, a, sb, gy, warp, ycopy, fg);
        else conv_tail<0, 8, 0>(acc, a, sb, gy, warp, ycopy, fg);
    } else {
        conv_tail<0, 16, 0>(acc, a, sb, gy, warp, ycopy, fg);
    }
}
#define CONV_LT6 const int dd = (lane >> 3) + (lane & 4) - (lane & 3); \
        const uint4 lt6 = make_uint4(prmt_v((dd & 3) * 288, 0u, idn), prmt_v(0x3254u + (dd >> 2) * 0x2222u, 0u, idn), \
            prmt_v(UPAD * 16 + (lane & 7) * 16 + ((lane >> 3) & 1) * (16 - ULO_B) + ULO_B - 32 + (lane & 16), 0u, idn), prmt_v(UPAD * 16 + (lane & 7) * 16 + ((lane >> 3) & 1) * ULO_B - 16 + (lane & 16), 0u, idn));
#define CONV_PRE \
        CONV_LT6 \
        const uint32_t ka = kw + lt6.x, sel = lt6.y, ks = kw + lt7.x; \
        const uint32_t ca0 = sb + SM_U + wg * USLOT_B + (warp & 3) * 128 + lt6.z, ca1 = sb + SM_U + wg * USLOT_B + (warp & 3) * 128 + lt6.w; \
        uint4 bd[3]; \
        band_quads(bd, lt7.w, (lane & 4) ? lt7.w >> 4 : lt7.w << 4);
#define CONV_PRE2 ConvPre ce_; conv_pre(ce_, ka, ks, sel);
#define CONV_BODY \
        Conv c; \
        uint32_t acc[32]; \
        conv_sums(c, acc, ce_, ca0, ca1, bd, ka, sel, warp & 3, lane & 4);
#define WS a_b_0_1_2_34_x__y567____c____de_r_
#define WS_STR2(x) #x
#define WS_STR(x) WS_STR2(x)
__device__ constexpr char wunit(int pt, int k) {
    constexpr char t[] = WS_STR(WS);
    int i = 0;
    for (; pt > 0 && t[i]; i++) pt -= t[i] == '_';
    for (; k > 0 && t[i] && t[i] != '_'; i++) k--;
    return t[i] == '_' ? 0 : t[i];
}
__device__ constexpr bool wsched_ok() {
    int seen = 0;
    for (int p = 0; p < 21; p++)
        for (int k = 0; wunit(p, k); k++) {
            const char c = wunit(p, k);
            const int bit = 1 << (c == 'r' ? 13 : c >= 'x' ? c - 'x' + 14 : c >= 'a' ? c - 'a' + 8 : c - '0');
            if ((seen & bit) || k >= (p < 16 ? 4 : 2) || (p < 5 && c >= '4' && c <= '7') || (p < 6 && (c == 'c' || c == 'd')) || (p < 16 && c == 'e')) return false;
            seen |= bit;
        }
    return seen == 0xffff;
}
struct WMaps { CUtensorMap g, u, gr, ur, d, dr; };
static_assert(GATE <= 2 && O4 >= 2, "resets");
static_assert(wsched_ok(), "weight schedule");
template <int PT, int K>
__device__ __forceinline__ void weight_units(uint32_t sb, const WMaps& m, int w) {
    constexpr char U = wunit(PT, K);
    if constexpr (U != 0) {
        if (w == K && elect_one()) {
            if (PT == 8) DELAY(K * WSP + WS0);
            const int P = blockIdx.x >> 1, odd = blockIdx.x & 1;
            constexpr int bar = SM_MISC + (U == 'e' ? 352 : U >= 'a' && U <= 'r' ? 336 : 328);
            if constexpr (U == 'e') { if (!odd) tma_2d(sb + SM_WD + 4 * 8192, &m.d, 256, 64 * P, sb + bar); }
            else if constexpr (U == 'r') tma_3d(sb + SM_WD + 40960, &m.dr, 0, 4096 + 8 * P, 5 * odd, sb + bar);
            else if constexpr (U >= 'x') tma_3d(sb + SM_WR + (U - 'x') * 4608, U == 'x' ? &m.gr : &m.ur, 4096 + 8 * P, 0, 2 * odd, sb + bar);
            else if constexpr (U >= 'a') tma_2d(sb + SM_WD + (U - 'a') * 8192, &m.d, 320 * odd + 64 * (U - 'a'), 64 * P, sb + bar);
            else tma_2d(sb + (U < '4' ? SM_WG : SM_WU) + (U & 3) * 9216, U < '4' ? &m.g : &m.u, 64 * P, 288 * odd + (U & 3) * 72, sb + bar);
        }
        weight_units<PT, K + 1>(sb, m, w);
    }
}
#define WPOINT(i, w) do { weight_units<i, 0>(sb, wm, w); } while (0)

__global__ void __launch_bounds__(NTHR, 1) __cluster_dims__(2, 1, 1)
fused_kernel(const Params p, const __grid_constant__ WMaps wm, const __grid_constant__ CUtensorMap tm_x,
             const __grid_constant__ CUtensorMap tm_y, const __grid_constant__ CUtensorMap tm_z) {
    extern __shared__ __align__(1024) unsigned char smem[];
    const uint32_t sb = smem_u32(smem);
    const int tid = threadIdx.x, warp = __shfl_sync(0xffffffffu, tid >> 5, 0), lane = tid & 31;
    const int b = blockIdx.x, P = b >> 1, odd = b & 1;
    const int g = lane >> 2, t = lane & 3;
    const int wg = warp >> 2, t128 = tid & 127;
    const uint32_t s_stat = sb + SM_MISC;
    const uint32_t s_key = sb + SM_MISC + 128;
    const uint32_t s_wm = sb + SM_MISC + 256;
    const uint32_t s_k16 = sb + SM_MISC + 192;
    const uint32_t s_fs = sb + SM_MISC + 256;
    const uint32_t s_cnt = sb + SM_MISC + 320;
    const uint32_t bar_w = sb + SM_MISC + 328, bar_d = bar_w + 8, bar_g = bar_w + 16, bar_r = bar_w + 32, bar_h = bar_w + 40, bar_x = bar_w + 48;
    STAMP(0);

    const unsigned tk0 = clock32();
    const bool lnw = (unsigned)(warp - 10) < 9u;
    const unsigned pm = tid + (tid < 512 ? 512 * b : 65024 + 128 * P), pq = (pm & ~127u) + 4 * lane;
    const uint32_t pl = ldg16(p.lar + pm), ldt = ldg16(p.ldt + (pm >> 7));
    const uint32_t pa2 = ldg16(p.aim + pm), pc = ldg16(p.cre + pm), pi = ldg16(p.cim + pm);
    const uint2 call_re = ldg64(p.cre + pq), call_im = ldg64(p.cim + pq);
    const uint32_t dskl = ldg16(p.dsk + (pm >> 7));
    const uint32_t ep = ld_poll32(p.s->hint + (b & 7) * 32 + 1 + (lane >> 5));
    if ((unsigned)(tid - 320) < 288u) {
        const bf16* xp = p.x + (unsigned)((32 * P + 2 * odd + TOKEN_OF(g)) * DM + ((tid - 320) & ~31) + 8 * t);
        const uint32_t xt = sb + SM_XT + ((tid - 320) & ~31) * 32 + lane * 16;
        asm volatile("cp.async.cg.shared.global [%0], [%1], 16;\ncp.async.cg.shared.global [%0 + 512], [%1 + 9216], 16;\n"
                     "cp.async.cg.shared.global [%0 + 9216], [%1 + 576], 16;\ncp.async.cg.shared.global [%0 + 9728], [%1 + 9792], 16;\n" ::"r"(xt), "l"(xp) : "memory");
    }
    uint32_t* const std_ = p.s->st + ((lane & 12) * 128 + odd * 256 + 4 * P + 2 * (lane & 1) + ((lane >> 1) & 1)) * 2;
    unsigned char* const ud = reinterpret_cast<unsigned char*>(p.s->uT) + (32 * (warp - UW) + 8 * (g >> 1) + (g & 1)) * 4096 + b * 32 + t * 8;
    if (warp == 0) {
        if (lane == 0) {
            mbar_init(bar_x, 1); mbar_init(bar_w, 1); mbar_init(bar_d, 1); mbar_init(bar_d + 16, 1); mbar_init(bar_g, 1); mbar_init(bar_h, 3); mbar_init(bar_r, 1);
            #pragma unroll
            for (int i = 1; i < 11; i++) mbar_init(bar_x + 8 * i, 4);
            asm volatile("fence.mbarrier_init.release.cluster;\n" ::: "memory");
            mbar_expect(bar_x, 16384); mbar_expect(bar_r, 8192);
            mbar_expect(bar_w, 2 * 41472); mbar_expect(bar_d, 32768 + 5120); mbar_expect(bar_d + 16, 8192); mbar_expect(bar_g, 9 * 512);
        }
        __syncwarp();
        bar_arrive(0, NWRK);
    }
    if (warp == 0 && elect_one()) tma_3d(sb + SM_XC, &tm_x, 8 * P, 0, 8 * odd, bar_x);
    asm volatile("barrier.cluster.arrive.relaxed.aligned;\n" ::: "memory");
    const uint32_t kw = sb + SM_KW + wg * KW_B;
    if (t128 < 2 * UPAD) sts128(sb + SM_U + wg * USLOT_B + (t128 & 1) * ULO_B + (t128 >> 1) * 16, 0u, 0u, 0u, 0u);
    sts128(kw + t128 * 16, 0u, 0u, 0u, 0u);
    if (t128 < KW_B / 16 - 128) sts128(kw + 2048 + t128 * 16, 0u, 0u, 0u, 0u);
    if (tid < 128) {
#pragma unroll
        for (int i = 0; i < 4; i++) sts128(sb + SM_ZERO + i * 2048 + tid * 16, 0u, 0u, 0u, 0u);
    }
    if (warp != 0) bar_sync(0, NWRK);
    STAMP(1);
    if (warp == 19 || warp == UW || warp == UW + 1) {
        if (warp == 19) {
            if (lane < 16) stg64(std_, 0u, 0u);
            if (lane < 9) asm volatile("prefetch.global.L2 [%0];\n" ::"l"(p.wr + lane * 64));
        } else {
#pragma unroll
            for (int k = 0; k < 4; k++) stg64(ud + k * 8192, 0u, 0u);
        }
    }
    uint32_t X[2][8];
    auto partial = [&]() {
        const uint32_t xt = sb + SM_XT + (warp - 10) * 1024 + lane * 16;
        asm volatile("cp.async.wait_all;\n" ::: "memory");
        STAMP(23);
        const uint4 a = lds128(xt), c = lds128(xt + 512), d = lds128(xt + 9216), e = lds128(xt + 9728);
        X[0][0] = a.x; X[0][1] = a.y; X[0][2] = a.z; X[0][3] = a.w; X[0][4] = d.x; X[0][5] = d.y; X[0][6] = d.z; X[0][7] = d.w;
        X[1][0] = c.x; X[1][1] = c.y; X[1][2] = c.z; X[1][3] = c.w; X[1][4] = e.x; X[1][5] = e.y; X[1][6] = e.z; X[1][7] = e.w;
        const uint32_t one[8] = {0x3f803f80u, 0x3f803f80u, 0x3f803f80u, 0x3f803f80u, 0x3f803f80u, 0x3f803f80u, 0x3f803f80u, 0x3f803f80u};
        ln_partial<8>(X, one, sb + SM_LNP, warp - 10, g, t);
        bar_arrive(6, 320);
    };
    auto finish = [&]() {
        bar_sync(6, 320);
        float mb, rc;
        ln_finish<9>(sb + SM_LNP, lane, mb, rc);
        const float rh = rbf(rc);
        const uint32_t s0 = (__float_as_uint(mb) >> 16) | (((ep & 0x7fffu) + 1u) << 16), s1 = pack_bf16(rh, rc - rh);
        if (lane < 16) { stg64(std_, s0, s1); sts64(s_stat + lane * 8, s0, s1); }
        if (lane == 16) sts32(s_cnt + 4, ep);
        bar_arrive(7, 352);
        STAMP(28);
    };
    auto upub = [&]() {
        const uint32_t utag = ((ep & 3u) + 1u) * 0x10001u;
        uint32_t U[2][4];
#pragma unroll
        for (int hf = 0; hf < 2; hf++) {
            const uint2 st = lds64(s_stat + (g + 8 * hf) * 8);
            const uint4 xv = lds128(sb + SM_XT + (16 + warp - UW) * 1024 + hf * 512 + lane * 16);
            const uint32_t xs[4] = {xv.x, xv.y, xv.z, xv.w};
#pragma unroll
            for (int k = 0; k < 4; k++) {
                const uint32_t u = ln_apply(xs[k], st);
                U[hf][k] = movm((pack_f16_rz(bf_lo(u), __uint_as_float(u)) & 0xfff8fff8u) | utag);
            }
        }
#pragma unroll
        for (int k = 0; k < 4; k++) stg64(ud + k * 8192, U[0][k], U[1][k]);
    };
    const uint32_t tb = table_buf(sb, warp);
    const float dt = rbf(expf(bf_lo(ldt)));
    KGen kg;
    kgen_setup(kg, pl | (pa2 << 16), dt);
    kgen_rows(kg, tb, lane);
    if (wg == 0) fence_async();
    if (lnw) {
        partial();
        kg.z128.x = __uint_as_float(prmt_v(__float_as_uint(kg.z128.x), X[0][0], 0x3210u + (warp >> 8)));
        kg.z1.x = __uint_as_float(prmt_v(__float_as_uint(kg.z1.x), X[0][0], 0x3210u + (warp >> 8)));
    }
    STAMP(2);
    WPOINT(0, warp - 4);
    const int ce = c_exponent(call_re, call_im);
    if (t128 == 0) sts64(s_fs + wg * 8, (uint32_t)min(max(ce + (int)(__float_as_uint(dt) >> 23) - 116, 0), 254) * 0x800080u, dskl << 16);
    kgen_chain(kg, pc | (pi << 16), __uint_as_float(((uint32_t)(244 - ce) << 23) | (__float_as_uint(dt) & 0x7fffffu)));
    STAMP(3);
    WPOINT(1, warp - 6);
    kgen_cols(kg, tb, lane);
    if (warp == 19) finish();
    if (warp < 10) bar_sync(7, 352);
    if (warp == UW || warp == UW + 1) upub();
    STAMP(4);
    WPOINT(2, warp - 8);
    const uint4* usrc = wg < 4 ? reinterpret_cast<const uint4*>(p.s->st) + odd * 512 + (lane & 1) * 128 + 16 * (warp & 7) + (lane >> 1)
                               : reinterpret_cast<const uint4*>(p.s->uT) + P * 256 + 2 * t128;
    const int ustep = wg < 4 ? 256 : 1;
    uint4 uv0, uv1;
    kgen_mma(kg, tb, lane);
    STAMP(26);
    WPOINT(3, warp - 5);
    const uint32_t idn = 0x3210u + (warp >> 8);
    uint4 lt7 = make_uint4(prmt_v(KW_T2 + ((lane >> 3) & 1) * KW_KH + (33 + (lane & 7)) * 16 - (lane & 16), 0u, idn), t * 288 + g * 8 + 8, (lane & 1) * 4096 + (lane >> 1) * 16,
                                 prmt_v(8u << ((lane >> 3) + (lane & 4)) >> (lane & 3), 0u, idn));
    asm volatile("barrier.cluster.wait.acquire.aligned;\n" ::: "memory");
    const bool pe = (int)(clock32() - tk0) >= (wg < 4 ? TP0 : TP4);
    if (pe) { uv0 = ld_poll(usrc); uv1 = ld_poll(usrc + ustep); }
    bar_sync(1 + wg, 128);
    kgen_combine(sb, warp, lane, kw, lt7.y);
    if (warp < 3 || warp > 6) bar_arrive(14, NWRK);
    STAMP(5);
    WPOINT(4, warp - 7);
    if (!pe) {
        while ((int)(clock32() - tk0) < (wg < 4 ? TP0 : TP4)) {}
        uv0 = ld_poll(usrc); uv1 = ld_poll(usrc + ustep);
    }
    if (wg < 4) {
        mbar_wait(bar_x);
        const bool far = warp < 8;
        const uint32_t xa = sb + SM_XC + (warp & 7) * 256 + (odd ^ far) * 8 + lt7.z;
        uint2 xv[4] = {lds64(xa), lds64(xa + 8192), lds64(xa + 2048), lds64(xa + 10240)};
        const uint32_t tag = ((ep & 0x7fffu) + 1u) << 16;
        int it = 0;
        while (true) {
            const bool bad = (((uv0.x ^ tag) | (uv0.z ^ tag)) | ((uv1.x ^ tag) | (uv1.z ^ tag))) >> 16;
            if (!__any_sync(0xffffffffu, bad)) break;
            if (++it > SPIN_LIMIT) TRAP();
            if (bad) { uv0 = ld_poll(usrc); uv1 = ld_poll(usrc + 256); }
        }
        STAMP(6);
        DBG(wg, it);
        const uint2 st[4] = {make_uint2(uv0.x, uv0.y), make_uint2(uv0.z, uv0.w), make_uint2(uv1.x, uv1.y), make_uint2(uv1.z, uv1.w)};
#pragma unroll
        for (int i = 0; i < 4; i++) {
            xv[i].x = ln_apply(xv[i].x, st[i]);
            xv[i].y = ln_apply(xv[i].y, st[i]);
        }
        const uint32_t ub = sb + SM_U + UPAD * 16 + odd * ULO_B + (warp & 7) * 256 + lane * 8;
        const uint32_t w[4][2] = {{pack_f16(bf_lo(xv[0].x), bf_lo(xv[1].x)), pack_f16(bf_lo(xv[2].x), bf_lo(xv[3].x))}, {HI2(xv[0].x, xv[1].x), HI2(xv[2].x, xv[3].x)},
                                  {pack_f16(bf_lo(xv[0].y), bf_lo(xv[1].y)), pack_f16(bf_lo(xv[2].y), bf_lo(xv[3].y))}, {HI2(xv[0].y, xv[1].y), HI2(xv[2].y, xv[3].y)}};
#pragma unroll
        for (int i = 0; i < 4; i++) {
            if (far) asm volatile("st.async.shared::cluster.mbarrier::complete_tx::bytes.v2.b32 [%0], {%1,%2}, [%3];\n" ::"r"((ub ^ 0x1000000u) + i * USLOT_B), "r"(w[i][0]), "r"(w[i][1]), "r"(bar_r ^ 0x1000000u) : "memory");
            else sts64(ub + i * USLOT_B, w[i][0], w[i][1]);
        }
    } else {
        const uint32_t utag = ((ep & 3u) + 1u) * 0x10001u;
        int it = 0;
        while (true) {
            const bool bad = (((uv0.x ^ utag) | (uv0.y ^ utag) | (uv0.z ^ utag) | (uv0.w ^ utag)) | ((uv1.x ^ utag) | (uv1.y ^ utag) | (uv1.z ^ utag) | (uv1.w ^ utag))) & 0x70007u;
            if (!__any_sync(0xffffffffu, bad)) break;
            if (++it > SPIN_LIMIT) TRAP();
            if (bad) { uv0 = ld_poll(usrc); uv1 = ld_poll(usrc + 1); }
        }
        STAMP(6);
        DBG(4, it);
        const uint32_t ub = sb + SM_U + UPAD * 16 + 4 * USLOT_B + (t128 >> 1) * 32 + (t128 & 1) * 8;
        sts64(ub, prmt(uv0.x, uv0.z, 0x5410u) ^ utag, prmt(uv1.x, uv1.z, 0x5410u) ^ utag);
        sts64(ub + 16, prmt(uv0.x, uv0.z, 0x7632u) ^ utag, prmt(uv1.x, uv1.z, 0x7632u) ^ utag);
        sts64(ub + ULO_B, prmt(uv0.y, uv0.w, 0x5410u) ^ utag, prmt(uv1.y, uv1.w, 0x5410u) ^ utag);
        sts64(ub + ULO_B + 16, prmt(uv0.y, uv0.w, 0x7632u) ^ utag, prmt(uv1.y, uv1.w, 0x7632u) ^ utag);
    }
    lt7.w = prmt_v(lt7.w, uv0.x, idn);
    CONV_PRE
    if (warp < 3 && elect_one()) tma_st_3d(warp < 2 ? &tm_y : &tm_z, sb + SM_ZERO, warp < 2 ? 128 * b : 32 * (512 + P), 0, 2 * (warp < 2 ? warp : odd));
    if (warp >= 3 && warp <= 6) {
        bar_sync(14, NWRK);
        WPOINT(5, warp - 3);
    }
    bar_sync(1 + wg, 128);
    CONV_PRE2
    mbar_wait(bar_r);
    fence_async();
    bar_sync(0, NWRK);
    STAMP(7);
    uint32_t hv0 = 0;
    {
        WPOINT(6, 19 - warp);
        CONV_BODY
        WPOINT(7, 19 - warp);
        if (wg != 3) bar_arrive(0, NWRK);
        STAMP(8);
        size_t ycopy = 0;
        auto hook = [&](auto gi) {
                     constexpr int G = decltype(gi)::value;
                     if (G == 4 && warp == HINTW) hv0 = ld_poll32(p.s->hint + (lane_v() & 7) * 32);
                     if (G == 4) mbar_wait(bar_h);
                     if (G == 2) WPOINT(9, warp - 16);
                     if (G == 3) { WPOINT(10, warp - 12); WPOINT(12, warp - 8); WPOINT(14, warp - 4); }
                     if (G == 5) { WPOINT(11, warp - 13); WPOINT(13, warp - 9); WPOINT(15, warp - 5); }
                     if (G == 1 && warp >= 17 && elect_one())
                         bulk_s2g(warp == 17 ? p.s->part + b * (PBYTES / 4) : warp == 18 ? p.s->rows + b * 1152 : p.s->sc + b * 64, sb + SM_ZERO, warp == 17 ? PBYTES : warp == 18 ? 4608 : 160);
                     if (G == 4 && warp >= 17 && elect_one()) {
                         asm volatile("cp.async.bulk.wait_group 0;\n" ::: "memory");
                         hint_arrive(p.s->hint, 2, b & 7);
                     }
                     if (G == 1 && warp < 3) {
                         if (elect_one()) {
                             asm volatile("cp.async.bulk.wait_group 0;\n" ::: "memory");
                             mbar_arrive(bar_h);
                             hint_arrive(p.s->hint, 0, b & 7);
                         }
                         __syncwarp();
                         STAMP(17);
                     }
                     if (G == 1) WPOINT(8, warp - 16);
                 };
        conv_main(c, acc, sb, sel, reinterpret_cast<unsigned char*>(p.s->y), warp, ycopy, hook);
        STAMP(10);
    }
    {
    const int warp = warp_v(), lane = lane_v(), tid = 32 * warp + lane, g = lane >> 2, t = lane & 3;
    if (warp == HINTW) {
        const uint32_t target = (lds32(s_cnt + 4) + 1u) * 48u;
        if (__any_sync(0xffffffffu, (int)(hv0 - target) < 0)) hint_wait(p.s->hint, 0, target);
    }
    const unsigned char* ys = reinterpret_cast<const unsigned char*>(p.s->y) + ((size_t)P * DM + 32 * warp + 8 * (g >> 1) + (g & 1)) * 64 + odd * 32 + t * 8;
    STAMP(27);
    bar_sync(0, NWRK);
    STAMP(11);
    const uint32_t zr = warp >> 8;
    auto late_rows = [&](auto pub) {
        const uint32_t k = lds32(s_key + (lane & 7) * 4), ep = lds32(s_cnt + 4);
        const bool late = k & 256u, mine = late && ((k & 255u) >> 1) == (uint32_t)b;
        uint32_t todo = __ballot_sync(0xffffffffu, mine) & 0xffu;
        if (todo) {
#pragma unroll 1
            while (todo) {
                const int s = __ffs(todo) - 1, row = (__shfl_sync(0xffffffffu, k, s) >> 9) & 15;
                todo &= todo - 1;
                if ((row & 7) == g) pub(row & 8, 2 * NCTA + s);
            }
            __threadfence();
            bar_sync(0, NWRK);
            if (tid < NSEL && mine) *reinterpret_cast<volatile unsigned*>(p.s->flag + tid) = ep + 1u;
        }
        int it = 0;
        if (__any_sync(0xffffffffu, late)) {
            while (__any_sync(0xffffffffu, late && ld_poll32(p.s->flag + (lane & 7)) != ep + 1u)) { if (++it > SPIN_LIMIT) TRAP(); }
            __threadfence();
        }
        const int gs = tid / 36;
        const uint4* src = reinterpret_cast<const uint4*>(p.s->rows) + __shfl_sync(0xffffffffu, late ? 2 * NCTA + (lane & 7) : (k & 255u), gs & 7) * 144 + 36 * odd + (tid - gs * 36);
        if (tid < 288) {
            uint4 v0;
            do { v0 = ld_poll(src); if (++it > SPIN_LIMIT) TRAP(); } while (!v0.x);
            sts128(sb + SM_XS + gs * XS_PITCH + (tid - gs * 36) * 16, v0.x, v0.y, v0.z, v0.w);
        }
        __syncwarp();
    };
    if (warp >= 18) {
        uint32_t* const kp = pin(p.s->sc + 64 * b + 32 * (19 - warp), zr);
        const uint32_t kid = pin(0xc0000000u | ((lane & 15) << 9) | 2 * b, zr), ka = pin(s_k16 + (warp & 1) * 288 + (lane & 15) * 4, zr), kb = pin(s_k16 + (warp & 1) * 288 + (lane & 16) * 2, zr);
        const uint4* ksrc = pin(reinterpret_cast<const uint4*>(p.s->sc) + 8 * (19 - warp) + 16 * lane, zr);
        const uint4* rsrc = pin(reinterpret_cast<const uint4*>(p.s->rows) + 36 * odd + t, zr);
        uint32_t bits, early = 0;
        if (warp == 18) {
            weight_units<20, 0>(sb, wm, 0); weight_units<20, 1>(sb, wm, 1);
            bar_sync(8, 640);
            float mb, rc;
            ln_finish<18>(sb + SM_LNP, lane, mb, rc);
            if (lane < 16) stat_store(s_stat + lane * 8, mb, rc, 0u);
            bar_arrive(13, 608);
            bar_sync(10, 640);
            early = lds32(s_wm + (lane & 15) * 4);
            bits = pack_bf16(0.f, sum18(sb + SM_LNP + (32 + (lane & 15)) * 80));
        } else {
            float sw = 0.f;
#pragma unroll
            for (int i = 0; i < 9; i++) { const uint32_t w = reinterpret_cast<const uint32_t*>(p.wr)[32 * i + lane]; sw += bf_lo(w) + bf_hi(w); }
#pragma unroll
            for (int i = 16; i; i >>= 1) sw += __shfl_xor_sync(0xffffffffu, sw, i);
            early = __any_sync(0xffffffffu, (int)(ld_poll32(p.s->hint + (lane & 7) * 32 + 2 + zr * __float_as_int(sw)) - (lds32(s_cnt + 4) + 1u) * 48u) < 0);
            bar_sync(8, 640);
            const float v = sum18(sb + SM_LNP + lane * 80), hw = sum18(sb + SM_LNP + (48 + (lane & 15)) * 80);
            const float o = __shfl_xor_sync(0xffffffffu, v, 16), mean = (lane < 16 ? v : o) * (1.0f / 576.0f);
            const float var = fmaxf(fmaf(lane < 16 ? o : v, 1.0f / 576.0f, -(mean * mean)), 0.f);
            bits = __float_as_uint(fmaf(-rbf(mean), sw, hw) * rcp_approx(rbf(sqrt_approx(rbf(rbf(var) + 1e-5f)))));
        }
        {
            const uint32_t me = (((bits ^ ((uint32_t)((int)bits >> 31) & 0x7fffffffu)) >> 1) & 0x7fffe000u) ^ kid;
            sts32(ka, me);
            __syncwarp();
            const uint4 v = lds128(kb), w = lds128(kb + 16);
#define GT(x) ((me - (x)) >> 31)
            uint32_t rank = pin(GT(v.x) + GT(v.y) + GT(v.z), zr) + pin(GT(v.w) + GT(w.x) + GT(w.y), zr) + pin(GT(w.z) + GT(w.w), zr);
#undef GT
            rank += __shfl_xor_sync(0xffffffffu, rank, 16);
            const uint32_t sl = warp == 18 ? early : rank;
            stg32(kp + rank, me + (sl < 2 ? sl : 256u));
            if (warp == 19) {
                sts32(s_wm + (lane & 15) * 4, rank);
                if (early) hint_wait(p.s->hint, 2, (lds32(s_cnt + 4) + 1u) * 48u);
                bar_arrive(10, 640); bar_arrive(11, 608);
            }
        }
        bool slow;
        int it = 0;
        uint4 q[4];
        STAMP(13);
        DELAY(warp == 19 ? KDEL : KDEL2);
#pragma unroll
        for (int i = 0; i < 4; i++) q[i] = ld_poll(ksrc + 512 * i);
        if (PB9 == 2 || (PB9 == 1 && warp == 19)) bar_arrive(9, 576 + 32 * PB9);
        while (true) {
            uint32_t a[4];
#pragma unroll
            for (int i = 0; i < 4; i++) a[i] = q[i].x & q[i].y & q[i].z & q[i].w;
            if (__all_sync(0xffffffffu, a[0] & a[1] & a[2] & a[3])) break;
#pragma unroll
            for (int i = 0; i < 4; i++)
                if (!a[i]) q[i] = ld_poll(ksrc + 512 * i);
            if (++it > SPIN_LIMIT) TRAP();
        }
        STAMP(16);
        if (warp == 18) {
            const uint32_t kt = sb + SM_KEYS;
#pragma unroll
            for (int i = 0; i < 4; i++) sts128(kt + i * 512 + lane * 16, q[i].x, q[i].y, q[i].z, q[i].w);
            bar_sync(15, 64);
            const uint32_t c = lds32(s_key + 32 + g * 4), e = lds32(kt + (c & 254u) * 8 + t * 4);
            const bool hit = ((e ^ c) & 0x1fffu) == 0u && !(c & 256u);
            if (hit) sts32(s_key + g * 4, e);
            const uint32_t lo = __reduce_min_sync(0xffffffffu, hit ? e : 0xffffffffu) | 0x1fffu;
#define GT(x) ((lo - (x)) >> 31)
            uint32_t n = hit ? 256u - GT(e) : 0u;
#pragma unroll
            for (int i = 0; i < 4; i++) n += pin(GT(q[i].x) + GT(q[i].y) + GT(q[i].z) + GT(q[i].w), zr) << 12;
#undef GT
            n = __reduce_add_sync(0xffffffffu, n);
            slow = (n >> 12) + (n & 4095u) != 2048u || (n & 4095u) <= 2040u;
            if (slow) {
                uint4 r[4];
                it = 0;
                while (true) {
#pragma unroll
                    for (int i = 0; i < 4; i++) r[i] = ld_poll(ksrc + 512 * i + 1);
                    if (__all_sync(0xffffffffu, all_nz(r[0]) && all_nz(r[1]) && all_nz(r[2]) && all_nz(r[3]))) break;
                    if (++it > SPIN_LIMIT) TRAP();
                }
                uint32_t m = 0u;
#pragma unroll 1
                for (int s = 0; s < 8; s++) {
                    uint32_t x = 0;
#pragma unroll
                    for (int i = 0; i < 4; i++) {
                        x = max(max(max(x, q[i].x - m), max(q[i].y - m, q[i].z - m)), q[i].w - m);
                        x = max(max(max(x, r[i].x - m), max(r[i].y - m, r[i].z - m)), r[i].w - m);
                    }
                    m += __reduce_max_sync(0xffffffffu, x);
                    if (lane == 0) sts32(s_key + s * 4, m);
                }
            }
            DBG(7, slow);
        } else {
            auto merge = [](const uint4& x, const uint4& y) {
                const uint32_t a = max(x.x, y.w), c = max(x.y, y.z), d = max(x.z, y.y), e = max(x.w, y.x);
                const uint32_t a2 = max(a, d), d2 = min(a, d), c2 = max(c, e), e2 = min(c, e);
                return make_uint4(max(a2, c2), min(a2, c2), max(d2, e2), min(d2, e2));
            };
            uint4 h = merge(merge(q[0], q[1]), merge(q[2], q[3]));
            uint4 v[9];
            uint32_t key = 0;
#pragma unroll
            for (int s = 0; s < 8; s++) {
                const uint32_t m = __reduce_max_sync(0xffffffffu, h.x);
                const bool w = h.x == m;
                h.x = w ? h.y : h.x; h.y = w ? h.z : h.y; h.z = w ? h.w : h.z; h.w = w ? 0u : h.w;
                if (g == s) key = m;
            }
            rsrc += (key & 255u) * 144;
#pragma unroll
            for (int j = 0; j < 9; j++) v[j] = ld_poll(rsrc + 4 * j);
            const uint32_t xsa = sb + SM_XS + g * XS_PITCH + t * 16;
            sts32(s_key + 32 + g * 4, key);
            sts32(xsa, 0u);
            bar_arrive(15, 64);
            bar_arrive(12, 608);
            STAMP(18);
#pragma unroll
            for (int j = 0; j < 9; j++) sts128(xsa + j * 64, v[j].x, v[j].y, v[j].z, v[j].w);
            slow = min(min(min(min(v[0].x, v[1].x), v[2].x), min(min(v[3].x, v[4].x), v[5].x)), min(min(v[6].x, v[7].x), v[8].x)) == 0u;
        }
        if (bar_or(0, NWRK, slow)) { late_rows([](bool, int) {}); bar_or(0, NWRK, false); }
        STAMP(19);
        const int fl = 16 * (b & 1) + ((tid >> 2) & 15), fc = 16 * (b >> 1) + (fl >> 2) + 8 * ((tid >> 1) & 1), fsl = 2 * (fl & 3) + (tid & 1);
        const uint32_t kk = lds32(s_key + fsl * 4);
        const uint32_t* fsrc = p.s->rows + ((kk & 256u) ? 2 * NCTA + fsl : (kk & 255u)) * DM + (fc >> 3) * 4;
        if (b < 72) {
            it = 0;
            uint4 u4, h4;
            do { u4 = ld_poll(fsrc); h4 = ld_poll(fsrc + 288); if (++it > SPIN_LIMIT) TRAP(); } while (!u4.x || !h4.x);
            const uint32_t uw = (fc & 4) ? ((fc & 2) ? u4.w : u4.z) : ((fc & 2) ? u4.y : u4.x), hw = (fc & 4) ? ((fc & 2) ? h4.w : h4.z) : ((fc & 2) ? h4.y : h4.x);
            const int row = (kk >> 9) & 15, ftok = 8 * (kk & 252u) + (kk & 2u) + TOKEN_OF(row & 7) + (row & 8);
            const unsigned k16 = (kk >> 15) & 0xffffu;
            const unsigned bits = (k16 & 0x8000u) ? (k16 & 0x7fffu) : (~k16 & 0xffffu);
            const float rs = 512.0f * rbf(__fdividef(1.0f, 1.0f + __expf(-__uint_as_float(bits << 16))));
            bf16* const op = p.out + (unsigned)(ftok * DM + fc);
            const float uv = (fc & 1) ? bf_hi(uw) : bf_lo(uw), hv = (fc & 1) ? bf_hi(hw) : bf_lo(hw);
            const uint32_t a = sb + SM_FIN + (tid - 576) * 80;
            sts128(a + 64, __float_as_uint(rs), __float_as_uint(uv), __float_as_uint(hv), (uint32_t)(size_t)op ^ (uint32_t)((size_t)op >> 32));
            bar_sync(14, 576);
            const uint4 p0 = lds128(a), p1 = lds128(a + 16), p2 = lds128(a + 32), p3 = lds128(a + 48);
#define F4(p) ((__uint_as_float(p.x) + __uint_as_float(p.y)) + (__uint_as_float(p.z) + __uint_as_float(p.w)))
            const float v0 = F4(p0), v1 = F4(p1), v2 = F4(p2), v3 = F4(p3);
#undef F4
            const float y3 = rbf(rbf((v0 + v1) + (v2 + v3)) * rs);
            asm volatile("st.global.u16 [%0], %1;\n" ::"l"(op), "h"((unsigned short)pack_bf16(hv + rbf(uv + y3), 0.f)) : "memory");
        }
        if (b == 0 && tid >= 632) *reinterpret_cast<volatile unsigned*>(p.s->hint + (tid & 7) * 32 + 1) = lds32(s_cnt + 4) + 1u;
    } else {
        uint32_t H[2][4], U2[2][4], WA[9][4], WD[18], WE[18];
        const int fkh = warp >= 9, fmt = warp - 9 * fkh;
        auto load_wa = [&](auto k0, auto k1) {
            if (k0.value >= k1.value) return;
            if (k0.value == 0) mbar_wait(bar_w);
            const int mi = lane >> 3, rr = lane & 7;
            const int row = fkh * 144 + rr + 8 * (mi >> 1);
            const uint32_t aad = sb + (fmt < 8 ? SM_WG + (mi & 1) * (SM_WU - SM_WG) + row * 128 + (fmt ^ rr) * 16 : SM_WR + (mi & 1) * 4608 + row * 16), ks = fmt < 8 ? 2048 : 256;
#pragma unroll
            for (int k = k0.value; k < k1.value; k++) ldsm_x4_t(WA[k][0], WA[k][1], WA[k][2], WA[k][3], aad + k * ks);
        };
        auto load_wd = [&](uint32_t (&WD)[18], int tile) {
            mbar_wait(bar_d);
            if (tile & 16) mbar_wait(bar_d + 16);
            const int mi = lane >> 3, rr = lane & 7;
            const uint32_t base = sb + SM_WD + rr * 128 + (((2 * tile + (mi & 1)) & 7) ^ rr) * 16;
#pragma unroll
            for (int k = 0; k < 4; k++) ldsm_x4_t(WD[4 * k], WD[4 * k + 1], WD[4 * k + 2], WD[4 * k + 3], base + (tile >> 2) * 8192 + (k * 16 + 8 * (mi >> 1)) * 128);
            ldsm_x2_t(WD[16], WD[17], base + 40960 + (tile >> 2) * 1024);
        };
        auto publish = [&](bool hi, int slot) {
            uint4* rowp = reinterpret_cast<uint4*>(p.s->rows) + (unsigned)(slot * 144 + warp * 4 + t);
            stg128(rowp, nzw(hi ? U2[1][0] : U2[0][0]), hi ? U2[1][1] : U2[0][1], hi ? U2[1][2] : U2[0][2], hi ? U2[1][3] : U2[0][3]);
            stg128(rowp + 72, nzw(hi ? H[1][0] : H[0][0]), hi ? H[1][1] : H[0][1], hi ? H[1][2] : H[0][2], hi ? H[1][3] : H[0][3]);
        };
        uint4 wr = make_uint4(0x3f803f80u, 0x3f803f80u, 0x3f803f80u, 0x3f803f80u);
        {
            uint2 yv[4];
#pragma unroll
            for (int k = 0; k < 4; k++) yv[k] = ld_poll64(ys + k * 128);
            if (g == 0) wr = ldg128(p.wr + 32 * warp + 8 * t);
            const uint4 x0 = lds128(sb + SM_XT + warp * 1024 + lane * 16), x1 = lds128(sb + SM_XT + warp * 1024 + 512 + lane * 16);
            load_wa(IC<0>(), IC<WA0>());
            int it = 0;
            while (!__all_sync(0xffffffffu, yv[0].x && yv[1].x && yv[2].x && yv[3].x)) {
#pragma unroll
                for (int k = 0; k < 4; k++) yv[k] = ld_poll64(ys + k * 128);
                if (++it > SPIN_LIMIT) TRAP();
            }
            STAMP(12);
            const uint32_t Z[2][4] = {{x0.x, x0.y, x0.z, x0.w}, {x1.x, x1.y, x1.z, x1.w}};
#pragma unroll
            for (int k = 0; k < 4; k++) {
                H[0][k] = hadd2_bf(Z[0][k], movm(yv[k].x));
                H[1][k] = hadd2_bf(Z[1][k], movm(yv[k].y));
            }
            const uint32_t bw[4] = {wr.x, wr.y, wr.z, wr.w};
            ln_partial<4>(H, bw, sb + SM_LNP, warp, g, t);
        }
        bar_arrive(8, 640);
        WPOINT(16, warp - 12);
        load_wa(IC<WA0>(), IC<WA1>());
        STAMP(13);
        bar_sync(13, 608);
        STAMP(14);
#pragma unroll
        for (int hf = 0; hf < 2; hf++) {
            const uint2 st = lds64(s_stat + (g + 8 * hf) * 8);
#pragma unroll
            for (int k = 0; k < 4; k++) U2[hf][k] = ln_apply(H[hf][k], st);
        }
        {
            float cs[4] = {0.f, 0.f, 0.f, 0.f}, ct[4] = {0.f, 0.f, 0.f, 0.f};
            mma_bf16(cs, U2[0][0], U2[1][0], U2[0][1], U2[1][1], wr.x, wr.y);
            mma_bf16(ct, U2[0][2], U2[1][2], U2[0][3], U2[1][3], wr.z, wr.w);
            if (t == 0) { stsf(sb + SM_LNP + ((32 + g) * 20 + warp) * 4, cs[0] + ct[0]); stsf(sb + SM_LNP + ((40 + g) * 20 + warp) * 4, cs[2] + ct[2]); }
            bar_arrive(10, 640);
        }
        load_wa(IC<WA1>(), IC<WA2>());
        bar_sync(11, 608);
        {
            const uint32_t rk[2] = {lds32(s_wm + g * 4), lds32(s_wm + 32 + g * 4)};
            uint32_t lo = min(rk[0], rk[1]), hi = max(rk[0], rk[1]);
#pragma unroll 1
            while (lo < 2) { publish(lo == rk[1], 2 * b + lo); lo = hi; hi = 16; }
        }
        if (PB9) bar_sync(9, 576 + 32 * PB9);
        load_wa(IC<WA2>(), IC<9>());
#pragma unroll
        for (int hf = 0; hf < 2; hf++)
            sts128(sb + SM_OUT + (g + 8 * hf) * OUT_PITCH + warp * 64 + t * 16,
                   hadd2_bf(H[hf][0], U2[hf][0]), hadd2_bf(H[hf][1], U2[hf][1]), hadd2_bf(H[hf][2], U2[hf][2]), hadd2_bf(H[hf][3], U2[hf][3]));
        fence_async();
        WPOINT(17, warp - 16);
        if ((WDAT == 0 || (WDAT == 2 && fkh)) && (warp < 16 || !odd)) load_wd(WD, warp);
        const uint32_t bad = pin(sb + SM_XS + (lane & 7) * XS_PITCH + (fkh * 144 + 8 * (lane >> 3)) * 2, zr), ex = pin(sb + SM_EX + warp * 512 + lane * 16, zr);
        uint32_t* pp = pin(p.s->part + ((size_t)(2 * (20 * odd + warp) + (lane >> 4)) * 64 + P) * 32 + (lane & 15) * 2, zr);
        bar_sync(12, 608);
        const bool routed = __any_sync(0xffffffffu, (lds32(s_key + 32 + (lane & 7) * 4) & 0x1efeu) == (uint32_t)((warp << 9) | 2 * b));
        auto store_row = [&]() { if (warp < 16 && elect_one()) bulk_s2g(p.out + (size_t)(32 * P + 2 * odd + TOKEN_OF(warp & 7) + (warp & 8)) * DM, sb + SM_OUT + warp * OUT_PITCH, DM * 2); };
        if (!routed) store_row();
        WPOINT(18, warp - 16);
        STAMP(15);
        bool again = zr;
#pragma unroll 1
        do {
            if (again) {
                if (routed) store_row();
                asm volatile("cp.async.bulk.wait_group 0;\n" ::: "memory");
                late_rows(publish);
            }
            again = bar_or(0, NWRK, false);
        } while (again);
        STAMP(19);
        float gp[4];
        {
            float c4[3][4];
#pragma unroll
            for (int i = 0; i < 3; i++)
#pragma unroll
                for (int j = 0; j < 4; j++) c4[i][j] = 0.f;
#pragma unroll
            for (int k = 0; k < 10; k += 2) {
                uint32_t b0, b1, b2, b3;
                ldsm_x4(b0, b1, b2, b3, bad + k * 32);
                mma_bf16(c4[k % 3], WA[k][0], WA[k][1], WA[k][2], WA[k][3], b0, b1);
                if (k < 8) mma_bf16(c4[(k + 1) % 3], WA[k + 1][0], WA[k + 1][1], WA[k + 1][2], WA[k + 1][3], b2, b3);
            }
#pragma unroll
            for (int j = 0; j < 4; j++) gp[j] = c4[0][j] + (c4[1][j] + c4[2][j]);
            if (warp >= 9) {
                sts128f(ex, gp);
                bar_arrive(6, 576);
            } else {
                bar_sync(6, 576);
                const uint4 o = lds128(ex + 4608);
                gp[0] += __uint_as_float(o.x); gp[1] += __uint_as_float(o.y); gp[2] += __uint_as_float(o.z); gp[3] += __uint_as_float(o.w);
                asm volatile("st.async.shared::cluster.mbarrier::complete_tx::bytes.v4.b32 [%0], {%1,%2,%3,%4}, [%5];\n"
                             ::"r"(ex ^ 0x1000000u), "r"(__float_as_uint(gp[0])), "r"(__float_as_uint(gp[1])), "r"(__float_as_uint(gp[2])), "r"(__float_as_uint(gp[3])), "r"(bar_g ^ 0x1000000u) : "memory");
                if (WDAT == 2) load_wd(WD, warp);
            }
            if (WDAT == 1 && (warp < 16 || !odd)) load_wd(WD, warp);
            if (warp >= 16 && !odd) load_wd(WE, warp + 2);
        }
        STAMP(20);
        if (warp < 9) {
            mbar_wait(bar_g);
            const uint4 u = lds128(ex);
            const uint32_t G = pack_bf16(gp[0] + __uint_as_float(u.x), gp[1] + __uint_as_float(u.y)), U = pack_bf16(gp[2] + __uint_as_float(u.z), gp[3] + __uint_as_float(u.w));
            const float G0 = bf_lo(G), G1 = bf_hi(G);
            sts32(sb + SM_GU + tid * 4, hmul2_bf(pack_bf16(G0 * rcp_approx(1.0f + ex2_approx(G0 * -1.4426950408889634f)), G1 * rcp_approx(1.0f + ex2_approx(G1 * -1.4426950408889634f))), U));
        }
        bar_sync(7, 576);
        STAMP(21);
        if (warp < 16 || !odd) {
            uint32_t gb[9];
            ldsm_x4_t(gb[0], gb[1], gb[2], gb[3], sb + SM_GU + lane * 16);
            ldsm_x4_t(gb[4], gb[5], gb[6], gb[7], sb + SM_GU + 512 + lane * 16);
            ldsm_x1_t(gb[8], sb + SM_GU + 1024 + (lane & 7) * 16);
            auto down = [&](const uint32_t (&W)[18], uint32_t* dst) {
                float c4[4] = {0.f, 0.f, 0.f, 0.f}, d4[4] = {0.f, 0.f, 0.f, 0.f}, e4[4] = {0.f, 0.f, 0.f, 0.f};
                mma_bf16(c4, W[0], W[1], W[2], W[3], gb[0], gb[1]);
                mma_bf16(d4, W[4], W[5], W[6], W[7], gb[2], gb[3]);
                mma_bf16(e4, W[8], W[9], W[10], W[11], gb[4], gb[5]);
                mma_bf16_k8(c4, W[16], W[17], gb[8]);
                mma_bf16(d4, W[12], W[13], W[14], W[15], gb[6], gb[7]);
                const float v0 = (c4[0] + e4[0]) + d4[0], v1 = (c4[1] + e4[1]) + d4[1], v2 = (c4[2] + e4[2]) + d4[2], v3 = (c4[3] + e4[3]) + d4[3];
                const uint32_t e = max(max(__float_as_uint(fmaxf(fabsf(v0), fabsf(v1))), __float_as_uint(fmaxf(fabsf(v2), fabsf(v3)))), 16u << 23) >> 23;
                const float sc = __uint_as_float((245u - e) << 23);
                stg64(dst, pack_f16(v0 * sc, v1 * sc) | ((e * 0x8002000u) & 0x60006000u), pack_f16(v2 * sc, v3 * sc) | ((e * 0x800200u) & 0x60006000u));
            };
            if (warp >= 16) { down(WE, pp + 4 * 64 * 32); down(WD, pp); }
            else down(WD, pp);
        }
        asm volatile("cp.async.bulk.wait_group.read 0;\n" ::: "memory");
        STAMP(22);
        if (b < 72 && warp < 16) {
            const uint2* src = reinterpret_cast<const uint2*>(p.s->part) + (unsigned)(b * 1024 + tid);
            uint2 a, c;
            int it = 0;
            DELAY(PDEL);
            a = ld_poll64(src); c = ld_poll64(src + 512);
            while (!__all_sync(0xffffffffu, a.y && c.y)) {
                a = ld_poll64(src); c = ld_poll64(src + 512);
                if (++it > SPIN_LIMIT) TRAP();
            }
            STAMP(24);
            const float ea = __uint_as_float((((a.y & 0x60006000u) | ((a.x >> 4) & 0x06000600u)) * 0x4001u) & 0x7f800000u);
            const float ec = __uint_as_float((((c.y & 0x60006000u) | ((c.x >> 4) & 0x06000600u)) * 0x4001u) & 0x7f800000u);
            a.x &= 0x9fff9fffu; a.y &= 0x9fff9fffu; c.x &= 0x9fff9fffu; c.y &= 0x9fff9fffu;
            const float s0 = fmaf(h_lo(a.x), ea, h_lo(c.x) * ec), s1 = fmaf(h_hi(a.x), ea, h_hi(c.x) * ec), s2 = fmaf(h_lo(a.y), ea, h_lo(c.y) * ec), s3 = fmaf(h_hi(a.y), ea, h_hi(c.y) * ec);
            const bool up = lane & 16;
            const float r0 = __shfl_xor_sync(0xffffffffu, up ? s0 : s2, 16), r1 = __shfl_xor_sync(0xffffffffu, up ? s1 : s3, 16);
            const uint32_t fa = sb + SM_FIN + ((lane & 15) * 4 + (up ? 2 : 0)) * 80 + warp * 4;
            stsf(fa, (up ? s2 : s0) + r0); stsf(fa + 80, (up ? s3 : s1) + r1);
            bar_arrive(14, 576);
        }
    }
    STAMP(25);
    }
}

typedef CUresult (*PFN_tmEncode)(CUtensorMap*, CUtensorMapDataType, cuuint32_t, void*, const cuuint64_t*, const cuuint64_t*, const cuuint32_t*,
                                 const cuuint32_t*, CUtensorMapInterleave, CUtensorMapSwizzle, CUtensorMapL2promotion, CUtensorMapFloatOOBfill);

extern "C" void kernel_launch(void* const* d_in, const int* in_sizes, int n_in, void* d_out, int out_size) {
    Params p;
    p.x = (const bf16*)d_in[0];
    p.lar = (const bf16*)d_in[1];
    p.aim = (const bf16*)d_in[2];
    p.cre = (const bf16*)d_in[3];
    p.cim = (const bf16*)d_in[4];
    p.ldt = (const bf16*)d_in[5];
    p.dsk = (const bf16*)d_in[6];
    p.wr = (const bf16*)d_in[8];
    p.out = (bf16*)d_out;
    static PFN_tmEncode enc = nullptr;
    static void* scratch = nullptr;
    if (!enc) {
        cudaFuncSetAttribute(fused_kernel, cudaFuncAttributeMaxDynamicSharedMemorySize, SMEM_TOTAL);
        void* fn = nullptr;
        cudaDriverEntryPointQueryResult qr;
        cudaGetDriverEntryPoint("cuTensorMapEncodeTiled", &fn, cudaEnableDefault, &qr);
        enc = (PFN_tmEncode)fn;
        cudaGetSymbolAddress(&scratch, g_scratch);
    }
    p.s = (Scratch*)scratch;
    WMaps wm;
    CUtensorMap tm_x, tm_y, tm_z;
    const cuuint64_t dims[2] = {FF, DM}, strides[1] = {FF * 2}, rdims[3] = {FF, 144, 4}, rstrides[2] = {FF * 2, 144 * FF * 2};
    const cuuint32_t box[2] = {64, 72}, rbox[3] = {8, 144, 2}, es3[3] = {1, 1, 1};
    for (int i = 0; i < 2; i++) {
        enc(i ? &wm.u : &wm.g, CU_TENSOR_MAP_DATA_TYPE_BFLOAT16, 2, d_in[9 + i], dims, strides, box, es3, CU_TENSOR_MAP_INTERLEAVE_NONE, CU_TENSOR_MAP_SWIZZLE_128B,
            CU_TENSOR_MAP_L2_PROMOTION_NONE, CU_TENSOR_MAP_FLOAT_OOB_FILL_NONE);
        enc(i ? &wm.ur : &wm.gr, CU_TENSOR_MAP_DATA_TYPE_BFLOAT16, 3, d_in[9 + i], rdims, rstrides, rbox, es3, CU_TENSOR_MAP_INTERLEAVE_NONE, CU_TENSOR_MAP_SWIZZLE_NONE,
            CU_TENSOR_MAP_L2_PROMOTION_NONE, CU_TENSOR_MAP_FLOAT_OOB_FILL_NONE);
    }
    const cuuint64_t ddims[2] = {DM, FF}, dstrides[1] = {DM * 2}, edims[3] = {64, FF, 9}, estrides[2] = {DM * 2, 128};
    const cuuint32_t dbox[2] = {64, 64}, ebox[3] = {64, 8, 5};
    enc(&wm.d, CU_TENSOR_MAP_DATA_TYPE_BFLOAT16, 2, d_in[11], ddims, dstrides, dbox, es3, CU_TENSOR_MAP_INTERLEAVE_NONE, CU_TENSOR_MAP_SWIZZLE_128B,
        CU_TENSOR_MAP_L2_PROMOTION_NONE, CU_TENSOR_MAP_FLOAT_OOB_FILL_NONE);
    enc(&wm.dr, CU_TENSOR_MAP_DATA_TYPE_BFLOAT16, 3, d_in[11], edims, estrides, ebox, es3, CU_TENSOR_MAP_INTERLEAVE_NONE, CU_TENSOR_MAP_SWIZZLE_128B,
        CU_TENSOR_MAP_L2_PROMOTION_NONE, CU_TENSOR_MAP_FLOAT_OOB_FILL_NONE);
    const cuuint64_t xdims[3] = {DM, LSEQ / 16, 16}, xstrides[2] = {16 * DM * 2, DM * 2};
    const cuuint32_t xbox[3] = {8, LSEQ / 16, 8};
    enc(&tm_x, CU_TENSOR_MAP_DATA_TYPE_BFLOAT16, 3, d_in[0], xdims, xstrides, xbox, es3, CU_TENSOR_MAP_INTERLEAVE_NONE, CU_TENSOR_MAP_SWIZZLE_NONE,
        CU_TENSOR_MAP_L2_PROMOTION_NONE, CU_TENSOR_MAP_FLOAT_OOB_FILL_NONE);
    const cuuint64_t ydims[3] = {DM * 32, 16, 4}, ystrides[2] = {DM * 64, 16 * DM * 64};
    const cuuint32_t ybox[3] = {128, 16, 2}, zbox[3] = {32, 16, 2};
    enc(&tm_y, CU_TENSOR_MAP_DATA_TYPE_BFLOAT16, 3, p.s->y, ydims, ystrides, ybox, es3, CU_TENSOR_MAP_INTERLEAVE_NONE, CU_TENSOR_MAP_SWIZZLE_NONE,
        CU_TENSOR_MAP_L2_PROMOTION_NONE, CU_TENSOR_MAP_FLOAT_OOB_FILL_NONE);
    enc(&tm_z, CU_TENSOR_MAP_DATA_TYPE_BFLOAT16, 3, p.s->y, ydims, ystrides, zbox, es3, CU_TENSOR_MAP_INTERLEAVE_NONE, CU_TENSOR_MAP_SWIZZLE_NONE,
        CU_TENSOR_MAP_L2_PROMOTION_NONE, CU_TENSOR_MAP_FLOAT_OOB_FILL_NONE);
    fused_kernel<<<NCTA, NTHR, SMEM_TOTAL>>>(p, wm, tm_x, tm_y, tm_z);
}
```
